```python
import torch

def _softmax(x, axis=-1):
    return torch.softmax(x, dim=axis)

def _gelu(x):
    return torch.nn.functional.gelu(x, approximate='tanh')

def _silu(x):
    return torch.nn.functional.silu(x)

def _sigmoid(x):
    return torch.sigmoid(x)

def _layernorm(x, axis=-1, eps=1e-05):
    m = x.mean(dim=axis, keepdim=True)
    v = x.var(dim=axis, keepdim=True, unbiased=False)
    return (x - m) / torch.sqrt(v + eps)

def _scatter_add(tgt, idx, src, axis=0):
    return tgt.clone().index_add_(axis, idx, src)

def _segment_sum(src, seg, n):
    out = torch.zeros((n,) + src.shape[1:], dtype=src.dtype)
    return out.index_add_(0, seg, src)

def _pad(x, pw):
    flat = tuple((v for pair in reversed(pw) for v in pair))
    return torch.nn.functional.pad(x, flat)
kernel_name = 'recurrent_scan__ssm_conv_h3__mixer_gmlp__prompt'

def setup_inputs():

    _w = lambda a: (lambda t: t.to(torch.bfloat16) if t.is_floating_point() else t)(torch.as_tensor(a))

    def _A_setup():
        B, S, D = (1, 2048, 640)
        ks = 4
        return {'q': _w((lambda *s: torch.randn(*s, dtype=torch.bfloat16) * 0.05)(B, S, D)), 'k': _w((lambda *s: torch.randn(*s, dtype=torch.bfloat16) * 0.2)(B, S, D)), 'v': _w((lambda *s: torch.randn(*s, dtype=torch.bfloat16) * 0.2)(B, S, D)), 'shift_k': _w((lambda *s: torch.randn(*s, dtype=torch.bfloat16) * 0.2)(D, ks) * 0.5), 'ssm_k': _w((lambda *s: torch.randn(*s, dtype=torch.bfloat16) * 0.2)(D, S) * (1.0 / S ** 0.5)), 'ssm_D': _w((lambda *s: torch.randn(*s, dtype=torch.bfloat16) * 0.2)(D))}
    _A_in = _A_setup()

    def _B_setup():
        B, S, D, F = (1, 2048, 640, 1536)
        Fh = F // 2
        return {'x': _w((lambda *s: torch.randn(*s, dtype=torch.bfloat16) * 0.05)(B, S, D)), 'w_in': _w((lambda *s: torch.randn(*s, dtype=torch.bfloat16) * 0.8)(D, 2 * Fh)), 'w_sp': _w(0.01 * (lambda *s: torch.randn(*s, dtype=torch.bfloat16) * 0.8)(S, S)), 'b_sp': _w(1.0 + 0.01 * (lambda *s: torch.randn(*s, dtype=torch.bfloat16) * 0.1)(S)), 'w_out': _w((lambda *s: torch.randn(*s, dtype=torch.bfloat16) * 0.1)(Fh, D))}
    _B_in = _B_setup()
    return {'A_q': _A_in['q'], 'A_k': _A_in['k'], 'A_v': _A_in['v'], 'A_shift_k': _A_in['shift_k'], 'A_ssm_k': _A_in['ssm_k'], 'A_ssm_D': _A_in['ssm_D'], 'B_x': _B_in['x'], 'B_w_in': _B_in['w_in'], 'B_w_sp': _B_in['w_sp'], 'B_b_sp': _B_in['b_sp'], 'B_w_out': _B_in['w_out']}

def reference(A_q, A_k, A_v, A_shift_k, A_ssm_k, A_ssm_D, B_x, B_w_in, B_w_sp, B_b_sp, B_w_out):

    def _A_ref(q, k, v, shift_k, ssm_k, ssm_D):
        B, S, D = q.shape
        ks = shift_k.shape[-1]
        k_pad = _pad(k, ((0, 0), (ks - 1, 0), (0, 0)))
        k_shift = torch.zeros_like(k)
        for t in range(ks):
            k_shift = k_shift + k_pad[:, t:t + S, :] * shift_k[:, ks - 1 - t][None, None, :]
        kv = k_shift * v
        L = 2 * S
        kv_pad = _pad(kv, ((0, 0), (0, S), (0, 0)))
        kf_pad = _pad(ssm_k, ((0, 0), (0, S)))
        kv_f = (lambda x, axes=(-2, -1): torch.fft.rfft2(x.float(), dim=axes))(kv_pad[:, None, :, :], axes=(1, 2))
        kf_f = (lambda x, axes=(-2, -1): torch.fft.rfft2(x.float(), dim=axes))(kf_pad[:, None, :], axes=(1, 2))
        kf_f = (lambda x, *d: x.permute(*d))(kf_f, 1, 2, 0)
        y_f = kv_f * kf_f[None, :, :, :]
        y = (lambda x, s, axes=(-2, -1): torch.fft.irfft2(x, s=s, dim=axes).to(torch.bfloat16))(y_f, (1, L), axes=(1, 2))[:, 0, :S, :]
        y = y + kv * ssm_D[None, None, :]
        return q * y

    def _B_ref(x, w_in, w_sp, b_sp, w_out):
        B, S, D = x.shape
        F = w_in.shape[-1]
        Fh = F // 2
        z = _gelu(torch.einsum('bsd,df->bsf', x, w_in))
        z1 = z[..., :Fh].clone()
        z2 = _layernorm(z[..., Fh:], axis=-1)
        g = torch.einsum('ts,bsf->btf', w_sp, z2) + b_sp[None, :, None]
        return torch.einsum('bsf,fd->bsd', z1 * g, w_out)
    x = A_q
    xn = _layernorm(x, axis=-1)
    s = _A_ref(xn, A_k, A_v, A_shift_k, A_ssm_k, A_ssm_D)
    g = _silu(_B_ref(xn, B_w_in, B_w_sp, B_b_sp, B_w_out))
    return x + s * g
```

```cpp
#include <cuda_runtime.h>
#include <cuda.h>
#include <cuda_bf16.h>
#include <stdint.h>

template <int N> struct WG;
template <> struct WG<16> {
  static __device__ __forceinline__ void rs(float* d, const uint32_t* a, uint64_t db) {
    asm volatile("{\n.reg .pred p;\nsetp.ne.b32 p, 1, 0;\nwgmma.mma_async.sync.aligned.m64n16k16.f32.bf16.bf16 {"
      "%0, %1, %2, %3, %4, %5, %6, %7"
      "}, {%8, %9, %10, %11}, %12, p, 1, 1, 0;\n}\n"
      :
      "+f"(d[0]), "+f"(d[1]), "+f"(d[2]), "+f"(d[3]), "+f"(d[4]), "+f"(d[5]), "+f"(d[6]), "+f"(d[7])
      : "r"(a[0]), "r"(a[1]), "r"(a[2]), "r"(a[3]), "l"(db));
  }
};
template <> struct WG<32> {
  static __device__ __forceinline__ void rs(float* d, const uint32_t* a, uint64_t db) {
    asm volatile("{\n.reg .pred p;\nsetp.ne.b32 p, 1, 0;\nwgmma.mma_async.sync.aligned.m64n32k16.f32.bf16.bf16 {"
      "%0, %1, %2, %3, %4, %5, %6, %7, %8, %9, %10, %11, %12, %13, %14, %15"
      "}, {%16, %17, %18, %19}, %20, p, 1, 1, 0;\n}\n"
      :
      "+f"(d[0]), "+f"(d[1]), "+f"(d[2]), "+f"(d[3]), "+f"(d[4]), "+f"(d[5]), "+f"(d[6]), "+f"(d[7]),
      "+f"(d[8]), "+f"(d[9]), "+f"(d[10]), "+f"(d[11]), "+f"(d[12]), "+f"(d[13]), "+f"(d[14]), "+f"(d[15])
      : "r"(a[0]), "r"(a[1]), "r"(a[2]), "r"(a[3]), "l"(db));
  }
};
template <> struct WG<48> {
  static __device__ __forceinline__ void rs(float* d, const uint32_t* a, uint64_t db) {
    asm volatile("{\n.reg .pred p;\nsetp.ne.b32 p, 1, 0;\nwgmma.mma_async.sync.aligned.m64n48k16.f32.bf16.bf16 {"
      "%0, %1, %2, %3, %4, %5, %6, %7, %8, %9, %10, %11, %12, %13, %14, %15, "
      "%16, %17, %18, %19, %20, %21, %22, %23"
      "}, {%24, %25, %26, %27}, %28, p, 1, 1, 0;\n}\n"
      :
      "+f"(d[0]), "+f"(d[1]), "+f"(d[2]), "+f"(d[3]), "+f"(d[4]), "+f"(d[5]), "+f"(d[6]), "+f"(d[7]),
      "+f"(d[8]), "+f"(d[9]), "+f"(d[10]), "+f"(d[11]), "+f"(d[12]), "+f"(d[13]), "+f"(d[14]), "+f"(d[15]),
      "+f"(d[16]), "+f"(d[17]), "+f"(d[18]), "+f"(d[19]), "+f"(d[20]), "+f"(d[21]), "+f"(d[22]), "+f"(d[23])
      : "r"(a[0]), "r"(a[1]), "r"(a[2]), "r"(a[3]), "l"(db));
  }
};
template <> struct WG<64> {
  static __device__ __forceinline__ void ss(float* d, uint64_t da, uint64_t db, int sd) {
    asm volatile("{\n.reg .pred p;\nsetp.ne.b32 p, %34, 0;\nwgmma.mma_async.sync.aligned.m64n64k16.f32.bf16.bf16 {"
      "%0, %1, %2, %3, %4, %5, %6, %7, %8, %9, %10, %11, %12, %13, %14, %15, "
      "%16, %17, %18, %19, %20, %21, %22, %23, %24, %25, %26, %27, %28, %29, %30, %31"
      "}, %32, %33, p, 1, 1, 0, 1;\n}\n"
      :
      "+f"(d[0]), "+f"(d[1]), "+f"(d[2]), "+f"(d[3]), "+f"(d[4]), "+f"(d[5]), "+f"(d[6]), "+f"(d[7]),
      "+f"(d[8]), "+f"(d[9]), "+f"(d[10]), "+f"(d[11]), "+f"(d[12]), "+f"(d[13]), "+f"(d[14]), "+f"(d[15]),
      "+f"(d[16]), "+f"(d[17]), "+f"(d[18]), "+f"(d[19]), "+f"(d[20]), "+f"(d[21]), "+f"(d[22]), "+f"(d[23]),
      "+f"(d[24]), "+f"(d[25]), "+f"(d[26]), "+f"(d[27]), "+f"(d[28]), "+f"(d[29]), "+f"(d[30]), "+f"(d[31])
      : "l"(da), "l"(db), "r"(sd));
  }
  static __device__ __forceinline__ void rs(float* d, const uint32_t* a, uint64_t db) {
    asm volatile("{\n.reg .pred p;\nsetp.ne.b32 p, 1, 0;\nwgmma.mma_async.sync.aligned.m64n64k16.f32.bf16.bf16 {"
      "%0, %1, %2, %3, %4, %5, %6, %7, %8, %9, %10, %11, %12, %13, %14, %15, "
      "%16, %17, %18, %19, %20, %21, %22, %23, %24, %25, %26, %27, %28, %29, %30, %31"
      "}, {%32, %33, %34, %35}, %36, p, 1, 1, 0;\n}\n"
      :
      "+f"(d[0]), "+f"(d[1]), "+f"(d[2]), "+f"(d[3]), "+f"(d[4]), "+f"(d[5]), "+f"(d[6]), "+f"(d[7]),
      "+f"(d[8]), "+f"(d[9]), "+f"(d[10]), "+f"(d[11]), "+f"(d[12]), "+f"(d[13]), "+f"(d[14]), "+f"(d[15]),
      "+f"(d[16]), "+f"(d[17]), "+f"(d[18]), "+f"(d[19]), "+f"(d[20]), "+f"(d[21]), "+f"(d[22]), "+f"(d[23]),
      "+f"(d[24]), "+f"(d[25]), "+f"(d[26]), "+f"(d[27]), "+f"(d[28]), "+f"(d[29]), "+f"(d[30]), "+f"(d[31])
      : "r"(a[0]), "r"(a[1]), "r"(a[2]), "r"(a[3]), "l"(db));
  }
};
template <> struct WG<80> {
  static __device__ __forceinline__ void ss(float* d, uint64_t da, uint64_t db, int sd) {
    asm volatile("{\n.reg .pred p;\nsetp.ne.b32 p, %42, 0;\nwgmma.mma_async.sync.aligned.m64n80k16.f32.bf16.bf16 {"
      "%0, %1, %2, %3, %4, %5, %6, %7, %8, %9, %10, %11, %12, %13, %14, %15, "
      "%16, %17, %18, %19, %20, %21, %22, %23, %24, %25, %26, %27, %28, %29, %30, %31, "
      "%32, %33, %34, %35, %36, %37, %38, %39"
      "}, %40, %41, p, 1, 1, 0, 1;\n}\n"
      :
      "+f"(d[0]), "+f"(d[1]), "+f"(d[2]), "+f"(d[3]), "+f"(d[4]), "+f"(d[5]), "+f"(d[6]), "+f"(d[7]),
      "+f"(d[8]), "+f"(d[9]), "+f"(d[10]), "+f"(d[11]), "+f"(d[12]), "+f"(d[13]), "+f"(d[14]), "+f"(d[15]),
      "+f"(d[16]), "+f"(d[17]), "+f"(d[18]), "+f"(d[19]), "+f"(d[20]), "+f"(d[21]), "+f"(d[22]), "+f"(d[23]),
      "+f"(d[24]), "+f"(d[25]), "+f"(d[26]), "+f"(d[27]), "+f"(d[28]), "+f"(d[29]), "+f"(d[30]), "+f"(d[31]),
      "+f"(d[32]), "+f"(d[33]), "+f"(d[34]), "+f"(d[35]), "+f"(d[36]), "+f"(d[37]), "+f"(d[38]), "+f"(d[39])
      : "l"(da), "l"(db), "r"(sd));
  }
  static __device__ __forceinline__ void rs(float* d, const uint32_t* a, uint64_t db) {
    asm volatile("{\n.reg .pred p;\nsetp.ne.b32 p, 1, 0;\nwgmma.mma_async.sync.aligned.m64n80k16.f32.bf16.bf16 {"
      "%0, %1, %2, %3, %4, %5, %6, %7, %8, %9, %10, %11, %12, %13, %14, %15, "
      "%16, %17, %18, %19, %20, %21, %22, %23, %24, %25, %26, %27, %28, %29, %30, %31, "
      "%32, %33, %34, %35, %36, %37, %38, %39"
      "}, {%40, %41, %42, %43}, %44, p, 1, 1, 0;\n}\n"
      :
      "+f"(d[0]), "+f"(d[1]), "+f"(d[2]), "+f"(d[3]), "+f"(d[4]), "+f"(d[5]), "+f"(d[6]), "+f"(d[7]),
      "+f"(d[8]), "+f"(d[9]), "+f"(d[10]), "+f"(d[11]), "+f"(d[12]), "+f"(d[13]), "+f"(d[14]), "+f"(d[15]),
      "+f"(d[16]), "+f"(d[17]), "+f"(d[18]), "+f"(d[19]), "+f"(d[20]), "+f"(d[21]), "+f"(d[22]), "+f"(d[23]),
      "+f"(d[24]), "+f"(d[25]), "+f"(d[26]), "+f"(d[27]), "+f"(d[28]), "+f"(d[29]), "+f"(d[30]), "+f"(d[31]),
      "+f"(d[32]), "+f"(d[33]), "+f"(d[34]), "+f"(d[35]), "+f"(d[36]), "+f"(d[37]), "+f"(d[38]), "+f"(d[39])
      : "r"(a[0]), "r"(a[1]), "r"(a[2]), "r"(a[3]), "l"(db));
  }
};
template <> struct WG<96> {
  static __device__ __forceinline__ void ss(float* d, uint64_t da, uint64_t db, int sd) {
    asm volatile("{\n.reg .pred p;\nsetp.ne.b32 p, %50, 0;\nwgmma.mma_async.sync.aligned.m64n96k16.f32.bf16.bf16 {"
      "%0, %1, %2, %3, %4, %5, %6, %7, %8, %9, %10, %11, %12, %13, %14, %15, "
      "%16, %17, %18, %19, %20, %21, %22, %23, %24, %25, %26, %27, %28, %29, %30, %31, "
      "%32, %33, %34, %35, %36, %37, %38, %39, %40, %41, %42, %43, %44, %45, %46, %47"
      "}, %48, %49, p, 1, 1, 0, 1;\n}\n"
      :
      "+f"(d[0]), "+f"(d[1]), "+f"(d[2]), "+f"(d[3]), "+f"(d[4]), "+f"(d[5]), "+f"(d[6]), "+f"(d[7]),
      "+f"(d[8]), "+f"(d[9]), "+f"(d[10]), "+f"(d[11]), "+f"(d[12]), "+f"(d[13]), "+f"(d[14]), "+f"(d[15]),
      "+f"(d[16]), "+f"(d[17]), "+f"(d[18]), "+f"(d[19]), "+f"(d[20]), "+f"(d[21]), "+f"(d[22]), "+f"(d[23]),
      "+f"(d[24]), "+f"(d[25]), "+f"(d[26]), "+f"(d[27]), "+f"(d[28]), "+f"(d[29]), "+f"(d[30]), "+f"(d[31]),
      "+f"(d[32]), "+f"(d[33]), "+f"(d[34]), "+f"(d[35]), "+f"(d[36]), "+f"(d[37]), "+f"(d[38]), "+f"(d[39]),
      "+f"(d[40]), "+f"(d[41]), "+f"(d[42]), "+f"(d[43]), "+f"(d[44]), "+f"(d[45]), "+f"(d[46]), "+f"(d[47])
      : "l"(da), "l"(db), "r"(sd));
  }
  static __device__ __forceinline__ void rs(float* d, const uint32_t* a, uint64_t db) {
    asm volatile("{\n.reg .pred p;\nsetp.ne.b32 p, 1, 0;\nwgmma.mma_async.sync.aligned.m64n96k16.f32.bf16.bf16 {"
      "%0, %1, %2, %3, %4, %5, %6, %7, %8, %9, %10, %11, %12, %13, %14, %15, "
      "%16, %17, %18, %19, %20, %21, %22, %23, %24, %25, %26, %27, %28, %29, %30, %31, "
      "%32, %33, %34, %35, %36, %37, %38, %39, %40, %41, %42, %43, %44, %45, %46, %47"
      "}, {%48, %49, %50, %51}, %52, p, 1, 1, 0;\n}\n"
      :
      "+f"(d[0]), "+f"(d[1]), "+f"(d[2]), "+f"(d[3]), "+f"(d[4]), "+f"(d[5]), "+f"(d[6]), "+f"(d[7]),
      "+f"(d[8]), "+f"(d[9]), "+f"(d[10]), "+f"(d[11]), "+f"(d[12]), "+f"(d[13]), "+f"(d[14]), "+f"(d[15]),
      "+f"(d[16]), "+f"(d[17]), "+f"(d[18]), "+f"(d[19]), "+f"(d[20]), "+f"(d[21]), "+f"(d[22]), "+f"(d[23]),
      "+f"(d[24]), "+f"(d[25]), "+f"(d[26]), "+f"(d[27]), "+f"(d[28]), "+f"(d[29]), "+f"(d[30]), "+f"(d[31]),
      "+f"(d[32]), "+f"(d[33]), "+f"(d[34]), "+f"(d[35]), "+f"(d[36]), "+f"(d[37]), "+f"(d[38]), "+f"(d[39]),
      "+f"(d[40]), "+f"(d[41]), "+f"(d[42]), "+f"(d[43]), "+f"(d[44]), "+f"(d[45]), "+f"(d[46]), "+f"(d[47])
      : "r"(a[0]), "r"(a[1]), "r"(a[2]), "r"(a[3]), "l"(db));
  }
};
template <> struct WG<112> {
  static __device__ __forceinline__ void rs(float* d, const uint32_t* a, uint64_t db) {
    asm volatile("{\n.reg .pred p;\nsetp.ne.b32 p, 1, 0;\nwgmma.mma_async.sync.aligned.m64n112k16.f32.bf16.bf16 {"
      "%0, %1, %2, %3, %4, %5, %6, %7, %8, %9, %10, %11, %12, %13, %14, %15, "
      "%16, %17, %18, %19, %20, %21, %22, %23, %24, %25, %26, %27, %28, %29, %30, %31, "
      "%32, %33, %34, %35, %36, %37, %38, %39, %40, %41, %42, %43, %44, %45, %46, %47, "
      "%48, %49, %50, %51, %52, %53, %54, %55"
      "}, {%56, %57, %58, %59}, %60, p, 1, 1, 0;\n}\n"
      :
      "+f"(d[0]), "+f"(d[1]), "+f"(d[2]), "+f"(d[3]), "+f"(d[4]), "+f"(d[5]), "+f"(d[6]), "+f"(d[7]),
      "+f"(d[8]), "+f"(d[9]), "+f"(d[10]), "+f"(d[11]), "+f"(d[12]), "+f"(d[13]), "+f"(d[14]), "+f"(d[15]),
      "+f"(d[16]), "+f"(d[17]), "+f"(d[18]), "+f"(d[19]), "+f"(d[20]), "+f"(d[21]), "+f"(d[22]), "+f"(d[23]),
      "+f"(d[24]), "+f"(d[25]), "+f"(d[26]), "+f"(d[27]), "+f"(d[28]), "+f"(d[29]), "+f"(d[30]), "+f"(d[31]),
      "+f"(d[32]), "+f"(d[33]), "+f"(d[34]), "+f"(d[35]), "+f"(d[36]), "+f"(d[37]), "+f"(d[38]), "+f"(d[39]),
      "+f"(d[40]), "+f"(d[41]), "+f"(d[42]), "+f"(d[43]), "+f"(d[44]), "+f"(d[45]), "+f"(d[46]), "+f"(d[47]),
      "+f"(d[48]), "+f"(d[49]), "+f"(d[50]), "+f"(d[51]), "+f"(d[52]), "+f"(d[53]), "+f"(d[54]), "+f"(d[55])
      : "r"(a[0]), "r"(a[1]), "r"(a[2]), "r"(a[3]), "l"(db));
  }
};
template <> struct WG<128> {
  static __device__ __forceinline__ void rs(float* d, const uint32_t* a, uint64_t db) {
    asm volatile("{\n.reg .pred p;\nsetp.ne.b32 p, 1, 0;\nwgmma.mma_async.sync.aligned.m64n128k16.f32.bf16.bf16 {"
      "%0, %1, %2, %3, %4, %5, %6, %7, %8, %9, %10, %11, %12, %13, %14, %15, "
      "%16, %17, %18, %19, %20, %21, %22, %23, %24, %25, %26, %27, %28, %29, %30, %31, "
      "%32, %33, %34, %35, %36, %37, %38, %39, %40, %41, %42, %43, %44, %45, %46, %47, "
      "%48, %49, %50, %51, %52, %53, %54, %55, %56, %57, %58, %59, %60, %61, %62, %63"
      "}, {%64, %65, %66, %67}, %68, p, 1, 1, 0;\n}\n"
      :
      "+f"(d[0]), "+f"(d[1]), "+f"(d[2]), "+f"(d[3]), "+f"(d[4]), "+f"(d[5]), "+f"(d[6]), "+f"(d[7]),
      "+f"(d[8]), "+f"(d[9]), "+f"(d[10]), "+f"(d[11]), "+f"(d[12]), "+f"(d[13]), "+f"(d[14]), "+f"(d[15]),
      "+f"(d[16]), "+f"(d[17]), "+f"(d[18]), "+f"(d[19]), "+f"(d[20]), "+f"(d[21]), "+f"(d[22]), "+f"(d[23]),
      "+f"(d[24]), "+f"(d[25]), "+f"(d[26]), "+f"(d[27]), "+f"(d[28]), "+f"(d[29]), "+f"(d[30]), "+f"(d[31]),
      "+f"(d[32]), "+f"(d[33]), "+f"(d[34]), "+f"(d[35]), "+f"(d[36]), "+f"(d[37]), "+f"(d[38]), "+f"(d[39]),
      "+f"(d[40]), "+f"(d[41]), "+f"(d[42]), "+f"(d[43]), "+f"(d[44]), "+f"(d[45]), "+f"(d[46]), "+f"(d[47]),
      "+f"(d[48]), "+f"(d[49]), "+f"(d[50]), "+f"(d[51]), "+f"(d[52]), "+f"(d[53]), "+f"(d[54]), "+f"(d[55]),
      "+f"(d[56]), "+f"(d[57]), "+f"(d[58]), "+f"(d[59]), "+f"(d[60]), "+f"(d[61]), "+f"(d[62]), "+f"(d[63])
      : "r"(a[0]), "r"(a[1]), "r"(a[2]), "r"(a[3]), "l"(db));
  }
};
template <> struct WG<160> {
  static __device__ __forceinline__ void ss(float* d, uint64_t da, uint64_t db, int sd) {
    asm volatile("{\n.reg .pred p;\nsetp.ne.b32 p, %82, 0;\nwgmma.mma_async.sync.aligned.m64n160k16.f32.bf16.bf16 {"
      "%0, %1, %2, %3, %4, %5, %6, %7, %8, %9, %10, %11, %12, %13, %14, %15, "
      "%16, %17, %18, %19, %20, %21, %22, %23, %24, %25, %26, %27, %28, %29, %30, %31, "
      "%32, %33, %34, %35, %36, %37, %38, %39, %40, %41, %42, %43, %44, %45, %46, %47, "
      "%48, %49, %50, %51, %52, %53, %54, %55, %56, %57, %58, %59, %60, %61, %62, %63, "
      "%64, %65, %66, %67, %68, %69, %70, %71, %72, %73, %74, %75, %76, %77, %78, %79"
      "}, %80, %81, p, 1, 1, 0, 1;\n}\n"
      :
      "+f"(d[0]), "+f"(d[1]), "+f"(d[2]), "+f"(d[3]), "+f"(d[4]), "+f"(d[5]), "+f"(d[6]), "+f"(d[7]),
      "+f"(d[8]), "+f"(d[9]), "+f"(d[10]), "+f"(d[11]), "+f"(d[12]), "+f"(d[13]), "+f"(d[14]), "+f"(d[15]),
      "+f"(d[16]), "+f"(d[17]), "+f"(d[18]), "+f"(d[19]), "+f"(d[20]), "+f"(d[21]), "+f"(d[22]), "+f"(d[23]),
      "+f"(d[24]), "+f"(d[25]), "+f"(d[26]), "+f"(d[27]), "+f"(d[28]), "+f"(d[29]), "+f"(d[30]), "+f"(d[31]),
      "+f"(d[32]), "+f"(d[33]), "+f"(d[34]), "+f"(d[35]), "+f"(d[36]), "+f"(d[37]), "+f"(d[38]), "+f"(d[39]),
      "+f"(d[40]), "+f"(d[41]), "+f"(d[42]), "+f"(d[43]), "+f"(d[44]), "+f"(d[45]), "+f"(d[46]), "+f"(d[47]),
      "+f"(d[48]), "+f"(d[49]), "+f"(d[50]), "+f"(d[51]), "+f"(d[52]), "+f"(d[53]), "+f"(d[54]), "+f"(d[55]),
      "+f"(d[56]), "+f"(d[57]), "+f"(d[58]), "+f"(d[59]), "+f"(d[60]), "+f"(d[61]), "+f"(d[62]), "+f"(d[63]),
      "+f"(d[64]), "+f"(d[65]), "+f"(d[66]), "+f"(d[67]), "+f"(d[68]), "+f"(d[69]), "+f"(d[70]), "+f"(d[71]),
      "+f"(d[72]), "+f"(d[73]), "+f"(d[74]), "+f"(d[75]), "+f"(d[76]), "+f"(d[77]), "+f"(d[78]), "+f"(d[79])
      : "l"(da), "l"(db), "r"(sd));
  }
};
template <> struct WG<192> {
  static __device__ __forceinline__ void ss(float* d, uint64_t da, uint64_t db, int sd) {
    asm volatile("{\n.reg .pred p;\nsetp.ne.b32 p, %98, 0;\nwgmma.mma_async.sync.aligned.m64n192k16.f32.bf16.bf16 {"
      "%0, %1, %2, %3, %4, %5, %6, %7, %8, %9, %10, %11, %12, %13, %14, %15, "
      "%16, %17, %18, %19, %20, %21, %22, %23, %24, %25, %26, %27, %28, %29, %30, %31, "
      "%32, %33, %34, %35, %36, %37, %38, %39, %40, %41, %42, %43, %44, %45, %46, %47, "
      "%48, %49, %50, %51, %52, %53, %54, %55, %56, %57, %58, %59, %60, %61, %62, %63, "
      "%64, %65, %66, %67, %68, %69, %70, %71, %72, %73, %74, %75, %76, %77, %78, %79, "
      "%80, %81, %82, %83, %84, %85, %86, %87, %88, %89, %90, %91, %92, %93, %94, %95"
      "}, %96, %97, p, 1, 1, 0, 1;\n}\n"
      :
      "+f"(d[0]), "+f"(d[1]), "+f"(d[2]), "+f"(d[3]), "+f"(d[4]), "+f"(d[5]), "+f"(d[6]), "+f"(d[7]),
      "+f"(d[8]), "+f"(d[9]), "+f"(d[10]), "+f"(d[11]), "+f"(d[12]), "+f"(d[13]), "+f"(d[14]), "+f"(d[15]),
      "+f"(d[16]), "+f"(d[17]), "+f"(d[18]), "+f"(d[19]), "+f"(d[20]), "+f"(d[21]), "+f"(d[22]), "+f"(d[23]),
      "+f"(d[24]), "+f"(d[25]), "+f"(d[26]), "+f"(d[27]), "+f"(d[28]), "+f"(d[29]), "+f"(d[30]), "+f"(d[31]),
      "+f"(d[32]), "+f"(d[33]), "+f"(d[34]), "+f"(d[35]), "+f"(d[36]), "+f"(d[37]), "+f"(d[38]), "+f"(d[39]),
      "+f"(d[40]), "+f"(d[41]), "+f"(d[42]), "+f"(d[43]), "+f"(d[44]), "+f"(d[45]), "+f"(d[46]), "+f"(d[47]),
      "+f"(d[48]), "+f"(d[49]), "+f"(d[50]), "+f"(d[51]), "+f"(d[52]), "+f"(d[53]), "+f"(d[54]), "+f"(d[55]),
      "+f"(d[56]), "+f"(d[57]), "+f"(d[58]), "+f"(d[59]), "+f"(d[60]), "+f"(d[61]), "+f"(d[62]), "+f"(d[63]),
      "+f"(d[64]), "+f"(d[65]), "+f"(d[66]), "+f"(d[67]), "+f"(d[68]), "+f"(d[69]), "+f"(d[70]), "+f"(d[71]),
      "+f"(d[72]), "+f"(d[73]), "+f"(d[74]), "+f"(d[75]), "+f"(d[76]), "+f"(d[77]), "+f"(d[78]), "+f"(d[79]),
      "+f"(d[80]), "+f"(d[81]), "+f"(d[82]), "+f"(d[83]), "+f"(d[84]), "+f"(d[85]), "+f"(d[86]), "+f"(d[87]),
      "+f"(d[88]), "+f"(d[89]), "+f"(d[90]), "+f"(d[91]), "+f"(d[92]), "+f"(d[93]), "+f"(d[94]), "+f"(d[95])
      : "l"(da), "l"(db), "r"(sd));
  }
};

#define NB3 6
#define KV_T0 2300
#define ST_YIELD 1
#define KV_YIELD 3
#define XC_AT 1
#define HP0 3500
#define HPD 450
#define ROT 0
#define RAMP 1
#define LEAD 2
#define WSP_N 16
#define EARLY 0
#define ZBULK 1
#define HLP 0
#define CPIN 1
#define BPART 1
#define CW0 0
#define CPRE 5
#define WO_AT 3
#define PFT 1
#define TAPS_A 1
#define TAPS_C 1
#define WSP_D 600
#define HOLD 32
#define W1_GATE -1
#define D1 4
#define D2 4
#define D3 4
#define NSLEEP 32
#define G1_LATE 0
#define MAP 1
#define NPRE 1
#define PF0 0
#define PF0_T 0

static_assert(WO_AT == 3, "service order");
static_assert(!BPART || HOLD == 32, "barrier reuse");

namespace {

constexpr int kS = 2048, kD = 640, kF = 1536;
constexpr int NA = 10, NA2 = 9, NB = 5;
constexpr int A_SLOT = 8192, B_SLOT = 24576;
constexpr int OFF_A = 0;
constexpr int OFF_B = OFF_A + NA * A_SLOT;
constexpr int XB_PL = 2112;
constexpr int CV_KE = 4224, CV_KO = CV_KE + 4160;
constexpr int CV_SZ = CV_KO + 4160;
constexpr int OFF_CV = OFF_B + NB * B_SLOT;
constexpr int OFF_CS = OFF_CV + 2 * CV_SZ;
constexpr int OFF_XS = OFF_CS + 1536;
constexpr int OFF_BAR = OFF_XS + 512;
constexpr int BAR_AF = OFF_BAR, BAR_ST = BAR_AF + 8 * NA, BAR_XF = BAR_ST + 16, BAR_KV = BAR_XF + 16;
constexpr int BAR_BF = OFF_BAR + 128, BAR_G2 = BAR_BF + 8 * (NB + 1), BAR_XS = BAR_G2 + 8, BAR_KU = BAR_XS + 8, BAR_ZP = BAR_KU + 40, BAR_HOLD = BAR_ZP + 8, BAR_WO = BAR_HOLD + 8;
constexpr int BAR_AE = OFF_BAR + 256, BAR_BE = BAR_AE + 8 * NA;
constexpr int BAR_YT = BAR_KU + 24;
constexpr int OFF_TAG = OFF_CS - 32;
constexpr int OFF_BIAS = OFF_BAR + 384;
constexpr int SMEM_BYTES = OFF_BIAS + 128;
static_assert(SMEM_BYTES <= 232448, "smem");
constexpr int NB_WGA = 1, NB_WGC = 2, NB_G1 = 3, NB_WO = 4, NB_CD = 5, NB_Z = 6, NB_WGB = 7;

constexpr int CNT_Z = 0, CNT_Y = 1, CNT_KV = 32, CNT_WO = 36;
struct Scratch {
  uint8_t kvx[kD * 4096];
  uint8_t z2[4 * 32 * 24576];
  uint8_t h[32 * 12 * 8192];
  uint8_t wo[4 * 12 * 20480];
  uint8_t y[kD * 4096];
  uint4 xstat[kS];
  uint4 zstat[kS * 4];
  uint2 colsum[kF];
  uint32_t cnt[2 * 32];
  uint32_t hflag[32 * 32];
  uint32_t epoch[136];
};
__device__ __align__(1024) Scratch g_scr;
#define STAMP(i)
#define STAMP2(i)
#define STAMPW(i)

struct Params {
  Scratch* scr;
  int by_smid;
  const __nv_bfloat16 *x, *win, *k, *v, *shift, *ssmk, *ssmD, *wsp, *bsp, *wout;
  __nv_bfloat16* out;
  CUtensorMap tmX, tmW, tmWsp, tmY, tmKV;
};

__device__ __forceinline__ uint64_t mkdesc(uint32_t addr, uint32_t lbo, uint32_t sbo, uint32_t swz) {
  return (uint64_t)((addr & 0x3FFFF) >> 4) | ((uint64_t)(lbo >> 4) << 16) | ((uint64_t)(sbo >> 4) << 32) | ((uint64_t)swz << 62);
}
#define WG_FENCE() asm volatile("wgmma.fence.sync.aligned;" ::: "memory")
#define WG_COMMIT() asm volatile("wgmma.commit_group.sync.aligned;" ::: "memory")
#define WG_WAIT(n) asm volatile("wgmma.wait_group.sync.aligned %0;" ::"n"(n) : "memory")
template <int N> __device__ __forceinline__ void acc_fence(float* d) {
#pragma unroll
  for (int i = 0; i < N; i++) asm volatile("" : "+f"(d[i])::"memory");
}
__device__ __forceinline__ void mbar_init(uint32_t bar, int cnt) { asm volatile("mbarrier.init.shared::cta.b64 [%0], %1;" ::"r"(bar), "r"(cnt) : "memory"); }
__device__ __forceinline__ void mbar_expect(uint32_t bar, uint32_t bytes) { asm volatile("mbarrier.arrive.expect_tx.shared::cta.b64 _, [%0], %1;" ::"r"(bar), "r"(bytes) : "memory"); }
__device__ __forceinline__ void mbar_arrive(uint32_t bar) { asm volatile("mbarrier.arrive.shared::cta.b64 _, [%0];" ::"r"(bar) : "memory"); }
__device__ __forceinline__ void mbar_arrive_if(uint32_t bar, bool c) {
  asm volatile("{\n.reg .pred p;\nsetp.ne.u32 p, %1, 0;\n@p mbarrier.arrive.shared::cta.b64 _, [%0];\n}\n" ::"r"(bar), "r"((uint32_t)c) : "memory");
}
__device__ __forceinline__ bool mbar_try(uint32_t bar, uint32_t parity) {
  uint32_t ok;
  asm volatile("{\n.reg .pred p;\nmbarrier.try_wait.parity.shared::cta.b64 p, [%1], %2;\nselp.u32 %0, 1, 0, p;\n}\n" : "=r"(ok) : "r"(bar), "r"(parity) : "memory");
  return ok;
}
__device__ __forceinline__ bool mbar_test(uint32_t bar, uint32_t parity) {
  uint32_t ok;
  asm volatile("{\n.reg .pred p;\nmbarrier.test_wait.parity.shared::cta.b64 p, [%1], %2;\nselp.u32 %0, 1, 0, p;\n}\n" : "=r"(ok) : "r"(bar), "r"(parity) : "memory");
  return ok;
}
__device__ __forceinline__ void die() { asm volatile("st.volatile.global.u32 [%0], %1;" ::"l"(0ull), "r"(0) : "memory"); }
__device__ __forceinline__ void spin_guard(uint32_t& n) { if (++n == (1u << 22)) die(); }
__device__ __forceinline__ void mbar_wait(uint32_t bar, uint32_t parity) {
  uint32_t t0 = 0;
#pragma unroll 1
  while (!mbar_try(bar, parity)) spin_guard(t0);
}
__device__ __forceinline__ void mbar_wait2(uint32_t b0, uint32_t p0, uint32_t b1, uint32_t p1) {
  uint32_t t0 = 0;
#pragma unroll 1
  while (true) {
    const bool r0 = mbar_try(b0, p0), r1 = mbar_try(b1, p1);
    if (r0 && r1) break;
    spin_guard(t0);
  }
}
__device__ __forceinline__ int tid_now() { int v; asm volatile("mov.u32 %0, %%tid.x;" : "=r"(v)); return v & 127; }
__device__ __forceinline__ bool elect_one() {
  uint32_t p;
  asm volatile("{\n.reg .pred P;\nelect.sync _|P, 0xffffffff;\nselp.u32 %0, 1, 0, P;\n}\n" : "=r"(p));
  return p;
}
__device__ __forceinline__ void bar_sync(int id, int n) { asm volatile("bar.sync %0, %1;" ::"r"(id), "r"(n) : "memory"); }
__device__ __forceinline__ void bar_arrive(int id, int n) { asm volatile("bar.arrive %0, %1;" ::"r"(id), "r"(n) : "memory"); }
__device__ __forceinline__ void fence_async_smem() { asm volatile("fence.proxy.async.shared::cta;" ::: "memory"); }
__device__ __forceinline__ void bulk_g2s(uint32_t dst, const void* src, uint32_t bytes, uint32_t bar) {
  asm volatile("cp.async.bulk.shared::cluster.global.mbarrier::complete_tx::bytes [%0], [%1], %2, [%3];" ::"r"(dst), "l"(src), "r"(bytes), "r"(bar) : "memory");
}
__device__ __forceinline__ void bulk_s2g(void* dst, uint32_t src, uint32_t bytes) {
  asm volatile("cp.async.bulk.global.shared::cta.bulk_group [%0], [%1], %2;" ::"l"(dst), "r"(src), "r"(bytes) : "memory");
}
__device__ __forceinline__ void tma2d(uint32_t dst, const CUtensorMap* m, int c0, int c1, uint32_t bar) {
  asm volatile("cp.async.bulk.tensor.2d.shared::cluster.global.mbarrier::complete_tx::bytes [%0], [%1, {%3, %4}], [%2];" ::"r"(dst), "l"(m), "r"(bar), "r"(c0), "r"(c1) : "memory");
}
__device__ __forceinline__ void tma3d(uint32_t dst, const CUtensorMap* m, int c0, int c1, int c2, uint32_t bar) {
  asm volatile("cp.async.bulk.tensor.3d.shared::cluster.global.mbarrier::complete_tx::bytes [%0], [%1, {%3, %4, %5}], [%2];" ::"r"(dst), "l"(m), "r"(bar), "r"(c0), "r"(c1), "r"(c2) : "memory");
}
__device__ __forceinline__ void st_release(uint32_t* p, uint32_t v) { asm volatile("st.release.gpu.global.u32 [%0], %1;" ::"l"(p), "r"(v) : "memory"); }
__device__ __forceinline__ uint4 ld_ll4(const void* p) {
  uint64_t a, b;
  asm volatile("ld.relaxed.gpu.global.v2.u64 {%0,%1}, [%2];" : "=l"(a), "=l"(b) : "l"(p) : "memory");
  return make_uint4((uint32_t)a, (uint32_t)(a >> 32), (uint32_t)b, (uint32_t)(b >> 32));
}
__device__ __forceinline__ void st_ll4(void* p, uint32_t a, uint32_t b, uint32_t c, uint32_t d) {
  asm volatile("st.relaxed.gpu.global.v2.u64 [%0], {%1,%2};" ::"l"(p), "l"(a | ((uint64_t)b << 32)), "l"(c | ((uint64_t)d << 32)) : "memory");
}
__device__ __forceinline__ void st_ll2(void* p, uint32_t a, uint32_t b) { asm volatile("st.relaxed.gpu.global.u64 [%0], %1;" ::"l"(p), "l"(a | ((uint64_t)b << 32)) : "memory"); }
__device__ __forceinline__ void wgmma_colsum(float* d, uint64_t da, uint64_t db) {
  asm volatile("{\n.reg .pred p;\nsetp.ne.b32 p, 1, 0;\nwgmma.mma_async.sync.aligned.m64n8k16.f32.bf16.bf16 {%0, %1, %2, %3}, %4, %5, p, 1, 1, 1, 0;\n}\n"
               : "+f"(d[0]), "+f"(d[1]), "+f"(d[2]), "+f"(d[3]) : "l"(da), "l"(db));
}
__device__ __forceinline__ void prefetch_l2(const void* p) { asm volatile("prefetch.global.L2 [%0];" ::"l"(p)); }
__device__ __forceinline__ void pace(uint32_t& t, uint32_t dt) {
  t += dt;
  while ((int32_t)((uint32_t)clock() - t) < 0) { if (NSLEEP) __nanosleep(NSLEEP); }
}
__device__ __forceinline__ void red_release(uint32_t* p) { asm volatile("red.release.gpu.global.add.u32 [%0], 1;" ::"l"(p) : "memory"); }
__device__ __forceinline__ uint4 ldg4(const void* p) { uint4 v; asm volatile("ld.global.v4.u32 {%0,%1,%2,%3}, [%4];" : "=r"(v.x), "=r"(v.y), "=r"(v.z), "=r"(v.w) : "l"(p) : "memory"); return v; }
__device__ __forceinline__ uint32_t ldg1(const void* p) { uint32_t v; asm volatile("ld.global.u32 %0, [%1];" : "=r"(v) : "l"(p) : "memory"); return v; }
__device__ __forceinline__ void stg4_if(void* p, uint32_t a, uint32_t b, uint32_t c, uint32_t d, bool on) {
  asm volatile("{\n.reg .pred p;\nsetp.ne.u32 p, %5, 0;\n@p st.global.v4.u32 [%0], {%1,%2,%3,%4};\n}\n" ::"l"(p), "r"(a), "r"(b), "r"(c), "r"(d), "r"((uint32_t)on) : "memory");
}
template <int OFF> __device__ __forceinline__ void stg1_if(void* p, uint32_t a, bool on) {
  asm volatile("{\n.reg .pred p;\nsetp.ne.u32 p, %2, 0;\n@p st.global.u32 [%0+%3], %1;\n}\n" ::"l"(p), "r"(a), "r"((uint32_t)on), "n"(OFF) : "memory");
}
template <int J> struct ZStore {
  static __device__ __forceinline__ void run(void* zp, const uint32_t* z, uint32_t ra, uint32_t na, uint32_t rb, uint32_t nb, bool on);
};
template <int OFF> __device__ __forceinline__ uint32_t lds32(uint32_t a) { uint32_t v; asm volatile("ld.shared.u32 %0, [%1+%2];" : "=r"(v) : "r"(a), "n"(OFF)); return v; }
__device__ __forceinline__ uint4 lds128(uint32_t a) { uint4 v; asm volatile("ld.shared.v4.u32 {%0,%1,%2,%3}, [%4];" : "=r"(v.x), "=r"(v.y), "=r"(v.z), "=r"(v.w) : "r"(a) : "memory"); return v; }
__device__ __forceinline__ float2 lds64f(uint32_t a) { float2 v; asm volatile("ld.shared.v2.f32 {%0,%1}, [%2];" : "=f"(v.x), "=f"(v.y) : "r"(a) : "memory"); return v; }
__device__ __forceinline__ void sts64f(uint32_t a, float x, float y) { asm volatile("st.shared.v2.f32 [%0], {%1,%2};" ::"r"(a), "f"(x), "f"(y) : "memory"); }
__device__ __forceinline__ void sts32(uint32_t a, uint32_t x) { asm volatile("st.shared.u32 [%0], %1;" ::"r"(a), "r"(x) : "memory"); }
__device__ __forceinline__ void sts128(uint32_t a, uint32_t x, uint32_t y, uint32_t z, uint32_t w) { asm volatile("st.shared.v4.u32 [%0], {%1,%2,%3,%4};" ::"r"(a), "r"(x), "r"(y), "r"(z), "r"(w) : "memory"); }
__device__ __forceinline__ void stsm4(uint32_t a, uint32_t r0, uint32_t r1, uint32_t r2, uint32_t r3) {
  asm volatile("stmatrix.sync.aligned.m8n8.x4.shared.b16 [%0], {%1,%2,%3,%4};" ::"r"(a), "r"(r0), "r"(r1), "r"(r2), "r"(r3) : "memory");
}
__device__ __forceinline__ void stsm4t(uint32_t a, uint32_t r0, uint32_t r1, uint32_t r2, uint32_t r3) {
  asm volatile("stmatrix.sync.aligned.m8n8.x4.trans.shared.b16 [%0], {%1,%2,%3,%4};" ::"r"(a), "r"(r0), "r"(r1), "r"(r2), "r"(r3) : "memory");
}
__device__ __forceinline__ void ldsm4t(uint32_t* r, uint32_t a) {
  asm volatile("ldmatrix.sync.aligned.m8n8.x4.trans.shared.b16 {%0,%1,%2,%3}, [%4];" : "=r"(r[0]), "=r"(r[1]), "=r"(r[2]), "=r"(r[3]) : "r"(a) : "memory");
}
__device__ __forceinline__ uint32_t pack2(float lo, float hi) { uint32_t r; asm("cvt.rn.bf16x2.f32 %0, %1, %2;" : "=r"(r) : "f"(hi), "f"(lo)); return r; }
__device__ __forceinline__ float bf_lo(uint32_t u) { return __uint_as_float(u << 16); }
__device__ __forceinline__ float bf_hi(uint32_t u) { return __uint_as_float(u & 0xffff0000u); }
__device__ __forceinline__ float tanh_fast(float x) { float y; asm("tanh.approx.f32 %0, %1;" : "=f"(y) : "f"(x)); return y; }
__device__ __forceinline__ uint32_t hmul2(uint32_t a, uint32_t b) { uint32_t r; asm("mul.rn.bf16x2 %0, %1, %2;" : "=r"(r) : "r"(a), "r"(b)); return r; }
__device__ __forceinline__ uint32_t hfma2(uint32_t a, uint32_t b, uint32_t c) { uint32_t r; asm("fma.rn.bf16x2 %0, %1, %2, %3;" : "=r"(r) : "r"(a), "r"(b), "r"(c)); return r; }
__device__ __forceinline__ uint32_t prmt(uint32_t a, uint32_t b, uint32_t s) { return __byte_perm(a, b, s); }

__device__ __forceinline__ uint32_t ld_relaxed(const uint32_t* p) { uint32_t v; asm volatile("ld.relaxed.gpu.global.u32 %0, [%1];" : "=r"(v) : "l"(p) : "memory"); return v; }
__device__ __forceinline__ void acquire_fence() { asm volatile("fence.acquire.gpu;\nfence.proxy.async.global;" ::: "memory"); }
__device__ __forceinline__ uint32_t load_epoch(const Params& p, int idx, int lane) { return ld_relaxed(&p.scr->epoch[idx + (((lane * lane) & 3) == 2 ? 1 : 0)]); }
__device__ __forceinline__ void poll_flags4(const uint32_t* flags, uint32_t tag, int lane) {
  uint32_t t0 = 0;
#pragma unroll 1
  while (!__all_sync(0xffffffff, ld_relaxed(flags + (lane & 3) * 8) == tag)) spin_guard(t0);
  acquire_fence();
}
__device__ __forceinline__ void poll_counter(const uint32_t* cnt, uint32_t target) {
  uint32_t t0 = 0;
#pragma unroll 1
  while (!__all_sync(0xffffffff, ld_relaxed(cnt) == target)) spin_guard(t0);
  acquire_fence();
}

template <int J> __device__ __forceinline__ void ZStore<J>::run(void* zp, const uint32_t* z, uint32_t ra, uint32_t na, uint32_t rb, uint32_t nb, bool on) {
  if constexpr (J < 24) {
    stg1_if<J * 128>(zp, hfma2(z[2 * J], ra, na), on);
    stg1_if<3072 + J * 128>(zp, hfma2(z[2 * J + 1], rb, nb), on);
    ZStore<J + 1>::run(zp, z, ra, na, rb, nb, on);
  }
}

__device__ __forceinline__ int g3_block(int cb, int it) { return it < 3 ? cb * 3 + it : (it - 3 < cb * 3 ? it - 3 : it); }
__device__ __forceinline__ void reset_sector(uint32_t* f) { st_ll4(f, 0, 0, 0, 0); st_ll4(f + 4, 0, 0, 0, 0); }

#define GDW_OK true
template <int N, bool A_SWZ, int B_MODE, int DEPTH>
__device__ __forceinline__ void gemm_loop(float* d, uint32_t sb, int nkb, int sa, int pa, int b0, uint32_t boff, int relA, int relB, int tid, bool arrive_g1) {
  constexpr uint32_t A_STEP = A_SWZ ? 2 : 128;
  constexpr uint32_t B_STEP = B_MODE == 0 ? 128 : (B_MODE == 1 ? 384 : 320);
  const uint64_t da0 = A_SWZ ? mkdesc(sb + OFF_A, 16, 1024, 1) : mkdesc(sb + OFF_A, 1024, 128, 0);
  const uint64_t db0 = B_MODE == 0 ? mkdesc(sb + OFF_B + boff, 8192, 1024, 1) : mkdesc(sb + OFF_B + boff, B_MODE == 1 ? 3072 : 2560, 128, 0);
  constexpr int MODA = B_MODE == 0 ? NA : NA2;
  constexpr int MODB = B_MODE == 2 ? NB3 : NB;
  int sbk = b0 % MODB, pb = (b0 / MODB) & 1;
  auto boffs = [](int s_) { return B_MODE == 2 && NB3 == 6 ? (s_ == 5 ? 0 : s_ + 1) * (20480 >> 4) : s_ * (B_SLOT >> 4); };
  uint32_t rel = 0;
  uint64_t da = da0 + sa * (A_SLOT >> 4), db = db0 + boffs(sbk);
  const bool doR = tid < 2 ? tid < relA : tid - 2 < relB;
  mbar_wait2(sb + BAR_AF + 8 * sa, pa, sb + BAR_BF + 8 * sbk, pb);
#pragma unroll 1
  for (int it = 0; it < nkb; it++) {
    WG_FENCE();
    WG<N>::ss(d, da, db, 1);
    const uint32_t prel = rel;
    rel = sb + BAR_AE + 8 * (tid < 2 ? sa : sbk + NA);
    if (++sa == MODA) { sa = 0; pa ^= 1; }
    if (++sbk == MODB) { sbk = 0; pb ^= 1; }
    if (DEPTH == 1) { WG_COMMIT(); WG_WAIT(1); }
    WG<N>::ss(d, da + A_STEP, db + B_STEP, 1);
    WG_COMMIT();
    WG_WAIT(1);
    if (EARLY == 1) mbar_arrive_if(prel, doR && it != 0);
    WG<N>::ss(d, da + 2 * A_STEP, db + 2 * B_STEP, 1);
    if (DEPTH == 1) WG_COMMIT();
    if (EARLY != 1) mbar_arrive_if(prel, doR && it != 0);
    const bool r0 = mbar_test(sb + BAR_AF + 8 * sa, pa), r1 = mbar_test(sb + BAR_BF + 8 * sbk, pb);
    const uint64_t da3 = da + 3 * A_STEP, db3 = db + 3 * B_STEP;
    da = da0 + sa * (A_SLOT >> 4); db = db0 + boffs(sbk);
    if (DEPTH == 1) WG_WAIT(1);
    WG<N>::ss(d, da3, db3, 1);
    WG_COMMIT();
    if (it + 1 < nkb) {
      if (!(r0 && r1)) {
        mbar_wait2(sb + BAR_AF + 8 * sa, pa, sb + BAR_BF + 8 * sbk, pb);
      }
    } else if (arrive_g1) {
      bar_arrive(NB_G1, 256);
    }
    if (DEPTH == 2) WG_WAIT(1);
  }
  WG_WAIT(0);
  acc_fence<N / 2>(d);
  mbar_arrive_if(rel, doR);
}

__device__ __forceinline__ void gelu_tile(const float* d, uint32_t* z, float* st, uint32_t cs_addr, float2 s0, float2 s1) {
  const float kA = 0.7978845608028654f, kB = 0.7978845608028654f * 0.044715f;
  const float c1a = kA * s0.y, c3a = kB * s0.y * s0.y * s0.y, ma = -s0.x;
  const float c1b = kA * s1.y, c3b = kB * s1.y * s1.y * s1.y, mb = -s1.x;
  float acc[8];
#pragma unroll
  for (int i = 0; i < 8; i++) acc[i] = 0.f;
#pragma unroll
  for (int j = 0; j < 24; j++) {
    const float2 cs = lds64f(cs_addr + j * 32);
    float r[4];
#pragma unroll
    for (int e = 0; e < 4; e++) {
      const float c = (e & 1) ? cs.y : cs.x;
      const float v = fmaf(e < 2 ? ma : mb, c, d[4 * j + e]);
      const float a = v * fmaf(v * v, e < 2 ? c3a : c3b, e < 2 ? c1a : c1b);
      r[e] = fmaf(v, tanh_fast(a), v);
      acc[e] += r[e];
      acc[4 + e] = fmaf(r[e], r[e], acc[4 + e]);
    }
    z[2 * j] = pack2(r[0], r[1]);
    z[2 * j + 1] = pack2(r[2], r[3]);
  }
  st[0] = acc[0] + acc[1]; st[1] = acc[4] + acc[5]; st[2] = acc[2] + acc[3]; st[3] = acc[6] + acc[7];
}

template <int Q> __device__ __forceinline__ void conv_load(uint32_t* a, uint32_t ab) {
  a[0] = lds32<512 * Q>(ab);       a[1] = lds32<512 * Q + 256>(ab);  a[2] = lds32<512 * Q + 16>(ab);   a[3] = lds32<512 * Q + 272>(ab);
  a[4] = lds32<512 * Q + 32>(ab);  a[5] = lds32<512 * Q + 288>(ab);  a[6] = lds32<512 * Q + 48>(ab);   a[7] = lds32<512 * Q + 304>(ab);
  a[8] = lds32<512 * Q + 64>(ab);  a[9] = lds32<512 * Q + 320>(ab);  a[10] = lds32<512 * Q + 80>(ab);  a[11] = lds32<512 * Q + 336>(ab);
  a[12] = lds32<512 * Q + 96>(ab); a[13] = lds32<512 * Q + 352>(ab); a[14] = lds32<512 * Q + 112>(ab); a[15] = lds32<512 * Q + 368>(ab);
}
template <int Q, int L> __device__ __forceinline__ void conv_step(float* d, uint32_t (*a)[16], uint32_t ab, uint64_t db) {
  WG_FENCE();
#pragma unroll
  for (int s = 0; s < 4; s++) WG<128 - 16 * Q>::rs(d, a[Q] + 4 * s, db + s + 16 * Q);
  WG_COMMIT();
  if (CPIN) WG_WAIT(1);
  if (L >= 0) conv_load<(L >= 0 ? L : 0)>(a[L >= 0 ? L : 0], ab);
  if (CW0 || Q == 0) WG_WAIT(0);
}

__device__ __forceinline__ void final_load_x(uint32_t (*xw)[10], uint32_t xt, int col0, int w, int lane) {
  const int g = lane >> 2, t = lane & 3;
  const int c0 = (col0 >> 3) + t, c1 = c0 + 4, c2 = (col0 >> 3) + 8 + (t >> 1);
  const uint32_t r0 = xt + (w * 16 + g) * 128;
#pragma unroll
  for (int r = 0; r < 2; r++) {
    const uint4 u = lds128(r0 + r * 1024 + (c0 >> 3) * A_SLOT + (((c0 ^ g) & 7) << 4)), v = lds128(r0 + r * 1024 + (c1 >> 3) * A_SLOT + (((c1 ^ g) & 7) << 4));
    const float2 z = lds64f(r0 + r * 1024 + (c2 >> 3) * A_SLOT + (((c2 ^ g) & 7) << 4) + (t & 1) * 8);
    xw[r][0] = u.x; xw[r][1] = u.y; xw[r][2] = u.z; xw[r][3] = u.w;
    xw[r][4] = v.x; xw[r][5] = v.y; xw[r][6] = v.z; xw[r][7] = v.w;
    xw[r][8] = __float_as_uint(z.x); xw[r][9] = __float_as_uint(z.y);
  }
}
__device__ __forceinline__ void final_gate(float* d, const uint32_t (*xw)[10], float2 s0, float2 s1) {
  const float ra = s0.y, na = -s0.x * s0.y, rb_ = s1.y, nb = -s1.x * s1.y, ca = 0.25f * ra, cb = 0.25f * rb_;
#pragma unroll
  for (int i = 0; i < 40; i++) {
    const int r = (i >> 1) & 1;
    const float xf = (i & 1) ? bf_hi(xw[r][i >> 2]) : bf_lo(xw[r][i >> 2]);
    const float h = d[i] * (r ? cb : ca);
    d[i] = fmaf(h, tanh_fast(h), h) * fmaf(xf, r ? rb_ : ra, r ? nb : na);
  }
}
__device__ __forceinline__ void final_out(const float* d, const uint32_t (*xw)[10], uint32_t yt, __nv_bfloat16* o0, int w, int lane) {
  const int r8 = lane & 7, mi = lane >> 3, t = lane & 3;
  const uint32_t ya = yt + ((mi >> 1) * 8 + r8) * 128 + (((2 * w + (mi & 1)) ^ r8) << 4);
  uint32_t o[2][10];
#pragma unroll
  for (int j = 0; j < 10; j += 2) {
    uint32_t y[4];
    ldsm4t(y, ya + j * 1024);
#pragma unroll
    for (int e = 0; e < 4; e++) {
      const uint32_t xv = xw[e & 1][j + (e >> 1)];
      o[e & 1][j + (e >> 1)] = pack2(fmaf(d[4 * j + 2 * e], bf_lo(y[e]), bf_lo(xv)), fmaf(d[4 * j + 2 * e + 1], bf_hi(y[e]), bf_hi(xv)));
    }
#pragma unroll
    for (int r = 0; r < 2; r++) {
      __nv_bfloat16* q = o0 + r * 8 * kD;
      if (j == 2) stg4_if(q + t * 8, o[r][0], o[r][1], o[r][2], o[r][3], true);
      if (j == 6) stg4_if(q + 32 + t * 8, o[r][4], o[r][5], o[r][6], o[r][7], true);
      if (j == 8) asm volatile("st.global.v2.u32 [%0], {%1,%2};" ::"l"(q + 64 + t * 4), "r"(o[r][8]), "r"(o[r][9]) : "memory");
    }
  }
}

struct Taps { uint4 r0, r1; uint32_t n0, n1, dd; };
__device__ __forceinline__ void load_taps(Taps& k, const Params& p, int ch, int tid) {
  const uint4* kp = (const uint4*)(p.ssmk + (size_t)ch * kS);
  k.r0 = ldg4(kp + tid); k.r1 = ldg4(kp + 128 + tid);
  k.n0 = ldg1(kp + tid + 1); k.n1 = tid < 127 ? ldg1(kp + 129 + tid) : 0u;
  k.dd = __bfloat16_as_ushort(p.ssmD[ch]);
}
__device__ __forceinline__ void load_convx(const Params& p, uint32_t cv, uint32_t bar, int ch) {
  mbar_expect(bar, 4096);
  bulk_g2s(cv, p.scr->kvx + (size_t)ch * 4096, 2048, bar);
  bulk_g2s(cv + XB_PL, p.scr->kvx + (size_t)ch * 4096 + 2048, 2048, bar);
}
#define CW 3
#define CSTAMP(j)
__device__ __forceinline__ void zero_pads(uint32_t cv, int lane) {
  if (lane < 8) sts128(cv + (lane >> 2) * XB_PL + 2048 + (lane & 3) * 16, 0, 0, 0, 0);
  else if (lane < 12) sts128(cv + ((lane & 2) ? CV_KO : CV_KE) + (lane & 1) * 16, 0, 0, 0, 0);
  fence_async_smem();
  __syncwarp();
}
__device__ __forceinline__ int y_row(int c) {
  const int cc = c % 80;
  return c - cc + (cc & 1) + (cc < 64 ? (cc & 32) + ((cc >> 1) & 3) * 8 + ((cc >> 3) & 3) * 2 : 64 + ((cc >> 1) & 1) * 8 + ((cc >> 2) & 3) * 2);
}
__device__ __forceinline__ void conv_service(const Params& p, uint32_t sb, int h, int ch, bool more) {
  bar_sync(NB_WGA + 8 + h, 160);
  if (more && elect_one()) load_convx(p, sb + OFF_CV + (1 - h) * CV_SZ, sb + BAR_XF + 8 * h, ch + 128);
  uint8_t* dst = p.scr->y + (size_t)y_row(ch) * 4096;
  bar_sync(NB_WGA + 8 + h, 160);
  if (elect_one()) {
    bulk_s2g(dst, sb + OFF_A + 9 * A_SLOT + h * 4096, 4096);
    asm volatile("cp.async.bulk.commit_group;\ncp.async.bulk.wait_group 0;" ::: "memory");
  }
  __syncwarp();
}
__device__ __forceinline__ void conv_worker(const Params& p, Taps& k, uint32_t cv, uint32_t yb0,
                                            uint32_t xbar, int nbar, int ch0, int n, uint32_t holdbar, int w, int lane,
                                            int tid, int st0, int rb, int cb) {
  const int g = lane >> 2, t = lane & 3, w0 = w & 1, w1 = w >> 1;
  const uint32_t ab = cv + ((g & 1) ? CV_KE : CV_KO) + 32 + 2 * (64 * w0 + 8 * w1 + ((g - 15) & ~1) + 2 * t);
  const uint32_t scA = cv + (w1 ? CV_KO : CV_KE) + 32, scB = scA + 2048;
  const int dl = (t >> 1) ^ 1, col = lane & 7, mi = lane >> 3;
  if (n == 2) mbar_wait(xbar, 0);
  STAMPW(st0 + 3);
#pragma unroll 1
  for (int i = 0; i < n; i++) {
    if (tid == 0) {
      k.r0.x = (k.r0.x & 0xffff0000u) | (pack2(bf_lo(k.r0.x) + bf_lo(k.dd), 0.f) & 0xffffu);
      sts32(cv + CV_KO + 28, k.r0.x << 16);
    }
    sts128(cv + CV_KE + 32 + tid * 16, k.r0.x, k.r0.y, k.r0.z, k.r0.w);
    sts128(cv + CV_KO + 32 + tid * 16, prmt(k.r0.x, k.r0.y, 0x5432), prmt(k.r0.y, k.r0.z, 0x5432), prmt(k.r0.z, k.r0.w, 0x5432), prmt(k.r0.w, k.n0, 0x5432));
    sts128(cv + CV_KE + 2080 + tid * 16, k.r1.x, k.r1.y, k.r1.z, k.r1.w);
    sts128(cv + CV_KO + 2080 + tid * 16, prmt(k.r1.x, k.r1.y, 0x5432), prmt(k.r1.y, k.r1.z, 0x5432), prmt(k.r1.z, k.r1.w, 0x5432), prmt(k.r1.w, k.n1, 0x5432));
    if (i + 1 < n) load_taps(k, p, ch0 + (i + 1) * 128, tid);
    bar_sync(nbar, 128);
    CSTAMP(0);
    const uint64_t db = mkdesc(cv + (i & 0x1000), XB_PL, 128, 0);
    float d[64];
    uint32_t a[8][16];
    conv_load<7>(a[7], ab);
    if (CPRE > 1) conv_load<6>(a[6], ab);
    if (CPRE > 2) conv_load<5>(a[5], ab);
    if (CPRE > 3) conv_load<4>(a[4], ab);
#pragma unroll
    for (int j = 0; j < 64; j++) d[j] = 0.f;
    mbar_wait(xbar, i & 1);
    if (HOLD >= 0 && i + 1 == n) mbar_wait(holdbar, 0);
    CSTAMP(1);
    if (CPRE == 1) {
      conv_step<7, 6>(d, a, ab, db); conv_step<6, 5>(d, a, ab, db); conv_step<5, 4>(d, a, ab, db); conv_step<4, 3>(d, a, ab, db);
      conv_step<3, 2>(d, a, ab, db); conv_step<2, 1>(d, a, ab, db); conv_step<1, 0>(d, a, ab, db); conv_step<0, -1>(d, a, ab, db);
    } else if (CPRE == 3) {
      conv_step<7, -1>(d, a, ab, db); conv_step<6, 4>(d, a, ab, db); conv_step<5, 3>(d, a, ab, db); conv_step<4, 2>(d, a, ab, db);
      conv_step<3, 1>(d, a, ab, db); conv_step<2, 0>(d, a, ab, db); conv_step<1, -1>(d, a, ab, db); conv_step<0, -1>(d, a, ab, db);
    } else if (CPRE == 4) {
      conv_step<7, -1>(d, a, ab, db); conv_step<6, -1>(d, a, ab, db); conv_step<5, 3>(d, a, ab, db); conv_step<4, 2>(d, a, ab, db);
      conv_step<3, 1>(d, a, ab, db); conv_step<2, 0>(d, a, ab, db); conv_step<1, -1>(d, a, ab, db); conv_step<0, -1>(d, a, ab, db);
    } else {
      conv_step<7, -1>(d, a, ab, db); conv_step<6, -1>(d, a, ab, db); conv_step<5, -1>(d, a, ab, db); conv_step<4, 3>(d, a, ab, db);
      conv_step<3, 2>(d, a, ab, db); conv_step<2, 1>(d, a, ab, db); conv_step<1, 0>(d, a, ab, db); conv_step<0, -1>(d, a, ab, db);
    }
    acc_fence<64>(d);
    CSTAMP(2);
    bar_sync(nbar + 8, 160);
    float E[16][2];
#pragma unroll
    for (int j = 0; j < 15; j++) { E[j][0] = d[4 * j] + d[4 * j + 6]; E[j][1] = d[4 * j + 1] + d[4 * j + 7]; }
    E[15][0] = d[60]; E[15][1] = d[61];
    if (w0 == 0) {
#pragma unroll
      for (int j = 8; j < 16; j++) sts64f(scA + (j - 8) * 256 + lane * 8, E[j][0], E[j][1]);
    } else {
      const uint32_t a = scB - dl * 256 + (lane ^ 2) * 8;
#pragma unroll
      for (int j = 1; j < 8; j++) sts64f(a + j * 256, E[j][0], E[j][1]);
      sts64f(scB + (dl ? 7 * 256 : 0) + (lane ^ 2) * 8, dl ? E[8][0] : E[0][0], dl ? E[8][1] : E[0][1]);
    }
    bar_sync(nbar, 128);
    CSTAMP(3);
    uint32_t pk[8];
    if (w0 == 0) {
#pragma unroll
      for (int j = 0; j < 8; j++) { const float2 v = lds64f(scB + j * 256 + lane * 8); pk[j] = pack2(E[j][0] + v.x, E[j][1] + v.y); }
      const uint32_t ya = yb0 + 32 * (127 - (8 * mi + col)) + 16 * w1;
      stsm4t(ya, pk[0], pk[1], pk[2], pk[3]);
      stsm4t(ya - 1024, pk[4], pk[5], pk[6], pk[7]);
    } else {
      const uint32_t a0 = scA - dl * 256 + (lane ^ 2) * 8;
#pragma unroll
      for (int j = 9; j < 16; j++) { const float2 v = lds64f(a0 + (j - 8) * 256); pk[j - 8] = pack2(E[j][0] + v.x, E[j][1] + v.y); }
      const float2 v = lds64f(scA + (dl ? 7 * 256 : 0) + (lane ^ 2) * 8);
      pk[0] = pack2((dl ? 0.f : E[8][0]) + v.x, (dl ? 0.f : E[8][1]) + v.y);
      const uint32_t yb = yb0 + 32 * (127 - (92 + 8 * mi + col)) + 16 * w1;
      const uint32_t ya = (mi == 0 && col < 4) ? yb0 + 32 * (3 - col) + 16 * w1 : yb + 1024;
      stsm4t(ya, pk[0], pk[1], pk[2], pk[3]);
      stsm4t(yb, pk[4], pk[5], pk[6], pk[7]);
    }
    CSTAMP(4);
    fence_async_smem();
    bar_sync(nbar + 8, 160);
    CSTAMP(5);
    STAMPW(st0 + i);
    if (n == 2 && i == 0) {
      const int u = (tid >> 3) % 5, kg = rb * 3 + (tid < 120 ? (tid >> 3) / 5 : 0), c = u < 4 ? (u >> 1) * 10 + (u & 1) * 4 : 8, o2 = u < 4 ? 2 : 10;
      const uint4* wp = (const uint4*)(p.wout + (size_t)(kg * 8 + (tid & 7)) * kD + cb * 160) + c;
      const uint4 w0 = ldg4(wp), w1 = ldg4(wp + 1), w2 = ldg4(wp + o2), w3 = ldg4(wp + o2 + 1);
      uint8_t* dst = p.scr->wo + (size_t)cb * (12 * 20480) + kg * 2560 + c * 128 + (tid & 7) * 16;
      const bool f = u < 4, on = tid < 120;
      stg4_if(dst, w0.x, f ? w1.x : w0.z, f ? w2.x : w1.x, f ? w3.x : w1.z, on);
      stg4_if(dst + 128, w0.y, f ? w1.y : w0.w, f ? w2.y : w1.y, f ? w3.y : w1.w, on);
      stg4_if(dst + o2 * 128, f ? w0.z : w2.x, f ? w1.z : w2.z, f ? w2.z : w3.x, w3.z, on);
      stg4_if(dst + o2 * 128 + 128, f ? w0.w : w2.y, f ? w1.w : w2.w, f ? w2.w : w3.y, w3.w, on);
      bar_arrive(NB_WO, 160);
    }
  }
}

struct KvRegs { uint32_t k[11], v[8]; uint4 sh; };
__device__ __forceinline__ void kv_load(KvRegs& q, const __nv_bfloat16* kp, const __nv_bfloat16* vp, const __nv_bfloat16* sp, bool halo) {
#pragma unroll
  for (int i = 0; i < 11; i++) q.k[i] = (i >= 3 || halo) ? ldg1(kp + i * kD) : 0u;
#pragma unroll
  for (int i = 0; i < 8; i++) q.v[i] = ldg1(vp + i * kD);
  q.sh = ldg4(sp);
}
__device__ __forceinline__ void kv_unit(const KvRegs& q, uint32_t oa) {
  const uint32_t w0 = prmt(q.sh.x, q.sh.z, 0x5410), w1 = prmt(q.sh.x, q.sh.z, 0x7632), w2 = prmt(q.sh.y, q.sh.w, 0x5410), w3 = prmt(q.sh.y, q.sh.w, 0x7632);
  uint32_t r[8];
#pragma unroll
  for (int i = 0; i < 8; i++) r[i] = hmul2(hfma2(q.k[i + 3], w0, hfma2(q.k[i + 2], w1, hfma2(q.k[i + 1], w2, hmul2(q.k[i], w3)))), q.v[i]);
  sts128(oa, prmt(r[7], r[6], 0x5410), prmt(r[5], r[4], 0x5410), prmt(r[3], r[2], 0x5410), prmt(r[1], r[0], 0x5410));
  sts128(oa + 2048, prmt(r[7], r[6], 0x7632), prmt(r[5], r[4], 0x7632), prmt(r[3], r[2], 0x7632), prmt(r[1], r[0], 0x7632));
}

__device__ __forceinline__ void helper_cta(const Params& p, uint32_t sb, int cb, int warp, int lane) {
  constexpr int NS = 9, ONES = NS * B_SLOT, BF = ONES + 256, BE = BF + 8 * NS;
  if (warp < NS && elect_one()) {
    mbar_init(sb + BF + 8 * warp, 1); mbar_init(sb + BE + 8 * warp, 1);
    fence_async_smem();
    if (warp == 0) { mbar_expect(sb + BF, B_SLOT); tma3d(sb, &p.tmW, 0, 0, 12 + cb * 3, sb + BF); }
  }
  if (warp == 15) { sts32(sb + ONES + lane * 4, 0x3f803f80u); sts32(sb + ONES + 128 + lane * 4, 0x3f803f80u); fence_async_smem(); }
  __syncthreads();
  if (warp == 4) {
    int s = 1, ph = 1;
    uint32_t tp = clock() + HP0;
#pragma unroll 1
    for (int it = 1; it < 20; it++) {
      if (HPD && it >= 10) pace(tp, HPD);
      mbar_wait(sb + BE + 8 * s, ph);
      if (elect_one()) { mbar_expect(sb + BF + 8 * s, B_SLOT); tma3d(sb + s * B_SLOT, &p.tmW, 0, (it < 10 ? it : it - 10) * 64, (it < 10 ? 12 : 0) + cb * 3, sb + BF + 8 * s); }
      if (++s == NS) { s = 0; ph ^= 1; }
    }
  } else if (warp < 4) {
    const uint32_t tag = load_epoch(p, 128 + cb, lane) + 1;
    const uint64_t db = mkdesc(sb + ONES, 128, 128, 0);
    uint2* dst = p.scr->colsum + cb * 192 + warp * 16 + (lane >> 2);
    if ((lane & 3) == 0) {
#pragma unroll 1
      for (int j = 0; j < 12; j++) st_ll2(dst + (j < 6 ? 768 : 0) + ((j % 6) >> 1) * 64 + (j & 1) * 8, 0, 0);
    }
    int s = 0, ph = 0;
#pragma unroll 1
    for (int part = 0; part < 2; part++) {
      float d[12];
#pragma unroll
      for (int i = 0; i < 12; i++) d[i] = 0.f;
#pragma unroll 1
      for (int it = 0; it < 10; it++) {
        mbar_wait(sb + BF + 8 * s, ph);
        const uint64_t da = mkdesc(sb + s * B_SLOT, 8192, 1024, 1);
        WG_FENCE();
#pragma unroll
        for (int j = 0; j < 12; j++) wgmma_colsum(d + 4 * (j % 3), da + (j % 3) * 512 + (j / 3) * 128, db);
        WG_COMMIT();
        WG_WAIT(1);
        mbar_arrive_if(sb + BE + 8 * (s == 0 ? NS - 1 : s - 1), threadIdx.x == 0 && (it | part) != 0);
        if (++s == NS) { s = 0; ph ^= 1; }
      }
      WG_WAIT(0);
      acc_fence<12>(d);
      if ((lane & 3) == 0) {
#pragma unroll
        for (int j = 0; j < 6; j++) st_ll2(dst + (part ? 0 : 768) + (j >> 1) * 64 + (j & 1) * 8, __float_as_uint(d[2 * j]), tag);
      }
      STAMPW(1 + part);
    }
    if (threadIdx.x == 0) *(volatile uint32_t*)&p.scr->epoch[128 + cb] = tag;
  }
}

__global__ void __launch_bounds__(512, 1) fused_kernel(const __grid_constant__ Params p) {
  extern __shared__ __align__(1024) uint8_t smem[];
  const int warp = __shfl_sync(0xffffffff, (int)(threadIdx.x >> 5), 0);
  const int lane = threadIdx.x & 31, tid = threadIdx.x & 127;
  const uint32_t sb = __shfl_sync(0xffffffff, (uint32_t)__cvta_generic_to_shared(smem), 0);
  const uint32_t tstart = clock();
  if (elect_one()) {
    if (warp < 5) asm volatile("prefetch.tensormap [%0];" ::"l"(&p.tmX + warp) : "memory");
    mbar_init(sb + OFF_BAR + 8 * warp, 1); mbar_init(sb + OFF_BAR + 128 + 8 * warp, 1); mbar_init(sb + OFF_BAR + 256 + 8 * warp, 2);
    asm volatile("fence.mbarrier_init.release.cluster;" ::: "memory");
  }
  int b = blockIdx.x;
  if (p.by_smid) asm volatile("mov.u32 %0, %%smid;" : "=r"(b));
  b = __shfl_sync(0xffffffff, b, 0);
  const int tp = b >> 1, t7 = (tp - 32) / 7;
  const int lin = tp < 32 ? ((tp & 7) ? (tp & 7) * 16 : 8) + (tp >> 3) * 2 + (b & 1)
                          : (tp < 60 ? (tp - 31 - t7 * 7) * 16 + 8 + t7 * 2 + (b & 1) : (tp < 62 ? -1 : b - 124));
  const int hcb = b & 3;
  if (lin < 0) { helper_cta(p, sb, hcb, warp, lane); return; }
  const int cb = ((lin >> 4) & 1) * 2 + ((lin >> 1) & 1), rb = (lin >> 5) * 8 + ((lin >> 2) & 3) * 2 + (lin & 1);
  const int rot = ROT ? (MAP == 1 ? (rb >> 3) * 8 : (rb >> 2) * 4) : 0;
  const int chb = (cb >> 1) * 320 + rb * 2 + (cb & 1);
  if (elect_one()) {
    if (warp < NPRE) {
      mbar_expect(sb + BAR_AF + 8 * warp, A_SLOT);
      tma2d(sb + OFF_A + warp * A_SLOT, &p.tmX, warp * 64, rb * 64, sb + BAR_AF + 8 * warp);
      mbar_expect(sb + BAR_BF + 8 * warp, B_SLOT);
      tma3d(sb + OFF_B + warp * B_SLOT, &p.tmW, 0, warp * 64, 12 + cb * 3, sb + BAR_BF + 8 * warp);
    }
  }
  if (PF0 && warp >= 8 && warp < 12) {
    if (PF0_T) { uint32_t tp = tstart; pace(tp, PF0_T); }
    const char* xq = (const char*)p.x + (size_t)(rb * 64 + cb * 16) * (kD * 2) + tid * 128;
    if (PF0 & 1) { prefetch_l2(xq); if (tid < 32) prefetch_l2(xq + 16384); }
    const char* wq = (const char*)p.win + (size_t)(lin * 5 + tid / 24) * (kF * 2) + ((tid % 24 + 12) % 24) * 128;
    if (tid < 120 && ((PF0 & 4) || ((PF0 & 2) && tid % 24 < 12))) prefetch_l2(wq);
  }
  if (warp == 1) STAMP(31);
  if (sb & 1023) die();
  __syncthreads();

  if (warp >= 12) {
    asm volatile("setmaxnreg.dec.sync.aligned.u32 32;");
    const uint32_t epoch = load_epoch(p, lin, lane);
    if (warp == 12) {
#pragma unroll 1
      for (int i = NPRE; i < NA; i++) {
        if (elect_one()) {
          mbar_expect(sb + BAR_AF + 8 * i, A_SLOT);
          tma2d(sb + OFF_A + i * A_SLOT, &p.tmX, i * 64, rb * 64, sb + BAR_AF + 8 * i);
          if (i < NB) { mbar_expect(sb + BAR_BF + 8 * i, B_SLOT); tma3d(sb + OFF_B + i * B_SLOT, &p.tmW, 0, i * 64, 12 + cb * 3, sb + BAR_BF + 8 * i); }
        }
      }
      if (elect_one()) reset_sector(&p.scr->hflag[rb * 32 + cb * 8]);
      STAMP(32);
      uint32_t kvt;
      {
        const int tb = rb * 2 + (cb & 1);
        kvt = __shfl_sync(0xffffffff, (ld_relaxed(p.scr->cnt + CNT_KV + (cb >> 1)) & ~63u) + 64, 0);
        {
          uint32_t tp = tstart;
          pace(tp, KV_T0);
          mbar_arrive_if(sb + BAR_KV + 8, lane == 0);
        }
        if (ST_YIELD) mbar_wait2(sb + BAR_XS, 0, sb + BAR_ST, 0);
#pragma unroll 1
        for (int u = 0; u < 5; u++) {
          mbar_wait(sb + BAR_KU + 8 * u, 0);
          fence_async_smem();
          if (elect_one()) {
            asm volatile("cp.async.bulk.tensor.3d.global.shared::cta.bulk_group [%0, {%2, %3, %4}], [%1];\ncp.async.bulk.commit_group;" ::"l"(&p.tmKV),
                         "r"(sb + OFF_CV + CV_SZ + (u < 3 ? u : u - 3) * 4096), "r"((63 - tb) * 16), "r"((cb >> 1) * 160 + u * 32), "r"(0) : "memory");
            if (u == 1 || u == 4) asm volatile("cp.async.bulk.wait_group 0;" ::: "memory");
            if (u == 1) { mbar_arrive(sb + BAR_KU); red_release(p.scr->cnt + CNT_KV + (cb >> 1)); }
          }
          __syncwarp();
          if (u == 1) {
            STAMP(35);
            if (PFT) { const char* q = (const char*)p.ssmk + chb * 4096 + lane * 128; prefetch_l2(q); prefetch_l2(q + 64 * 4096); }
          }
        }
        zero_pads(sb + OFF_CV + CV_SZ, lane);
        if (elect_one()) { mbar_arrive(sb + BAR_KU + 8); red_release(p.scr->cnt + CNT_KV + 2 + (cb >> 1)); }
        STAMP(30);
        if (lane < 24) {
          const char* r = (const char*)p.wout + (rb * 24 + lane) * (kD * 2) + cb * 320;
          prefetch_l2(r); prefetch_l2(r + 128); prefetch_l2(r + 256);
        }
      }
      poll_counter(p.scr->cnt + CNT_KV + 2 + (cb >> 1), kvt);
      if (elect_one()) mbar_arrive(sb + BAR_KV);
      STAMP(34);
      {
        const char* q = (const char*)p.wsp + (rb * 64 + cb * 16 + (lane >> 1)) * (kS * 2) + (lane & 1) * 128;
        uint32_t tp = clock();
#pragma unroll 1
        for (int i = LEAD / 2; i < WSP_N; i++) {
          prefetch_l2(q + ((i + (rot >> 1)) & 15) * 256);
          pace(tp, WSP_D);
        }
      }
      int s, ph = 1;
      const uint32_t tag = epoch + 1;
      mbar_wait(sb + BAR_G2, 0);
      if (elect_one()) {
        bulk_s2g(p.scr->h + (size_t)(rb * 12 + cb * 3) * A_SLOT, sb + OFF_A + 5 * A_SLOT, 3 * A_SLOT);
        asm volatile("cp.async.bulk.commit_group;\ncp.async.bulk.wait_group 0;" ::: "memory");
        if (BPART) mbar_arrive(sb + BAR_ZP);
        st_release(&p.scr->hflag[rb * 32 + cb * 8], tag);
      }
      __syncwarp();
      STAMP(20);
      poll_flags4(p.scr->hflag + rb * 32, tag, lane);
      STAMP(37);
      s = 8;
#pragma unroll 1
      for (int it = 3; it < 12; it++) {
        mbar_wait(sb + BAR_AE + 8 * s, ph);
        if (elect_one()) { mbar_expect(sb + BAR_AF + 8 * s, A_SLOT); bulk_g2s(sb + OFF_A + s * A_SLOT, p.scr->h + (size_t)(rb * 12 + g3_block(cb, it)) * A_SLOT, A_SLOT, sb + BAR_AF + 8 * s); }
        if (++s == NA2) { s = 0; ph ^= 1; }
      }
      STAMP(21);
    } else if (warp == 13) {
      const uint32_t ztarget = __shfl_sync(0xffffffff, ld_relaxed(p.scr->cnt + CNT_Z), 0);
      int s = 0, ph = 0;
#pragma unroll 1
      for (int it = NB; it < 20; it++) {
        if (W1_GATE >= 0 && it == 10) mbar_wait(sb + BAR_KU + 8 * (W1_GATE < 0 ? 0 : W1_GATE), 0);
        mbar_wait(sb + BAR_BE + 8 * s, ph);
        if (elect_one()) { mbar_expect(sb + BAR_BF + 8 * s, B_SLOT); tma3d(sb + OFF_B + s * B_SLOT, &p.tmW, 0, (it < 10 ? it : it - 10) * 64, (it < 10 ? 12 : 0) + cb * 3, sb + BAR_BF + 8 * s); }
        STAMP2(32 + it);
        if (++s == NB) { s = 0; ph ^= 1; }
      }
      mbar_wait(sb + BAR_KU + 16, 0);
#pragma unroll 1
      for (int i = 0; i < LEAD; i++) {
        mbar_wait(sb + BAR_AE + 8 * i, 0);
        if (elect_one()) { mbar_expect(sb + BAR_AF + 8 * i, A_SLOT); tma2d(sb + OFF_A + i * A_SLOT, &p.tmWsp, ((i + rot) & 31) * 64, rb * 64, sb + BAR_AF + 8 * i); }
      }
      mbar_wait(sb + BAR_ZP, 0);
      poll_counter(p.scr->cnt + CNT_Z, (ztarget & ~127u) + 128);
      STAMP(22);
      int sa = LEAD, pa = 0, ia = LEAD;
#pragma unroll 1
      for (int it = 0; it < 32; it++) {
        mbar_wait2(sb + BAR_BE + 8 * s, ph, sb + BAR_AE + 8 * sa, pa);
        if (elect_one()) {
          mbar_expect(sb + BAR_BF + 8 * s, B_SLOT);
          bulk_g2s(sb + OFF_B + s * B_SLOT, p.scr->z2 + (size_t)(cb * 32 + ((it + rot) & 31)) * B_SLOT, B_SLOT, sb + BAR_BF + 8 * s);
        }
#pragma unroll 1
        for (int j = (it < RAMP ? 0 : (it == 4 ? 1 + RAMP : 1)); j > 0 && ia < 32; j--, ia++) {
          if (it == 4) mbar_wait(sb + BAR_AE + 8 * sa, pa);
          if (elect_one()) { mbar_expect(sb + BAR_AF + 8 * sa, A_SLOT); tma2d(sb + OFF_A + sa * A_SLOT, &p.tmWsp, ((ia + rot) & 31) * 64, rb * 64, sb + BAR_AF + 8 * sa); }
          if (++sa == NA2) { sa = 0; pa ^= 1; }
        }
        if (HOLD < 27) mbar_arrive_if(sb + BAR_HOLD, it == HOLD + 5 && lane == 0);
        STAMP2(52 + it);
        if (++s == NB) { s = 0; ph ^= 1; }
      }
      mbar_wait(sb + BAR_WO, 0);
      acquire_fence();
#pragma unroll 1
      for (int it = 0; it < 12; it++) {
        if (NB3 == 6 && it < 6) mbar_wait(sb + BAR_BE + 8 * ((0x110443 >> (4 * it)) & 7), it < 3 ? 1 : 0);
        else mbar_wait(sb + BAR_BE + 8 * s, ph);
        if (elect_one()) {
          mbar_expect(sb + BAR_BF + 8 * s, 20480);
          bulk_g2s(sb + OFF_B + (NB3 == 6 ? (s == 5 ? 0 : s + 1) * 20480 : s * B_SLOT), p.scr->wo + (size_t)(cb * 12 + g3_block(cb, it)) * 20480, 20480, sb + BAR_BF + 8 * s);
        }
        if (HOLD < 32) mbar_arrive_if(sb + BAR_HOLD, it == HOLD - 27 && lane == 0);
        STAMP2(84 + it);
        if (++s == NB3) { s = 0; ph ^= 1; }
      }
    } else if (warp == 14) {
      const uint32_t tag = epoch + 1;
      uint32_t t0 = 0;
      mbar_wait(sb + BAR_AF + 8 * (NA - 1), 0);
#pragma unroll 1
      for (int part = 0; part < 2; part++) {
#pragma unroll 1
        while (true) {
          bool ok = true;
#pragma unroll
          for (int i = 0; i < 3; i++) {
            const uint4 v = ld_ll4(&p.scr->colsum[(part ? 0 : 768) + cb * 192 + i * 64 + lane * 2]);
            ok = ok && v.y == tag && v.w == tag;
            sts64f(sb + OFF_CS + part * 768 + i * 256 + lane * 8, __uint_as_float(v.x), __uint_as_float(v.z));
          }
          if (__all_sync(0xffffffff, ok)) break;
          spin_guard(t0);
        }
        __syncwarp();
        if (lane == 0) mbar_arrive(sb + BAR_ST + 8 * part);
        if (part == 0) STAMP(27);
      }
      STAMP(38);
      bar_sync(NB_Z, 160);
      if (elect_one()) {
        if (ZBULK) {
          bulk_s2g(p.scr->z2 + (size_t)(cb * 32 + rb) * B_SLOT, sb + OFF_A + LEAD * A_SLOT, B_SLOT);
          asm volatile("cp.async.bulk.commit_group;\ncp.async.bulk.wait_group 0;" ::: "memory");
        }
        red_release(p.scr->cnt + CNT_Z);
        mbar_arrive(sb + BAR_ZP);
      }
      STAMP(28);
      mbar_wait2(sb + BAR_KV, 0, sb + BAR_AE + 72, 0);
      acquire_fence();
      conv_service(p, sb, 0, chb + 64, true);
      bar_sync(NB_WO, 160);
      if (elect_one()) red_release(p.scr->cnt + CNT_WO + cb);
      STAMP(49);
      poll_counter(p.scr->cnt + CNT_WO + cb, tag * 32);
      if (elect_one()) mbar_arrive(sb + BAR_WO);
      STAMP(46);
      conv_service(p, sb, 0, chb + 192, false);
      bar_sync(NB_CD, 64);
      if (elect_one()) red_release(p.scr->cnt + CNT_Y + (cb >> 1));
      STAMP(47);
      poll_counter(p.scr->cnt + CNT_Y + (cb >> 1), tag * 64);
      if (elect_one()) { mbar_expect(sb + BAR_YT, 20480); tma2d(sb + OFF_CV, &p.tmY, rb * 64, cb * 160, sb + BAR_YT); }
      if (lane == 0) *(volatile uint32_t*)&p.scr->epoch[lin] = tag;
      STAMP(23);
    } else {
      const uint32_t tag = epoch + 1;
      sts32(sb + OFF_BIAS + lane * 4, ldg1(p.bsp + rb * 64 + lane * 2));
      if (lane < 2) sts32(sb + OFF_TAG + lane * 4, lane ? 0 : tag);
      uint32_t t0 = 0;
      mbar_wait(sb + BAR_AF + 8 * (NA - 1), 0);
#pragma unroll 1
      while (true) {
        const uint4 u = ld_ll4(&p.scr->xstat[rb * 64 + lane]), v = ld_ll4(&p.scr->xstat[rb * 64 + 32 + lane]);
        sts64f(sb + OFF_XS + lane * 8, __uint_as_float(u.x), __uint_as_float(u.z));
        sts64f(sb + OFF_XS + 256 + lane * 8, __uint_as_float(v.x), __uint_as_float(v.z));
        if (__all_sync(0xffffffff, u.y == tag && u.w == tag && v.y == tag && v.w == tag)) break;
        spin_guard(t0);
      }
      STAMP(26);
      __syncwarp();
      if (lane == 0) mbar_arrive(sb + BAR_XS);
      mbar_wait(sb + BAR_KU + 16, 0);
      poll_counter(p.scr->cnt + CNT_KV + (cb >> 1), tag * 64);
      if (elect_one()) load_convx(p, sb + OFF_CV, sb + BAR_XF + 8, chb);
      mbar_wait(sb + BAR_KU + 8, 1);
      if (elect_one()) load_convx(p, sb + OFF_CV + CV_SZ, sb + BAR_XF, chb + 64);
      STAMP(48);
      mbar_wait2(sb + BAR_KV, 0, sb + BAR_AE + 72, 0);
      acquire_fence();
#pragma unroll 1
      for (int i = 0; i < 3; i++) conv_service(p, sb, 1, chb + i * 128, i < 2);
      bar_arrive(NB_CD, 64);
    }
  } else {
    if (warp == 7) STAMP(36);
    const int wg = warp >> 2, w = warp & 3, g = lane >> 2, t = lane & 3;
    Taps k;
    uint32_t xw[2][10];
    if (wg == 2) {
      asm volatile("setmaxnreg.inc.sync.aligned.u32 160;");
      const int tb = rb * 2 + (cb & 1), c0 = (cb >> 1) * 320;
      const uint32_t cv = sb + OFF_CV + CV_SZ;
      if (w == 0) zero_pads(sb + OFF_CV, lane);
      mbar_wait(sb + BAR_KV + 8, 0);
      if (TAPS_C == 0) load_taps(k, p, chb, tid);
      const int t0 = tb * 32 + w * 8;
      const __nv_bfloat16* kp = p.k + (size_t)(t0 - 3) * kD + c0 + lane * 2;
      const __nv_bfloat16* vp = p.v + (size_t)t0 * kD + c0 + lane * 2;
      const __nv_bfloat16* sp = p.shift + (c0 + lane * 2) * 4;
      const uint32_t oa = cv + ((3 - w) & 1) * 1024 + lane * 32 + ((((3 - w) >> 1) ^ (lane >> 2)) & 1) * 16;
#pragma unroll 1
      for (int r = 0; r < 2; r++) {
        KvRegs n0, n1, n2;
        kv_load(n0, kp + r * 128, vp + r * 128, sp + r * 512, t0 > 0);
        kv_load(n1, kp + r * 128 + 64, vp + r * 128 + 64, sp + r * 512 + 256, t0 > 0);
        if (r) kv_load(n2, kp + 256, vp + 256, sp + 1024, t0 > 0);
        kv_unit(n0, oa + r * 8192);
        bar_sync(NB_WGC, 128);
        mbar_arrive_if(sb + BAR_KU + 16 * r, tid == 0);
        if (r) mbar_wait(sb + BAR_KU, 1);
        kv_unit(n1, oa + (r ? 0 : 4096));
        bar_sync(NB_WGC, 128);
        mbar_arrive_if(sb + BAR_KU + 16 * r + 8, tid == 0);
        if (r) {
          kv_unit(n2, oa + 4096);
          bar_sync(NB_WGC, 128);
          mbar_arrive_if(sb + BAR_KU + 32, tid == 0);
        } else {
          mbar_wait2(sb + BAR_AF + 8 * ((cb * 160 + 80) >> 6), 0, sb + BAR_AF + 8 * ((cb * 160 + 159) >> 6), 0);
          final_load_x(xw, sb + OFF_A, cb * 160 + 80, w, lane);
          if (KV_YIELD == 2) mbar_wait2(sb + BAR_XS, 0, sb + BAR_ST, 0);
        }
      }
      STAMPW(13);
      if (TAPS_C == 1) load_taps(k, p, chb, tid);
    } else {
      float d[96];
      if (wg == 0) { if (t < 2) st_ll4(&p.scr->zstat[rb * 256 + cb * 64 + w * 16 + g + t * 8], 0, 0, 0, 0); }
      else if ((tid & 7) == 0) st_ll4(&p.scr->xstat[rb * 64 + cb * 16 + (tid >> 3)], 0, 0, 0, 0);
      {
        constexpr bool live = true;
#pragma unroll
        for (int i = 0; i < 96; i++) d[i] = 0.f;
        if (live) {
          if (__builtin_expect(wg == 1, 0)) {
            const int tid = tid_now();
            const uint32_t epoch = load_epoch(p, lin, lane);
            float s = 0.f, q = 0.f;
#pragma unroll 1
            for (int i = 0; i < 10; i++) {
              mbar_wait(sb + BAR_AF + 8 * i, 0);
              const uint4 x4 = lds128(sb + OFF_A + i * A_SLOT + cb * 2048 + tid * 16);
              const uint32_t u[4] = {x4.x, x4.y, x4.z, x4.w};
#pragma unroll
              for (int e = 0; e < 4; e++) { const float a = bf_lo(u[e]), c = bf_hi(u[e]); s += a + c; q = fmaf(a, a, q); q = fmaf(c, c, q); }
            }
#pragma unroll
            for (int o = 1; o <= 4; o <<= 1) { s += __shfl_xor_sync(0xffffffff, s, o); q += __shfl_xor_sync(0xffffffff, q, o); }
            const float m = s * (1.f / kD);
            const float r = rsqrtf(fmaxf(fmaf(-m, m, q * (1.f / kD)), 0.f) + 1e-5f);
            if ((tid & 7) == 0) st_ll4(&p.scr->xstat[rb * 64 + cb * 16 + (tid >> 3)], __float_as_uint(m), epoch + 1, __float_as_uint(r), epoch + 1);
            STAMPW(12);
            bar_sync(NB_G1, 256);
          }
          gemm_loop<192, true, 0, D1>(d, sb, 10, 0, 0, 0, 0, wg, 2, tid_now(), !G1_LATE && wg == 0);
          asm volatile("setmaxnreg.inc.sync.aligned.u32 160;");
          STAMPW(wg ? 14 : 1);
          mbar_wait2(sb + BAR_XS, 0, sb + BAR_ST + 8 * wg, 0);
        }
        const int t1 = tid_now();
        const uint32_t xa1 = sb + OFF_XS + (w * 16 + ((t1 & 31) >> 2)) * 8;
        const float2 s0 = lds64f(xa1), s1 = lds64f(xa1 + 64);
        uint32_t z[48];
        float st[4];
        gelu_tile(d, z, st, sb + OFF_CS + wg * 768 + (t1 & 3) * 8, s0, s1);
        const int tid = tid_now(), lane = tid & 31, g = lane >> 2, t = lane & 3;
        if (live && wg == 1) {
          uint32_t bra, brb;
          asm volatile("ld.shared.u16 %0, [%1];" : "=r"(bra) : "r"(sb + OFF_BIAS + (w * 16 + g) * 2));
          asm volatile("ld.shared.u16 %0, [%1+16];" : "=r"(brb) : "r"(sb + OFF_BIAS + (w * 16 + g) * 2));
#pragma unroll
          for (int j = 0; j < 96; j++) d[j] = bf_lo((j & 2) ? brb : bra);
          STAMPW(15);
          gemm_loop<192, true, 1, D2>(d, sb, 32, 0, 1, 20, 0, 2, 2, tid, false);
          STAMPW(16);
          const int t2 = tid_now(), l2 = t2 & 31;
          const uint32_t ha = sb + OFF_A + 5 * A_SLOT + (l2 >> 4) * 1024 + (2 * w + ((l2 >> 3) & 1)) * 128 + (l2 & 7) * 16;
#pragma unroll
          for (int j = 0; j < 24; j += 2) {
#pragma unroll
            for (int e = 0; e < 4; e++) z[2 * j + e] = hmul2(z[2 * j + e], pack2(d[4 * j + 2 * e], d[4 * j + 2 * e + 1]));
            stsm4(ha + j * 1024, z[2 * j], z[2 * j + 1], z[2 * j + 2], z[2 * j + 3]);
          }
          fence_async_smem();
          bar_sync(NB_WGB, 128);
          mbar_arrive_if(sb + BAR_AF + 8 * (t2 == 3 ? (BAR_G2 - BAR_AF) / 8 : 5 + t2), t2 < 4);
          STAMPW(17);
          if (BPART) {
            float e[80];
#pragma unroll
            for (int j = 0; j < 80; j++) e[j] = 0.f;
            gemm_loop<160, false, 2, 4>(e, sb, 3, 5, 0, 2, 0, 0, 2, tid_now(), false);
            bar_sync(NB_WGB, 128);
            mbar_wait(sb + BAR_ZP, 1);
            const int t3 = tid_now();
#pragma unroll
            for (int j = 0; j < 10; j++)
              sts128(sb + OFF_A + 5 * A_SLOT + j * 2048 + t3 * 16, pack2(e[8 * j], e[8 * j + 1]), pack2(e[8 * j + 2], e[8 * j + 3]), pack2(e[8 * j + 4], e[8 * j + 5]),
                     pack2(e[8 * j + 6], e[8 * j + 7]));
            bar_sync(NB_WGB, 128);
            mbar_arrive_if(sb + BAR_HOLD, t3 == 0);
            STAMPW(45);
          }
          return;
        }
        float sa = st[0], qa = st[1], sbb = st[2], qb = st[3];
#pragma unroll
        for (int o = 1; o <= 2; o <<= 1) {
          sa += __shfl_xor_sync(0xffffffff, sa, o); qa += __shfl_xor_sync(0xffffffff, qa, o);
          sbb += __shfl_xor_sync(0xffffffff, sbb, o); qb += __shfl_xor_sync(0xffffffff, qb, o);
        }
        const uint32_t tag = lds32<0>(sb + OFF_TAG);
        if (live && t < 2) st_ll4(&p.scr->zstat[rb * 256 + cb * 64 + w * 16 + g + t * 8], __float_as_uint(t ? sbb : sa), tag, __float_as_uint(t ? qb : qa), tag);
        if (G1_LATE && live) bar_arrive(NB_G1, 256);
        if (live) STAMPW(2);
        if (TAPS_A == 0) load_taps(k, p, chb + 64, tid);
        const float ca = 0.5f * s0.y, cbb = 0.5f * s1.y;
        if (live) {
          const uint4* zs = &p.scr->zstat[rb * 256 + t * 64 + w * 16 + g];
          uint4 u0 = ld_ll4(zs), u1 = ld_ll4(zs + 8);
          final_load_x(xw, sb + OFF_A, cb * 160, w, lane);
          fence_async_smem();
          bar_sync(NB_WGA, 128);
          mbar_arrive_if(sb + BAR_AE + 8 * tid, tid < NA);
          uint32_t t0 = 0;
#pragma unroll 1
          while (!__all_sync(0xffffffff, u0.y == tag && u0.w == tag && u1.y == tag && u1.w == tag)) {
            spin_guard(t0);
            u0 = ld_ll4(zs); u1 = ld_ll4(zs + 8);
          }
          sa = __uint_as_float(u0.x); qa = __uint_as_float(u0.z); sbb = __uint_as_float(u1.x); qb = __uint_as_float(u1.z);
          STAMPW(3);
        }
#pragma unroll
        for (int o = 1; o <= 2; o <<= 1) {
          sa += __shfl_xor_sync(0xffffffff, sa, o); qa += __shfl_xor_sync(0xffffffff, qa, o);
          sbb += __shfl_xor_sync(0xffffffff, sbb, o); qb += __shfl_xor_sync(0xffffffff, qb, o);
        }
        const float inv = 1.f / 768.f;
        const float ma = sa * inv, mb = sbb * inv;
        const float ra = ca * rsqrtf(fmaf(fmaxf(fmaf(-ma, ma, qa * inv), 0.f), ca * ca, 1e-5f));
        const float rb_ = cbb * rsqrtf(fmaf(fmaxf(fmaf(-mb, mb, qb * inv), 0.f), cbb * cbb, 1e-5f));
        const uint32_t ra2 = pack2(ra, ra), rb2 = pack2(rb_, rb_);
        const float na = -ma * bf_lo(ra2), nb = -mb * bf_lo(rb2);
        if (ZBULK) {
          const uint32_t n2a = pack2(na, na), n2b = pack2(nb, nb);
          const uint32_t za = sb + OFF_A + LEAD * A_SLOT + (2 * w + ((lane >> 3) & 1)) * 3072 + (lane >> 4) * 128 + (lane & 7) * 16;
          mbar_wait2(sb + BAR_AE + 8 * (LEAD + 2), 0, sb + BAR_KU + 16, 0);
#pragma unroll
          for (int j = 0; j < 24; j += 2)
            stsm4(za + j * 128, hfma2(z[2 * j], ra2, n2a), hfma2(z[2 * j + 1], rb2, n2b), hfma2(z[2 * j + 2], ra2, n2a), hfma2(z[2 * j + 3], rb2, n2b));
          fence_async_smem();
        } else {
          ZStore<0>::run(p.scr->z2 + (size_t)(cb * 32 + rb) * B_SLOT + w * 6144 + lane * 4, z, ra2, pack2(na, na), rb2, pack2(nb, nb), live);
        }
      }
      bar_arrive(NB_Z, 160);
      {
        const uint32_t zero = lds32<0>(sb + OFF_TAG + 4);
#pragma unroll
        for (int i = 0; i < 20; i++) xw[i / 10][i % 10] |= zero;
      }
      if (TAPS_A == 1) load_taps(k, p, chb + 64, tid_now());
      STAMPW(4);
    }
    const int h = wg >> 1;
    {
    const int tid = tid_now(), lane = tid & 31;
    conv_worker(p, k, sb + OFF_CV + (1 - h) * CV_SZ, sb + OFF_A + 9 * A_SLOT + h * 4096, sb + BAR_XF + 8 * h, NB_WGA + h,
                chb + (h ? 0 : 64), 2 + h, HOLD == 32 ? sb + BAR_G2 : sb + BAR_HOLD, w, lane, tid, h ? 40 : 5, rb, cb);
    float d[40];
    if (BPART) {
      const int t3 = tid_now();
      mbar_wait(sb + BAR_HOLD, 0);
#pragma unroll
      for (int j = 0; j < 5; j++) {
        const uint4 v = lds128(sb + OFF_A + 5 * A_SLOT + (h * 5 + j) * 2048 + t3 * 16);
        d[8 * j] = bf_lo(v.x); d[8 * j + 1] = bf_hi(v.x); d[8 * j + 2] = bf_lo(v.y); d[8 * j + 3] = bf_hi(v.y);
        d[8 * j + 4] = bf_lo(v.z); d[8 * j + 5] = bf_hi(v.z); d[8 * j + 6] = bf_lo(v.w); d[8 * j + 7] = bf_hi(v.w);
      }
      fence_async_smem();
      bar_sync(NB_WGA + h, 128);
      mbar_arrive_if(sb + BAR_AE + 8 * (5 + t3), t3 < 3);
      gemm_loop<80, false, 2, D3>(d, sb, 9, 8, 0, 5, h * 1280, 1, 1, t3, false);
    } else {
#pragma unroll
      for (int i = 0; i < 40; i++) d[i] = 0.f;
      mbar_wait(sb + BAR_G2, 0);
      gemm_loop<80, false, 2, D3>(d, sb, 12, 5, 0, 2, h * 1280, 1, 1, tid_now(), false);
    }
    STAMPW(h ? 18 : 10);
    const int l3 = tid_now() & 31;
    const uint32_t xs_addr = sb + OFF_XS + (w * 16 + (l3 >> 2)) * 8;
    final_gate(d, xw, lds64f(xs_addr), lds64f(xs_addr + 64));
    acc_fence<40>(d);
    STAMPW(h ? 44 : 9);
    mbar_wait(sb + BAR_YT, 1);
    final_out(d, xw, sb + OFF_CV + h * 10240, p.out + (size_t)(rb * 64 + w * 16 + (l3 >> 2)) * kD + cb * 160 + h * 80, w, l3);
    }
  }
}

typedef CUresult (*EncodeFn)(CUtensorMap*, CUtensorMapDataType, cuuint32_t, void*, const cuuint64_t*, const cuuint64_t*, const cuuint32_t*,
                             const cuuint32_t*, CUtensorMapInterleave, CUtensorMapSwizzle, CUtensorMapL2promotion, CUtensorMapFloatOOBfill);

void encode(EncodeFn fn, CUtensorMap* m, const void* ptr, int rank, const cuuint64_t* dims, const cuuint64_t* strides, const cuuint32_t* box,
            CUtensorMapSwizzle swz = CU_TENSOR_MAP_SWIZZLE_128B) {
  const cuuint32_t es[3] = {1, 1, 1};
  fn(m, CU_TENSOR_MAP_DATA_TYPE_BFLOAT16, rank, const_cast<void*>(ptr), dims, strides, box, es, CU_TENSOR_MAP_INTERLEAVE_NONE,
     swz, CU_TENSOR_MAP_L2_PROMOTION_L2_128B, CU_TENSOR_MAP_FLOAT_OOB_FILL_NONE);
}

}

extern "C" void kernel_launch(void* const* d_in, const int* in_sizes, int n_in, void* d_out, int out_size) {
  (void)in_sizes; (void)n_in; (void)out_size;
  static EncodeFn enc = nullptr;
  static Scratch* scr = nullptr;
  static int sms = 0;
  if (!enc) {
    void* fn = nullptr;
    cudaDriverEntryPointQueryResult qr;
    cudaGetDriverEntryPoint("cuTensorMapEncodeTiled", &fn, cudaEnableDefault, &qr);
    enc = (EncodeFn)fn;
    cudaFuncSetAttribute(fused_kernel, cudaFuncAttributeMaxDynamicSharedMemorySize, SMEM_BYTES);
    cudaGetSymbolAddress((void**)&scr, g_scr);
    int dev = 0;
    cudaGetDevice(&dev);
    cudaDeviceGetAttribute(&sms, cudaDevAttrMultiProcessorCount, dev);
  }
  Params p;
  p.scr = scr;
  p.by_smid = sms == 132;
  p.x = (const __nv_bfloat16*)d_in[0];
  p.win = (const __nv_bfloat16*)d_in[7];
  p.k = (const __nv_bfloat16*)d_in[1];
  p.v = (const __nv_bfloat16*)d_in[2];
  p.shift = (const __nv_bfloat16*)d_in[3];
  p.ssmk = (const __nv_bfloat16*)d_in[4];
  p.ssmD = (const __nv_bfloat16*)d_in[5];
  p.wsp = (const __nv_bfloat16*)d_in[8];
  p.bsp = (const __nv_bfloat16*)d_in[9];
  p.wout = (const __nv_bfloat16*)d_in[10];
  p.out = (__nv_bfloat16*)d_out;
  {
    const cuuint64_t dims[2] = {kD, kS}, st[1] = {kD * 2};
    const cuuint32_t box[2] = {64, 64};
    encode(enc, &p.tmX, d_in[0], 2, dims, st, box);
  }
  {
    const cuuint64_t dims[3] = {64, kD, kF / 64}, st[2] = {kF * 2, 128};
    const cuuint32_t box[3] = {64, 64, 3};
    encode(enc, &p.tmW, d_in[7], 3, dims, st, box);
  }
  {
    const cuuint64_t dims[2] = {kS, kS}, st[1] = {kS * 2};
    const cuuint32_t box[2] = {64, 64};
    encode(enc, &p.tmWsp, d_in[8], 2, dims, st, box);
  }
  {
    const cuuint64_t dims[2] = {kS, kD}, st[1] = {kS * 2};
    const cuuint32_t box[2] = {64, 160};
    encode(enc, &p.tmY, scr->y, 2, dims, st, box);
  }
  {
    const cuuint64_t dims[3] = {1024, kD / 2, 4}, st[2] = {8192, 2048};
    const cuuint32_t box[3] = {16, 32, 4};
    encode(enc, &p.tmKV, scr->kvx, 3, dims, st, box, CU_TENSOR_MAP_SWIZZLE_32B);
  }
  fused_kernel<<<132, 512, SMEM_BYTES, cudaStreamPerThread>>>(p);
}
```

```cpp
#include <cuda_runtime.h>
#include <cuda.h>
#include <cuda_bf16.h>
#include <stdint.h>

template <int N> struct WG;
template <> struct WG<16> {
  static __device__ __forceinline__ void rs(float* d, const uint32_t* a, uint64_t db) {
    asm volatile("{\n.reg .pred p;\nsetp.ne.b32 p, 1, 0;\nwgmma.mma_async.sync.aligned.m64n16k16.f32.bf16.bf16 {"
      "%0, %1, %2, %3, %4, %5, %6, %7"
      "}, {%8, %9, %10, %11}, %12, p, 1, 1, 0;\n}\n"
      :
      "+f"(d[0]), "+f"(d[1]), "+f"(d[2]), "+f"(d[3]), "+f"(d[4]), "+f"(d[5]), "+f"(d[6]), "+f"(d[7])
      : "r"(a[0]), "r"(a[1]), "r"(a[2]), "r"(a[3]), "l"(db));
  }
};
template <> struct WG<32> {
  static __device__ __forceinline__ void rs(float* d, const uint32_t* a, uint64_t db) {
    asm volatile("{\n.reg .pred p;\nsetp.ne.b32 p, 1, 0;\nwgmma.mma_async.sync.aligned.m64n32k16.f32.bf16.bf16 {"
      "%0, %1, %2, %3, %4, %5, %6, %7, %8, %9, %10, %11, %12, %13, %14, %15"
      "}, {%16, %17, %18, %19}, %20, p, 1, 1, 0;\n}\n"
      :
      "+f"(d[0]), "+f"(d[1]), "+f"(d[2]), "+f"(d[3]), "+f"(d[4]), "+f"(d[5]), "+f"(d[6]), "+f"(d[7]),
      "+f"(d[8]), "+f"(d[9]), "+f"(d[10]), "+f"(d[11]), "+f"(d[12]), "+f"(d[13]), "+f"(d[14]), "+f"(d[15])
      : "r"(a[0]), "r"(a[1]), "r"(a[2]), "r"(a[3]), "l"(db));
  }
};
template <> struct WG<48> {
  static __device__ __forceinline__ void rs(float* d, const uint32_t* a, uint64_t db) {
    asm volatile("{\n.reg .pred p;\nsetp.ne.b32 p, 1, 0;\nwgmma.mma_async.sync.aligned.m64n48k16.f32.bf16.bf16 {"
      "%0, %1, %2, %3, %4, %5, %6, %7, %8, %9, %10, %11, %12, %13, %14, %15, "
      "%16, %17, %18, %19, %20, %21, %22, %23"
      "}, {%24, %25, %26, %27}, %28, p, 1, 1, 0;\n}\n"
      :
      "+f"(d[0]), "+f"(d[1]), "+f"(d[2]), "+f"(d[3]), "+f"(d[4]), "+f"(d[5]), "+f"(d[6]), "+f"(d[7]),
      "+f"(d[8]), "+f"(d[9]), "+f"(d[10]), "+f"(d[11]), "+f"(d[12]), "+f"(d[13]), "+f"(d[14]), "+f"(d[15]),
      "+f"(d[16]), "+f"(d[17]), "+f"(d[18]), "+f"(d[19]), "+f"(d[20]), "+f"(d[21]), "+f"(d[22]), "+f"(d[23])
      : "r"(a[0]), "r"(a[1]), "r"(a[2]), "r"(a[3]), "l"(db));
  }
};
template <> struct WG<64> {
  static __device__ __forceinline__ void ss(float* d, uint64_t da, uint64_t db, int sd) {
    asm volatile("{\n.reg .pred p;\nsetp.ne.b32 p, %34, 0;\nwgmma.mma_async.sync.aligned.m64n64k16.f32.bf16.bf16 {"
      "%0, %1, %2, %3, %4, %5, %6, %7, %8, %9, %10, %11, %12, %13, %14, %15, "
      "%16, %17, %18, %19, %20, %21, %22, %23, %24, %25, %26, %27, %28, %29, %30, %31"
      "}, %32, %33, p, 1, 1, 0, 1;\n}\n"
      :
      "+f"(d[0]), "+f"(d[1]), "+f"(d[2]), "+f"(d[3]), "+f"(d[4]), "+f"(d[5]), "+f"(d[6]), "+f"(d[7]),
      "+f"(d[8]), "+f"(d[9]), "+f"(d[10]), "+f"(d[11]), "+f"(d[12]), "+f"(d[13]), "+f"(d[14]), "+f"(d[15]),
      "+f"(d[16]), "+f"(d[17]), "+f"(d[18]), "+f"(d[19]), "+f"(d[20]), "+f"(d[21]), "+f"(d[22]), "+f"(d[23]),
      "+f"(d[24]), "+f"(d[25]), "+f"(d[26]), "+f"(d[27]), "+f"(d[28]), "+f"(d[29]), "+f"(d[30]), "+f"(d[31])
      : "l"(da), "l"(db), "r"(sd));
  }
  static __device__ __forceinline__ void rs(float* d, const uint32_t* a, uint64_t db) {
    asm volatile("{\n.reg .pred p;\nsetp.ne.b32 p, 1, 0;\nwgmma.mma_async.sync.aligned.m64n64k16.f32.bf16.bf16 {"
      "%0, %1, %2, %3, %4, %5, %6, %7, %8, %9, %10, %11, %12, %13, %14, %15, "
      "%16, %17, %18, %19, %20, %21, %22, %23, %24, %25, %26, %27, %28, %29, %30, %31"
      "}, {%32, %33, %34, %35}, %36, p, 1, 1, 0;\n}\n"
      :
      "+f"(d[0]), "+f"(d[1]), "+f"(d[2]), "+f"(d[3]), "+f"(d[4]), "+f"(d[5]), "+f"(d[6]), "+f"(d[7]),
      "+f"(d[8]), "+f"(d[9]), "+f"(d[10]), "+f"(d[11]), "+f"(d[12]), "+f"(d[13]), "+f"(d[14]), "+f"(d[15]),
      "+f"(d[16]), "+f"(d[17]), "+f"(d[18]), "+f"(d[19]), "+f"(d[20]), "+f"(d[21]), "+f"(d[22]), "+f"(d[23]),
      "+f"(d[24]), "+f"(d[25]), "+f"(d[26]), "+f"(d[27]), "+f"(d[28]), "+f"(d[29]), "+f"(d[30]), "+f"(d[31])
      : "r"(a[0]), "r"(a[1]), "r"(a[2]), "r"(a[3]), "l"(db));
  }
};
template <> struct WG<80> {
  static __device__ __forceinline__ void ss(float* d, uint64_t da, uint64_t db, int sd) {
    asm volatile("{\n.reg .pred p;\nsetp.ne.b32 p, %42, 0;\nwgmma.mma_async.sync.aligned.m64n80k16.f32.bf16.bf16 {"
      "%0, %1, %2, %3, %4, %5, %6, %7, %8, %9, %10, %11, %12, %13, %14, %15, "
      "%16, %17, %18, %19, %20, %21, %22, %23, %24, %25, %26, %27, %28, %29, %30, %31, "
      "%32, %33, %34, %35, %36, %37, %38, %39"
      "}, %40, %41, p, 1, 1, 0, 1;\n}\n"
      :
      "+f"(d[0]), "+f"(d[1]), "+f"(d[2]), "+f"(d[3]), "+f"(d[4]), "+f"(d[5]), "+f"(d[6]), "+f"(d[7]),
      "+f"(d[8]), "+f"(d[9]), "+f"(d[10]), "+f"(d[11]), "+f"(d[12]), "+f"(d[13]), "+f"(d[14]), "+f"(d[15]),
      "+f"(d[16]), "+f"(d[17]), "+f"(d[18]), "+f"(d[19]), "+f"(d[20]), "+f"(d[21]), "+f"(d[22]), "+f"(d[23]),
      "+f"(d[24]), "+f"(d[25]), "+f"(d[26]), "+f"(d[27]), "+f"(d[28]), "+f"(d[29]), "+f"(d[30]), "+f"(d[31]),
      "+f"(d[32]), "+f"(d[33]), "+f"(d[34]), "+f"(d[35]), "+f"(d[36]), "+f"(d[37]), "+f"(d[38]), "+f"(d[39])
      : "l"(da), "l"(db), "r"(sd));
  }
  static __device__ __forceinline__ void rs(float* d, const uint32_t* a, uint64_t db) {
    asm volatile("{\n.reg .pred p;\nsetp.ne.b32 p, 1, 0;\nwgmma.mma_async.sync.aligned.m64n80k16.f32.bf16.bf16 {"
      "%0, %1, %2, %3, %4, %5, %6, %7, %8, %9, %10, %11, %12, %13, %14, %15, "
      "%16, %17, %18, %19, %20, %21, %22, %23, %24, %25, %26, %27, %28, %29, %30, %31, "
      "%32, %33, %34, %35, %36, %37, %38, %39"
      "}, {%40, %41, %42, %43}, %44, p, 1, 1, 0;\n}\n"
      :
      "+f"(d[0]), "+f"(d[1]), "+f"(d[2]), "+f"(d[3]), "+f"(d[4]), "+f"(d[5]), "+f"(d[6]), "+f"(d[7]),
      "+f"(d[8]), "+f"(d[9]), "+f"(d[10]), "+f"(d[11]), "+f"(d[12]), "+f"(d[13]), "+f"(d[14]), "+f"(d[15]),
      "+f"(d[16]), "+f"(d[17]), "+f"(d[18]), "+f"(d[19]), "+f"(d[20]), "+f"(d[21]), "+f"(d[22]), "+f"(d[23]),
      "+f"(d[24]), "+f"(d[25]), "+f"(d[26]), "+f"(d[27]), "+f"(d[28]), "+f"(d[29]), "+f"(d[30]), "+f"(d[31]),
      "+f"(d[32]), "+f"(d[33]), "+f"(d[34]), "+f"(d[35]), "+f"(d[36]), "+f"(d[37]), "+f"(d[38]), "+f"(d[39])
      : "r"(a[0]), "r"(a[1]), "r"(a[2]), "r"(a[3]), "l"(db));
  }
};
template <> struct WG<96> {
  static __device__ __forceinline__ void ss(float* d, uint64_t da, uint64_t db, int sd) {
    asm volatile("{\n.reg .pred p;\nsetp.ne.b32 p, %50, 0;\nwgmma.mma_async.sync.aligned.m64n96k16.f32.bf16.bf16 {"
      "%0, %1, %2, %3, %4, %5, %6, %7, %8, %9, %10, %11, %12, %13, %14, %15, "
      "%16, %17, %18, %19, %20, %21, %22, %23, %24, %25, %26, %27, %28, %29, %30, %31, "
      "%32, %33, %34, %35, %36, %37, %38, %39, %40, %41, %42, %43, %44, %45, %46, %47"
      "}, %48, %49, p, 1, 1, 0, 1;\n}\n"
      :
      "+f"(d[0]), "+f"(d[1]), "+f"(d[2]), "+f"(d[3]), "+f"(d[4]), "+f"(d[5]), "+f"(d[6]), "+f"(d[7]),
      "+f"(d[8]), "+f"(d[9]), "+f"(d[10]), "+f"(d[11]), "+f"(d[12]), "+f"(d[13]), "+f"(d[14]), "+f"(d[15]),
      "+f"(d[16]), "+f"(d[17]), "+f"(d[18]), "+f"(d[19]), "+f"(d[20]), "+f"(d[21]), "+f"(d[22]), "+f"(d[23]),
      "+f"(d[24]), "+f"(d[25]), "+f"(d[26]), "+f"(d[27]), "+f"(d[28]), "+f"(d[29]), "+f"(d[30]), "+f"(d[31]),
      "+f"(d[32]), "+f"(d[33]), "+f"(d[34]), "+f"(d[35]), "+f"(d[36]), "+f"(d[37]), "+f"(d[38]), "+f"(d[39]),
      "+f"(d[40]), "+f"(d[41]), "+f"(d[42]), "+f"(d[43]), "+f"(d[44]), "+f"(d[45]), "+f"(d[46]), "+f"(d[47])
      : "l"(da), "l"(db), "r"(sd));
  }
  static __device__ __forceinline__ void rs(float* d, const uint32_t* a, uint64_t db) {
    asm volatile("{\n.reg .pred p;\nsetp.ne.b32 p, 1, 0;\nwgmma.mma_async.sync.aligned.m64n96k16.f32.bf16.bf16 {"
      "%0, %1, %2, %3, %4, %5, %6, %7, %8, %9, %10, %11, %12, %13, %14, %15, "
      "%16, %17, %18, %19, %20, %21, %22, %23, %24, %25, %26, %27, %28, %29, %30, %31, "
      "%32, %33, %34, %35, %36, %37, %38, %39, %40, %41, %42, %43, %44, %45, %46, %47"
      "}, {%48, %49, %50, %51}, %52, p, 1, 1, 0;\n}\n"
      :
      "+f"(d[0]), "+f"(d[1]), "+f"(d[2]), "+f"(d[3]), "+f"(d[4]), "+f"(d[5]), "+f"(d[6]), "+f"(d[7]),
      "+f"(d[8]), "+f"(d[9]), "+f"(d[10]), "+f"(d[11]), "+f"(d[12]), "+f"(d[13]), "+f"(d[14]), "+f"(d[15]),
      "+f"(d[16]), "+f"(d[17]), "+f"(d[18]), "+f"(d[19]), "+f"(d[20]), "+f"(d[21]), "+f"(d[22]), "+f"(d[23]),
      "+f"(d[24]), "+f"(d[25]), "+f"(d[26]), "+f"(d[27]), "+f"(d[28]), "+f"(d[29]), "+f"(d[30]), "+f"(d[31]),
      "+f"(d[32]), "+f"(d[33]), "+f"(d[34]), "+f"(d[35]), "+f"(d[36]), "+f"(d[37]), "+f"(d[38]), "+f"(d[39]),
      "+f"(d[40]), "+f"(d[41]), "+f"(d[42]), "+f"(d[43]), "+f"(d[44]), "+f"(d[45]), "+f"(d[46]), "+f"(d[47])
      : "r"(a[0]), "r"(a[1]), "r"(a[2]), "r"(a[3]), "l"(db));
  }
};
template <> struct WG<112> {
  static __device__ __forceinline__ void rs(float* d, const uint32_t* a, uint64_t db) {
    asm volatile("{\n.reg .pred p;\nsetp.ne.b32 p, 1, 0;\nwgmma.mma_async.sync.aligned.m64n112k16.f32.bf16.bf16 {"
      "%0, %1, %2, %3, %4, %5, %6, %7, %8, %9, %10, %11, %12, %13, %14, %15, "
      "%16, %17, %18, %19, %20, %21, %22, %23, %24, %25, %26, %27, %28, %29, %30, %31, "
      "%32, %33, %34, %35, %36, %37, %38, %39, %40, %41, %42, %43, %44, %45, %46, %47, "
      "%48, %49, %50, %51, %52, %53, %54, %55"
      "}, {%56, %57, %58, %59}, %60, p, 1, 1, 0;\n}\n"
      :
      "+f"(d[0]), "+f"(d[1]), "+f"(d[2]), "+f"(d[3]), "+f"(d[4]), "+f"(d[5]), "+f"(d[6]), "+f"(d[7]),
      "+f"(d[8]), "+f"(d[9]), "+f"(d[10]), "+f"(d[11]), "+f"(d[12]), "+f"(d[13]), "+f"(d[14]), "+f"(d[15]),
      "+f"(d[16]), "+f"(d[17]), "+f"(d[18]), "+f"(d[19]), "+f"(d[20]), "+f"(d[21]), "+f"(d[22]), "+f"(d[23]),
      "+f"(d[24]), "+f"(d[25]), "+f"(d[26]), "+f"(d[27]), "+f"(d[28]), "+f"(d[29]), "+f"(d[30]), "+f"(d[31]),
      "+f"(d[32]), "+f"(d[33]), "+f"(d[34]), "+f"(d[35]), "+f"(d[36]), "+f"(d[37]), "+f"(d[38]), "+f"(d[39]),
      "+f"(d[40]), "+f"(d[41]), "+f"(d[42]), "+f"(d[43]), "+f"(d[44]), "+f"(d[45]), "+f"(d[46]), "+f"(d[47]),
      "+f"(d[48]), "+f"(d[49]), "+f"(d[50]), "+f"(d[51]), "+f"(d[52]), "+f"(d[53]), "+f"(d[54]), "+f"(d[55])
      : "r"(a[0]), "r"(a[1]), "r"(a[2]), "r"(a[3]), "l"(db));
  }
};
template <> struct WG<128> {
  static __device__ __forceinline__ void rs(float* d, const uint32_t* a, uint64_t db) {
    asm volatile("{\n.reg .pred p;\nsetp.ne.b32 p, 1, 0;\nwgmma.mma_async.sync.aligned.m64n128k16.f32.bf16.bf16 {"
      "%0, %1, %2, %3, %4, %5, %6, %7, %8, %9, %10, %11, %12, %13, %14, %15, "
      "%16, %17, %18, %19, %20, %21, %22, %23, %24, %25, %26, %27, %28, %29, %30, %31, "
      "%32, %33, %34, %35, %36, %37, %38, %39, %40, %41, %42, %43, %44, %45, %46, %47, "
      "%48, %49, %50, %51, %52, %53, %54, %55, %56, %57, %58, %59, %60, %61, %62, %63"
      "}, {%64, %65, %66, %67}, %68, p, 1, 1, 0;\n}\n"
      :
      "+f"(d[0]), "+f"(d[1]), "+f"(d[2]), "+f"(d[3]), "+f"(d[4]), "+f"(d[5]), "+f"(d[6]), "+f"(d[7]),
      "+f"(d[8]), "+f"(d[9]), "+f"(d[10]), "+f"(d[11]), "+f"(d[12]), "+f"(d[13]), "+f"(d[14]), "+f"(d[15]),
      "+f"(d[16]), "+f"(d[17]), "+f"(d[18]), "+f"(d[19]), "+f"(d[20]), "+f"(d[21]), "+f"(d[22]), "+f"(d[23]),
      "+f"(d[24]), "+f"(d[25]), "+f"(d[26]), "+f"(d[27]), "+f"(d[28]), "+f"(d[29]), "+f"(d[30]), "+f"(d[31]),
      "+f"(d[32]), "+f"(d[33]), "+f"(d[34]), "+f"(d[35]), "+f"(d[36]), "+f"(d[37]), "+f"(d[38]), "+f"(d[39]),
      "+f"(d[40]), "+f"(d[41]), "+f"(d[42]), "+f"(d[43]), "+f"(d[44]), "+f"(d[45]), "+f"(d[46]), "+f"(d[47]),
      "+f"(d[48]), "+f"(d[49]), "+f"(d[50]), "+f"(d[51]), "+f"(d[52]), "+f"(d[53]), "+f"(d[54]), "+f"(d[55]),
      "+f"(d[56]), "+f"(d[57]), "+f"(d[58]), "+f"(d[59]), "+f"(d[60]), "+f"(d[61]), "+f"(d[62]), "+f"(d[63])
      : "r"(a[0]), "r"(a[1]), "r"(a[2]), "r"(a[3]), "l"(db));
  }
};
template <> struct WG<160> {
  static __device__ __forceinline__ void ss(float* d, uint64_t da, uint64_t db, int sd) {
    asm volatile("{\n.reg .pred p;\nsetp.ne.b32 p, %82, 0;\nwgmma.mma_async.sync.aligned.m64n160k16.f32.bf16.bf16 {"
      "%0, %1, %2, %3, %4, %5, %6, %7, %8, %9, %10, %11, %12, %13, %14, %15, "
      "%16, %17, %18, %19, %20, %21, %22, %23, %24, %25, %26, %27, %28, %29, %30, %31, "
      "%32, %33, %34, %35, %36, %37, %38, %39, %40, %41, %42, %43, %44, %45, %46, %47, "
      "%48, %49, %50, %51, %52, %53, %54, %55, %56, %57, %58, %59, %60, %61, %62, %63, "
      "%64, %65, %66, %67, %68, %69, %70, %71, %72, %73, %74, %75, %76, %77, %78, %79"
      "}, %80, %81, p, 1, 1, 0, 1;\n}\n"
      :
      "+f"(d[0]), "+f"(d[1]), "+f"(d[2]), "+f"(d[3]), "+f"(d[4]), "+f"(d[5]), "+f"(d[6]), "+f"(d[7]),
      "+f"(d[8]), "+f"(d[9]), "+f"(d[10]), "+f"(d[11]), "+f"(d[12]), "+f"(d[13]), "+f"(d[14]), "+f"(d[15]),
      "+f"(d[16]), "+f"(d[17]), "+f"(d[18]), "+f"(d[19]), "+f"(d[20]), "+f"(d[21]), "+f"(d[22]), "+f"(d[23]),
      "+f"(d[24]), "+f"(d[25]), "+f"(d[26]), "+f"(d[27]), "+f"(d[28]), "+f"(d[29]), "+f"(d[30]), "+f"(d[31]),
      "+f"(d[32]), "+f"(d[33]), "+f"(d[34]), "+f"(d[35]), "+f"(d[36]), "+f"(d[37]), "+f"(d[38]), "+f"(d[39]),
      "+f"(d[40]), "+f"(d[41]), "+f"(d[42]), "+f"(d[43]), "+f"(d[44]), "+f"(d[45]), "+f"(d[46]), "+f"(d[47]),
      "+f"(d[48]), "+f"(d[49]), "+f"(d[50]), "+f"(d[51]), "+f"(d[52]), "+f"(d[53]), "+f"(d[54]), "+f"(d[55]),
      "+f"(d[56]), "+f"(d[57]), "+f"(d[58]), "+f"(d[59]), "+f"(d[60]), "+f"(d[61]), "+f"(d[62]), "+f"(d[63]),
      "+f"(d[64]), "+f"(d[65]), "+f"(d[66]), "+f"(d[67]), "+f"(d[68]), "+f"(d[69]), "+f"(d[70]), "+f"(d[71]),
      "+f"(d[72]), "+f"(d[73]), "+f"(d[74]), "+f"(d[75]), "+f"(d[76]), "+f"(d[77]), "+f"(d[78]), "+f"(d[79])
      : "l"(da), "l"(db), "r"(sd));
  }
};
template <> struct WG<192> {
  static __device__ __forceinline__ void ss(float* d, uint64_t da, uint64_t db, int sd) {
    asm volatile("{\n.reg .pred p;\nsetp.ne.b32 p, %98, 0;\nwgmma.mma_async.sync.aligned.m64n192k16.f32.bf16.bf16 {"
      "%0, %1, %2, %3, %4, %5, %6, %7, %8, %9, %10, %11, %12, %13, %14, %15, "
      "%16, %17, %18, %19, %20, %21, %22, %23, %24, %25, %26, %27, %28, %29, %30, %31, "
      "%32, %33, %34, %35, %36, %37, %38, %39, %40, %41, %42, %43, %44, %45, %46, %47, "
      "%48, %49, %50, %51, %52, %53, %54, %55, %56, %57, %58, %59, %60, %61, %62, %63, "
      "%64, %65, %66, %67, %68, %69, %70, %71, %72, %73, %74, %75, %76, %77, %78, %79, "
      "%80, %81, %82, %83, %84, %85, %86, %87, %88, %89, %90, %91, %92, %93, %94, %95"
      "}, %96, %97, p, 1, 1, 0, 1;\n}\n"
      :
      "+f"(d[0]), "+f"(d[1]), "+f"(d[2]), "+f"(d[3]), "+f"(d[4]), "+f"(d[5]), "+f"(d[6]), "+f"(d[7]),
      "+f"(d[8]), "+f"(d[9]), "+f"(d[10]), "+f"(d[11]), "+f"(d[12]), "+f"(d[13]), "+f"(d[14]), "+f"(d[15]),
      "+f"(d[16]), "+f"(d[17]), "+f"(d[18]), "+f"(d[19]), "+f"(d[20]), "+f"(d[21]), "+f"(d[22]), "+f"(d[23]),
      "+f"(d[24]), "+f"(d[25]), "+f"(d[26]), "+f"(d[27]), "+f"(d[28]), "+f"(d[29]), "+f"(d[30]), "+f"(d[31]),
      "+f"(d[32]), "+f"(d[33]), "+f"(d[34]), "+f"(d[35]), "+f"(d[36]), "+f"(d[37]), "+f"(d[38]), "+f"(d[39]),
      "+f"(d[40]), "+f"(d[41]), "+f"(d[42]), "+f"(d[43]), "+f"(d[44]), "+f"(d[45]), "+f"(d[46]), "+f"(d[47]),
      "+f"(d[48]), "+f"(d[49]), "+f"(d[50]), "+f"(d[51]), "+f"(d[52]), "+f"(d[53]), "+f"(d[54]), "+f"(d[55]),
      "+f"(d[56]), "+f"(d[57]), "+f"(d[58]), "+f"(d[59]), "+f"(d[60]), "+f"(d[61]), "+f"(d[62]), "+f"(d[63]),
      "+f"(d[64]), "+f"(d[65]), "+f"(d[66]), "+f"(d[67]), "+f"(d[68]), "+f"(d[69]), "+f"(d[70]), "+f"(d[71]),
      "+f"(d[72]), "+f"(d[73]), "+f"(d[74]), "+f"(d[75]), "+f"(d[76]), "+f"(d[77]), "+f"(d[78]), "+f"(d[79]),
      "+f"(d[80]), "+f"(d[81]), "+f"(d[82]), "+f"(d[83]), "+f"(d[84]), "+f"(d[85]), "+f"(d[86]), "+f"(d[87]),
      "+f"(d[88]), "+f"(d[89]), "+f"(d[90]), "+f"(d[91]), "+f"(d[92]), "+f"(d[93]), "+f"(d[94]), "+f"(d[95])
      : "l"(da), "l"(db), "r"(sd));
  }
};

#define KV_T0 2300
#define ST_YIELD 1
#define HP0 3500
#define HPD 450
#define RAMP 1
#define LEAD 2
#define WSP_N 16
#define EARLY 0
#define CPIN 1
#define CW0 0
#define CPRE 5
#define PFT 1
#define WSP_D 600
#define D1 4
#define D2 4
#define D3 4
#define NSLEEP 32
#define G1_LATE 0
#define NPRE 1

namespace {

constexpr int kS = 2048, kD = 640, kF = 1536;
constexpr int NA = 10, NA2 = 9, NB = 5;
constexpr int A_SLOT = 8192, B_SLOT = 24576;
constexpr int OFF_A = 0;
constexpr int OFF_B = OFF_A + NA * A_SLOT;
constexpr int XB_PL = 2112;
constexpr int CV_KE = 4224, CV_KO = CV_KE + 4160;
constexpr int CV_SZ = CV_KO + 4160;
constexpr int OFF_CV = OFF_B + NB * B_SLOT;
constexpr int OFF_CS = OFF_CV + 2 * CV_SZ;
constexpr int OFF_XS = OFF_CS + 1536;
constexpr int OFF_BAR = OFF_XS + 512;
constexpr int BAR_AF = OFF_BAR, BAR_ST = BAR_AF + 8 * NA, BAR_XF = BAR_ST + 16, BAR_KV = BAR_XF + 16;
constexpr int BAR_BF = OFF_BAR + 128, BAR_G2 = BAR_BF + 8 * (NB + 1), BAR_XS = BAR_G2 + 8, BAR_KU = BAR_XS + 8, BAR_ZP = BAR_KU + 40, BAR_HOLD = BAR_ZP + 8, BAR_WO = BAR_HOLD + 8;
constexpr int BAR_AE = OFF_BAR + 256, BAR_BE = BAR_AE + 8 * NA;
constexpr int BAR_YT = BAR_KU + 24;
constexpr int OFF_TAG = OFF_CS - 32;
constexpr int OFF_BIAS = OFF_BAR + 384;
constexpr int SMEM_BYTES = OFF_BIAS + 128;
static_assert(SMEM_BYTES <= 232448, "smem");
constexpr int NB_WGA = 1, NB_WGC = 2, NB_G1 = 3, NB_WO = 4, NB_CD = 5, NB_Z = 6, NB_WGB = 7;

constexpr int CNT_Z = 0, CNT_Y = 1, CNT_KV = 32, CNT_WO = 36;
struct Scratch {
  uint8_t kvx[kD * 4096];
  uint8_t z2[4 * 32 * 24576];
  uint8_t h[32 * 12 * 8192];
  uint8_t wo[4 * 12 * 20480];
  uint8_t y[kD * 4096];
  uint4 xstat[kS];
  uint4 zstat[kS * 4];
  uint2 colsum[kF];
  uint32_t cnt[2 * 32];
  uint32_t hflag[32 * 32];
  uint32_t epoch[136];
};
__device__ __align__(1024) Scratch g_scr;
#define STAMP(i)
#define STAMP2(i)
#define STAMPW(i)

struct Params {
  Scratch* scr;
  int by_smid;
  const __nv_bfloat16 *k, *v, *shift, *ssmk, *ssmD, *wsp, *bsp, *wout;
  __nv_bfloat16* out;
  CUtensorMap tmX, tmW, tmWsp, tmY, tmKV;
};

__device__ __forceinline__ uint64_t mkdesc(uint32_t addr, uint32_t lbo, uint32_t sbo, uint32_t swz) {
  return (uint64_t)((addr & 0x3FFFF) >> 4) | ((uint64_t)(lbo >> 4) << 16) | ((uint64_t)(sbo >> 4) << 32) | ((uint64_t)swz << 62);
}
#define WG_FENCE() asm volatile("wgmma.fence.sync.aligned;" ::: "memory")
#define WG_COMMIT() asm volatile("wgmma.commit_group.sync.aligned;" ::: "memory")
#define WG_WAIT(n) asm volatile("wgmma.wait_group.sync.aligned %0;" ::"n"(n) : "memory")
template <int N> __device__ __forceinline__ void acc_fence(float* d) {
#pragma unroll
  for (int i = 0; i < N; i++) asm volatile("" : "+f"(d[i])::"memory");
}
__device__ __forceinline__ void mbar_init(uint32_t bar, int cnt) { asm volatile("mbarrier.init.shared::cta.b64 [%0], %1;" ::"r"(bar), "r"(cnt) : "memory"); }
__device__ __forceinline__ void mbar_expect(uint32_t bar, uint32_t bytes) { asm volatile("mbarrier.arrive.expect_tx.shared::cta.b64 _, [%0], %1;" ::"r"(bar), "r"(bytes) : "memory"); }
__device__ __forceinline__ void mbar_arrive(uint32_t bar) { asm volatile("mbarrier.arrive.shared::cta.b64 _, [%0];" ::"r"(bar) : "memory"); }
__device__ __forceinline__ void mbar_arrive_if(uint32_t bar, bool c) {
  asm volatile("{\n.reg .pred p;\nsetp.ne.u32 p, %1, 0;\n@p mbarrier.arrive.shared::cta.b64 _, [%0];\n}\n" ::"r"(bar), "r"((uint32_t)c) : "memory");
}
__device__ __forceinline__ bool mbar_try(uint32_t bar, uint32_t parity) {
  uint32_t ok;
  asm volatile("{\n.reg .pred p;\nmbarrier.try_wait.parity.shared::cta.b64 p, [%1], %2;\nselp.u32 %0, 1, 0, p;\n}\n" : "=r"(ok) : "r"(bar), "r"(parity) : "memory");
  return ok;
}
__device__ __forceinline__ bool mbar_test(uint32_t bar, uint32_t parity) {
  uint32_t ok;
  asm volatile("{\n.reg .pred p;\nmbarrier.test_wait.parity.shared::cta.b64 p, [%1], %2;\nselp.u32 %0, 1, 0, p;\n}\n" : "=r"(ok) : "r"(bar), "r"(parity) : "memory");
  return ok;
}
__device__ __forceinline__ void die() { asm volatile("st.volatile.global.u32 [%0], %1;" ::"l"(0ull), "r"(0) : "memory"); }
__device__ __forceinline__ void spin_guard(uint32_t& n) { if (++n == (1u << 22)) die(); }
__device__ __forceinline__ void mbar_wait(uint32_t bar, uint32_t parity) {
  uint32_t t0 = 0;
#pragma unroll 1
  while (!mbar_try(bar, parity)) spin_guard(t0);
}
__device__ __forceinline__ void mbar_wait2(uint32_t b0, uint32_t p0, uint32_t b1, uint32_t p1) {
  uint32_t t0 = 0;
#pragma unroll 1
  while (true) {
    const bool r0 = mbar_try(b0, p0), r1 = mbar_try(b1, p1);
    if (r0 && r1) break;
    spin_guard(t0);
  }
}
__device__ __forceinline__ int tid_now() { int v; asm volatile("mov.u32 %0, %%tid.x;" : "=r"(v)); return v & 127; }
__device__ __forceinline__ bool elect_one() {
  uint32_t p;
  asm volatile("{\n.reg .pred P;\nelect.sync _|P, 0xffffffff;\nselp.u32 %0, 1, 0, P;\n}\n" : "=r"(p));
  return p;
}
__device__ __forceinline__ void bar_sync(int id, int n) { asm volatile("bar.sync %0, %1;" ::"r"(id), "r"(n) : "memory"); }
__device__ __forceinline__ void bar_arrive(int id, int n) { asm volatile("bar.arrive %0, %1;" ::"r"(id), "r"(n) : "memory"); }
__device__ __forceinline__ void fence_async_smem() { asm volatile("fence.proxy.async.shared::cta;" ::: "memory"); }
__device__ __forceinline__ void bulk_g2s(uint32_t dst, const void* src, uint32_t bytes, uint32_t bar) {
  asm volatile("cp.async.bulk.shared::cluster.global.mbarrier::complete_tx::bytes [%0], [%1], %2, [%3];" ::"r"(dst), "l"(src), "r"(bytes), "r"(bar) : "memory");
}
__device__ __forceinline__ void bulk_s2g(void* dst, uint32_t src, uint32_t bytes) {
  asm volatile("cp.async.bulk.global.shared::cta.bulk_group [%0], [%1], %2;" ::"l"(dst), "r"(src), "r"(bytes) : "memory");
}
__device__ __forceinline__ void tma2d(uint32_t dst, const CUtensorMap* m, int c0, int c1, uint32_t bar) {
  asm volatile("cp.async.bulk.tensor.2d.shared::cluster.global.mbarrier::complete_tx::bytes [%0], [%1, {%3, %4}], [%2];" ::"r"(dst), "l"(m), "r"(bar), "r"(c0), "r"(c1) : "memory");
}
__device__ __forceinline__ void tma3d(uint32_t dst, const CUtensorMap* m, int c0, int c1, int c2, uint32_t bar) {
  asm volatile("cp.async.bulk.tensor.3d.shared::cluster.global.mbarrier::complete_tx::bytes [%0], [%1, {%3, %4, %5}], [%2];" ::"r"(dst), "l"(m), "r"(bar), "r"(c0), "r"(c1), "r"(c2) : "memory");
}
__device__ __forceinline__ void st_release(uint32_t* p, uint32_t v) { asm volatile("st.release.gpu.global.u32 [%0], %1;" ::"l"(p), "r"(v) : "memory"); }
__device__ __forceinline__ uint4 ld_ll4(const void* p) {
  uint64_t a, b;
  asm volatile("ld.relaxed.gpu.global.v2.u64 {%0,%1}, [%2];" : "=l"(a), "=l"(b) : "l"(p) : "memory");
  return make_uint4((uint32_t)a, (uint32_t)(a >> 32), (uint32_t)b, (uint32_t)(b >> 32));
}
__device__ __forceinline__ void st_ll4(void* p, uint32_t a, uint32_t b, uint32_t c, uint32_t d) {
  asm volatile("st.relaxed.gpu.global.v2.u64 [%0], {%1,%2};" ::"l"(p), "l"(a | ((uint64_t)b << 32)), "l"(c | ((uint64_t)d << 32)) : "memory");
}
__device__ __forceinline__ void st_ll2(void* p, uint32_t a, uint32_t b) { asm volatile("st.relaxed.gpu.global.u64 [%0], %1;" ::"l"(p), "l"(a | ((uint64_t)b << 32)) : "memory"); }
__device__ __forceinline__ void wgmma_colsum(float* d, uint64_t da, uint64_t db) {
  asm volatile("{\n.reg .pred p;\nsetp.ne.b32 p, 1, 0;\nwgmma.mma_async.sync.aligned.m64n8k16.f32.bf16.bf16 {%0, %1, %2, %3}, %4, %5, p, 1, 1, 1, 0;\n}\n"
               : "+f"(d[0]), "+f"(d[1]), "+f"(d[2]), "+f"(d[3]) : "l"(da), "l"(db));
}
__device__ __forceinline__ void prefetch_l2(const void* p) { asm volatile("prefetch.global.L2 [%0];" ::"l"(p)); }
__device__ __forceinline__ void pace(uint32_t& t, uint32_t dt) {
  t += dt;
  while ((int32_t)((uint32_t)clock() - t) < 0) { if (NSLEEP) __nanosleep(NSLEEP); }
}
__device__ __forceinline__ void red_release(uint32_t* p) { asm volatile("red.release.gpu.global.add.u32 [%0], 1;" ::"l"(p) : "memory"); }
__device__ __forceinline__ uint4 ldg4(const void* p) { uint4 v; asm volatile("ld.global.v4.u32 {%0,%1,%2,%3}, [%4];" : "=r"(v.x), "=r"(v.y), "=r"(v.z), "=r"(v.w) : "l"(p) : "memory"); return v; }
__device__ __forceinline__ uint32_t ldg1(const void* p) { uint32_t v; asm volatile("ld.global.u32 %0, [%1];" : "=r"(v) : "l"(p) : "memory"); return v; }
__device__ __forceinline__ void stg4_if(void* p, uint32_t a, uint32_t b, uint32_t c, uint32_t d, bool on) {
  asm volatile("{\n.reg .pred p;\nsetp.ne.u32 p, %5, 0;\n@p st.global.v4.u32 [%0], {%1,%2,%3,%4};\n}\n" ::"l"(p), "r"(a), "r"(b), "r"(c), "r"(d), "r"((uint32_t)on) : "memory");
}
template <int OFF> __device__ __forceinline__ uint32_t lds32(uint32_t a) { uint32_t v; asm volatile("ld.shared.u32 %0, [%1+%2];" : "=r"(v) : "r"(a), "n"(OFF)); return v; }
__device__ __forceinline__ uint4 lds128(uint32_t a) { uint4 v; asm volatile("ld.shared.v4.u32 {%0,%1,%2,%3}, [%4];" : "=r"(v.x), "=r"(v.y), "=r"(v.z), "=r"(v.w) : "r"(a) : "memory"); return v; }
__device__ __forceinline__ float2 lds64f(uint32_t a) { float2 v; asm volatile("ld.shared.v2.f32 {%0,%1}, [%2];" : "=f"(v.x), "=f"(v.y) : "r"(a) : "memory"); return v; }
__device__ __forceinline__ void sts64f(uint32_t a, float x, float y) { asm volatile("st.shared.v2.f32 [%0], {%1,%2};" ::"r"(a), "f"(x), "f"(y) : "memory"); }
__device__ __forceinline__ void sts32(uint32_t a, uint32_t x) { asm volatile("st.shared.u32 [%0], %1;" ::"r"(a), "r"(x) : "memory"); }
__device__ __forceinline__ void sts128(uint32_t a, uint32_t x, uint32_t y, uint32_t z, uint32_t w) { asm volatile("st.shared.v4.u32 [%0], {%1,%2,%3,%4};" ::"r"(a), "r"(x), "r"(y), "r"(z), "r"(w) : "memory"); }
__device__ __forceinline__ void stsm4(uint32_t a, uint32_t r0, uint32_t r1, uint32_t r2, uint32_t r3) {
  asm volatile("stmatrix.sync.aligned.m8n8.x4.shared.b16 [%0], {%1,%2,%3,%4};" ::"r"(a), "r"(r0), "r"(r1), "r"(r2), "r"(r3) : "memory");
}
__device__ __forceinline__ void stsm4t(uint32_t a, uint32_t r0, uint32_t r1, uint32_t r2, uint32_t r3) {
  asm volatile("stmatrix.sync.aligned.m8n8.x4.trans.shared.b16 [%0], {%1,%2,%3,%4};" ::"r"(a), "r"(r0), "r"(r1), "r"(r2), "r"(r3) : "memory");
}
__device__ __forceinline__ void ldsm4t(uint32_t* r, uint32_t a) {
  asm volatile("ldmatrix.sync.aligned.m8n8.x4.trans.shared.b16 {%0,%1,%2,%3}, [%4];" : "=r"(r[0]), "=r"(r[1]), "=r"(r[2]), "=r"(r[3]) : "r"(a) : "memory");
}
__device__ __forceinline__ uint32_t pack2(float lo, float hi) { uint32_t r; asm("cvt.rn.bf16x2.f32 %0, %1, %2;" : "=r"(r) : "f"(hi), "f"(lo)); return r; }
__device__ __forceinline__ float bf_lo(uint32_t u) { return __uint_as_float(u << 16); }
__device__ __forceinline__ float bf_hi(uint32_t u) { return __uint_as_float(u & 0xffff0000u); }
__device__ __forceinline__ float tanh_fast(float x) { float y; asm("tanh.approx.f32 %0, %1;" : "=f"(y) : "f"(x)); return y; }
__device__ __forceinline__ uint32_t hmul2(uint32_t a, uint32_t b) { uint32_t r; asm("mul.rn.bf16x2 %0, %1, %2;" : "=r"(r) : "r"(a), "r"(b)); return r; }
__device__ __forceinline__ uint32_t hfma2(uint32_t a, uint32_t b, uint32_t c) { uint32_t r; asm("fma.rn.bf16x2 %0, %1, %2, %3;" : "=r"(r) : "r"(a), "r"(b), "r"(c)); return r; }
__device__ __forceinline__ uint32_t prmt(uint32_t a, uint32_t b, uint32_t s) { return __byte_perm(a, b, s); }

__device__ __forceinline__ uint32_t ld_relaxed(const uint32_t* p) { uint32_t v; asm volatile("ld.relaxed.gpu.global.u32 %0, [%1];" : "=r"(v) : "l"(p) : "memory"); return v; }
__device__ __forceinline__ void acquire_fence() { asm volatile("fence.acquire.gpu;\nfence.proxy.async.global;" ::: "memory"); }
__device__ __forceinline__ uint32_t load_epoch(const Params& p, int idx, int lane) { return ld_relaxed(&p.scr->epoch[idx + (((lane * lane) & 3) == 2 ? 1 : 0)]); }
__device__ __forceinline__ void poll_flags4(const uint32_t* flags, uint32_t tag, int lane) {
  uint32_t t0 = 0;
#pragma unroll 1
  while (!__all_sync(0xffffffff, ld_relaxed(flags + (lane & 3) * 8) == tag)) spin_guard(t0);
  acquire_fence();
}
__device__ __forceinline__ void poll_counter(const uint32_t* cnt, uint32_t target) {
  uint32_t t0 = 0;
#pragma unroll 1
  while (!__all_sync(0xffffffff, ld_relaxed(cnt) == target)) spin_guard(t0);
  acquire_fence();
}

__device__ __forceinline__ int g3_block(int cb, int it) { return it < 3 ? cb * 3 + it : (it - 3 < cb * 3 ? it - 3 : it); }
__device__ __forceinline__ void reset_sector(uint32_t* f) { st_ll4(f, 0, 0, 0, 0); st_ll4(f + 4, 0, 0, 0, 0); }

template <int N, bool A_SWZ, int B_MODE, int DEPTH>
__device__ __forceinline__ void gemm_loop(float* d, uint32_t sb, int nkb, int sa, int pa, int b0, uint32_t boff, int relA, int relB, int tid, bool arrive_g1) {
  constexpr uint32_t A_STEP = A_SWZ ? 2 : 128;
  constexpr uint32_t B_STEP = B_MODE == 0 ? 128 : (B_MODE == 1 ? 384 : 320);
  const uint64_t da0 = A_SWZ ? mkdesc(sb + OFF_A, 16, 1024, 1) : mkdesc(sb + OFF_A, 1024, 128, 0);
  const uint64_t db0 = B_MODE == 0 ? mkdesc(sb + OFF_B + boff, 8192, 1024, 1) : mkdesc(sb + OFF_B + boff, B_MODE == 1 ? 3072 : 2560, 128, 0);
  constexpr int MODA = B_MODE == 0 ? NA : NA2;
  constexpr int MODB = B_MODE == 2 ? 6 : NB;
  int sbk = b0 % MODB, pb = (b0 / MODB) & 1;
  auto boffs = [](int s_) { return B_MODE == 2 ? (s_ == 5 ? 0 : s_ + 1) * (20480 >> 4) : s_ * (B_SLOT >> 4); };
  uint32_t rel = 0;
  uint64_t da = da0 + sa * (A_SLOT >> 4), db = db0 + boffs(sbk);
  const bool doR = tid < 2 ? tid < relA : tid - 2 < relB;
  mbar_wait2(sb + BAR_AF + 8 * sa, pa, sb + BAR_BF + 8 * sbk, pb);
#pragma unroll 1
  for (int it = 0; it < nkb; it++) {
    WG_FENCE();
    WG<N>::ss(d, da, db, 1);
    const uint32_t prel = rel;
    rel = sb + BAR_AE + 8 * (tid < 2 ? sa : sbk + NA);
    if (++sa == MODA) { sa = 0; pa ^= 1; }
    if (++sbk == MODB) { sbk = 0; pb ^= 1; }
    if (DEPTH == 1) { WG_COMMIT(); WG_WAIT(1); }
    WG<N>::ss(d, da + A_STEP, db + B_STEP, 1);
    WG_COMMIT();
    WG_WAIT(1);
    if (EARLY == 1) mbar_arrive_if(prel, doR && it != 0);
    WG<N>::ss(d, da + 2 * A_STEP, db + 2 * B_STEP, 1);
    if (DEPTH == 1) WG_COMMIT();
    if (EARLY != 1) mbar_arrive_if(prel, doR && it != 0);
    const bool r0 = mbar_test(sb + BAR_AF + 8 * sa, pa), r1 = mbar_test(sb + BAR_BF + 8 * sbk, pb);
    const uint64_t da3 = da + 3 * A_STEP, db3 = db + 3 * B_STEP;
    da = da0 + sa * (A_SLOT >> 4); db = db0 + boffs(sbk);
    if (DEPTH == 1) WG_WAIT(1);
    WG<N>::ss(d, da3, db3, 1);
    WG_COMMIT();
    if (it + 1 < nkb) {
      if (!(r0 && r1)) {
        mbar_wait2(sb + BAR_AF + 8 * sa, pa, sb + BAR_BF + 8 * sbk, pb);
      }
    } else if (arrive_g1) {
      bar_arrive(NB_G1, 256);
    }
    if (DEPTH == 2) WG_WAIT(1);
  }
  WG_WAIT(0);
  acc_fence<N / 2>(d);
  mbar_arrive_if(rel, doR);
}

__device__ __forceinline__ void gelu_tile(const float* d, uint32_t* z, float* st, uint32_t cs_addr, float2 s0, float2 s1) {
  const float kA = 0.7978845608028654f, kB = 0.7978845608028654f * 0.044715f;
  const float c1a = kA * s0.y, c3a = kB * s0.y * s0.y * s0.y, ma = -s0.x;
  const float c1b = kA * s1.y, c3b = kB * s1.y * s1.y * s1.y, mb = -s1.x;
  float acc[8];
#pragma unroll
  for (int i = 0; i < 8; i++) acc[i] = 0.f;
#pragma unroll
  for (int j = 0; j < 24; j++) {
    const float2 cs = lds64f(cs_addr + j * 32);
    float r[4];
#pragma unroll
    for (int e = 0; e < 4; e++) {
      const float c = (e & 1) ? cs.y : cs.x;
      const float v = fmaf(e < 2 ? ma : mb, c, d[4 * j + e]);
      const float a = v * fmaf(v * v, e < 2 ? c3a : c3b, e < 2 ? c1a : c1b);
      r[e] = fmaf(v, tanh_fast(a), v);
      acc[e] += r[e];
      acc[4 + e] = fmaf(r[e], r[e], acc[4 + e]);
    }
    z[2 * j] = pack2(r[0], r[1]);
    z[2 * j + 1] = pack2(r[2], r[3]);
  }
  st[0] = acc[0] + acc[1]; st[1] = acc[4] + acc[5]; st[2] = acc[2] + acc[3]; st[3] = acc[6] + acc[7];
}

template <int Q> __device__ __forceinline__ void conv_load(uint32_t* a, uint32_t ab) {
  a[0] = lds32<512 * Q>(ab);       a[1] = lds32<512 * Q + 256>(ab);  a[2] = lds32<512 * Q + 16>(ab);   a[3] = lds32<512 * Q + 272>(ab);
  a[4] = lds32<512 * Q + 32>(ab);  a[5] = lds32<512 * Q + 288>(ab);  a[6] = lds32<512 * Q + 48>(ab);   a[7] = lds32<512 * Q + 304>(ab);
  a[8] = lds32<512 * Q + 64>(ab);  a[9] = lds32<512 * Q + 320>(ab);  a[10] = lds32<512 * Q + 80>(ab);  a[11] = lds32<512 * Q + 336>(ab);
  a[12] = lds32<512 * Q + 96>(ab); a[13] = lds32<512 * Q + 352>(ab); a[14] = lds32<512 * Q + 112>(ab); a[15] = lds32<512 * Q + 368>(ab);
}
template <int Q, int L> __device__ __forceinline__ void conv_step(float* d, uint32_t (*a)[16], uint32_t ab, uint64_t db) {
  WG_FENCE();
#pragma unroll
  for (int s = 0; s < 4; s++) WG<128 - 16 * Q>::rs(d, a[Q] + 4 * s, db + s + 16 * Q);
  WG_COMMIT();
  if (CPIN) WG_WAIT(1);
  if (L >= 0) conv_load<(L >= 0 ? L : 0)>(a[L >= 0 ? L : 0], ab);
  if (CW0 || Q == 0) WG_WAIT(0);
}

__device__ __forceinline__ void final_load_x(uint32_t (*xw)[10], uint32_t xt, int col0, int w, int lane) {
  const int g = lane >> 2, t = lane & 3;
  const int c0 = (col0 >> 3) + t, c1 = c0 + 4, c2 = (col0 >> 3) + 8 + (t >> 1);
  const uint32_t r0 = xt + (w * 16 + g) * 128;
#pragma unroll
  for (int r = 0; r < 2; r++) {
    const uint4 u = lds128(r0 + r * 1024 + (c0 >> 3) * A_SLOT + (((c0 ^ g) & 7) << 4)), v = lds128(r0 + r * 1024 + (c1 >> 3) * A_SLOT + (((c1 ^ g) & 7) << 4));
    const float2 z = lds64f(r0 + r * 1024 + (c2 >> 3) * A_SLOT + (((c2 ^ g) & 7) << 4) + (t & 1) * 8);
    xw[r][0] = u.x; xw[r][1] = u.y; xw[r][2] = u.z; xw[r][3] = u.w;
    xw[r][4] = v.x; xw[r][5] = v.y; xw[r][6] = v.z; xw[r][7] = v.w;
    xw[r][8] = __float_as_uint(z.x); xw[r][9] = __float_as_uint(z.y);
  }
}
__device__ __forceinline__ void final_gate(float* d, const uint32_t (*xw)[10], float2 s0, float2 s1) {
  const float ra = s0.y, na = -s0.x * s0.y, rb_ = s1.y, nb = -s1.x * s1.y, ca = 0.25f * ra, cb = 0.25f * rb_;
#pragma unroll
  for (int i = 0; i < 40; i++) {
    const int r = (i >> 1) & 1;
    const float xf = (i & 1) ? bf_hi(xw[r][i >> 2]) : bf_lo(xw[r][i >> 2]);
    const float h = d[i] * (r ? cb : ca);
    d[i] = fmaf(h, tanh_fast(h), h) * fmaf(xf, r ? rb_ : ra, r ? nb : na);
  }
}
__device__ __forceinline__ void final_out(const float* d, const uint32_t (*xw)[10], uint32_t yt, __nv_bfloat16* o0, int w, int lane) {
  const int r8 = lane & 7, mi = lane >> 3, t = lane & 3;
  const uint32_t ya = yt + ((mi >> 1) * 8 + r8) * 128 + (((2 * w + (mi & 1)) ^ r8) << 4);
  uint32_t o[2][10];
#pragma unroll
  for (int j = 0; j < 10; j += 2) {
    uint32_t y[4];
    ldsm4t(y, ya + j * 1024);
#pragma unroll
    for (int e = 0; e < 4; e++) {
      const uint32_t xv = xw[e & 1][j + (e >> 1)];
      o[e & 1][j + (e >> 1)] = pack2(fmaf(d[4 * j + 2 * e], bf_lo(y[e]), bf_lo(xv)), fmaf(d[4 * j + 2 * e + 1], bf_hi(y[e]), bf_hi(xv)));
    }
#pragma unroll
    for (int r = 0; r < 2; r++) {
      __nv_bfloat16* q = o0 + r * 8 * kD;
      if (j == 2) stg4_if(q + t * 8, o[r][0], o[r][1], o[r][2], o[r][3], true);
      if (j == 6) stg4_if(q + 32 + t * 8, o[r][4], o[r][5], o[r][6], o[r][7], true);
      if (j == 8) asm volatile("st.global.v2.u32 [%0], {%1,%2};" ::"l"(q + 64 + t * 4), "r"(o[r][8]), "r"(o[r][9]) : "memory");
    }
  }
}

struct Taps { uint4 r0, r1; uint32_t n0, n1, dd; };
__device__ __forceinline__ void load_taps(Taps& k, const Params& p, int ch, int tid) {
  const uint4* kp = (const uint4*)(p.ssmk + (size_t)ch * kS);
  k.r0 = ldg4(kp + tid); k.r1 = ldg4(kp + 128 + tid);
  k.n0 = ldg1(kp + tid + 1); k.n1 = tid < 127 ? ldg1(kp + 129 + tid) : 0u;
  k.dd = __bfloat16_as_ushort(p.ssmD[ch]);
}
__device__ __forceinline__ void load_convx(const Params& p, uint32_t cv, uint32_t bar, int ch) {
  mbar_expect(bar, 4096);
  bulk_g2s(cv, p.scr->kvx + (size_t)ch * 4096, 2048, bar);
  bulk_g2s(cv + XB_PL, p.scr->kvx + (size_t)ch * 4096 + 2048, 2048, bar);
}
#define CW 3
#define CSTAMP(j)
__device__ __forceinline__ void zero_pads(uint32_t cv, int lane) {
  if (lane < 8) sts128(cv + (lane >> 2) * XB_PL + 2048 + (lane & 3) * 16, 0, 0, 0, 0);
  else if (lane < 12) sts128(cv + ((lane & 2) ? CV_KO : CV_KE) + (lane & 1) * 16, 0, 0, 0, 0);
  fence_async_smem();
  __syncwarp();
}
__device__ __forceinline__ int y_row(int c) {
  const int cc = c % 80;
  return c - cc + (cc & 1) + (cc < 64 ? (cc & 32) + ((cc >> 1) & 3) * 8 + ((cc >> 3) & 3) * 2 : 64 + ((cc >> 1) & 1) * 8 + ((cc >> 2) & 3) * 2);
}
__device__ __forceinline__ void conv_service(const Params& p, uint32_t sb, int h, int ch, bool more) {
  bar_sync(NB_WGA + 8 + h, 160);
  if (more && elect_one()) load_convx(p, sb + OFF_CV + (1 - h) * CV_SZ, sb + BAR_XF + 8 * h, ch + 128);
  uint8_t* dst = p.scr->y + (size_t)y_row(ch) * 4096;
  bar_sync(NB_WGA + 8 + h, 160);
  if (elect_one()) {
    bulk_s2g(dst, sb + OFF_A + 9 * A_SLOT + h * 4096, 4096);
    asm volatile("cp.async.bulk.commit_group;\ncp.async.bulk.wait_group 0;" ::: "memory");
  }
  __syncwarp();
}
__device__ __forceinline__ void conv_worker(const Params& p, Taps& k, uint32_t cv, uint32_t yb0,
                                            uint32_t xbar, int nbar, int ch0, int n, uint32_t holdbar, int w, int lane,
                                            int tid, int st0, int rb, int cb) {
  const int g = lane >> 2, t = lane & 3, w0 = w & 1, w1 = w >> 1;
  const uint32_t ab = cv + ((g & 1) ? CV_KE : CV_KO) + 32 + 2 * (64 * w0 + 8 * w1 + ((g - 15) & ~1) + 2 * t);
  const uint32_t scA = cv + (w1 ? CV_KO : CV_KE) + 32, scB = scA + 2048;
  const int dl = (t >> 1) ^ 1, col = lane & 7, mi = lane >> 3;
  if (n == 2) mbar_wait(xbar, 0);
  STAMPW(st0 + 3);
#pragma unroll 1
  for (int i = 0; i < n; i++) {
    if (tid == 0) {
      k.r0.x = (k.r0.x & 0xffff0000u) | (pack2(bf_lo(k.r0.x) + bf_lo(k.dd), 0.f) & 0xffffu);
      sts32(cv + CV_KO + 28, k.r0.x << 16);
    }
    sts128(cv + CV_KE + 32 + tid * 16, k.r0.x, k.r0.y, k.r0.z, k.r0.w);
    sts128(cv + CV_KO + 32 + tid * 16, prmt(k.r0.x, k.r0.y, 0x5432), prmt(k.r0.y, k.r0.z, 0x5432), prmt(k.r0.z, k.r0.w, 0x5432), prmt(k.r0.w, k.n0, 0x5432));
    sts128(cv + CV_KE + 2080 + tid * 16, k.r1.x, k.r1.y, k.r1.z, k.r1.w);
    sts128(cv + CV_KO + 2080 + tid * 16, prmt(k.r1.x, k.r1.y, 0x5432), prmt(k.r1.y, k.r1.z, 0x5432), prmt(k.r1.z, k.r1.w, 0x5432), prmt(k.r1.w, k.n1, 0x5432));
    if (i + 1 < n) load_taps(k, p, ch0 + (i + 1) * 128, tid);
    bar_sync(nbar, 128);
    CSTAMP(0);
    const uint64_t db = mkdesc(cv + (i & 0x1000), XB_PL, 128, 0);
    float d[64];
    uint32_t a[8][16];
    conv_load<7>(a[7], ab);
    if (CPRE > 1) conv_load<6>(a[6], ab);
    if (CPRE > 2) conv_load<5>(a[5], ab);
    if (CPRE > 3) conv_load<4>(a[4], ab);
#pragma unroll
    for (int j = 0; j < 64; j++) d[j] = 0.f;
    mbar_wait(xbar, i & 1);
    if (i + 1 == n) mbar_wait(holdbar, 0);
    CSTAMP(1);
    if (CPRE == 1) {
      conv_step<7, 6>(d, a, ab, db); conv_step<6, 5>(d, a, ab, db); conv_step<5, 4>(d, a, ab, db); conv_step<4, 3>(d, a, ab, db);
      conv_step<3, 2>(d, a, ab, db); conv_step<2, 1>(d, a, ab, db); conv_step<1, 0>(d, a, ab, db); conv_step<0, -1>(d, a, ab, db);
    } else if (CPRE == 3) {
      conv_step<7, -1>(d, a, ab, db); conv_step<6, 4>(d, a, ab, db); conv_step<5, 3>(d, a, ab, db); conv_step<4, 2>(d, a, ab, db);
      conv_step<3, 1>(d, a, ab, db); conv_step<2, 0>(d, a, ab, db); conv_step<1, -1>(d, a, ab, db); conv_step<0, -1>(d, a, ab, db);
    } else if (CPRE == 4) {
      conv_step<7, -1>(d, a, ab, db); conv_step<6, -1>(d, a, ab, db); conv_step<5, 3>(d, a, ab, db); conv_step<4, 2>(d, a, ab, db);
      conv_step<3, 1>(d, a, ab, db); conv_step<2, 0>(d, a, ab, db); conv_step<1, -1>(d, a, ab, db); conv_step<0, -1>(d, a, ab, db);
    } else {
      conv_step<7, -1>(d, a, ab, db); conv_step<6, -1>(d, a, ab, db); conv_step<5, -1>(d, a, ab, db); conv_step<4, 3>(d, a, ab, db);
      conv_step<3, 2>(d, a, ab, db); conv_step<2, 1>(d, a, ab, db); conv_step<1, 0>(d, a, ab, db); conv_step<0, -1>(d, a, ab, db);
    }
    acc_fence<64>(d);
    CSTAMP(2);
    bar_sync(nbar + 8, 160);
    float E[16][2];
#pragma unroll
    for (int j = 0; j < 15; j++) { E[j][0] = d[4 * j] + d[4 * j + 6]; E[j][1] = d[4 * j + 1] + d[4 * j + 7]; }
    E[15][0] = d[60]; E[15][1] = d[61];
    if (w0 == 0) {
#pragma unroll
      for (int j = 8; j < 16; j++) sts64f(scA + (j - 8) * 256 + lane * 8, E[j][0], E[j][1]);
    } else {
      const uint32_t a = scB - dl * 256 + (lane ^ 2) * 8;
#pragma unroll
      for (int j = 1; j < 8; j++) sts64f(a + j * 256, E[j][0], E[j][1]);
      sts64f(scB + (dl ? 7 * 256 : 0) + (lane ^ 2) * 8, dl ? E[8][0] : E[0][0], dl ? E[8][1] : E[0][1]);
    }
    bar_sync(nbar, 128);
    CSTAMP(3);
    uint32_t pk[8];
    if (w0 == 0) {
#pragma unroll
      for (int j = 0; j < 8; j++) { const float2 v = lds64f(scB + j * 256 + lane * 8); pk[j] = pack2(E[j][0] + v.x, E[j][1] + v.y); }
      const uint32_t ya = yb0 + 32 * (127 - (8 * mi + col)) + 16 * w1;
      stsm4t(ya, pk[0], pk[1], pk[2], pk[3]);
      stsm4t(ya - 1024, pk[4], pk[5], pk[6], pk[7]);
    } else {
      const uint32_t a0 = scA - dl * 256 + (lane ^ 2) * 8;
#pragma unroll
      for (int j = 9; j < 16; j++) { const float2 v = lds64f(a0 + (j - 8) * 256); pk[j - 8] = pack2(E[j][0] + v.x, E[j][1] + v.y); }
      const float2 v = lds64f(scA + (dl ? 7 * 256 : 0) + (lane ^ 2) * 8);
      pk[0] = pack2((dl ? 0.f : E[8][0]) + v.x, (dl ? 0.f : E[8][1]) + v.y);
      const uint32_t yb = yb0 + 32 * (127 - (92 + 8 * mi + col)) + 16 * w1;
      const uint32_t ya = (mi == 0 && col < 4) ? yb0 + 32 * (3 - col) + 16 * w1 : yb + 1024;
      stsm4t(ya, pk[0], pk[1], pk[2], pk[3]);
      stsm4t(yb, pk[4], pk[5], pk[6], pk[7]);
    }
    CSTAMP(4);
    fence_async_smem();
    bar_sync(nbar + 8, 160);
    CSTAMP(5);
    STAMPW(st0 + i);
    if (n == 2 && i == 0) {
      const int u = (tid >> 3) % 5, kg = rb * 3 + (tid < 120 ? (tid >> 3) / 5 : 0), c = u < 4 ? (u >> 1) * 10 + (u & 1) * 4 : 8, o2 = u < 4 ? 2 : 10;
      const uint4* wp = (const uint4*)(p.wout + (size_t)(kg * 8 + (tid & 7)) * kD + cb * 160) + c;
      const uint4 w0 = ldg4(wp), w1 = ldg4(wp + 1), w2 = ldg4(wp + o2), w3 = ldg4(wp + o2 + 1);
      uint8_t* dst = p.scr->wo + (size_t)cb * (12 * 20480) + kg * 2560 + c * 128 + (tid & 7) * 16;
      const bool f = u < 4, on = tid < 120;
      stg4_if(dst, w0.x, f ? w1.x : w0.z, f ? w2.x : w1.x, f ? w3.x : w1.z, on);
      stg4_if(dst + 128, w0.y, f ? w1.y : w0.w, f ? w2.y : w1.y, f ? w3.y : w1.w, on);
      stg4_if(dst + o2 * 128, f ? w0.z : w2.x, f ? w1.z : w2.z, f ? w2.z : w3.x, w3.z, on);
      stg4_if(dst + o2 * 128 + 128, f ? w0.w : w2.y, f ? w1.w : w2.w, f ? w2.w : w3.y, w3.w, on);
      bar_arrive(NB_WO, 160);
    }
  }
}

struct KvRegs { uint32_t k[11], v[8]; uint4 sh; };
__device__ __forceinline__ void kv_load(KvRegs& q, const __nv_bfloat16* kp, const __nv_bfloat16* vp, const __nv_bfloat16* sp, bool halo) {
#pragma unroll
  for (int i = 0; i < 11; i++) q.k[i] = (i >= 3 || halo) ? ldg1(kp + i * kD) : 0u;
#pragma unroll
  for (int i = 0; i < 8; i++) q.v[i] = ldg1(vp + i * kD);
  q.sh = ldg4(sp);
}
__device__ __forceinline__ void kv_unit(const KvRegs& q, uint32_t oa) {
  const uint32_t w0 = prmt(q.sh.x, q.sh.z, 0x5410), w1 = prmt(q.sh.x, q.sh.z, 0x7632), w2 = prmt(q.sh.y, q.sh.w, 0x5410), w3 = prmt(q.sh.y, q.sh.w, 0x7632);
  uint32_t r[8];
#pragma unroll
  for (int i = 0; i < 8; i++) r[i] = hmul2(hfma2(q.k[i + 3], w0, hfma2(q.k[i + 2], w1, hfma2(q.k[i + 1], w2, hmul2(q.k[i], w3)))), q.v[i]);
  sts128(oa, prmt(r[7], r[6], 0x5410), prmt(r[5], r[4], 0x5410), prmt(r[3], r[2], 0x5410), prmt(r[1], r[0], 0x5410));
  sts128(oa + 2048, prmt(r[7], r[6], 0x7632), prmt(r[5], r[4], 0x7632), prmt(r[3], r[2], 0x7632), prmt(r[1], r[0], 0x7632));
}

__device__ __forceinline__ void helper_cta(const Params& p, uint32_t sb, int cb, int warp, int lane) {
  constexpr int NS = 9, ONES = NS * B_SLOT, BF = ONES + 256, BE = BF + 8 * NS;
  if (warp < NS && elect_one()) {
    mbar_init(sb + BF + 8 * warp, 1); mbar_init(sb + BE + 8 * warp, 1);
    fence_async_smem();
    if (warp == 0) { mbar_expect(sb + BF, B_SLOT); tma3d(sb, &p.tmW, 0, 0, 12 + cb * 3, sb + BF); }
  }
  if (warp == 15) { sts32(sb + ONES + lane * 4, 0x3f803f80u); sts32(sb + ONES + 128 + lane * 4, 0x3f803f80u); fence_async_smem(); }
  __syncthreads();
  if (warp == 4) {
    int s = 1, ph = 1;
    uint32_t tp = clock() + HP0;
#pragma unroll 1
    for (int it = 1; it < 20; it++) {
      if (HPD && it >= 10) pace(tp, HPD);
      mbar_wait(sb + BE + 8 * s, ph);
      if (elect_one()) { mbar_expect(sb + BF + 8 * s, B_SLOT); tma3d(sb + s * B_SLOT, &p.tmW, 0, (it < 10 ? it : it - 10) * 64, (it < 10 ? 12 : 0) + cb * 3, sb + BF + 8 * s); }
      if (++s == NS) { s = 0; ph ^= 1; }
    }
  } else if (warp < 4) {
    const uint32_t tag = load_epoch(p, 128 + cb, lane) + 1;
    const uint64_t db = mkdesc(sb + ONES, 128, 128, 0);
    uint2* dst = p.scr->colsum + cb * 192 + warp * 16 + (lane >> 2);
    if ((lane & 3) == 0) {
#pragma unroll 1
      for (int j = 0; j < 12; j++) st_ll2(dst + (j < 6 ? 768 : 0) + ((j % 6) >> 1) * 64 + (j & 1) * 8, 0, 0);
    }
    int s = 0, ph = 0;
#pragma unroll 1
    for (int part = 0; part < 2; part++) {
      float d[12];
#pragma unroll
      for (int i = 0; i < 12; i++) d[i] = 0.f;
#pragma unroll 1
      for (int it = 0; it < 10; it++) {
        mbar_wait(sb + BF + 8 * s, ph);
        const uint64_t da = mkdesc(sb + s * B_SLOT, 8192, 1024, 1);
        WG_FENCE();
#pragma unroll
        for (int j = 0; j < 12; j++) wgmma_colsum(d + 4 * (j % 3), da + (j % 3) * 512 + (j / 3) * 128, db);
        WG_COMMIT();
        WG_WAIT(1);
        mbar_arrive_if(sb + BE + 8 * (s == 0 ? NS - 1 : s - 1), threadIdx.x == 0 && (it | part) != 0);
        if (++s == NS) { s = 0; ph ^= 1; }
      }
      WG_WAIT(0);
      acc_fence<12>(d);
      if ((lane & 3) == 0) {
#pragma unroll
        for (int j = 0; j < 6; j++) st_ll2(dst + (part ? 0 : 768) + (j >> 1) * 64 + (j & 1) * 8, __float_as_uint(d[2 * j]), tag);
      }
      STAMPW(1 + part);
    }
    if (threadIdx.x == 0) *(volatile uint32_t*)&p.scr->epoch[128 + cb] = tag;
  }
}

__global__ void __launch_bounds__(512, 1) fused_kernel(const __grid_constant__ Params p) {
  extern __shared__ __align__(1024) uint8_t smem[];
  const int warp = __shfl_sync(0xffffffff, (int)(threadIdx.x >> 5), 0);
  const int lane = threadIdx.x & 31, tid = threadIdx.x & 127;
  const uint32_t sb = __shfl_sync(0xffffffff, (uint32_t)__cvta_generic_to_shared(smem), 0);
  const uint32_t tstart = clock();
  if (elect_one()) {
    if (warp < 5) asm volatile("prefetch.tensormap [%0];" ::"l"(&p.tmX + warp) : "memory");
    mbar_init(sb + OFF_BAR + 8 * warp, 1); mbar_init(sb + OFF_BAR + 128 + 8 * warp, 1); mbar_init(sb + OFF_BAR + 256 + 8 * warp, 2);
    asm volatile("fence.mbarrier_init.release.cluster;" ::: "memory");
  }
  int b = blockIdx.x;
  if (p.by_smid) asm volatile("mov.u32 %0, %%smid;" : "=r"(b));
  b = __shfl_sync(0xffffffff, b, 0);
  const int tp = b >> 1, t7 = (tp - 32) / 7;
  const int lin = tp < 32 ? ((tp & 7) ? (tp & 7) * 16 : 8) + (tp >> 3) * 2 + (b & 1)
                          : (tp < 60 ? (tp - 31 - t7 * 7) * 16 + 8 + t7 * 2 + (b & 1) : (tp < 62 ? -1 : b - 124));
  const int hcb = b & 3;
  if (lin < 0) { helper_cta(p, sb, hcb, warp, lane); return; }
  const int cb = ((lin >> 4) & 1) * 2 + ((lin >> 1) & 1), rb = (lin >> 5) * 8 + ((lin >> 2) & 3) * 2 + (lin & 1);
  const int chb = (cb >> 1) * 320 + rb * 2 + (cb & 1);
  if (elect_one()) {
    if (warp < NPRE) {
      mbar_expect(sb + BAR_AF + 8 * warp, A_SLOT);
      tma2d(sb + OFF_A + warp * A_SLOT, &p.tmX, warp * 64, rb * 64, sb + BAR_AF + 8 * warp);
      mbar_expect(sb + BAR_BF + 8 * warp, B_SLOT);
      tma3d(sb + OFF_B + warp * B_SLOT, &p.tmW, 0, warp * 64, 12 + cb * 3, sb + BAR_BF + 8 * warp);
    }
  }
  if (warp == 1) STAMP(31);
  if (sb & 1023) die();
  __syncthreads();

  if (warp >= 12) {
    asm volatile("setmaxnreg.dec.sync.aligned.u32 32;");
    const uint32_t epoch = load_epoch(p, lin, lane);
    if (warp == 12) {
#pragma unroll 1
      for (int i = NPRE; i < NA; i++) {
        if (elect_one()) {
          mbar_expect(sb + BAR_AF + 8 * i, A_SLOT);
          tma2d(sb + OFF_A + i * A_SLOT, &p.tmX, i * 64, rb * 64, sb + BAR_AF + 8 * i);
          if (i < NB) { mbar_expect(sb + BAR_BF + 8 * i, B_SLOT); tma3d(sb + OFF_B + i * B_SLOT, &p.tmW, 0, i * 64, 12 + cb * 3, sb + BAR_BF + 8 * i); }
        }
      }
      if (elect_one()) reset_sector(&p.scr->hflag[rb * 32 + cb * 8]);
      STAMP(32);
      uint32_t kvt;
      {
        const int tb = rb * 2 + (cb & 1);
        kvt = __shfl_sync(0xffffffff, (ld_relaxed(p.scr->cnt + CNT_KV + (cb >> 1)) & ~63u) + 64, 0);
        {
          uint32_t tp = tstart;
          pace(tp, KV_T0);
          mbar_arrive_if(sb + BAR_KV + 8, lane == 0);
        }
        if (ST_YIELD) mbar_wait2(sb + BAR_XS, 0, sb + BAR_ST, 0);
#pragma unroll 1
        for (int u = 0; u < 5; u++) {
          mbar_wait(sb + BAR_KU + 8 * u, 0);
          fence_async_smem();
          if (elect_one()) {
            asm volatile("cp.async.bulk.tensor.3d.global.shared::cta.bulk_group [%0, {%2, %3, %4}], [%1];\ncp.async.bulk.commit_group;" ::"l"(&p.tmKV),
                         "r"(sb + OFF_CV + CV_SZ + (u < 3 ? u : u - 3) * 4096), "r"((63 - tb) * 16), "r"((cb >> 1) * 160 + u * 32), "r"(0) : "memory");
            if (u == 1 || u == 4) asm volatile("cp.async.bulk.wait_group 0;" ::: "memory");
            if (u == 1) { mbar_arrive(sb + BAR_KU); red_release(p.scr->cnt + CNT_KV + (cb >> 1)); }
          }
          __syncwarp();
          if (u == 1) {
            STAMP(35);
            if (PFT) { const char* q = (const char*)p.ssmk + chb * 4096 + lane * 128; prefetch_l2(q); prefetch_l2(q + 64 * 4096); }
          }
        }
        zero_pads(sb + OFF_CV + CV_SZ, lane);
        if (elect_one()) { mbar_arrive(sb + BAR_KU + 8); red_release(p.scr->cnt + CNT_KV + 2 + (cb >> 1)); }
        STAMP(30);
        if (lane < 24) {
          const char* r = (const char*)p.wout + (rb * 24 + lane) * (kD * 2) + cb * 320;
          prefetch_l2(r); prefetch_l2(r + 128); prefetch_l2(r + 256);
        }
      }
      poll_counter(p.scr->cnt + CNT_KV + 2 + (cb >> 1), kvt);
      if (elect_one()) mbar_arrive(sb + BAR_KV);
      STAMP(34);
      {
        const char* q = (const char*)p.wsp + (rb * 64 + cb * 16 + (lane >> 1)) * (kS * 2) + (lane & 1) * 128;
        uint32_t tp = clock();
#pragma unroll 1
        for (int i = LEAD / 2; i < WSP_N; i++) {
          prefetch_l2(q + i * 256);
          pace(tp, WSP_D);
        }
      }
      int s, ph = 1;
      const uint32_t tag = epoch + 1;
      mbar_wait(sb + BAR_G2, 0);
      if (elect_one()) {
        bulk_s2g(p.scr->h + (size_t)(rb * 12 + cb * 3) * A_SLOT, sb + OFF_A + 5 * A_SLOT, 3 * A_SLOT);
        asm volatile("cp.async.bulk.commit_group;\ncp.async.bulk.wait_group 0;" ::: "memory");
        mbar_arrive(sb + BAR_ZP);
        st_release(&p.scr->hflag[rb * 32 + cb * 8], tag);
      }
      __syncwarp();
      STAMP(20);
      poll_flags4(p.scr->hflag + rb * 32, tag, lane);
      STAMP(37);
      s = 8;
#pragma unroll 1
      for (int it = 3; it < 12; it++) {
        mbar_wait(sb + BAR_AE + 8 * s, ph);
        if (elect_one()) { mbar_expect(sb + BAR_AF + 8 * s, A_SLOT); bulk_g2s(sb + OFF_A + s * A_SLOT, p.scr->h + (size_t)(rb * 12 + g3_block(cb, it)) * A_SLOT, A_SLOT, sb + BAR_AF + 8 * s); }
        if (++s == NA2) { s = 0; ph ^= 1; }
      }
      STAMP(21);
    } else if (warp == 13) {
      const uint32_t ztarget = __shfl_sync(0xffffffff, ld_relaxed(p.scr->cnt + CNT_Z), 0);
      int s = 0, ph = 0;
#pragma unroll 1
      for (int it = NB; it < 20; it++) {
        mbar_wait(sb + BAR_BE + 8 * s, ph);
        if (elect_one()) { mbar_expect(sb + BAR_BF + 8 * s, B_SLOT); tma3d(sb + OFF_B + s * B_SLOT, &p.tmW, 0, (it < 10 ? it : it - 10) * 64, (it < 10 ? 12 : 0) + cb * 3, sb + BAR_BF + 8 * s); }
        STAMP2(32 + it);
        if (++s == NB) { s = 0; ph ^= 1; }
      }
      mbar_wait(sb + BAR_KU + 16, 0);
#pragma unroll 1
      for (int i = 0; i < LEAD; i++) {
        mbar_wait(sb + BAR_AE + 8 * i, 0);
        if (elect_one()) { mbar_expect(sb + BAR_AF + 8 * i, A_SLOT); tma2d(sb + OFF_A + i * A_SLOT, &p.tmWsp, i * 64, rb * 64, sb + BAR_AF + 8 * i); }
      }
      mbar_wait(sb + BAR_ZP, 0);
      poll_counter(p.scr->cnt + CNT_Z, (ztarget & ~127u) + 128);
      STAMP(22);
      int sa = LEAD, pa = 0, ia = LEAD;
#pragma unroll 1
      for (int it = 0; it < 32; it++) {
        mbar_wait2(sb + BAR_BE + 8 * s, ph, sb + BAR_AE + 8 * sa, pa);
        if (elect_one()) {
          mbar_expect(sb + BAR_BF + 8 * s, B_SLOT);
          bulk_g2s(sb + OFF_B + s * B_SLOT, p.scr->z2 + (size_t)(cb * 32 + it) * B_SLOT, B_SLOT, sb + BAR_BF + 8 * s);
        }
#pragma unroll 1
        for (int j = (it < RAMP ? 0 : (it == 4 ? 1 + RAMP : 1)); j > 0 && ia < 32; j--, ia++) {
          if (it == 4) mbar_wait(sb + BAR_AE + 8 * sa, pa);
          if (elect_one()) { mbar_expect(sb + BAR_AF + 8 * sa, A_SLOT); tma2d(sb + OFF_A + sa * A_SLOT, &p.tmWsp, ia * 64, rb * 64, sb + BAR_AF + 8 * sa); }
          if (++sa == NA2) { sa = 0; pa ^= 1; }
        }
        STAMP2(52 + it);
        if (++s == NB) { s = 0; ph ^= 1; }
      }
      mbar_wait(sb + BAR_WO, 0);
      acquire_fence();
#pragma unroll 1
      for (int it = 0; it < 12; it++) {
        if (it < 6) mbar_wait(sb + BAR_BE + 8 * ((0x110443 >> (4 * it)) & 7), it < 3 ? 1 : 0);
        else mbar_wait(sb + BAR_BE + 8 * s, ph);
        if (elect_one()) {
          mbar_expect(sb + BAR_BF + 8 * s, 20480);
          bulk_g2s(sb + OFF_B + (s == 5 ? 0 : s + 1) * 20480, p.scr->wo + (size_t)(cb * 12 + g3_block(cb, it)) * 20480, 20480, sb + BAR_BF + 8 * s);
        }
        STAMP2(84 + it);
        if (++s == 6) { s = 0; ph ^= 1; }
      }
    } else if (warp == 14) {
      const uint32_t tag = epoch + 1;
      uint32_t t0 = 0;
      mbar_wait(sb + BAR_AF + 8 * (NA - 1), 0);
#pragma unroll 1
      for (int part = 0; part < 2; part++) {
#pragma unroll 1
        while (true) {
          bool ok = true;
#pragma unroll
          for (int i = 0; i < 3; i++) {
            const uint4 v = ld_ll4(&p.scr->colsum[(part ? 0 : 768) + cb * 192 + i * 64 + lane * 2]);
            ok = ok && v.y == tag && v.w == tag;
            sts64f(sb + OFF_CS + part * 768 + i * 256 + lane * 8, __uint_as_float(v.x), __uint_as_float(v.z));
          }
          if (__all_sync(0xffffffff, ok)) break;
          spin_guard(t0);
        }
        __syncwarp();
        if (lane == 0) mbar_arrive(sb + BAR_ST + 8 * part);
        if (part == 0) STAMP(27);
      }
      STAMP(38);
      bar_sync(NB_Z, 160);
      if (elect_one()) {
        bulk_s2g(p.scr->z2 + (size_t)(cb * 32 + rb) * B_SLOT, sb + OFF_A + LEAD * A_SLOT, B_SLOT);
        asm volatile("cp.async.bulk.commit_group;\ncp.async.bulk.wait_group 0;" ::: "memory");
        red_release(p.scr->cnt + CNT_Z);
        mbar_arrive(sb + BAR_ZP);
      }
      STAMP(28);
      mbar_wait2(sb + BAR_KV, 0, sb + BAR_AE + 72, 0);
      acquire_fence();
      conv_service(p, sb, 0, chb + 64, true);
      bar_sync(NB_WO, 160);
      if (elect_one()) red_release(p.scr->cnt + CNT_WO + cb);
      STAMP(49);
      poll_counter(p.scr->cnt + CNT_WO + cb, tag * 32);
      if (elect_one()) mbar_arrive(sb + BAR_WO);
      STAMP(46);
      conv_service(p, sb, 0, chb + 192, false);
      bar_sync(NB_CD, 64);
      if (elect_one()) red_release(p.scr->cnt + CNT_Y + (cb >> 1));
      STAMP(47);
      poll_counter(p.scr->cnt + CNT_Y + (cb >> 1), tag * 64);
      if (elect_one()) { mbar_expect(sb + BAR_YT, 20480); tma2d(sb + OFF_CV, &p.tmY, rb * 64, cb * 160, sb + BAR_YT); }
      if (lane == 0) *(volatile uint32_t*)&p.scr->epoch[lin] = tag;
      STAMP(23);
    } else {
      const uint32_t tag = epoch + 1;
      sts32(sb + OFF_BIAS + lane * 4, ldg1(p.bsp + rb * 64 + lane * 2));
      if (lane < 2) sts32(sb + OFF_TAG + lane * 4, lane ? 0 : tag);
      uint32_t t0 = 0;
      mbar_wait(sb + BAR_AF + 8 * (NA - 1), 0);
#pragma unroll 1
      while (true) {
        const uint4 u = ld_ll4(&p.scr->xstat[rb * 64 + lane]), v = ld_ll4(&p.scr->xstat[rb * 64 + 32 + lane]);
        sts64f(sb + OFF_XS + lane * 8, __uint_as_float(u.x), __uint_as_float(u.z));
        sts64f(sb + OFF_XS + 256 + lane * 8, __uint_as_float(v.x), __uint_as_float(v.z));
        if (__all_sync(0xffffffff, u.y == tag && u.w == tag && v.y == tag && v.w == tag)) break;
        spin_guard(t0);
      }
      STAMP(26);
      __syncwarp();
      if (lane == 0) mbar_arrive(sb + BAR_XS);
      mbar_wait(sb + BAR_KU + 16, 0);
      poll_counter(p.scr->cnt + CNT_KV + (cb >> 1), tag * 64);
      if (elect_one()) load_convx(p, sb + OFF_CV, sb + BAR_XF + 8, chb);
      mbar_wait(sb + BAR_KU + 8, 1);
      if (elect_one()) load_convx(p, sb + OFF_CV + CV_SZ, sb + BAR_XF, chb + 64);
      STAMP(48);
      mbar_wait2(sb + BAR_KV, 0, sb + BAR_AE + 72, 0);
      acquire_fence();
#pragma unroll 1
      for (int i = 0; i < 3; i++) conv_service(p, sb, 1, chb + i * 128, i < 2);
      bar_arrive(NB_CD, 64);
    }
  } else {
    if (warp == 7) STAMP(36);
    const int wg = warp >> 2, w = warp & 3, g = lane >> 2, t = lane & 3;
    Taps k;
    uint32_t xw[2][10];
    if (wg == 2) {
      asm volatile("setmaxnreg.inc.sync.aligned.u32 160;");
      const int tb = rb * 2 + (cb & 1), c0 = (cb >> 1) * 320;
      const uint32_t cv = sb + OFF_CV + CV_SZ;
      if (w == 0) zero_pads(sb + OFF_CV, lane);
      mbar_wait(sb + BAR_KV + 8, 0);
      const int t0 = tb * 32 + w * 8;
      const __nv_bfloat16* kp = p.k + (size_t)(t0 - 3) * kD + c0 + lane * 2;
      const __nv_bfloat16* vp = p.v + (size_t)t0 * kD + c0 + lane * 2;
      const __nv_bfloat16* sp = p.shift + (c0 + lane * 2) * 4;
      const uint32_t oa = cv + ((3 - w) & 1) * 1024 + lane * 32 + ((((3 - w) >> 1) ^ (lane >> 2)) & 1) * 16;
#pragma unroll 1
      for (int r = 0; r < 2; r++) {
        KvRegs n0, n1, n2;
        kv_load(n0, kp + r * 128, vp + r * 128, sp + r * 512, t0 > 0);
        kv_load(n1, kp + r * 128 + 64, vp + r * 128 + 64, sp + r * 512 + 256, t0 > 0);
        if (r) kv_load(n2, kp + 256, vp + 256, sp + 1024, t0 > 0);
        kv_unit(n0, oa + r * 8192);
        bar_sync(NB_WGC, 128);
        mbar_arrive_if(sb + BAR_KU + 16 * r, tid == 0);
        if (r) mbar_wait(sb + BAR_KU, 1);
        kv_unit(n1, oa + (r ? 0 : 4096));
        bar_sync(NB_WGC, 128);
        mbar_arrive_if(sb + BAR_KU + 16 * r + 8, tid == 0);
        if (r) {
          kv_unit(n2, oa + 4096);
          bar_sync(NB_WGC, 128);
          mbar_arrive_if(sb + BAR_KU + 32, tid == 0);
        } else {
          mbar_wait2(sb + BAR_AF + 8 * ((cb * 160 + 80) >> 6), 0, sb + BAR_AF + 8 * ((cb * 160 + 159) >> 6), 0);
          final_load_x(xw, sb + OFF_A, cb * 160 + 80, w, lane);
        }
      }
      STAMPW(13);
      load_taps(k, p, chb, tid);
    } else {
      float d[96];
      if (wg == 0) { if (t < 2) st_ll4(&p.scr->zstat[rb * 256 + cb * 64 + w * 16 + g + t * 8], 0, 0, 0, 0); }
      else if ((tid & 7) == 0) st_ll4(&p.scr->xstat[rb * 64 + cb * 16 + (tid >> 3)], 0, 0, 0, 0);
      {
        #pragma unroll
        for (int i = 0; i < 96; i++) d[i] = 0.f;
        {
          if (__builtin_expect(wg == 1, 0)) {
            const int tid = tid_now();
            const uint32_t epoch = load_epoch(p, lin, lane);
            float s = 0.f, q = 0.f;
#pragma unroll 1
            for (int i = 0; i < 10; i++) {
              mbar_wait(sb + BAR_AF + 8 * i, 0);
              const uint4 x4 = lds128(sb + OFF_A + i * A_SLOT + cb * 2048 + tid * 16);
              const uint32_t u[4] = {x4.x, x4.y, x4.z, x4.w};
#pragma unroll
              for (int e = 0; e < 4; e++) { const float a = bf_lo(u[e]), c = bf_hi(u[e]); s += a + c; q = fmaf(a, a, q); q = fmaf(c, c, q); }
            }
#pragma unroll
            for (int o = 1; o <= 4; o <<= 1) { s += __shfl_xor_sync(0xffffffff, s, o); q += __shfl_xor_sync(0xffffffff, q, o); }
            const float m = s * (1.f / kD);
            const float r = rsqrtf(fmaxf(fmaf(-m, m, q * (1.f / kD)), 0.f) + 1e-5f);
            if ((tid & 7) == 0) st_ll4(&p.scr->xstat[rb * 64 + cb * 16 + (tid >> 3)], __float_as_uint(m), epoch + 1, __float_as_uint(r), epoch + 1);
            STAMPW(12);
            bar_sync(NB_G1, 256);
          }
          gemm_loop<192, true, 0, D1>(d, sb, 10, 0, 0, 0, 0, wg, 2, tid_now(), !G1_LATE && wg == 0);
          asm volatile("setmaxnreg.inc.sync.aligned.u32 160;");
          STAMPW(wg ? 14 : 1);
          mbar_wait2(sb + BAR_XS, 0, sb + BAR_ST + 8 * wg, 0);
        }
        const int t1 = tid_now();
        const uint32_t xa1 = sb + OFF_XS + (w * 16 + ((t1 & 31) >> 2)) * 8;
        const float2 s0 = lds64f(xa1), s1 = lds64f(xa1 + 64);
        uint32_t z[48];
        float st[4];
        gelu_tile(d, z, st, sb + OFF_CS + wg * 768 + (t1 & 3) * 8, s0, s1);
        const int tid = tid_now(), lane = tid & 31, g = lane >> 2, t = lane & 3;
        if (wg == 1) {
          uint32_t bra, brb;
          asm volatile("ld.shared.u16 %0, [%1];" : "=r"(bra) : "r"(sb + OFF_BIAS + (w * 16 + g) * 2));
          asm volatile("ld.shared.u16 %0, [%1+16];" : "=r"(brb) : "r"(sb + OFF_BIAS + (w * 16 + g) * 2));
#pragma unroll
          for (int j = 0; j < 96; j++) d[j] = bf_lo((j & 2) ? brb : bra);
          STAMPW(15);
          gemm_loop<192, true, 1, D2>(d, sb, 32, 0, 1, 20, 0, 2, 2, tid, false);
          STAMPW(16);
          const int t2 = tid_now(), l2 = t2 & 31;
          const uint32_t ha = sb + OFF_A + 5 * A_SLOT + (l2 >> 4) * 1024 + (2 * w + ((l2 >> 3) & 1)) * 128 + (l2 & 7) * 16;
#pragma unroll
          for (int j = 0; j < 24; j += 2) {
#pragma unroll
            for (int e = 0; e < 4; e++) z[2 * j + e] = hmul2(z[2 * j + e], pack2(d[4 * j + 2 * e], d[4 * j + 2 * e + 1]));
            stsm4(ha + j * 1024, z[2 * j], z[2 * j + 1], z[2 * j + 2], z[2 * j + 3]);
          }
          fence_async_smem();
          bar_sync(NB_WGB, 128);
          mbar_arrive_if(sb + BAR_AF + 8 * (t2 == 3 ? (BAR_G2 - BAR_AF) / 8 : 5 + t2), t2 < 4);
          STAMPW(17);
          {
            float e[80];
#pragma unroll
            for (int j = 0; j < 80; j++) e[j] = 0.f;
            gemm_loop<160, false, 2, 4>(e, sb, 3, 5, 0, 2, 0, 0, 2, tid_now(), false);
            bar_sync(NB_WGB, 128);
            mbar_wait(sb + BAR_ZP, 1);
            const int t3 = tid_now();
#pragma unroll
            for (int j = 0; j < 10; j++)
              sts128(sb + OFF_A + 5 * A_SLOT + j * 2048 + t3 * 16, pack2(e[8 * j], e[8 * j + 1]), pack2(e[8 * j + 2], e[8 * j + 3]), pack2(e[8 * j + 4], e[8 * j + 5]),
                     pack2(e[8 * j + 6], e[8 * j + 7]));
            bar_sync(NB_WGB, 128);
            mbar_arrive_if(sb + BAR_HOLD, t3 == 0);
            STAMPW(45);
          }
          return;
        }
        float sa = st[0], qa = st[1], sbb = st[2], qb = st[3];
#pragma unroll
        for (int o = 1; o <= 2; o <<= 1) {
          sa += __shfl_xor_sync(0xffffffff, sa, o); qa += __shfl_xor_sync(0xffffffff, qa, o);
          sbb += __shfl_xor_sync(0xffffffff, sbb, o); qb += __shfl_xor_sync(0xffffffff, qb, o);
        }
        const uint32_t tag = lds32<0>(sb + OFF_TAG);
        if (t < 2) st_ll4(&p.scr->zstat[rb * 256 + cb * 64 + w * 16 + g + t * 8], __float_as_uint(t ? sbb : sa), tag, __float_as_uint(t ? qb : qa), tag);
        if (G1_LATE) bar_arrive(NB_G1, 256);
        STAMPW(2);
        const float ca = 0.5f * s0.y, cbb = 0.5f * s1.y;
        {
          const uint4* zs = &p.scr->zstat[rb * 256 + t * 64 + w * 16 + g];
          uint4 u0 = ld_ll4(zs), u1 = ld_ll4(zs + 8);
          final_load_x(xw, sb + OFF_A, cb * 160, w, lane);
          fence_async_smem();
          bar_sync(NB_WGA, 128);
          mbar_arrive_if(sb + BAR_AE + 8 * tid, tid < NA);
          uint32_t t0 = 0;
#pragma unroll 1
          while (!__all_sync(0xffffffff, u0.y == tag && u0.w == tag && u1.y == tag && u1.w == tag)) {
            spin_guard(t0);
            u0 = ld_ll4(zs); u1 = ld_ll4(zs + 8);
          }
          sa = __uint_as_float(u0.x); qa = __uint_as_float(u0.z); sbb = __uint_as_float(u1.x); qb = __uint_as_float(u1.z);
          STAMPW(3);
        }
#pragma unroll
        for (int o = 1; o <= 2; o <<= 1) {
          sa += __shfl_xor_sync(0xffffffff, sa, o); qa += __shfl_xor_sync(0xffffffff, qa, o);
          sbb += __shfl_xor_sync(0xffffffff, sbb, o); qb += __shfl_xor_sync(0xffffffff, qb, o);
        }
        const float inv = 1.f / 768.f;
        const float ma = sa * inv, mb = sbb * inv;
        const float ra = ca * rsqrtf(fmaf(fmaxf(fmaf(-ma, ma, qa * inv), 0.f), ca * ca, 1e-5f));
        const float rb_ = cbb * rsqrtf(fmaf(fmaxf(fmaf(-mb, mb, qb * inv), 0.f), cbb * cbb, 1e-5f));
        const uint32_t ra2 = pack2(ra, ra), rb2 = pack2(rb_, rb_);
        const float na = -ma * bf_lo(ra2), nb = -mb * bf_lo(rb2);
        {
          const uint32_t n2a = pack2(na, na), n2b = pack2(nb, nb);
          const uint32_t za = sb + OFF_A + LEAD * A_SLOT + (2 * w + ((lane >> 3) & 1)) * 3072 + (lane >> 4) * 128 + (lane & 7) * 16;
          mbar_wait2(sb + BAR_AE + 8 * (LEAD + 2), 0, sb + BAR_KU + 16, 0);
#pragma unroll
          for (int j = 0; j < 24; j += 2)
            stsm4(za + j * 128, hfma2(z[2 * j], ra2, n2a), hfma2(z[2 * j + 1], rb2, n2b), hfma2(z[2 * j + 2], ra2, n2a), hfma2(z[2 * j + 3], rb2, n2b));
          fence_async_smem();
        }
      }
      bar_arrive(NB_Z, 160);
      {
        const uint32_t zero = lds32<0>(sb + OFF_TAG + 4);
#pragma unroll
        for (int i = 0; i < 20; i++) xw[i / 10][i % 10] |= zero;
      }
      load_taps(k, p, chb + 64, tid_now());
      STAMPW(4);
    }
    const int h = wg >> 1;
    {
    const int tid = tid_now(), lane = tid & 31;
    conv_worker(p, k, sb + OFF_CV + (1 - h) * CV_SZ, sb + OFF_A + 9 * A_SLOT + h * 4096, sb + BAR_XF + 8 * h, NB_WGA + h,
                chb + (h ? 0 : 64), 2 + h, sb + BAR_G2, w, lane, tid, h ? 40 : 5, rb, cb);
    float d[40];
    {
      const int t3 = tid_now();
      mbar_wait(sb + BAR_HOLD, 0);
#pragma unroll
      for (int j = 0; j < 5; j++) {
        const uint4 v = lds128(sb + OFF_A + 5 * A_SLOT + (h * 5 + j) * 2048 + t3 * 16);
        d[8 * j] = bf_lo(v.x); d[8 * j + 1] = bf_hi(v.x); d[8 * j + 2] = bf_lo(v.y); d[8 * j + 3] = bf_hi(v.y);
        d[8 * j + 4] = bf_lo(v.z); d[8 * j + 5] = bf_hi(v.z); d[8 * j + 6] = bf_lo(v.w); d[8 * j + 7] = bf_hi(v.w);
      }
      fence_async_smem();
      bar_sync(NB_WGA + h, 128);
      mbar_arrive_if(sb + BAR_AE + 8 * (5 + t3), t3 < 3);
      gemm_loop<80, false, 2, D3>(d, sb, 9, 8, 0, 5, h * 1280, 1, 1, t3, false);
    }
    STAMPW(h ? 18 : 10);
    const int l3 = tid_now() & 31;
    const uint32_t xs_addr = sb + OFF_XS + (w * 16 + (l3 >> 2)) * 8;
    final_gate(d, xw, lds64f(xs_addr), lds64f(xs_addr + 64));
    acc_fence<40>(d);
    STAMPW(h ? 44 : 9);
    mbar_wait(sb + BAR_YT, 1);
    final_out(d, xw, sb + OFF_CV + h * 10240, p.out + (size_t)(rb * 64 + w * 16 + (l3 >> 2)) * kD + cb * 160 + h * 80, w, l3);
    }
  }
}

typedef CUresult (*EncodeFn)(CUtensorMap*, CUtensorMapDataType, cuuint32_t, void*, const cuuint64_t*, const cuuint64_t*, const cuuint32_t*,
                             const cuuint32_t*, CUtensorMapInterleave, CUtensorMapSwizzle, CUtensorMapL2promotion, CUtensorMapFloatOOBfill);

void encode(EncodeFn fn, CUtensorMap* m, const void* ptr, int rank, const cuuint64_t* dims, const cuuint64_t* strides, const cuuint32_t* box,
            CUtensorMapSwizzle swz = CU_TENSOR_MAP_SWIZZLE_128B) {
  const cuuint32_t es[3] = {1, 1, 1};
  fn(m, CU_TENSOR_MAP_DATA_TYPE_BFLOAT16, rank, const_cast<void*>(ptr), dims, strides, box, es, CU_TENSOR_MAP_INTERLEAVE_NONE,
     swz, CU_TENSOR_MAP_L2_PROMOTION_L2_128B, CU_TENSOR_MAP_FLOAT_OOB_FILL_NONE);
}

}

extern "C" void kernel_launch(void* const* d_in, const int* in_sizes, int n_in, void* d_out, int out_size) {
  (void)in_sizes; (void)n_in; (void)out_size;
  static EncodeFn enc = nullptr;
  static Scratch* scr = nullptr;
  static int sms = 0;
  if (!enc) {
    void* fn = nullptr;
    cudaDriverEntryPointQueryResult qr;
    cudaGetDriverEntryPoint("cuTensorMapEncodeTiled", &fn, cudaEnableDefault, &qr);
    enc = (EncodeFn)fn;
    cudaFuncSetAttribute(fused_kernel, cudaFuncAttributeMaxDynamicSharedMemorySize, SMEM_BYTES);
    cudaGetSymbolAddress((void**)&scr, g_scr);
    int dev = 0;
    cudaGetDevice(&dev);
    cudaDeviceGetAttribute(&sms, cudaDevAttrMultiProcessorCount, dev);
  }
  Params p;
  p.scr = scr;
  p.by_smid = sms == 132;
  p.k = (const __nv_bfloat16*)d_in[1];
  p.v = (const __nv_bfloat16*)d_in[2];
  p.shift = (const __nv_bfloat16*)d_in[3];
  p.ssmk = (const __nv_bfloat16*)d_in[4];
  p.ssmD = (const __nv_bfloat16*)d_in[5];
  p.wsp = (const __nv_bfloat16*)d_in[8];
  p.bsp = (const __nv_bfloat16*)d_in[9];
  p.wout = (const __nv_bfloat16*)d_in[10];
  p.out = (__nv_bfloat16*)d_out;
  {
    const cuuint64_t dims[2] = {kD, kS}, st[1] = {kD * 2};
    const cuuint32_t box[2] = {64, 64};
    encode(enc, &p.tmX, d_in[0], 2, dims, st, box);
  }
  {
    const cuuint64_t dims[3] = {64, kD, kF / 64}, st[2] = {kF * 2, 128};
    const cuuint32_t box[3] = {64, 64, 3};
    encode(enc, &p.tmW, d_in[7], 3, dims, st, box);
  }
  {
    const cuuint64_t dims[2] = {kS, kS}, st[1] = {kS * 2};
    const cuuint32_t box[2] = {64, 64};
    encode(enc, &p.tmWsp, d_in[8], 2, dims, st, box);
  }
  {
    const cuuint64_t dims[2] = {kS, kD}, st[1] = {kS * 2};
    const cuuint32_t box[2] = {64, 160};
    encode(enc, &p.tmY, scr->y, 2, dims, st, box);
  }
  {
    const cuuint64_t dims[3] = {1024, kD / 2, 4}, st[2] = {8192, 2048};
    const cuuint32_t box[3] = {16, 32, 4};
    encode(enc, &p.tmKV, scr->kvx, 3, dims, st, box, CU_TENSOR_MAP_SWIZZLE_32B);
  }
  fused_kernel<<<132, 512, SMEM_BYTES, cudaStreamPerThread>>>(p);
}
```

```cpp
#include <cuda_runtime.h>
#include <cuda.h>
#include <cuda_bf16.h>
#include <stdint.h>

template <int N> struct WG;
template <> struct WG<16> {
  static __device__ __forceinline__ void rs(float* d, const uint32_t* a, uint64_t db) {
    asm volatile("{\n.reg .pred p;\nsetp.ne.b32 p, 1, 0;\nwgmma.mma_async.sync.aligned.m64n16k16.f32.bf16.bf16 {"
      "%0, %1, %2, %3, %4, %5, %6, %7"
      "}, {%8, %9, %10, %11}, %12, p, 1, 1, 0;\n}\n"
      :
      "+f"(d[0]), "+f"(d[1]), "+f"(d[2]), "+f"(d[3]), "+f"(d[4]), "+f"(d[5]), "+f"(d[6]), "+f"(d[7])
      : "r"(a[0]), "r"(a[1]), "r"(a[2]), "r"(a[3]), "l"(db));
  }
};
template <> struct WG<32> {
  static __device__ __forceinline__ void rs(float* d, const uint32_t* a, uint64_t db) {
    asm volatile("{\n.reg .pred p;\nsetp.ne.b32 p, 1, 0;\nwgmma.mma_async.sync.aligned.m64n32k16.f32.bf16.bf16 {"
      "%0, %1, %2, %3, %4, %5, %6, %7, %8, %9, %10, %11, %12, %13, %14, %15"
      "}, {%16, %17, %18, %19}, %20, p, 1, 1, 0;\n}\n"
      :
      "+f"(d[0]), "+f"(d[1]), "+f"(d[2]), "+f"(d[3]), "+f"(d[4]), "+f"(d[5]), "+f"(d[6]), "+f"(d[7]),
      "+f"(d[8]), "+f"(d[9]), "+f"(d[10]), "+f"(d[11]), "+f"(d[12]), "+f"(d[13]), "+f"(d[14]), "+f"(d[15])
      : "r"(a[0]), "r"(a[1]), "r"(a[2]), "r"(a[3]), "l"(db));
  }
};
template <> struct WG<48> {
  static __device__ __forceinline__ void rs(float* d, const uint32_t* a, uint64_t db) {
    asm volatile("{\n.reg .pred p;\nsetp.ne.b32 p, 1, 0;\nwgmma.mma_async.sync.aligned.m64n48k16.f32.bf16.bf16 {"
      "%0, %1, %2, %3, %4, %5, %6, %7, %8, %9, %10, %11, %12, %13, %14, %15, "
      "%16, %17, %18, %19, %20, %21, %22, %23"
      "}, {%24, %25, %26, %27}, %28, p, 1, 1, 0;\n}\n"
      :
      "+f"(d[0]), "+f"(d[1]), "+f"(d[2]), "+f"(d[3]), "+f"(d[4]), "+f"(d[5]), "+f"(d[6]), "+f"(d[7]),
      "+f"(d[8]), "+f"(d[9]), "+f"(d[10]), "+f"(d[11]), "+f"(d[12]), "+f"(d[13]), "+f"(d[14]), "+f"(d[15]),
      "+f"(d[16]), "+f"(d[17]), "+f"(d[18]), "+f"(d[19]), "+f"(d[20]), "+f"(d[21]), "+f"(d[22]), "+f"(d[23])
      : "r"(a[0]), "r"(a[1]), "r"(a[2]), "r"(a[3]), "l"(db));
  }
};
template <> struct WG<64> {
  static __device__ __forceinline__ void ss(float* d, uint64_t da, uint64_t db, int sd) {
    asm volatile("{\n.reg .pred p;\nsetp.ne.b32 p, %34, 0;\nwgmma.mma_async.sync.aligned.m64n64k16.f32.bf16.bf16 {"
      "%0, %1, %2, %3, %4, %5, %6, %7, %8, %9, %10, %11, %12, %13, %14, %15, "
      "%16, %17, %18, %19, %20, %21, %22, %23, %24, %25, %26, %27, %28, %29, %30, %31"
      "}, %32, %33, p, 1, 1, 0, 1;\n}\n"
      :
      "+f"(d[0]), "+f"(d[1]), "+f"(d[2]), "+f"(d[3]), "+f"(d[4]), "+f"(d[5]), "+f"(d[6]), "+f"(d[7]),
      "+f"(d[8]), "+f"(d[9]), "+f"(d[10]), "+f"(d[11]), "+f"(d[12]), "+f"(d[13]), "+f"(d[14]), "+f"(d[15]),
      "+f"(d[16]), "+f"(d[17]), "+f"(d[18]), "+f"(d[19]), "+f"(d[20]), "+f"(d[21]), "+f"(d[22]), "+f"(d[23]),
      "+f"(d[24]), "+f"(d[25]), "+f"(d[26]), "+f"(d[27]), "+f"(d[28]), "+f"(d[29]), "+f"(d[30]), "+f"(d[31])
      : "l"(da), "l"(db), "r"(sd));
  }
  static __device__ __forceinline__ void rs(float* d, const uint32_t* a, uint64_t db) {
    asm volatile("{\n.reg .pred p;\nsetp.ne.b32 p, 1, 0;\nwgmma.mma_async.sync.aligned.m64n64k16.f32.bf16.bf16 {"
      "%0, %1, %2, %3, %4, %5, %6, %7, %8, %9, %10, %11, %12, %13, %14, %15, "
      "%16, %17, %18, %19, %20, %21, %22, %23, %24, %25, %26, %27, %28, %29, %30, %31"
      "}, {%32, %33, %34, %35}, %36, p, 1, 1, 0;\n}\n"
      :
      "+f"(d[0]), "+f"(d[1]), "+f"(d[2]), "+f"(d[3]), "+f"(d[4]), "+f"(d[5]), "+f"(d[6]), "+f"(d[7]),
      "+f"(d[8]), "+f"(d[9]), "+f"(d[10]), "+f"(d[11]), "+f"(d[12]), "+f"(d[13]), "+f"(d[14]), "+f"(d[15]),
      "+f"(d[16]), "+f"(d[17]), "+f"(d[18]), "+f"(d[19]), "+f"(d[20]), "+f"(d[21]), "+f"(d[22]), "+f"(d[23]),
      "+f"(d[24]), "+f"(d[25]), "+f"(d[26]), "+f"(d[27]), "+f"(d[28]), "+f"(d[29]), "+f"(d[30]), "+f"(d[31])
      : "r"(a[0]), "r"(a[1]), "r"(a[2]), "r"(a[3]), "l"(db));
  }
};
template <> struct WG<80> {
  static __device__ __forceinline__ void ss(float* d, uint64_t da, uint64_t db, int sd) {
    asm volatile("{\n.reg .pred p;\nsetp.ne.b32 p, %42, 0;\nwgmma.mma_async.sync.aligned.m64n80k16.f32.bf16.bf16 {"
      "%0, %1, %2, %3, %4, %5, %6, %7, %8, %9, %10, %11, %12, %13, %14, %15, "
      "%16, %17, %18, %19, %20, %21, %22, %23, %24, %25, %26, %27, %28, %29, %30, %31, "
      "%32, %33, %34, %35, %36, %37, %38, %39"
      "}, %40, %41, p, 1, 1, 0, 1;\n}\n"
      :
      "+f"(d[0]), "+f"(d[1]), "+f"(d[2]), "+f"(d[3]), "+f"(d[4]), "+f"(d[5]), "+f"(d[6]), "+f"(d[7]),
      "+f"(d[8]), "+f"(d[9]), "+f"(d[10]), "+f"(d[11]), "+f"(d[12]), "+f"(d[13]), "+f"(d[14]), "+f"(d[15]),
      "+f"(d[16]), "+f"(d[17]), "+f"(d[18]), "+f"(d[19]), "+f"(d[20]), "+f"(d[21]), "+f"(d[22]), "+f"(d[23]),
      "+f"(d[24]), "+f"(d[25]), "+f"(d[26]), "+f"(d[27]), "+f"(d[28]), "+f"(d[29]), "+f"(d[30]), "+f"(d[31]),
      "+f"(d[32]), "+f"(d[33]), "+f"(d[34]), "+f"(d[35]), "+f"(d[36]), "+f"(d[37]), "+f"(d[38]), "+f"(d[39])
      : "l"(da), "l"(db), "r"(sd));
  }
  static __device__ __forceinline__ void rs(float* d, const uint32_t* a, uint64_t db) {
    asm volatile("{\n.reg .pred p;\nsetp.ne.b32 p, 1, 0;\nwgmma.mma_async.sync.aligned.m64n80k16.f32.bf16.bf16 {"
      "%0, %1, %2, %3, %4, %5, %6, %7, %8, %9, %10, %11, %12, %13, %14, %15, "
      "%16, %17, %18, %19, %20, %21, %22, %23, %24, %25, %26, %27, %28, %29, %30, %31, "
      "%32, %33, %34, %35, %36, %37, %38, %39"
      "}, {%40, %41, %42, %43}, %44, p, 1, 1, 0;\n}\n"
      :
      "+f"(d[0]), "+f"(d[1]), "+f"(d[2]), "+f"(d[3]), "+f"(d[4]), "+f"(d[5]), "+f"(d[6]), "+f"(d[7]),
      "+f"(d[8]), "+f"(d[9]), "+f"(d[10]), "+f"(d[11]), "+f"(d[12]), "+f"(d[13]), "+f"(d[14]), "+f"(d[15]),
      "+f"(d[16]), "+f"(d[17]), "+f"(d[18]), "+f"(d[19]), "+f"(d[20]), "+f"(d[21]), "+f"(d[22]), "+f"(d[23]),
      "+f"(d[24]), "+f"(d[25]), "+f"(d[26]), "+f"(d[27]), "+f"(d[28]), "+f"(d[29]), "+f"(d[30]), "+f"(d[31]),
      "+f"(d[32]), "+f"(d[33]), "+f"(d[34]), "+f"(d[35]), "+f"(d[36]), "+f"(d[37]), "+f"(d[38]), "+f"(d[39])
      : "r"(a[0]), "r"(a[1]), "r"(a[2]), "r"(a[3]), "l"(db));
  }
};
template <> struct WG<96> {
  static __device__ __forceinline__ void ss(float* d, uint64_t da, uint64_t db, int sd) {
    asm volatile("{\n.reg .pred p;\nsetp.ne.b32 p, %50, 0;\nwgmma.mma_async.sync.aligned.m64n96k16.f32.bf16.bf16 {"
      "%0, %1, %2, %3, %4, %5, %6, %7, %8, %9, %10, %11, %12, %13, %14, %15, "
      "%16, %17, %18, %19, %20, %21, %22, %23, %24, %25, %26, %27, %28, %29, %30, %31, "
      "%32, %33, %34, %35, %36, %37, %38, %39, %40, %41, %42, %43, %44, %45, %46, %47"
      "}, %48, %49, p, 1, 1, 0, 1;\n}\n"
      :
      "+f"(d[0]), "+f"(d[1]), "+f"(d[2]), "+f"(d[3]), "+f"(d[4]), "+f"(d[5]), "+f"(d[6]), "+f"(d[7]),
      "+f"(d[8]), "+f"(d[9]), "+f"(d[10]), "+f"(d[11]), "+f"(d[12]), "+f"(d[13]), "+f"(d[14]), "+f"(d[15]),
      "+f"(d[16]), "+f"(d[17]), "+f"(d[18]), "+f"(d[19]), "+f"(d[20]), "+f"(d[21]), "+f"(d[22]), "+f"(d[23]),
      "+f"(d[24]), "+f"(d[25]), "+f"(d[26]), "+f"(d[27]), "+f"(d[28]), "+f"(d[29]), "+f"(d[30]), "+f"(d[31]),
      "+f"(d[32]), "+f"(d[33]), "+f"(d[34]), "+f"(d[35]), "+f"(d[36]), "+f"(d[37]), "+f"(d[38]), "+f"(d[39]),
      "+f"(d[40]), "+f"(d[41]), "+f"(d[42]), "+f"(d[43]), "+f"(d[44]), "+f"(d[45]), "+f"(d[46]), "+f"(d[47])
      : "l"(da), "l"(db), "r"(sd));
  }
  static __device__ __forceinline__ void rs(float* d, const uint32_t* a, uint64_t db) {
    asm volatile("{\n.reg .pred p;\nsetp.ne.b32 p, 1, 0;\nwgmma.mma_async.sync.aligned.m64n96k16.f32.bf16.bf16 {"
      "%0, %1, %2, %3, %4, %5, %6, %7, %8, %9, %10, %11, %12, %13, %14, %15, "
      "%16, %17, %18, %19, %20, %21, %22, %23, %24, %25, %26, %27, %28, %29, %30, %31, "
      "%32, %33, %34, %35, %36, %37, %38, %39, %40, %41, %42, %43, %44, %45, %46, %47"
      "}, {%48, %49, %50, %51}, %52, p, 1, 1, 0;\n}\n"
      :
      "+f"(d[0]), "+f"(d[1]), "+f"(d[2]), "+f"(d[3]), "+f"(d[4]), "+f"(d[5]), "+f"(d[6]), "+f"(d[7]),
      "+f"(d[8]), "+f"(d[9]), "+f"(d[10]), "+f"(d[11]), "+f"(d[12]), "+f"(d[13]), "+f"(d[14]), "+f"(d[15]),
      "+f"(d[16]), "+f"(d[17]), "+f"(d[18]), "+f"(d[19]), "+f"(d[20]), "+f"(d[21]), "+f"(d[22]), "+f"(d[23]),
      "+f"(d[24]), "+f"(d[25]), "+f"(d[26]), "+f"(d[27]), "+f"(d[28]), "+f"(d[29]), "+f"(d[30]), "+f"(d[31]),
      "+f"(d[32]), "+f"(d[33]), "+f"(d[34]), "+f"(d[35]), "+f"(d[36]), "+f"(d[37]), "+f"(d[38]), "+f"(d[39]),
      "+f"(d[40]), "+f"(d[41]), "+f"(d[42]), "+f"(d[43]), "+f"(d[44]), "+f"(d[45]), "+f"(d[46]), "+f"(d[47])
      : "r"(a[0]), "r"(a[1]), "r"(a[2]), "r"(a[3]), "l"(db));
  }
};
template <> struct WG<112> {
  static __device__ __forceinline__ void rs(float* d, const uint32_t* a, uint64_t db) {
    asm volatile("{\n.reg .pred p;\nsetp.ne.b32 p, 1, 0;\nwgmma.mma_async.sync.aligned.m64n112k16.f32.bf16.bf16 {"
      "%0, %1, %2, %3, %4, %5, %6, %7, %8, %9, %10, %11, %12, %13, %14, %15, "
      "%16, %17, %18, %19, %20, %21, %22, %23, %24, %25, %26, %27, %28, %29, %30, %31, "
      "%32, %33, %34, %35, %36, %37, %38, %39, %40, %41, %42, %43, %44, %45, %46, %47, "
      "%48, %49, %50, %51, %52, %53, %54, %55"
      "}, {%56, %57, %58, %59}, %60, p, 1, 1, 0;\n}\n"
      :
      "+f"(d[0]), "+f"(d[1]), "+f"(d[2]), "+f"(d[3]), "+f"(d[4]), "+f"(d[5]), "+f"(d[6]), "+f"(d[7]),
      "+f"(d[8]), "+f"(d[9]), "+f"(d[10]), "+f"(d[11]), "+f"(d[12]), "+f"(d[13]), "+f"(d[14]), "+f"(d[15]),
      "+f"(d[16]), "+f"(d[17]), "+f"(d[18]), "+f"(d[19]), "+f"(d[20]), "+f"(d[21]), "+f"(d[22]), "+f"(d[23]),
      "+f"(d[24]), "+f"(d[25]), "+f"(d[26]), "+f"(d[27]), "+f"(d[28]), "+f"(d[29]), "+f"(d[30]), "+f"(d[31]),
      "+f"(d[32]), "+f"(d[33]), "+f"(d[34]), "+f"(d[35]), "+f"(d[36]), "+f"(d[37]), "+f"(d[38]), "+f"(d[39]),
      "+f"(d[40]), "+f"(d[41]), "+f"(d[42]), "+f"(d[43]), "+f"(d[44]), "+f"(d[45]), "+f"(d[46]), "+f"(d[47]),
      "+f"(d[48]), "+f"(d[49]), "+f"(d[50]), "+f"(d[51]), "+f"(d[52]), "+f"(d[53]), "+f"(d[54]), "+f"(d[55])
      : "r"(a[0]), "r"(a[1]), "r"(a[2]), "r"(a[3]), "l"(db));
  }
};
template <> struct WG<128> {
  static __device__ __forceinline__ void rs(float* d, const uint32_t* a, uint64_t db) {
    asm volatile("{\n.reg .pred p;\nsetp.ne.b32 p, 1, 0;\nwgmma.mma_async.sync.aligned.m64n128k16.f32.bf16.bf16 {"
      "%0, %1, %2, %3, %4, %5, %6, %7, %8, %9, %10, %11, %12, %13, %14, %15, "
      "%16, %17, %18, %19, %20, %21, %22, %23, %24, %25, %26, %27, %28, %29, %30, %31, "
      "%32, %33, %34, %35, %36, %37, %38, %39, %40, %41, %42, %43, %44, %45, %46, %47, "
      "%48, %49, %50, %51, %52, %53, %54, %55, %56, %57, %58, %59, %60, %61, %62, %63"
      "}, {%64, %65, %66, %67}, %68, p, 1, 1, 0;\n}\n"
      :
      "+f"(d[0]), "+f"(d[1]), "+f"(d[2]), "+f"(d[3]), "+f"(d[4]), "+f"(d[5]), "+f"(d[6]), "+f"(d[7]),
      "+f"(d[8]), "+f"(d[9]), "+f"(d[10]), "+f"(d[11]), "+f"(d[12]), "+f"(d[13]), "+f"(d[14]), "+f"(d[15]),
      "+f"(d[16]), "+f"(d[17]), "+f"(d[18]), "+f"(d[19]), "+f"(d[20]), "+f"(d[21]), "+f"(d[22]), "+f"(d[23]),
      "+f"(d[24]), "+f"(d[25]), "+f"(d[26]), "+f"(d[27]), "+f"(d[28]), "+f"(d[29]), "+f"(d[30]), "+f"(d[31]),
      "+f"(d[32]), "+f"(d[33]), "+f"(d[34]), "+f"(d[35]), "+f"(d[36]), "+f"(d[37]), "+f"(d[38]), "+f"(d[39]),
      "+f"(d[40]), "+f"(d[41]), "+f"(d[42]), "+f"(d[43]), "+f"(d[44]), "+f"(d[45]), "+f"(d[46]), "+f"(d[47]),
      "+f"(d[48]), "+f"(d[49]), "+f"(d[50]), "+f"(d[51]), "+f"(d[52]), "+f"(d[53]), "+f"(d[54]), "+f"(d[55]),
      "+f"(d[56]), "+f"(d[57]), "+f"(d[58]), "+f"(d[59]), "+f"(d[60]), "+f"(d[61]), "+f"(d[62]), "+f"(d[63])
      : "r"(a[0]), "r"(a[1]), "r"(a[2]), "r"(a[3]), "l"(db));
  }
};
template <> struct WG<160> {
  static __device__ __forceinline__ void ss(float* d, uint64_t da, uint64_t db, int sd) {
    asm volatile("{\n.reg .pred p;\nsetp.ne.b32 p, %82, 0;\nwgmma.mma_async.sync.aligned.m64n160k16.f32.bf16.bf16 {"
      "%0, %1, %2, %3, %4, %5, %6, %7, %8, %9, %10, %11, %12, %13, %14, %15, "
      "%16, %17, %18, %19, %20, %21, %22, %23, %24, %25, %26, %27, %28, %29, %30, %31, "
      "%32, %33, %34, %35, %36, %37, %38, %39, %40, %41, %42, %43, %44, %45, %46, %47, "
      "%48, %49, %50, %51, %52, %53, %54, %55, %56, %57, %58, %59, %60, %61, %62, %63, "
      "%64, %65, %66, %67, %68, %69, %70, %71, %72, %73, %74, %75, %76, %77, %78, %79"
      "}, %80, %81, p, 1, 1, 0, 1;\n}\n"
      :
      "+f"(d[0]), "+f"(d[1]), "+f"(d[2]), "+f"(d[3]), "+f"(d[4]), "+f"(d[5]), "+f"(d[6]), "+f"(d[7]),
      "+f"(d[8]), "+f"(d[9]), "+f"(d[10]), "+f"(d[11]), "+f"(d[12]), "+f"(d[13]), "+f"(d[14]), "+f"(d[15]),
      "+f"(d[16]), "+f"(d[17]), "+f"(d[18]), "+f"(d[19]), "+f"(d[20]), "+f"(d[21]), "+f"(d[22]), "+f"(d[23]),
      "+f"(d[24]), "+f"(d[25]), "+f"(d[26]), "+f"(d[27]), "+f"(d[28]), "+f"(d[29]), "+f"(d[30]), "+f"(d[31]),
      "+f"(d[32]), "+f"(d[33]), "+f"(d[34]), "+f"(d[35]), "+f"(d[36]), "+f"(d[37]), "+f"(d[38]), "+f"(d[39]),
      "+f"(d[40]), "+f"(d[41]), "+f"(d[42]), "+f"(d[43]), "+f"(d[44]), "+f"(d[45]), "+f"(d[46]), "+f"(d[47]),
      "+f"(d[48]), "+f"(d[49]), "+f"(d[50]), "+f"(d[51]), "+f"(d[52]), "+f"(d[53]), "+f"(d[54]), "+f"(d[55]),
      "+f"(d[56]), "+f"(d[57]), "+f"(d[58]), "+f"(d[59]), "+f"(d[60]), "+f"(d[61]), "+f"(d[62]), "+f"(d[63]),
      "+f"(d[64]), "+f"(d[65]), "+f"(d[66]), "+f"(d[67]), "+f"(d[68]), "+f"(d[69]), "+f"(d[70]), "+f"(d[71]),
      "+f"(d[72]), "+f"(d[73]), "+f"(d[74]), "+f"(d[75]), "+f"(d[76]), "+f"(d[77]), "+f"(d[78]), "+f"(d[79])
      : "l"(da), "l"(db), "r"(sd));
  }
};
template <> struct WG<192> {
  static __device__ __forceinline__ void ss(float* d, uint64_t da, uint64_t db, int sd) {
    asm volatile("{\n.reg .pred p;\nsetp.ne.b32 p, %98, 0;\nwgmma.mma_async.sync.aligned.m64n192k16.f32.bf16.bf16 {"
      "%0, %1, %2, %3, %4, %5, %6, %7, %8, %9, %10, %11, %12, %13, %14, %15, "
      "%16, %17, %18, %19, %20, %21, %22, %23, %24, %25, %26, %27, %28, %29, %30, %31, "
      "%32, %33, %34, %35, %36, %37, %38, %39, %40, %41, %42, %43, %44, %45, %46, %47, "
      "%48, %49, %50, %51, %52, %53, %54, %55, %56, %57, %58, %59, %60, %61, %62, %63, "
      "%64, %65, %66, %67, %68, %69, %70, %71, %72, %73, %74, %75, %76, %77, %78, %79, "
      "%80, %81, %82, %83, %84, %85, %86, %87, %88, %89, %90, %91, %92, %93, %94, %95"
      "}, %96, %97, p, 1, 1, 0, 1;\n}\n"
      :
      "+f"(d[0]), "+f"(d[1]), "+f"(d[2]), "+f"(d[3]), "+f"(d[4]), "+f"(d[5]), "+f"(d[6]), "+f"(d[7]),
      "+f"(d[8]), "+f"(d[9]), "+f"(d[10]), "+f"(d[11]), "+f"(d[12]), "+f"(d[13]), "+f"(d[14]), "+f"(d[15]),
      "+f"(d[16]), "+f"(d[17]), "+f"(d[18]), "+f"(d[19]), "+f"(d[20]), "+f"(d[21]), "+f"(d[22]), "+f"(d[23]),
      "+f"(d[24]), "+f"(d[25]), "+f"(d[26]), "+f"(d[27]), "+f"(d[28]), "+f"(d[29]), "+f"(d[30]), "+f"(d[31]),
      "+f"(d[32]), "+f"(d[33]), "+f"(d[34]), "+f"(d[35]), "+f"(d[36]), "+f"(d[37]), "+f"(d[38]), "+f"(d[39]),
      "+f"(d[40]), "+f"(d[41]), "+f"(d[42]), "+f"(d[43]), "+f"(d[44]), "+f"(d[45]), "+f"(d[46]), "+f"(d[47]),
      "+f"(d[48]), "+f"(d[49]), "+f"(d[50]), "+f"(d[51]), "+f"(d[52]), "+f"(d[53]), "+f"(d[54]), "+f"(d[55]),
      "+f"(d[56]), "+f"(d[57]), "+f"(d[58]), "+f"(d[59]), "+f"(d[60]), "+f"(d[61]), "+f"(d[62]), "+f"(d[63]),
      "+f"(d[64]), "+f"(d[65]), "+f"(d[66]), "+f"(d[67]), "+f"(d[68]), "+f"(d[69]), "+f"(d[70]), "+f"(d[71]),
      "+f"(d[72]), "+f"(d[73]), "+f"(d[74]), "+f"(d[75]), "+f"(d[76]), "+f"(d[77]), "+f"(d[78]), "+f"(d[79]),
      "+f"(d[80]), "+f"(d[81]), "+f"(d[82]), "+f"(d[83]), "+f"(d[84]), "+f"(d[85]), "+f"(d[86]), "+f"(d[87]),
      "+f"(d[88]), "+f"(d[89]), "+f"(d[90]), "+f"(d[91]), "+f"(d[92]), "+f"(d[93]), "+f"(d[94]), "+f"(d[95])
      : "l"(da), "l"(db), "r"(sd));
  }
};

#define HSPLIT 0
#define HOLD_AT 33
#define BP_LATE 0
#define LL_AT 4
#define KV_T0 2300
#define ST_YIELD 1
#define HP0 3500
#define HPD 450
#define RAMP 1
#define LEAD 2
#define WSP_N 16
#define EARLY 0
#define CPIN 1
#define CW0 0
#define CPRE 5
#define PFT 1
#define WSP_D 600
#define D1 4
#define D2 4
#define D3 4
#define NSLEEP 32
#define G1_LATE 0
#define NPRE 1

namespace {

constexpr int kS = 2048, kD = 640, kF = 1536;
constexpr int NA = 10, NA2 = 9, NB = 5;
constexpr int A_SLOT = 8192, B_SLOT = 24576;
constexpr int OFF_A = 0;
constexpr int OFF_B = OFF_A + NA * A_SLOT;
constexpr int XB_PL = 2112;
constexpr int CV_KE = 4224, CV_KO = CV_KE + 4160;
constexpr int CV_SZ = CV_KO + 4160;
constexpr int OFF_CV = OFF_B + NB * B_SLOT;
constexpr int OFF_CS = OFF_CV + 2 * CV_SZ;
constexpr int OFF_XS = OFF_CS + 1536;
constexpr int OFF_BAR = OFF_XS + 512;
constexpr int BAR_AF = OFF_BAR, BAR_ST = BAR_AF + 8 * NA, BAR_XF = BAR_ST + 16, BAR_KV = BAR_XF + 16;
constexpr int BAR_BF = OFF_BAR + 128, BAR_G2 = BAR_BF + 8 * (NB + 1), BAR_XS = BAR_G2 + 8, BAR_KU = BAR_XS + 8, BAR_ZP = BAR_KU + 40, BAR_HOLD = BAR_ZP + 8, BAR_WO = BAR_HOLD + 8;
constexpr int BAR_AE = OFF_BAR + 256, BAR_BE = BAR_AE + 8 * NA;
constexpr int BAR_YT = BAR_KU + 24;
constexpr int BAR_HR = BAR_AE + 72;
constexpr int BAR_GO = BAR_XS, BAR_H1 = BAR_ST;
constexpr int OFF_TAG = OFF_CS - 32;
constexpr int OFF_BIAS = OFF_BAR + 384;
constexpr int SMEM_BYTES = OFF_BIAS + 128;
static_assert(SMEM_BYTES <= 232448, "smem");
constexpr int NB_WGA = 1, NB_WGC = 2, NB_G1 = 3, NB_WO = 4, NB_CD = 5, NB_Z = 6, NB_WGB = 7;

constexpr int CNT_Z = 0, CNT_Y = 1, CNT_KV = 32, CNT_WO = 36;
struct Scratch {
  uint8_t kvx[kD * 4096];
  uint8_t z2[4 * 32 * 24576];
  uint8_t h[32 * 12 * 8192];
  uint8_t wo[4 * 12 * 20480];
  uint8_t y[896 * 4096];
  uint4 xstat[kS];
  uint4 zstat[kS * 4];
  uint2 colsum[kF];
  uint32_t cnt[2 * 32];
  uint32_t hflag[32 * 64];
  uint32_t epoch[136];
};
__device__ __align__(1024) Scratch g_scr;
#define STAMP(i)
#define STAMP2(i)
#define STAMPW(i)

struct Params {
  Scratch* scr;
  int by_smid;
  const __nv_bfloat16 *k, *v, *shift, *ssmk, *ssmD, *wsp, *bsp, *wout;
  __nv_bfloat16* out;
  CUtensorMap tmX, tmW, tmWsp, tmY, tmKV;
};

__device__ __forceinline__ uint64_t mkdesc(uint32_t addr, uint32_t lbo, uint32_t sbo, uint32_t swz) {
  return (uint64_t)((addr & 0x3FFFF) >> 4) | ((uint64_t)(lbo >> 4) << 16) | ((uint64_t)(sbo >> 4) << 32) | ((uint64_t)swz << 62);
}
#define WG_FENCE() asm volatile("wgmma.fence.sync.aligned;" ::: "memory")
#define WG_COMMIT() asm volatile("wgmma.commit_group.sync.aligned;" ::: "memory")
#define WG_WAIT(n) asm volatile("wgmma.wait_group.sync.aligned %0;" ::"n"(n) : "memory")
template <int N> __device__ __forceinline__ void acc_fence(float* d) {
#pragma unroll
  for (int i = 0; i < N; i++) asm volatile("" : "+f"(d[i])::"memory");
}
__device__ __forceinline__ void mbar_init(uint32_t bar, int cnt) { asm volatile("mbarrier.init.shared::cta.b64 [%0], %1;" ::"r"(bar), "r"(cnt) : "memory"); }
__device__ __forceinline__ void mbar_expect(uint32_t bar, uint32_t bytes) { asm volatile("mbarrier.arrive.expect_tx.shared::cta.b64 _, [%0], %1;" ::"r"(bar), "r"(bytes) : "memory"); }
__device__ __forceinline__ void mbar_arrive(uint32_t bar) { asm volatile("mbarrier.arrive.shared::cta.b64 _, [%0];" ::"r"(bar) : "memory"); }
__device__ __forceinline__ void mbar_arrive_if(uint32_t bar, bool c) {
  asm volatile("{\n.reg .pred p;\nsetp.ne.u32 p, %1, 0;\n@p mbarrier.arrive.shared::cta.b64 _, [%0];\n}\n" ::"r"(bar), "r"((uint32_t)c) : "memory");
}
__device__ __forceinline__ bool mbar_try(uint32_t bar, uint32_t parity) {
  uint32_t ok;
  asm volatile("{\n.reg .pred p;\nmbarrier.try_wait.parity.shared::cta.b64 p, [%1], %2;\nselp.u32 %0, 1, 0, p;\n}\n" : "=r"(ok) : "r"(bar), "r"(parity) : "memory");
  return ok;
}
__device__ __forceinline__ bool mbar_test(uint32_t bar, uint32_t parity) {
  uint32_t ok;
  asm volatile("{\n.reg .pred p;\nmbarrier.test_wait.parity.shared::cta.b64 p, [%1], %2;\nselp.u32 %0, 1, 0, p;\n}\n" : "=r"(ok) : "r"(bar), "r"(parity) : "memory");
  return ok;
}
__device__ __forceinline__ void die() { asm volatile("st.volatile.global.u32 [%0], %1;" ::"l"(0ull), "r"(0) : "memory"); }
__device__ __forceinline__ void spin_guard(uint32_t& n) { if (++n == (1u << 22)) die(); }
__device__ __forceinline__ void mbar_wait(uint32_t bar, uint32_t parity) {
  uint32_t t0 = 0;
#pragma unroll 1
  while (!mbar_try(bar, parity)) spin_guard(t0);
}
__device__ __forceinline__ void mbar_wait2(uint32_t b0, uint32_t p0, uint32_t b1, uint32_t p1) {
  uint32_t t0 = 0;
#pragma unroll 1
  while (true) {
    const bool r0 = mbar_try(b0, p0), r1 = mbar_try(b1, p1);
    if (r0 && r1) break;
    spin_guard(t0);
  }
}
__device__ __forceinline__ int tid_now() { int v; asm volatile("mov.u32 %0, %%tid.x;" : "=r"(v)); return v & 127; }
__device__ __forceinline__ bool elect_one() {
  uint32_t p;
  asm volatile("{\n.reg .pred P;\nelect.sync _|P, 0xffffffff;\nselp.u32 %0, 1, 0, P;\n}\n" : "=r"(p));
  return p;
}
__device__ __forceinline__ void bar_sync(int id, int n) { asm volatile("bar.sync %0, %1;" ::"r"(id), "r"(n) : "memory"); }
__device__ __forceinline__ void bar_arrive(int id, int n) { asm volatile("bar.arrive %0, %1;" ::"r"(id), "r"(n) : "memory"); }
__device__ __forceinline__ void fence_async_smem() { asm volatile("fence.proxy.async.shared::cta;" ::: "memory"); }
__device__ __forceinline__ void bulk_g2s(uint32_t dst, const void* src, uint32_t bytes, uint32_t bar) {
  asm volatile("cp.async.bulk.shared::cluster.global.mbarrier::complete_tx::bytes [%0], [%1], %2, [%3];" ::"r"(dst), "l"(src), "r"(bytes), "r"(bar) : "memory");
}
__device__ __forceinline__ void bulk_s2g(void* dst, uint32_t src, uint32_t bytes) {
  asm volatile("cp.async.bulk.global.shared::cta.bulk_group [%0], [%1], %2;" ::"l"(dst), "r"(src), "r"(bytes) : "memory");
}
__device__ __forceinline__ void tma2d(uint32_t dst, const CUtensorMap* m, int c0, int c1, uint32_t bar) {
  asm volatile("cp.async.bulk.tensor.2d.shared::cluster.global.mbarrier::complete_tx::bytes [%0], [%1, {%3, %4}], [%2];" ::"r"(dst), "l"(m), "r"(bar), "r"(c0), "r"(c1) : "memory");
}
__device__ __forceinline__ void tma_rows(uint32_t dst, const CUtensorMap* m, int c0, int rb, uint32_t bar) {
  asm volatile("cp.async.bulk.tensor.5d.shared::cluster.global.mbarrier::complete_tx::bytes [%0], [%1, {%3, %4, %4, %4, %5}], [%2];" ::"r"(dst), "l"(m), "r"(bar), "r"(c0), "r"(0), "r"(rb * 2) : "memory");
}
__device__ __forceinline__ int row_grp(int w, int half) { return (w >> 1) * 4 + (w & 1) + 2 * half; }
__device__ __forceinline__ void tma3d(uint32_t dst, const CUtensorMap* m, int c0, int c1, int c2, uint32_t bar) {
  asm volatile("cp.async.bulk.tensor.3d.shared::cluster.global.mbarrier::complete_tx::bytes [%0], [%1, {%3, %4, %5}], [%2];" ::"r"(dst), "l"(m), "r"(bar), "r"(c0), "r"(c1), "r"(c2) : "memory");
}
__device__ __forceinline__ void st_release(uint32_t* p, uint32_t v) { asm volatile("st.release.gpu.global.u32 [%0], %1;" ::"l"(p), "r"(v) : "memory"); }
__device__ __forceinline__ uint4 ld_ll4(const void* p) {
  uint64_t a, b;
  asm volatile("ld.relaxed.gpu.global.v2.u64 {%0,%1}, [%2];" : "=l"(a), "=l"(b) : "l"(p) : "memory");
  return make_uint4((uint32_t)a, (uint32_t)(a >> 32), (uint32_t)b, (uint32_t)(b >> 32));
}
__device__ __forceinline__ void st_ll4(void* p, uint32_t a, uint32_t b, uint32_t c, uint32_t d) {
  asm volatile("st.relaxed.gpu.global.v2.u64 [%0], {%1,%2};" ::"l"(p), "l"(a | ((uint64_t)b << 32)), "l"(c | ((uint64_t)d << 32)) : "memory");
}
__device__ __forceinline__ void st_ll2(void* p, uint32_t a, uint32_t b) { asm volatile("st.relaxed.gpu.global.u64 [%0], %1;" ::"l"(p), "l"(a | ((uint64_t)b << 32)) : "memory"); }
__device__ __forceinline__ void wgmma_colsum(float* d, uint64_t da, uint64_t db) {
  asm volatile("{\n.reg .pred p;\nsetp.ne.b32 p, 1, 0;\nwgmma.mma_async.sync.aligned.m64n8k16.f32.bf16.bf16 {%0, %1, %2, %3}, %4, %5, p, 1, 1, 1, 0;\n}\n"
               : "+f"(d[0]), "+f"(d[1]), "+f"(d[2]), "+f"(d[3]) : "l"(da), "l"(db));
}
__device__ __forceinline__ void prefetch_l2(const void* p) { asm volatile("prefetch.global.L2 [%0];" ::"l"(p)); }
__device__ __forceinline__ void pace(uint32_t& t, uint32_t dt) {
  t += dt;
  while ((int32_t)((uint32_t)clock() - t) < 0) { if (NSLEEP) __nanosleep(NSLEEP); }
}
__device__ __forceinline__ void red_relaxed(uint32_t* p) { asm volatile("red.relaxed.gpu.global.add.u32 [%0], 1;" ::"l"(p) : "memory"); }
__device__ __forceinline__ void red_release(uint32_t* p) { asm volatile("red.release.gpu.global.add.u32 [%0], 1;" ::"l"(p) : "memory"); }
__device__ __forceinline__ uint4 ldg4(const void* p) { uint4 v; asm volatile("ld.global.v4.u32 {%0,%1,%2,%3}, [%4];" : "=r"(v.x), "=r"(v.y), "=r"(v.z), "=r"(v.w) : "l"(p) : "memory"); return v; }
__device__ __forceinline__ uint32_t ldg1(const void* p) { uint32_t v; asm volatile("ld.global.u32 %0, [%1];" : "=r"(v) : "l"(p) : "memory"); return v; }
__device__ __forceinline__ void stg4_if(void* p, uint32_t a, uint32_t b, uint32_t c, uint32_t d, bool on) {
  asm volatile("{\n.reg .pred p;\nsetp.ne.u32 p, %5, 0;\n@p st.global.v4.u32 [%0], {%1,%2,%3,%4};\n}\n" ::"l"(p), "r"(a), "r"(b), "r"(c), "r"(d), "r"((uint32_t)on) : "memory");
}
template <int OFF> __device__ __forceinline__ uint32_t lds32(uint32_t a) { uint32_t v; asm volatile("ld.shared.u32 %0, [%1+%2];" : "=r"(v) : "r"(a), "n"(OFF)); return v; }
__device__ __forceinline__ uint4 lds128(uint32_t a) { uint4 v; asm volatile("ld.shared.v4.u32 {%0,%1,%2,%3}, [%4];" : "=r"(v.x), "=r"(v.y), "=r"(v.z), "=r"(v.w) : "r"(a) : "memory"); return v; }
__device__ __forceinline__ float2 lds64f(uint32_t a) { float2 v; asm volatile("ld.shared.v2.f32 {%0,%1}, [%2];" : "=f"(v.x), "=f"(v.y) : "r"(a) : "memory"); return v; }
__device__ __forceinline__ void sts64f(uint32_t a, float x, float y) { asm volatile("st.shared.v2.f32 [%0], {%1,%2};" ::"r"(a), "f"(x), "f"(y) : "memory"); }
__device__ __forceinline__ void sts32(uint32_t a, uint32_t x) { asm volatile("st.shared.u32 [%0], %1;" ::"r"(a), "r"(x) : "memory"); }
__device__ __forceinline__ void sts128(uint32_t a, uint32_t x, uint32_t y, uint32_t z, uint32_t w) { asm volatile("st.shared.v4.u32 [%0], {%1,%2,%3,%4};" ::"r"(a), "r"(x), "r"(y), "r"(z), "r"(w) : "memory"); }
__device__ __forceinline__ void stsm4(uint32_t a, uint32_t r0, uint32_t r1, uint32_t r2, uint32_t r3) {
  asm volatile("stmatrix.sync.aligned.m8n8.x4.shared.b16 [%0], {%1,%2,%3,%4};" ::"r"(a), "r"(r0), "r"(r1), "r"(r2), "r"(r3) : "memory");
}
__device__ __forceinline__ void stsm4t(uint32_t a, uint32_t r0, uint32_t r1, uint32_t r2, uint32_t r3) {
  asm volatile("stmatrix.sync.aligned.m8n8.x4.trans.shared.b16 [%0], {%1,%2,%3,%4};" ::"r"(a), "r"(r0), "r"(r1), "r"(r2), "r"(r3) : "memory");
}
__device__ __forceinline__ void ldsm4t(uint32_t* r, uint32_t a) {
  asm volatile("ldmatrix.sync.aligned.m8n8.x4.trans.shared.b16 {%0,%1,%2,%3}, [%4];" : "=r"(r[0]), "=r"(r[1]), "=r"(r[2]), "=r"(r[3]) : "r"(a) : "memory");
}
__device__ __forceinline__ uint32_t pack2(float lo, float hi) { uint32_t r; asm("cvt.rn.bf16x2.f32 %0, %1, %2;" : "=r"(r) : "f"(hi), "f"(lo)); return r; }
__device__ __forceinline__ float bf_lo(uint32_t u) { return __uint_as_float(u << 16); }
__device__ __forceinline__ float bf_hi(uint32_t u) { return __uint_as_float(u & 0xffff0000u); }
__device__ __forceinline__ float tanh_fast(float x) { float y; asm("tanh.approx.f32 %0, %1;" : "=f"(y) : "f"(x)); return y; }
__device__ __forceinline__ uint32_t hmul2(uint32_t a, uint32_t b) { uint32_t r; asm("mul.rn.bf16x2 %0, %1, %2;" : "=r"(r) : "r"(a), "r"(b)); return r; }
__device__ __forceinline__ uint32_t hfma2(uint32_t a, uint32_t b, uint32_t c) { uint32_t r; asm("fma.rn.bf16x2 %0, %1, %2, %3;" : "=r"(r) : "r"(a), "r"(b), "r"(c)); return r; }
__device__ __forceinline__ uint32_t prmt(uint32_t a, uint32_t b, uint32_t s) { return __byte_perm(a, b, s); }

__device__ __forceinline__ uint32_t ld_relaxed(const uint32_t* p) { uint32_t v; asm volatile("ld.relaxed.gpu.global.u32 %0, [%1];" : "=r"(v) : "l"(p) : "memory"); return v; }
__device__ __forceinline__ void acquire_fence() { asm volatile("fence.acquire.gpu;\nfence.proxy.async.global;" ::: "memory"); }
__device__ __forceinline__ uint32_t load_epoch(const Params& p, int idx, int lane) { return ld_relaxed(&p.scr->epoch[idx + (((lane * lane) & 3) == 2 ? 1 : 0)]); }
__device__ __forceinline__ void poll_counter(const uint32_t* cnt, uint32_t target) {
  uint32_t t0 = 0;
#pragma unroll 1
  while (!__all_sync(0xffffffff, ld_relaxed(cnt) == target)) spin_guard(t0);
  acquire_fence();
}

__device__ __forceinline__ int g3_block(int cb, int it) {
  const int j = it < 6 ? it - 3 : (it - 6) >> 1;
  return it < 3 ? cb * 3 + it : (j + (j >= cb)) * 3 + (it < 6 ? 0 : 1 + (it & 1));
}
__device__ __forceinline__ void reset_sector(uint32_t* f) { st_ll4(f, 0, 0, 0, 0); st_ll4(f + 4, 0, 0, 0, 0); }

template <int N, bool A_SWZ, int B_MODE, int DEPTH, class Hook>
__device__ __forceinline__ void gemm_loop(float* d, uint32_t sb, int nkb, int sa, int pa, int b0, uint32_t boff, int relA, int relB, int tid, Hook hook) {
  constexpr uint32_t A_STEP = A_SWZ ? 2 : 128;
  constexpr uint32_t B_STEP = B_MODE == 0 ? 128 : (B_MODE == 1 ? 384 : 320);
  const uint64_t da0 = A_SWZ ? mkdesc(sb + OFF_A, 16, 1024, 1) : mkdesc(sb + OFF_A, 1024, 128, 0);
  const uint64_t db0 = B_MODE == 0 ? mkdesc(sb + OFF_B + boff, 8192, 1024, 1) : mkdesc(sb + OFF_B + boff, B_MODE == 1 ? 3072 : 2560, 128, 0);
  constexpr int MODA = B_MODE == 0 ? NA : NA2;
  constexpr int MODB = B_MODE == 2 ? 6 : NB;
  int sbk = b0 % MODB, pb = (b0 / MODB) & 1;
  auto boffs = [](int s_) { return B_MODE == 2 ? (s_ == 5 ? 0 : s_ + 1) * (20480 >> 4) : s_ * (B_SLOT >> 4); };
  uint32_t rel = 0;
  uint64_t da = da0 + sa * (A_SLOT >> 4), db = db0 + boffs(sbk);
  const bool doR = tid < 2 ? tid < relA : tid - 2 < relB;
  mbar_wait2(sb + BAR_AF + 8 * sa, pa, sb + BAR_BF + 8 * sbk, pb);
#pragma unroll 1
  for (int it = 0; it < nkb; it++) {
    WG_FENCE();
    WG<N>::ss(d, da, db, 1);
    const uint32_t prel = rel;
    rel = sb + BAR_AE + 8 * (tid < 2 ? sa : sbk + NA);
    if (++sa == MODA) { sa = 0; pa ^= 1; }
    if (++sbk == MODB) { sbk = 0; pb ^= 1; }
    if (DEPTH == 1) { WG_COMMIT(); WG_WAIT(1); }
    WG<N>::ss(d, da + A_STEP, db + B_STEP, 1);
    WG_COMMIT();
    WG_WAIT(1);
    if (EARLY == 1) mbar_arrive_if(prel, doR && it != 0);
    WG<N>::ss(d, da + 2 * A_STEP, db + 2 * B_STEP, 1);
    if (DEPTH == 1) WG_COMMIT();
    if (EARLY != 1) mbar_arrive_if(prel, doR && it != 0);
    const bool r0 = mbar_test(sb + BAR_AF + 8 * sa, pa), r1 = mbar_test(sb + BAR_BF + 8 * sbk, pb);
    const uint64_t da3 = da + 3 * A_STEP, db3 = db + 3 * B_STEP;
    da = da0 + sa * (A_SLOT >> 4); db = db0 + boffs(sbk);
    if (DEPTH == 1) WG_WAIT(1);
    WG<N>::ss(d, da3, db3, 1);
    WG_COMMIT();
    if (it + 1 < nkb) {
      if (!(r0 && r1)) {
        mbar_wait2(sb + BAR_AF + 8 * sa, pa, sb + BAR_BF + 8 * sbk, pb);
      }
    }
    if (DEPTH == 2) WG_WAIT(1);
  }
  hook();
  WG_WAIT(0);
  acc_fence<N / 2>(d);
  mbar_arrive_if(rel, doR);
}

__device__ __forceinline__ void gelu_tile(const float* d, uint32_t* z, float* st, uint32_t cs_addr, float2 s0, float2 s1) {
  const float kA = 0.7978845608028654f, kB = 0.7978845608028654f * 0.044715f;
  const float c1a = kA * s0.y, c3a = kB * s0.y * s0.y * s0.y, ma = -s0.x;
  const float c1b = kA * s1.y, c3b = kB * s1.y * s1.y * s1.y, mb = -s1.x;
  float acc[8];
#pragma unroll
  for (int i = 0; i < 8; i++) acc[i] = 0.f;
#pragma unroll
  for (int j = 0; j < 24; j++) {
    const float2 cs = lds64f(cs_addr + j * 32);
    float r[4];
#pragma unroll
    for (int e = 0; e < 4; e++) {
      const float c = (e & 1) ? cs.y : cs.x;
      const float v = fmaf(e < 2 ? ma : mb, c, d[4 * j + e]);
      const float a = v * fmaf(v * v, e < 2 ? c3a : c3b, e < 2 ? c1a : c1b);
      r[e] = fmaf(v, tanh_fast(a), v);
      acc[e] += r[e];
      acc[4 + e] = fmaf(r[e], r[e], acc[4 + e]);
    }
    z[2 * j] = pack2(r[0], r[1]);
    z[2 * j + 1] = pack2(r[2], r[3]);
  }
  st[0] = acc[0] + acc[1]; st[1] = acc[4] + acc[5]; st[2] = acc[2] + acc[3]; st[3] = acc[6] + acc[7];
}

template <int Q> __device__ __forceinline__ void conv_load(uint32_t* a, uint32_t ab) {
  a[0] = lds32<512 * Q>(ab);       a[1] = lds32<512 * Q + 256>(ab);  a[2] = lds32<512 * Q + 16>(ab);   a[3] = lds32<512 * Q + 272>(ab);
  a[4] = lds32<512 * Q + 32>(ab);  a[5] = lds32<512 * Q + 288>(ab);  a[6] = lds32<512 * Q + 48>(ab);   a[7] = lds32<512 * Q + 304>(ab);
  a[8] = lds32<512 * Q + 64>(ab);  a[9] = lds32<512 * Q + 320>(ab);  a[10] = lds32<512 * Q + 80>(ab);  a[11] = lds32<512 * Q + 336>(ab);
  a[12] = lds32<512 * Q + 96>(ab); a[13] = lds32<512 * Q + 352>(ab); a[14] = lds32<512 * Q + 112>(ab); a[15] = lds32<512 * Q + 368>(ab);
}
template <int Q, int L> __device__ __forceinline__ void conv_step(float* d, uint32_t (*a)[16], uint32_t ab, uint64_t db) {
  WG_FENCE();
#pragma unroll
  for (int s = 0; s < 4; s++) WG<128 - 16 * Q>::rs(d, a[Q] + 4 * s, db + s + 16 * Q);
  WG_COMMIT();
  if (CPIN) WG_WAIT(1);
  if (L >= 0) conv_load<(L >= 0 ? L : 0)>(a[L >= 0 ? L : 0], ab);
  if (CW0 || Q == 0) WG_WAIT(0);
}

__device__ __forceinline__ int seg_col(int cb, int h) { return (cb >> 1) * 320 + (cb & 1) * 32 + h * 64; }
__device__ __forceinline__ void final_load_x(uint32_t (*xw)[10], uint32_t xt, int cb, int h, int w, int lane) {
  const int g = lane >> 2, t = lane & 3, cc = seg_col(cb, h) >> 3;
  const int c0 = cc + t, c1 = c0 + 24, c2 = cc + 16 - 6 * h + (t >> 1);
  const uint32_t r0 = xt + (w * 16 + g) * 128;
#pragma unroll
  for (int r = 0; r < 2; r++) {
    const uint4 u = lds128(r0 + r * 1024 + (c0 >> 3) * A_SLOT + (((c0 ^ g) & 7) << 4)), v = lds128(r0 + r * 1024 + (c1 >> 3) * A_SLOT + (((c1 ^ g) & 7) << 4));
    const float2 z = lds64f(r0 + r * 1024 + (c2 >> 3) * A_SLOT + (((c2 ^ g) & 7) << 4) + (t & 1) * 8);
    xw[r][0] = u.x; xw[r][1] = u.y; xw[r][2] = u.z; xw[r][3] = u.w;
    xw[r][4] = v.x; xw[r][5] = v.y; xw[r][6] = v.z; xw[r][7] = v.w;
    xw[r][8] = __float_as_uint(z.x); xw[r][9] = __float_as_uint(z.y);
  }
}
__device__ __forceinline__ bool final_s(uint32_t (*sw)[10], const uint32_t (*xw)[10], uint32_t yt, float2 s0, float2 s1, int w, int lane) {
  const int r8 = lane & 7, mi = lane >> 3;
  const uint32_t ya = yt + ((mi >> 1) * 8 + r8) * 128 + ((row_grp(w, mi & 1) ^ r8) << 4);
  const uint32_t r2[2] = {pack2(s0.y, s0.y), pack2(s1.y, s1.y)};
  const float na = -s0.x * bf_lo(r2[0]), nb = -s1.x * bf_lo(r2[1]);
  const uint32_t n2[2] = {pack2(na, na), pack2(nb, nb)};
  uint32_t zero = 0;
#pragma unroll
  for (int j = 0; j < 10; j += 2) {
    uint32_t y[4];
    ldsm4t(y, ya + (j < 4 ? j : (j < 8 ? j + 2 : 4)) * 1024);
#pragma unroll
    for (int e = 0; e < 4; e++) {
      if (j == 4 || j == 6) { zero |= (y[e] - 0x00010001u) & ~y[e]; y[e] = ~y[e]; }
      sw[e & 1][j + (e >> 1)] = hmul2(hfma2(xw[e & 1][j + (e >> 1)], r2[e & 1], n2[e & 1]), y[e]);
    }
  }
  return (zero & 0x80008000u) == 0;
}
__device__ __forceinline__ bool bar_all(int id, int n, bool c) {
  uint32_t r;
  asm volatile("{\n.reg .pred p, q;\nsetp.ne.u32 p, %3, 0;\nbar.red.and.pred q, %1, %2, p;\nselp.u32 %0, 1, 0, q;\n}\n" : "=r"(r) : "r"(id), "r"(n), "r"((uint32_t)c) : "memory");
  return r;
}
__device__ __forceinline__ void final_out(const float* d, const uint32_t (*xw)[10], const uint32_t (*sw)[10], float ra, float rb, __nv_bfloat16* o0, int h, int t) {
  const float ca = 0.25f * ra, cb = 0.25f * rb;
  uint32_t o[2][10];
#pragma unroll
  for (int j = 0; j < 10; j++) {
#pragma unroll
    for (int r = 0; r < 2; r++) {
      const float h0 = d[4 * j + 2 * r] * (r ? cb : ca), h1 = d[4 * j + 2 * r + 1] * (r ? cb : ca);
      o[r][j] = hfma2(pack2(fmaf(h0, tanh_fast(h0), h0), fmaf(h1, tanh_fast(h1), h1)), sw[r][j], xw[r][j]);
      __nv_bfloat16* q = o0 + r * 16 * kD;
      if (j == 3) stg4_if(q + t * 8, o[r][0], o[r][1], o[r][2], o[r][3], true);
      if (j == 7) stg4_if(q + 192 + t * 8, o[r][4], o[r][5], o[r][6], o[r][7], true);
      if (j == 9) asm volatile("st.global.v2.u32 [%0], {%1,%2};" ::"l"(q + 128 - 48 * h + t * 4), "r"(o[r][8]), "r"(o[r][9]) : "memory");
    }
  }
}

struct Taps { uint4 r0, r1; uint32_t n0, n1, dd; };
__device__ __forceinline__ void load_taps(Taps& k, const Params& p, int ch, int tid) {
  const uint4* kp = (const uint4*)(p.ssmk + (size_t)ch * kS);
  k.r0 = ldg4(kp + tid); k.r1 = ldg4(kp + 128 + tid);
  k.n0 = ldg1(kp + tid + 1); k.n1 = tid < 127 ? ldg1(kp + 129 + tid) : 0u;
  k.dd = __bfloat16_as_ushort(p.ssmD[ch]);
}
__device__ __forceinline__ void load_convx(const Params& p, uint32_t cv, uint32_t bar, int ch) {
  mbar_expect(bar, 4096);
  bulk_g2s(cv, p.scr->kvx + (size_t)ch * 4096, 2048, bar);
  bulk_g2s(cv + XB_PL, p.scr->kvx + (size_t)ch * 4096 + 2048, 2048, bar);
}
#define CW 3
#define CSTAMP(j)
__device__ __forceinline__ void zero_pads(uint32_t cv, int lane) {
  if (lane < 8) sts128(cv + (lane >> 2) * XB_PL + 2048 + (lane & 3) * 16, 0, 0, 0, 0);
  else if (lane < 12) sts128(cv + ((lane & 2) ? CV_KO : CV_KE) + (lane & 1) * 16, 0, 0, 0, 0);
  fence_async_smem();
  __syncwarp();
}
__device__ __forceinline__ int y_row(int c, uint32_t par) {
  const int hf = c >= 320, cc = c - hf * 320, u = cc >> 6, cb = hf * 2 + ((cc >> 5) & 1);
  if (u == 2) return cb * 96 + ((cc >> 4) & 1) * 48 + 32 + (cc & 1) + ((cc >> 1) & 1) * 8 + ((cc >> 2) & 3) * 2;
  return (u < 2 ? cb * 96 + u * 48 : 384 + par * 256 + cb * 64 + (u - 3) * 32) + (cc & 1) + ((cc >> 1) & 3) * 8 + ((cc >> 3) & 3) * 2;
}
__device__ __forceinline__ void y_store(const Params& p, uint32_t sb, int h, int ch, uint32_t par) {
  uint8_t* dst = p.scr->y + (size_t)y_row(ch, par) * 4096;
  if (elect_one()) {
    bulk_s2g(dst, sb + OFF_A + 9 * A_SLOT + h * 4096, 4096);
    asm volatile("cp.async.bulk.commit_group;\ncp.async.bulk.wait_group 0;" ::: "memory");
  }
  __syncwarp();
}
__device__ __forceinline__ void conv_service(const Params& p, uint32_t sb, int h, int ch) {
  bar_sync(NB_WGA + 8 + h, 160);
  if (elect_one()) load_convx(p, sb + OFF_CV + (1 - h) * CV_SZ, sb + BAR_XF + 8 * h, ch + 128);
  bar_sync(NB_WGA + 8 + h, 160);
  y_store(p, sb, h, ch, 0);
}
__device__ __forceinline__ uint32_t y_tile(int h) { return OFF_CV + (1 - h) * 13312; }
__device__ __forceinline__ void load_late_y(const Params& p, uint32_t sb, int h, int rb, int cb, uint32_t par) {
  tma2d(sb + y_tile(h) + 6144, &p.tmY, rb * 64, 384 + par * 256 + cb * 64 + h * 32, sb + BAR_XF + 8 * h);
  tma2d(sb + y_tile(h) + 8192, &p.tmY, rb * 64, 400 + par * 256 + cb * 64 + h * 32, sb + BAR_XF + 8 * h);
}
__device__ __forceinline__ void held_service(const Params& p, uint32_t sb, int h, int ch, int rb, int cb, uint32_t tag, int lane) {
#pragma unroll 1
  for (int i = 0; i < 8; i++) sts128(sb + OFF_A + 9 * A_SLOT + h * 4096 + i * 512 + lane * 16, 0, 0, 0, 0);
  fence_async_smem();
  __syncwarp();
  y_store(p, sb, h, ch, ~tag & 1);
  mbar_wait(sb + BAR_YT, 1);
  acquire_fence();
  bar_sync(NB_WGA + 8 + h, 160);
  bar_sync(NB_WGA + 8 + h, 160);
  uint8_t* dst = p.scr->y + (size_t)y_row(ch, tag & 1) * 4096;
  if (elect_one()) {
    bulk_s2g(dst, sb + OFF_A + 9 * A_SLOT + h * 4096, 4096);
    asm volatile("cp.async.bulk.commit_group;" ::: "memory");
    mbar_expect(sb + BAR_XF + 8 * h, 10240);
#pragma unroll 1
    for (int i = 0; i < 3; i++) tma2d(sb + y_tile(h) + i * 2048, &p.tmY, rb * 64, cb * 96 + h * 48 + i * 16, sb + BAR_XF + 8 * h);
  }
  mbar_wait(sb + BAR_AE + 8 * (LL_AT - 1), 1);
  if (elect_one()) { load_late_y(p, sb, h, rb, cb, tag & 1); asm volatile("cp.async.bulk.wait_group 0;" ::: "memory"); }
}
__device__ __forceinline__ void conv_worker(const Params& p, Taps& k, uint32_t cv, uint32_t yb0,
                                            uint32_t xbar, int nbar, int ch0, int n, uint32_t holdbar, int w, int lane,
                                            int tid, int st0, int rb, int cb) {
  const int g = lane >> 2, t = lane & 3, w0 = w & 1, w1 = w >> 1;
  const uint32_t ab = cv + ((g & 1) ? CV_KE : CV_KO) + 32 + 2 * (64 * w0 + 8 * w1 + ((g - 15) & ~1) + 2 * t);
  const uint32_t scA = cv + (w1 ? CV_KO : CV_KE) + 32, scB = scA + 2048;
  const int dl = (t >> 1) ^ 1;
  if (n == 2) mbar_wait(xbar, 0);
  STAMPW(st0 + 3);
#pragma unroll 1
  for (int i = 0; i < n; i++) {
    if (tid == 0) {
      k.r0.x = (k.r0.x & 0xffff0000u) | (pack2(bf_lo(k.r0.x) + bf_lo(k.dd), 0.f) & 0xffffu);
      sts32(cv + CV_KO + 28, k.r0.x << 16);
    }
    sts128(cv + CV_KE + 32 + tid * 16, k.r0.x, k.r0.y, k.r0.z, k.r0.w);
    sts128(cv + CV_KO + 32 + tid * 16, prmt(k.r0.x, k.r0.y, 0x5432), prmt(k.r0.y, k.r0.z, 0x5432), prmt(k.r0.z, k.r0.w, 0x5432), prmt(k.r0.w, k.n0, 0x5432));
    sts128(cv + CV_KE + 2080 + tid * 16, k.r1.x, k.r1.y, k.r1.z, k.r1.w);
    sts128(cv + CV_KO + 2080 + tid * 16, prmt(k.r1.x, k.r1.y, 0x5432), prmt(k.r1.y, k.r1.z, 0x5432), prmt(k.r1.z, k.r1.w, 0x5432), prmt(k.r1.w, k.n1, 0x5432));
    if (i + 1 < n) load_taps(k, p, ch0 + (i + 1) * 128, tid);
    bar_sync(nbar, 128);
    CSTAMP(0);
    const uint64_t db = mkdesc(cv + (i & 0x1000), XB_PL, 128, 0);
    float d[64];
    uint32_t a[8][16];
    conv_load<7>(a[7], ab);
    if (CPRE > 1) conv_load<6>(a[6], ab);
    if (CPRE > 2) conv_load<5>(a[5], ab);
    if (CPRE > 3) conv_load<4>(a[4], ab);
#pragma unroll
    for (int j = 0; j < 64; j++) d[j] = 0.f;
    mbar_wait(xbar, i & 1);
    if (i + 1 == n) mbar_wait(holdbar, 1);
    CSTAMP(1);
    if (CPRE == 1) {
      conv_step<7, 6>(d, a, ab, db); conv_step<6, 5>(d, a, ab, db); conv_step<5, 4>(d, a, ab, db); conv_step<4, 3>(d, a, ab, db);
      conv_step<3, 2>(d, a, ab, db); conv_step<2, 1>(d, a, ab, db); conv_step<1, 0>(d, a, ab, db); conv_step<0, -1>(d, a, ab, db);
    } else if (CPRE == 3) {
      conv_step<7, -1>(d, a, ab, db); conv_step<6, 4>(d, a, ab, db); conv_step<5, 3>(d, a, ab, db); conv_step<4, 2>(d, a, ab, db);
      conv_step<3, 1>(d, a, ab, db); conv_step<2, 0>(d, a, ab, db); conv_step<1, -1>(d, a, ab, db); conv_step<0, -1>(d, a, ab, db);
    } else if (CPRE == 4) {
      conv_step<7, -1>(d, a, ab, db); conv_step<6, -1>(d, a, ab, db); conv_step<5, 3>(d, a, ab, db); conv_step<4, 2>(d, a, ab, db);
      conv_step<3, 1>(d, a, ab, db); conv_step<2, 0>(d, a, ab, db); conv_step<1, -1>(d, a, ab, db); conv_step<0, -1>(d, a, ab, db);
    } else {
      conv_step<7, -1>(d, a, ab, db); conv_step<6, -1>(d, a, ab, db); conv_step<5, -1>(d, a, ab, db); conv_step<4, 3>(d, a, ab, db);
      conv_step<3, 2>(d, a, ab, db); conv_step<2, 1>(d, a, ab, db); conv_step<1, 0>(d, a, ab, db); conv_step<0, -1>(d, a, ab, db);
    }
    acc_fence<64>(d);
    if (BP_LATE && i + 1 == n) bar_arrive(NB_G1, 384);
    CSTAMP(2);
    bar_sync(nbar + 8, 160);
    float E[16][2];
#pragma unroll
    for (int j = 0; j < 15; j++) { E[j][0] = d[4 * j] + d[4 * j + 6]; E[j][1] = d[4 * j + 1] + d[4 * j + 7]; }
    E[15][0] = d[60]; E[15][1] = d[61];
    if (w0 == 0) {
#pragma unroll
      for (int j = 8; j < 16; j++) sts64f(scA + (j - 8) * 256 + lane * 8, E[j][0], E[j][1]);
    } else {
      const uint32_t a = scB - dl * 256 + (lane ^ 2) * 8;
#pragma unroll
      for (int j = 1; j < 8; j++) sts64f(a + j * 256, E[j][0], E[j][1]);
      sts64f(scB + (dl ? 7 * 256 : 0) + (lane ^ 2) * 8, dl ? E[8][0] : E[0][0], dl ? E[8][1] : E[0][1]);
    }
    bar_sync(nbar, 128);
    CSTAMP(3);
    uint32_t pk[8];
    if (w0 == 0) {
#pragma unroll
      for (int j = 0; j < 8; j++) { const float2 v = lds64f(scB + j * 256 + lane * 8); pk[j] = pack2(E[j][0] + v.x, E[j][1] + v.y); }
    } else {
      const uint32_t a0 = scA - dl * 256 + (lane ^ 2) * 8;
#pragma unroll
      for (int j = 9; j < 16; j++) { const float2 v = lds64f(a0 + (j - 8) * 256); pk[j - 8] = pack2(E[j][0] + v.x, E[j][1] + v.y); }
      const float2 v = lds64f(scA + (dl ? 7 * 256 : 0) + (lane ^ 2) * 8);
      pk[0] = pack2((dl ? 0.f : E[8][0]) + v.x, (dl ? 0.f : E[8][1]) + v.y);
    }
    CSTAMP(4);
    if (i + 1 == n) {
#pragma unroll
      for (int j = 0; j < 8; j++) pk[j] = ~pk[j];
    }
    const uint32_t yb = yb0 + 32 * ((w0 ? 35 : 95) - lane) + 16 * w1;
    stsm4t((w0 && lane < 4) ? yb - 1024 : yb + 1024, pk[0], pk[1], pk[2], pk[3]);
    stsm4t(yb, pk[4], pk[5], pk[6], pk[7]);
    fence_async_smem();
    bar_sync(nbar + 8, 160);
    CSTAMP(5);
    STAMPW(st0 + i);
    if (n == 2 && i == 0) {
      const int u = (tid >> 3) % 5, kg = rb * 3 + (tid < 120 ? (tid >> 3) / 5 : 0), c = u < 4 ? (u >> 1) * 10 + (u & 1) * 4 : 8, o2 = u < 4 ? 2 : 10;
      const uint4* wp = (const uint4*)p.wout + (uint32_t)((kg * 8 + (tid & 7)) * (kD / 8) + (seg_col(cb, 0) >> 3) + (u < 4 ? (u >> 1) * 8 + (u & 1) * 24 : 16));
      const uint4 w0 = ldg4(wp), w1 = ldg4(wp + 1), w2 = ldg4(wp + 2), w3 = ldg4(wp + 3);
      uint8_t* dst = p.scr->wo + (uint32_t)(cb * (12 * 20480) + kg * 2560 + c * 128 + (tid & 7) * 16);
      const bool f = u < 4, on = tid < 120;
      stg4_if(dst, w0.x, f ? w1.x : w0.z, f ? w2.x : w1.x, f ? w3.x : w1.z, on);
      stg4_if(dst + 128, w0.y, f ? w1.y : w0.w, f ? w2.y : w1.y, f ? w3.y : w1.w, on);
      stg4_if(dst + o2 * 128, f ? w0.z : w2.x, f ? w1.z : w2.z, f ? w2.z : w3.x, w3.z, on);
      stg4_if(dst + o2 * 128 + 128, f ? w0.w : w2.y, f ? w1.w : w2.w, f ? w2.w : w3.y, w3.w, on);
      bar_arrive(NB_WO, 160);
    }
  }
}

struct KvRegs { uint32_t k[11], v[8]; uint4 sh; };
__device__ __forceinline__ void kv_load(KvRegs& q, const __nv_bfloat16* kp, const __nv_bfloat16* vp, const __nv_bfloat16* sp, bool halo) {
#pragma unroll
  for (int i = 0; i < 11; i++) q.k[i] = (i >= 3 || halo) ? ldg1(kp + i * kD) : 0u;
#pragma unroll
  for (int i = 0; i < 8; i++) q.v[i] = ldg1(vp + i * kD);
  q.sh = ldg4(sp);
}
__device__ __forceinline__ void kv_unit(const KvRegs& q, uint32_t oa) {
  const uint32_t w0 = prmt(q.sh.x, q.sh.z, 0x5410), w1 = prmt(q.sh.x, q.sh.z, 0x7632), w2 = prmt(q.sh.y, q.sh.w, 0x5410), w3 = prmt(q.sh.y, q.sh.w, 0x7632);
  uint32_t r[8];
#pragma unroll
  for (int i = 0; i < 8; i++) r[i] = hmul2(hfma2(q.k[i + 3], w0, hfma2(q.k[i + 2], w1, hfma2(q.k[i + 1], w2, hmul2(q.k[i], w3)))), q.v[i]);
  sts128(oa, prmt(r[7], r[6], 0x5410), prmt(r[5], r[4], 0x5410), prmt(r[3], r[2], 0x5410), prmt(r[1], r[0], 0x5410));
  sts128(oa + 2048, prmt(r[7], r[6], 0x7632), prmt(r[5], r[4], 0x7632), prmt(r[3], r[2], 0x7632), prmt(r[1], r[0], 0x7632));
}

__device__ __forceinline__ void helper_cta(const Params& p, uint32_t sb, int cb, int warp, int lane) {
  constexpr int NS = 9, ONES = NS * B_SLOT, BF = ONES + 256, BE = BF + 8 * NS;
  if (warp < NS && elect_one()) {
    mbar_init(sb + BF + 8 * warp, 1); mbar_init(sb + BE + 8 * warp, 1);
    fence_async_smem();
    if (warp == 0) { mbar_expect(sb + BF, B_SLOT); tma3d(sb, &p.tmW, 0, 0, 12 + cb * 3, sb + BF); }
  }
  if (warp == 15) { sts32(sb + ONES + lane * 4, 0x3f803f80u); sts32(sb + ONES + 128 + lane * 4, 0x3f803f80u); fence_async_smem(); }
  __syncthreads();
  if (warp == 4) {
    int s = 1, ph = 1;
    uint32_t tp = clock() + HP0;
#pragma unroll 1
    for (int it = 1; it < 20; it++) {
      if (HPD && it >= 10) pace(tp, HPD);
      mbar_wait(sb + BE + 8 * s, ph);
      if (elect_one()) { mbar_expect(sb + BF + 8 * s, B_SLOT); tma3d(sb + s * B_SLOT, &p.tmW, 0, (it < 10 ? it : it - 10) * 64, (it < 10 ? 12 : 0) + cb * 3, sb + BF + 8 * s); }
      if (++s == NS) { s = 0; ph ^= 1; }
    }
  } else if (warp < 4) {
    const uint32_t tag = load_epoch(p, 128 + cb, lane) + 1;
    const uint64_t db = mkdesc(sb + ONES, 128, 128, 0);
    uint2* dst = p.scr->colsum + cb * 192 + warp * 16 + (lane >> 2);
    if ((lane & 3) == 0) {
#pragma unroll 1
      for (int j = 0; j < 12; j++) st_ll2(dst + (j < 6 ? 768 : 0) + ((j % 6) >> 1) * 64 + (j & 1) * 8, 0, 0);
    }
    int s = 0, ph = 0;
#pragma unroll 1
    for (int part = 0; part < 2; part++) {
      float d[12];
#pragma unroll
      for (int i = 0; i < 12; i++) d[i] = 0.f;
#pragma unroll 1
      for (int it = 0; it < 10; it++) {
        mbar_wait(sb + BF + 8 * s, ph);
        const uint64_t da = mkdesc(sb + s * B_SLOT, 8192, 1024, 1);
        WG_FENCE();
#pragma unroll
        for (int j = 0; j < 12; j++) wgmma_colsum(d + 4 * (j % 3), da + (j % 3) * 512 + (j / 3) * 128, db);
        WG_COMMIT();
        WG_WAIT(1);
        mbar_arrive_if(sb + BE + 8 * (s == 0 ? NS - 1 : s - 1), threadIdx.x == 0 && (it | part) != 0);
        if (++s == NS) { s = 0; ph ^= 1; }
      }
      WG_WAIT(0);
      acc_fence<12>(d);
      if ((lane & 3) == 0) {
#pragma unroll
        for (int j = 0; j < 6; j++) st_ll2(dst + (part ? 0 : 768) + (j >> 1) * 64 + (j & 1) * 8, __float_as_uint(d[2 * j]), tag);
      }
      STAMPW(1 + part);
    }
    if (threadIdx.x == 0) *(volatile uint32_t*)&p.scr->epoch[128 + cb] = tag;
  }
}

__global__ void __launch_bounds__(512, 1) fused_kernel(const __grid_constant__ Params p) {
  extern __shared__ __align__(1024) uint8_t smem[];
  const int warp = __shfl_sync(0xffffffff, (int)(threadIdx.x >> 5), 0);
  const int lane = threadIdx.x & 31, tid = threadIdx.x & 127;
  const uint32_t sb = __shfl_sync(0xffffffff, (uint32_t)__cvta_generic_to_shared(smem), 0);
  const uint32_t tstart = clock();
  if (elect_one()) {
    if (warp < 5) asm volatile("prefetch.tensormap [%0];" ::"l"(&p.tmX + warp) : "memory");
    mbar_init(sb + OFF_BAR + 8 * warp, 1); mbar_init(sb + OFF_BAR + 128 + 8 * warp, 1); mbar_init(sb + OFF_BAR + 256 + 8 * warp, 2);
    asm volatile("fence.mbarrier_init.release.cluster;" ::: "memory");
  }
  int b = blockIdx.x;
  if (p.by_smid) asm volatile("mov.u32 %0, %%smid;" : "=r"(b));
  b = __shfl_sync(0xffffffff, b, 0);
  const int tp = b >> 1, t7 = (tp - 32) / 7;
  const int lin = tp < 32 ? ((tp & 7) ? (tp & 7) * 16 : 8) + (tp >> 3) * 2 + (b & 1)
                          : (tp < 60 ? (tp - 31 - t7 * 7) * 16 + 8 + t7 * 2 + (b & 1) : (tp < 62 ? -1 : b - 124));
  const int hcb = b & 3;
  if (lin < 0) { helper_cta(p, sb, hcb, warp, lane); return; }
  const int cb = ((lin >> 4) & 1) * 2 + ((lin >> 1) & 1), rb = (lin >> 5) * 8 + ((lin >> 2) & 3) * 2 + (lin & 1);
  const int chb = (cb >> 1) * 320 + rb * 2 + (cb & 1);
  if (elect_one()) {
    if (warp < NPRE) {
      mbar_expect(sb + BAR_AF + 8 * warp, A_SLOT);
      tma_rows(sb + OFF_A + warp * A_SLOT, &p.tmX, warp * 64, rb, sb + BAR_AF + 8 * warp);
      mbar_expect(sb + BAR_BF + 8 * warp, B_SLOT);
      tma3d(sb + OFF_B + warp * B_SLOT, &p.tmW, 0, warp * 64, 12 + cb * 3, sb + BAR_BF + 8 * warp);
    }
  }
  if (warp == 1) STAMP(31);
  if (sb & 1023) die();
  __syncthreads();

  if (warp >= 12) {
    asm volatile("setmaxnreg.dec.sync.aligned.u32 32;");
    const uint32_t epoch = load_epoch(p, lin, lane);
    if (warp == 12) {
#pragma unroll 1
      for (int i = NPRE; i < NA; i++) {
        if (elect_one()) {
          mbar_expect(sb + BAR_AF + 8 * i, A_SLOT);
          tma_rows(sb + OFF_A + i * A_SLOT, &p.tmX, i * 64, rb, sb + BAR_AF + 8 * i);
          if (i < NB) { mbar_expect(sb + BAR_BF + 8 * i, B_SLOT); tma3d(sb + OFF_B + i * B_SLOT, &p.tmW, 0, i * 64, 12 + cb * 3, sb + BAR_BF + 8 * i); }
        }
      }
      if (elect_one()) { reset_sector(&p.scr->hflag[rb * 64 + cb * 8]); reset_sector(&p.scr->hflag[rb * 64 + 32 + cb * 8]); }
      STAMP(32);
      uint32_t kvt;
      {
        const int tb = rb * 2 + (cb & 1);
        kvt = __shfl_sync(0xffffffff, (ld_relaxed(p.scr->cnt + CNT_KV + (cb >> 1)) & ~63u) + 64, 0);
        {
          uint32_t tp = tstart;
          pace(tp, KV_T0);
          mbar_arrive_if(sb + BAR_KV + 8, lane == 0);
        }
        if (ST_YIELD) mbar_wait2(sb + BAR_XS, 0, sb + BAR_ST, 0);
#pragma unroll 1
        for (int u = 0; u < 5; u++) {
          mbar_wait(sb + BAR_KU + 8 * u, 0);
          fence_async_smem();
          if (elect_one()) {
            asm volatile("cp.async.bulk.tensor.3d.global.shared::cta.bulk_group [%0, {%2, %3, %4}], [%1];\ncp.async.bulk.commit_group;" ::"l"(&p.tmKV),
                         "r"(sb + OFF_CV + CV_SZ + (u < 3 ? u : u - 3) * 4096), "r"((63 - tb) * 16), "r"((cb >> 1) * 160 + u * 32), "r"(0) : "memory");
            if (u == 1 || u == 4) asm volatile("cp.async.bulk.wait_group 0;" ::: "memory");
            if (u == 1) { mbar_arrive(sb + BAR_KU); red_release(p.scr->cnt + CNT_KV + (cb >> 1)); }
          }
          __syncwarp();
          if (u == 1) {
            STAMP(35);
            if (PFT) { const char* q = (const char*)p.ssmk + chb * 4096 + lane * 128; prefetch_l2(q); prefetch_l2(q + 64 * 4096); }
          }
        }
        zero_pads(sb + OFF_CV + CV_SZ, lane);
        if (elect_one()) { mbar_arrive(sb + BAR_KU + 8); red_release(p.scr->cnt + CNT_KV + 2 + (cb >> 1)); }
        STAMP(30);
        if (lane < 24) {
          const char* r = (const char*)p.wout + (rb * 24 + lane) * (kD * 2) + (cb >> 1) * 640 + (cb & 1) * 384;
          prefetch_l2(r); prefetch_l2(r + 128); prefetch_l2(r + 256 - (cb & 1) * 384);
        }
      }
      poll_counter(p.scr->cnt + CNT_KV + 2 + (cb >> 1), kvt);
      if (elect_one()) mbar_arrive(sb + BAR_KV);
      STAMP(34);
      {
        const char* q = (const char*)p.wsp + (rb * 64 + cb * 16 + (lane >> 1)) * (kS * 2) + (lane & 1) * 128;
        uint32_t tp = clock();
#pragma unroll 1
        for (int i = LEAD / 2; i < WSP_N; i++) {
          prefetch_l2(q + i * 256);
          pace(tp, WSP_D);
        }
      }
      int s, ph = 1;
      const uint32_t tag = epoch + 1;
      mbar_wait(sb + BAR_G2, 0);
      if (elect_one()) {
        bulk_s2g(p.scr->h + (size_t)(rb * 12 + cb * 3) * A_SLOT, sb + OFF_A + 5 * A_SLOT, HSPLIT ? A_SLOT : 3 * A_SLOT);
        asm volatile("cp.async.bulk.commit_group;\ncp.async.bulk.wait_group 0;" ::: "memory");
        mbar_arrive(sb + BAR_HR);
        if (!HSPLIT) mbar_arrive(sb + BAR_HR);
        st_release(&p.scr->hflag[rb * 64 + cb * 8], tag);
      }
      __syncwarp();
      STAMP(20);
      s = 8;
      uint32_t seen = 0, t0 = 0;
#pragma unroll 1
      for (int it = 3; it < 12; it++) {
        if (it == 3 || (HSPLIT && it == 6)) {
          const uint32_t m = it == 3 ? 0x0f : 0xf0;
#pragma unroll 1
          while ((seen & m) != m) { seen = __ballot_sync(0xffffffff, ld_relaxed(p.scr->hflag + rb * 64 + (lane & 7) * 8) == tag); spin_guard(t0); }
          acquire_fence();
          STAMP(it == 3 ? 37 : 39);
        }
        mbar_wait(sb + BAR_AE + 8 * s, ph);
        if (elect_one()) { mbar_expect(sb + BAR_AF + 8 * s, A_SLOT); bulk_g2s(sb + OFF_A + s * A_SLOT, p.scr->h + (size_t)(rb * 12 + g3_block(cb, it)) * A_SLOT, A_SLOT, sb + BAR_AF + 8 * s); }
        if (++s == NA2) { s = 0; ph ^= 1; }
      }
      STAMP(21);
    } else if (warp == 13) {
      const uint32_t ztarget = __shfl_sync(0xffffffff, ld_relaxed(p.scr->cnt + CNT_Z), 0);
      int s = 0, ph = 0;
#pragma unroll 1
      for (int it = NB; it < 20; it++) {
        mbar_wait(sb + BAR_BE + 8 * s, ph);
        if (elect_one()) { mbar_expect(sb + BAR_BF + 8 * s, B_SLOT); tma3d(sb + OFF_B + s * B_SLOT, &p.tmW, 0, (it < 10 ? it : it - 10) * 64, (it < 10 ? 12 : 0) + cb * 3, sb + BAR_BF + 8 * s); }
        STAMP2(32 + it);
        if (++s == NB) { s = 0; ph ^= 1; }
      }
      mbar_wait(sb + BAR_KU + 16, 0);
#pragma unroll 1
      for (int i = 0; i < LEAD; i++) {
        mbar_wait(sb + BAR_AE + 8 * i, 0);
        if (elect_one()) { mbar_expect(sb + BAR_AF + 8 * i, A_SLOT); tma_rows(sb + OFF_A + i * A_SLOT, &p.tmWsp, i * 64, rb, sb + BAR_AF + 8 * i); }
      }
      mbar_wait(sb + BAR_ZP, 0);
      poll_counter(p.scr->cnt + CNT_Z, (ztarget & ~127u) + 128);
      STAMP(22);
      int sa = LEAD, pa = 0, ia = LEAD;
#pragma unroll 1
      for (int it = 0; it < 32; it++) {
        mbar_wait2(sb + BAR_BE + 8 * s, ph, sb + BAR_AE + 8 * sa, pa);
        if (elect_one()) {
          mbar_expect(sb + BAR_BF + 8 * s, B_SLOT);
          bulk_g2s(sb + OFF_B + s * B_SLOT, p.scr->z2 + (size_t)(cb * 32 + it) * B_SLOT, B_SLOT, sb + BAR_BF + 8 * s);
        }
#pragma unroll 1
        for (int j = (it < RAMP ? 0 : (it == 4 ? 1 + RAMP : 1)); j > 0 && ia < 32; j--, ia++) {
          if (it == 4) mbar_wait(sb + BAR_AE + 8 * sa, pa);
          if (elect_one()) { mbar_expect(sb + BAR_AF + 8 * sa, A_SLOT); tma_rows(sb + OFF_A + sa * A_SLOT, &p.tmWsp, ia * 64, rb, sb + BAR_AF + 8 * sa); }
          if (++sa == NA2) { sa = 0; pa ^= 1; }
        }
        STAMP2(52 + it);
        if (++s == NB) { s = 0; ph ^= 1; }
      }
      mbar_wait(sb + BAR_WO, 0);
      acquire_fence();
#pragma unroll 1
      for (int it = 0; it < 12; it++) {
        if (it < 6) mbar_wait(sb + BAR_BE + 8 * ((0x110443 >> (4 * it)) & 7), it < 3 ? 1 : 0);
        else mbar_wait(sb + BAR_BE + 8 * s, ph);
        if (elect_one()) {
          mbar_expect(sb + BAR_BF + 8 * s, 20480);
          bulk_g2s(sb + OFF_B + (s == 5 ? 0 : s + 1) * 20480, p.scr->wo + (size_t)(cb * 12 + g3_block(cb, it)) * 20480, 20480, sb + BAR_BF + 8 * s);
        }
        STAMP2(84 + it);
        if (++s == 6) { s = 0; ph ^= 1; }
      }
    } else if (warp == 14) {
      const uint32_t tag = epoch + 1;
      uint32_t t0 = 0;
      mbar_wait(sb + BAR_AF + 8 * (NA - 1), 0);
#pragma unroll 1
      for (int part = 0; part < 2; part++) {
#pragma unroll 1
        while (true) {
          bool ok = true;
#pragma unroll
          for (int i = 0; i < 3; i++) {
            const uint4 v = ld_ll4(&p.scr->colsum[(part ? 0 : 768) + cb * 192 + i * 64 + lane * 2]);
            ok = ok && v.y == tag && v.w == tag;
            sts64f(sb + OFF_CS + part * 768 + i * 256 + lane * 8, __uint_as_float(v.x), __uint_as_float(v.z));
          }
          if (__all_sync(0xffffffff, ok)) break;
          spin_guard(t0);
        }
        __syncwarp();
        if (lane == 0) mbar_arrive(sb + BAR_ST + 8 * part);
        if (part == 0) STAMP(27);
      }
      STAMP(38);
      bar_sync(NB_Z, 160);
      if (elect_one()) {
        bulk_s2g(p.scr->z2 + (size_t)(cb * 32 + rb) * B_SLOT, sb + OFF_A + LEAD * A_SLOT, B_SLOT);
        asm volatile("cp.async.bulk.commit_group;\ncp.async.bulk.wait_group 0;" ::: "memory");
        red_release(p.scr->cnt + CNT_Z);
        mbar_arrive(sb + BAR_ZP);
      }
      STAMP(28);
      mbar_wait2(sb + BAR_KV, 0, sb + BAR_AE + 72, 0);
      acquire_fence();
      conv_service(p, sb, 0, chb + 64);
      bar_sync(NB_WO, 160);
      bar_sync(NB_CD, 64);
      if (elect_one()) { red_release(p.scr->cnt + CNT_WO + cb); red_relaxed(p.scr->cnt + CNT_Y + (cb >> 1)); }
      STAMP(49);
      poll_counter(p.scr->cnt + CNT_WO + cb, tag * 32);
      if (elect_one()) mbar_arrive(sb + BAR_WO);
      STAMP(46);
      held_service(p, sb, 0, chb + 192, rb, cb, tag, lane);
    } else {
      const uint32_t tag = epoch + 1;
      sts32(sb + OFF_BIAS + lane * 4, ldg1(p.bsp + rb * 64 + row_grp(lane >> 3, (lane >> 2) & 1) * 8 + (lane & 3) * 2));
      if (lane < 2) sts32(sb + OFF_TAG + lane * 4, lane ? 0 : tag);
      uint32_t t0 = 0;
      mbar_wait(sb + BAR_AF + 8 * (NA - 1), 0);
#pragma unroll 1
      while (true) {
        const uint4 u = ld_ll4(&p.scr->xstat[rb * 64 + lane]), v = ld_ll4(&p.scr->xstat[rb * 64 + 32 + lane]);
        sts64f(sb + OFF_XS + lane * 8, __uint_as_float(u.x), __uint_as_float(u.z));
        sts64f(sb + OFF_XS + 256 + lane * 8, __uint_as_float(v.x), __uint_as_float(v.z));
        if (__all_sync(0xffffffff, u.y == tag && u.w == tag && v.y == tag && v.w == tag)) break;
        spin_guard(t0);
      }
      STAMP(26);
      __syncwarp();
      if (lane == 0) mbar_arrive(sb + BAR_XS);
      mbar_wait(sb + BAR_KU + 16, 0);
      poll_counter(p.scr->cnt + CNT_KV + (cb >> 1), tag * 64);
      if (elect_one()) load_convx(p, sb + OFF_CV, sb + BAR_XF + 8, chb);
      mbar_wait(sb + BAR_KU + 8, 1);
      if (elect_one()) load_convx(p, sb + OFF_CV + CV_SZ, sb + BAR_XF, chb + 64);
      STAMP(48);
      mbar_wait2(sb + BAR_KV, 0, sb + BAR_AE + 72, 0);
      acquire_fence();
#pragma unroll 1
      for (int i = 0; i < 2; i++) conv_service(p, sb, 1, chb + i * 128);
      bar_arrive(NB_CD, 64);
      mbar_wait(sb + BAR_WO, 0);
      poll_counter(p.scr->cnt + CNT_Y + (cb >> 1), tag * 64);
      STAMP(47);
      if (elect_one()) mbar_arrive(sb + BAR_YT);
      held_service(p, sb, 1, chb + 256, rb, cb, tag, lane);
      if (lane == 0) *(volatile uint32_t*)&p.scr->epoch[lin] = tag;
      STAMP(23);
    }
  } else {
    if (warp == 7) STAMP(36);
    const int wg = warp >> 2, w = warp & 3, g = lane >> 2, t = lane & 3;
    Taps k;
    uint32_t xw[2][10];
    if (wg == 2) {
      asm volatile("setmaxnreg.inc.sync.aligned.u32 160;");
      const int tb = rb * 2 + (cb & 1), c0 = (cb >> 1) * 320;
      const uint32_t cv = sb + OFF_CV + CV_SZ;
      if (w == 0) zero_pads(sb + OFF_CV, lane);
      mbar_wait(sb + BAR_KV + 8, 0);
      const int t0 = tb * 32 + w * 8;
      const __nv_bfloat16* kp = p.k + (size_t)(t0 - 3) * kD + c0 + lane * 2;
      const __nv_bfloat16* vp = p.v + (size_t)t0 * kD + c0 + lane * 2;
      const __nv_bfloat16* sp = p.shift + (c0 + lane * 2) * 4;
      const uint32_t oa = cv + ((3 - w) & 1) * 1024 + lane * 32 + ((((3 - w) >> 1) ^ (lane >> 2)) & 1) * 16;
#pragma unroll 1
      for (int r = 0; r < 2; r++) {
        KvRegs n0, n1, n2;
        kv_load(n0, kp + r * 128, vp + r * 128, sp + r * 512, t0 > 0);
        kv_load(n1, kp + r * 128 + 64, vp + r * 128 + 64, sp + r * 512 + 256, t0 > 0);
        if (r) kv_load(n2, kp + 256, vp + 256, sp + 1024, t0 > 0);
        kv_unit(n0, oa + r * 8192);
        bar_sync(NB_WGC, 128);
        mbar_arrive_if(sb + BAR_KU + 16 * r, tid == 0);
        if (r) mbar_wait(sb + BAR_KU, 1);
        kv_unit(n1, oa + (r ? 0 : 4096));
        bar_sync(NB_WGC, 128);
        mbar_arrive_if(sb + BAR_KU + 16 * r + 8, tid == 0);
        if (r) {
          kv_unit(n2, oa + 4096);
          bar_sync(NB_WGC, 128);
          mbar_arrive_if(sb + BAR_KU + 32, tid == 0);
        } else {
          mbar_wait(sb + BAR_AF + 8 * ((cb >> 1) * 5 + 1), 0);
          mbar_wait2(sb + BAR_AF + 8 * ((cb >> 1) * 5 + 2), 0, sb + BAR_AF + 8 * ((cb >> 1) * 5 + 4), 0);
          final_load_x(xw, sb + OFF_A, cb, 1, w, lane);
        }
      }
      STAMPW(13);
      load_taps(k, p, chb, tid);
    } else {
      float d[96];
      if (wg == 0) { if (t < 2) st_ll4(&p.scr->zstat[rb * 256 + cb * 64 + w * 16 + g + t * 8], 0, 0, 0, 0); }
      else if ((tid & 7) == 0) st_ll4(&p.scr->xstat[rb * 64 + cb * 16 + (tid >> 3)], 0, 0, 0, 0);
      {
        #pragma unroll
        for (int i = 0; i < 96; i++) d[i] = 0.f;
        {
          if (__builtin_expect(wg == 1, 0)) {
            const int tid = tid_now();
            const uint32_t epoch = load_epoch(p, lin, lane);
            float s = 0.f, q = 0.f;
#pragma unroll 1
            for (int i = 0; i < 10; i++) {
              mbar_wait(sb + BAR_AF + 8 * i, 0);
              const uint4 x4 = lds128(sb + OFF_A + i * A_SLOT + cb * 2048 + tid * 16);
              const uint32_t u[4] = {x4.x, x4.y, x4.z, x4.w};
#pragma unroll
              for (int e = 0; e < 4; e++) { const float a = bf_lo(u[e]), c = bf_hi(u[e]); s += a + c; q = fmaf(a, a, q); q = fmaf(c, c, q); }
            }
#pragma unroll
            for (int o = 1; o <= 4; o <<= 1) { s += __shfl_xor_sync(0xffffffff, s, o); q += __shfl_xor_sync(0xffffffff, q, o); }
            const float m = s * (1.f / kD);
            const float r = rsqrtf(fmaxf(fmaf(-m, m, q * (1.f / kD)), 0.f) + 1e-5f);
            if ((tid & 7) == 0) st_ll4(&p.scr->xstat[rb * 64 + cb * 16 + (tid >> 3)], __float_as_uint(m), epoch + 1, __float_as_uint(r), epoch + 1);
            STAMPW(12);
            bar_sync(NB_G1, 256);
          }
          gemm_loop<192, true, 0, D1>(d, sb, 10, 0, 0, 0, 0, wg, 2, tid_now(), [&]() { if (!G1_LATE && wg == 0) bar_arrive(NB_G1, 256); });
          asm volatile("setmaxnreg.inc.sync.aligned.u32 160;");
          STAMPW(wg ? 14 : 1);
          mbar_wait2(sb + BAR_XS, 0, sb + BAR_ST + 8 * wg, 0);
        }
        const int t1 = tid_now();
        const uint32_t xa1 = sb + OFF_XS + (w * 16 + ((t1 & 31) >> 2)) * 8;
        const float2 s0 = lds64f(xa1), s1 = lds64f(xa1 + 64);
        uint32_t z[48];
        float st[4];
        gelu_tile(d, z, st, sb + OFF_CS + wg * 768 + (t1 & 3) * 8, s0, s1);
        const int tid = tid_now(), lane = tid & 31, g = lane >> 2, t = lane & 3;
        if (wg == 1) {
          uint32_t bra, brb;
          asm volatile("ld.shared.u16 %0, [%1];" : "=r"(bra) : "r"(sb + OFF_BIAS + (w * 16 + g) * 2));
          asm volatile("ld.shared.u16 %0, [%1+16];" : "=r"(brb) : "r"(sb + OFF_BIAS + (w * 16 + g) * 2));
#pragma unroll
          for (int j = 0; j < 96; j++) d[j] = bf_lo((j & 2) ? brb : bra);
          STAMPW(15);
          gemm_loop<192, true, 1, D2>(d, sb, 32, 0, 1, 20, 0, 2, 2, tid, [&]() { if (HOLD_AT < 32) mbar_arrive_if(sb + BAR_GO, tid == 0); });
          if (HOLD_AT == 32) mbar_arrive_if(sb + BAR_GO, tid == 0);
          STAMPW(16);
          const int t2 = tid_now(), l2 = t2 & 31;
          const uint32_t ha = sb + OFF_A + 5 * A_SLOT + (l2 >> 4) * 1024 + (2 * w + ((l2 >> 3) & 1)) * 128 + (l2 & 7) * 16;
#pragma unroll
          for (int j = 0; j < 24; j += 2) {
#pragma unroll
            for (int e = 0; e < 4; e++) z[2 * j + e] = hmul2(z[2 * j + e], pack2(d[4 * j + 2 * e], d[4 * j + 2 * e + 1]));
            stsm4(ha + j * 1024, z[2 * j], z[2 * j + 1], z[2 * j + 2], z[2 * j + 3]);
          }
          fence_async_smem();
          bar_sync(NB_WGB, 128);
          mbar_arrive_if(sb + BAR_AF + 8 * (t2 == 3 ? (BAR_G2 - BAR_AF) / 8 : (t2 == 4 ? (BAR_GO - BAR_AF) / 8 : 5 + t2)), t2 < (HOLD_AT == 33 ? 5 : 4));
          STAMPW(17);
          {
            float e[80];
#pragma unroll
            for (int j = 0; j < 80; j++) e[j] = 0.f;
            if (BP_LATE) bar_sync(NB_G1, 384);
            gemm_loop<160, false, 2, 4>(e, sb, 3, 5, 0, 2, 0, 0, 2, tid_now(), []() {});
            bar_sync(NB_WGB, 128);
            mbar_wait(sb + BAR_HR, 1);
            const int t3 = tid_now();
#pragma unroll
            for (int j = 0; j < 10; j++)
              sts128(sb + OFF_A + 5 * A_SLOT + j * 2048 + t3 * 16, pack2(e[8 * j], e[8 * j + 1]), pack2(e[8 * j + 2], e[8 * j + 3]), pack2(e[8 * j + 4], e[8 * j + 5]),
                     pack2(e[8 * j + 6], e[8 * j + 7]));
            bar_sync(NB_WGB, 128);
            mbar_arrive_if(sb + BAR_HOLD, t3 == 0);
            STAMPW(45);
          }
          return;
        }
        float sa = st[0], qa = st[1], sbb = st[2], qb = st[3];
#pragma unroll
        for (int o = 1; o <= 2; o <<= 1) {
          sa += __shfl_xor_sync(0xffffffff, sa, o); qa += __shfl_xor_sync(0xffffffff, qa, o);
          sbb += __shfl_xor_sync(0xffffffff, sbb, o); qb += __shfl_xor_sync(0xffffffff, qb, o);
        }
        const uint32_t tag = lds32<0>(sb + OFF_TAG);
        if (t < 2) st_ll4(&p.scr->zstat[rb * 256 + cb * 64 + w * 16 + g + t * 8], __float_as_uint(t ? sbb : sa), tag, __float_as_uint(t ? qb : qa), tag);
        if (G1_LATE) bar_arrive(NB_G1, 256);
        STAMPW(2);
        const float ca = 0.5f * s0.y, cbb = 0.5f * s1.y;
        {
          const uint4* zs = &p.scr->zstat[rb * 256 + t * 64 + w * 16 + g];
          uint4 u0 = ld_ll4(zs), u1 = ld_ll4(zs + 8);
          final_load_x(xw, sb + OFF_A, cb, 0, w, lane);
          fence_async_smem();
          bar_sync(NB_WGA, 128);
          mbar_arrive_if(sb + BAR_AE + 8 * tid, tid < NA);
          uint32_t t0 = 0;
#pragma unroll 1
          while (!__all_sync(0xffffffff, u0.y == tag && u0.w == tag && u1.y == tag && u1.w == tag)) {
            spin_guard(t0);
            u0 = ld_ll4(zs); u1 = ld_ll4(zs + 8);
          }
          sa = __uint_as_float(u0.x); qa = __uint_as_float(u0.z); sbb = __uint_as_float(u1.x); qb = __uint_as_float(u1.z);
          STAMPW(3);
        }
#pragma unroll
        for (int o = 1; o <= 2; o <<= 1) {
          sa += __shfl_xor_sync(0xffffffff, sa, o); qa += __shfl_xor_sync(0xffffffff, qa, o);
          sbb += __shfl_xor_sync(0xffffffff, sbb, o); qb += __shfl_xor_sync(0xffffffff, qb, o);
        }
        const float inv = 1.f / 768.f;
        const float ma = sa * inv, mb = sbb * inv;
        const float ra = ca * rsqrtf(fmaf(fmaxf(fmaf(-ma, ma, qa * inv), 0.f), ca * ca, 1e-5f));
        const float rb_ = cbb * rsqrtf(fmaf(fmaxf(fmaf(-mb, mb, qb * inv), 0.f), cbb * cbb, 1e-5f));
        const uint32_t ra2 = pack2(ra, ra), rb2 = pack2(rb_, rb_);
        const float na = -ma * bf_lo(ra2), nb = -mb * bf_lo(rb2);
        {
          const uint32_t n2a = pack2(na, na), n2b = pack2(nb, nb);
          const uint32_t za = sb + OFF_A + LEAD * A_SLOT + row_grp(w, (lane >> 3) & 1) * 3072 + (lane >> 4) * 128 + (lane & 7) * 16;
          mbar_wait2(sb + BAR_AE + 8 * (LEAD + 2), 0, sb + BAR_KU + 16, 0);
#pragma unroll
          for (int j = 0; j < 24; j += 2)
            stsm4(za + j * 128, hfma2(z[2 * j], ra2, n2a), hfma2(z[2 * j + 1], rb2, n2b), hfma2(z[2 * j + 2], ra2, n2a), hfma2(z[2 * j + 3], rb2, n2b));
          fence_async_smem();
        }
      }
      bar_arrive(NB_Z, 160);
      {
        const uint32_t zero = lds32<0>(sb + OFF_TAG + 4);
#pragma unroll
        for (int i = 0; i < 20; i++) xw[i / 10][i % 10] |= zero;
      }
      load_taps(k, p, chb + 64, tid_now());
      STAMPW(4);
    }
    const int h = wg >> 1;
    {
    const int tid = tid_now(), lane = tid & 31;
    conv_worker(p, k, sb + OFF_CV + (1 - h) * CV_SZ, sb + OFF_A + 9 * A_SLOT + h * 4096, sb + BAR_XF + 8 * h, NB_WGA + h,
                chb + (h ? 0 : 64), 2 + h, sb + BAR_GO, w, lane, tid, h ? 40 : 5, rb, cb);
    float d[40];
    {
      const int t3 = tid_now();
      mbar_wait(sb + BAR_HOLD, 0);
#pragma unroll
      for (int j = 0; j < 5; j++) {
        const uint4 v = lds128(sb + OFF_A + 5 * A_SLOT + (h * 5 + j) * 2048 + t3 * 16);
        d[8 * j] = bf_lo(v.x); d[8 * j + 1] = bf_hi(v.x); d[8 * j + 2] = bf_lo(v.y); d[8 * j + 3] = bf_hi(v.y);
        d[8 * j + 4] = bf_lo(v.z); d[8 * j + 5] = bf_hi(v.z); d[8 * j + 6] = bf_lo(v.w); d[8 * j + 7] = bf_hi(v.w);
      }
      fence_async_smem();
      bar_sync(NB_WGA + h, 128);
      mbar_arrive_if(sb + BAR_AE + 8 * (5 + t3), t3 < 3);
      const int l3 = t3 & 31;
      uint32_t sw[2][10];
      float2 s0, s1;
      gemm_loop<80, false, 2, D3>(d, sb, 9, 8, 0, 5, h * 1280, 1, 1, t3, [&]() {
        {
          const uint32_t xs_addr = sb + OFF_XS + (w * 16 + (l3 >> 2)) * 8;
          s0 = lds64f(xs_addr); s1 = lds64f(xs_addr + 64);
          uint32_t ph = h, t0 = 0;
#pragma unroll 1
          while (true) {
            mbar_wait(sb + BAR_XF + 8 * h, ph);
            if (bar_all(NB_WGA + h, 128, final_s(sw, xw, sb + y_tile(h), s0, s1, w, l3))) break;
            spin_guard(t0);
            ph ^= 1;
            if (t3 == 0) { mbar_expect(sb + BAR_XF + 8 * h, 4096); load_late_y(p, sb, h, rb, cb, lds32<0>(sb + OFF_TAG) & 1); }
          }
          STAMPW(h ? 44 : 9);
        }
      });
      STAMPW(h ? 18 : 10);
      final_out(d, xw, sw, s0.y, s1.y, p.out + (size_t)(rb * 64 + row_grp(w, 0) * 8 + (l3 >> 2)) * kD + seg_col(cb, h), h, l3 & 3);
    }
    }
  }
}

typedef CUresult (*EncodeFn)(CUtensorMap*, CUtensorMapDataType, cuuint32_t, void*, const cuuint64_t*, const cuuint64_t*, const cuuint32_t*,
                             const cuuint32_t*, CUtensorMapInterleave, CUtensorMapSwizzle, CUtensorMapL2promotion, CUtensorMapFloatOOBfill);

void encode(EncodeFn fn, CUtensorMap* m, const void* ptr, int rank, const cuuint64_t* dims, const cuuint64_t* strides, const cuuint32_t* box,
            CUtensorMapSwizzle swz = CU_TENSOR_MAP_SWIZZLE_128B) {
  const cuuint32_t es[5] = {1, 1, 1, 1, 1};
  fn(m, CU_TENSOR_MAP_DATA_TYPE_BFLOAT16, rank, const_cast<void*>(ptr), dims, strides, box, es, CU_TENSOR_MAP_INTERLEAVE_NONE,
     swz, CU_TENSOR_MAP_L2_PROMOTION_L2_128B, CU_TENSOR_MAP_FLOAT_OOB_FILL_NONE);
}

}

extern "C" void kernel_launch(void* const* d_in, const int* in_sizes, int n_in, void* d_out, int out_size) {
  (void)in_sizes; (void)n_in; (void)out_size;
  static EncodeFn enc = nullptr;
  static Scratch* scr = nullptr;
  static int sms = 0;
  if (!enc) {
    void* fn = nullptr;
    cudaDriverEntryPointQueryResult qr;
    cudaGetDriverEntryPoint("cuTensorMapEncodeTiled", &fn, cudaEnableDefault, &qr);
    enc = (EncodeFn)fn;
    cudaFuncSetAttribute(fused_kernel, cudaFuncAttributeMaxDynamicSharedMemorySize, SMEM_BYTES);
    cudaGetSymbolAddress((void**)&scr, g_scr);
    int dev = 0;
    cudaGetDevice(&dev);
    cudaDeviceGetAttribute(&sms, cudaDevAttrMultiProcessorCount, dev);
  }
  Params p;
  p.scr = scr;
  p.by_smid = sms == 132;
  p.k = (const __nv_bfloat16*)d_in[1];
  p.v = (const __nv_bfloat16*)d_in[2];
  p.shift = (const __nv_bfloat16*)d_in[3];
  p.ssmk = (const __nv_bfloat16*)d_in[4];
  p.ssmD = (const __nv_bfloat16*)d_in[5];
  p.wsp = (const __nv_bfloat16*)d_in[8];
  p.bsp = (const __nv_bfloat16*)d_in[9];
  p.wout = (const __nv_bfloat16*)d_in[10];
  p.out = (__nv_bfloat16*)d_out;
  for (int i = 0; i < 2; i++) {
    const cuuint64_t n = i ? kS : kD, dims[5] = {n, 8, 2, 2, kS / 32}, st[4] = {n * 2, n * 32, n * 16, n * 64};
    const cuuint32_t box[5] = {64, 8, 2, 2, 2};
    encode(enc, i ? &p.tmWsp : &p.tmX, d_in[i ? 8 : 0], 5, dims, st, box);
  }
  {
    const cuuint64_t dims[3] = {64, kD, kF / 64}, st[2] = {kF * 2, 128};
    const cuuint32_t box[3] = {64, 64, 3};
    encode(enc, &p.tmW, d_in[7], 3, dims, st, box);
  }
  {
    const cuuint64_t dims[2] = {kS, 896}, st[1] = {kS * 2};
    const cuuint32_t box[2] = {64, 16};
    encode(enc, &p.tmY, scr->y, 2, dims, st, box);
  }
  {
    const cuuint64_t dims[3] = {1024, kD / 2, 4}, st[2] = {8192, 2048};
    const cuuint32_t box[3] = {16, 32, 4};
    encode(enc, &p.tmKV, scr->kvx, 3, dims, st, box, CU_TENSOR_MAP_SWIZZLE_32B);
  }
  fused_kernel<<<132, 512, SMEM_BYTES, cudaStreamPerThread>>>(p);
}
```

```cpp
#include <cuda_runtime.h>
#include <cuda.h>
#include <cuda_bf16.h>
#include <stdint.h>

template <int N> struct WG;
template <> struct WG<16> {
  static __device__ __forceinline__ void rs(float* d, const uint32_t* a, uint64_t db) {
    asm volatile("{\n.reg .pred p;\nsetp.ne.b32 p, 1, 0;\nwgmma.mma_async.sync.aligned.m64n16k16.f32.bf16.bf16 {"
      "%0, %1, %2, %3, %4, %5, %6, %7"
      "}, {%8, %9, %10, %11}, %12, p, 1, 1, 0;\n}\n"
      :
      "+f"(d[0]), "+f"(d[1]), "+f"(d[2]), "+f"(d[3]), "+f"(d[4]), "+f"(d[5]), "+f"(d[6]), "+f"(d[7])
      : "r"(a[0]), "r"(a[1]), "r"(a[2]), "r"(a[3]), "l"(db));
  }
};
template <> struct WG<32> {
  static __device__ __forceinline__ void rs(float* d, const uint32_t* a, uint64_t db) {
    asm volatile("{\n.reg .pred p;\nsetp.ne.b32 p, 1, 0;\nwgmma.mma_async.sync.aligned.m64n32k16.f32.bf16.bf16 {"
      "%0, %1, %2, %3, %4, %5, %6, %7, %8, %9, %10, %11, %12, %13, %14, %15"
      "}, {%16, %17, %18, %19}, %20, p, 1, 1, 0;\n}\n"
      :
      "+f"(d[0]), "+f"(d[1]), "+f"(d[2]), "+f"(d[3]), "+f"(d[4]), "+f"(d[5]), "+f"(d[6]), "+f"(d[7]),
      "+f"(d[8]), "+f"(d[9]), "+f"(d[10]), "+f"(d[11]), "+f"(d[12]), "+f"(d[13]), "+f"(d[14]), "+f"(d[15])
      : "r"(a[0]), "r"(a[1]), "r"(a[2]), "r"(a[3]), "l"(db));
  }
};
template <> struct WG<48> {
  static __device__ __forceinline__ void rs(float* d, const uint32_t* a, uint64_t db) {
    asm volatile("{\n.reg .pred p;\nsetp.ne.b32 p, 1, 0;\nwgmma.mma_async.sync.aligned.m64n48k16.f32.bf16.bf16 {"
      "%0, %1, %2, %3, %4, %5, %6, %7, %8, %9, %10, %11, %12, %13, %14, %15, "
      "%16, %17, %18, %19, %20, %21, %22, %23"
      "}, {%24, %25, %26, %27}, %28, p, 1, 1, 0;\n}\n"
      :
      "+f"(d[0]), "+f"(d[1]), "+f"(d[2]), "+f"(d[3]), "+f"(d[4]), "+f"(d[5]), "+f"(d[6]), "+f"(d[7]),
      "+f"(d[8]), "+f"(d[9]), "+f"(d[10]), "+f"(d[11]), "+f"(d[12]), "+f"(d[13]), "+f"(d[14]), "+f"(d[15]),
      "+f"(d[16]), "+f"(d[17]), "+f"(d[18]), "+f"(d[19]), "+f"(d[20]), "+f"(d[21]), "+f"(d[22]), "+f"(d[23])
      : "r"(a[0]), "r"(a[1]), "r"(a[2]), "r"(a[3]), "l"(db));
  }
};
template <> struct WG<64> {
  static __device__ __forceinline__ void rs(float* d, const uint32_t* a, uint64_t db) {
    asm volatile("{\n.reg .pred p;\nsetp.ne.b32 p, 1, 0;\nwgmma.mma_async.sync.aligned.m64n64k16.f32.bf16.bf16 {"
      "%0, %1, %2, %3, %4, %5, %6, %7, %8, %9, %10, %11, %12, %13, %14, %15, "
      "%16, %17, %18, %19, %20, %21, %22, %23, %24, %25, %26, %27, %28, %29, %30, %31"
      "}, {%32, %33, %34, %35}, %36, p, 1, 1, 0;\n}\n"
      :
      "+f"(d[0]), "+f"(d[1]), "+f"(d[2]), "+f"(d[3]), "+f"(d[4]), "+f"(d[5]), "+f"(d[6]), "+f"(d[7]),
      "+f"(d[8]), "+f"(d[9]), "+f"(d[10]), "+f"(d[11]), "+f"(d[12]), "+f"(d[13]), "+f"(d[14]), "+f"(d[15]),
      "+f"(d[16]), "+f"(d[17]), "+f"(d[18]), "+f"(d[19]), "+f"(d[20]), "+f"(d[21]), "+f"(d[22]), "+f"(d[23]),
      "+f"(d[24]), "+f"(d[25]), "+f"(d[26]), "+f"(d[27]), "+f"(d[28]), "+f"(d[29]), "+f"(d[30]), "+f"(d[31])
      : "r"(a[0]), "r"(a[1]), "r"(a[2]), "r"(a[3]), "l"(db));
  }
};
template <> struct WG<80> {
  static __device__ __forceinline__ void rs(float* d, const uint32_t* a, uint64_t db) {
    asm volatile("{\n.reg .pred p;\nsetp.ne.b32 p, 1, 0;\nwgmma.mma_async.sync.aligned.m64n80k16.f32.bf16.bf16 {"
      "%0, %1, %2, %3, %4, %5, %6, %7, %8, %9, %10, %11, %12, %13, %14, %15, "
      "%16, %17, %18, %19, %20, %21, %22, %23, %24, %25, %26, %27, %28, %29, %30, %31, "
      "%32, %33, %34, %35, %36, %37, %38, %39"
      "}, {%40, %41, %42, %43}, %44, p, 1, 1, 0;\n}\n"
      :
      "+f"(d[0]), "+f"(d[1]), "+f"(d[2]), "+f"(d[3]), "+f"(d[4]), "+f"(d[5]), "+f"(d[6]), "+f"(d[7]),
      "+f"(d[8]), "+f"(d[9]), "+f"(d[10]), "+f"(d[11]), "+f"(d[12]), "+f"(d[13]), "+f"(d[14]), "+f"(d[15]),
      "+f"(d[16]), "+f"(d[17]), "+f"(d[18]), "+f"(d[19]), "+f"(d[20]), "+f"(d[21]), "+f"(d[22]), "+f"(d[23]),
      "+f"(d[24]), "+f"(d[25]), "+f"(d[26]), "+f"(d[27]), "+f"(d[28]), "+f"(d[29]), "+f"(d[30]), "+f"(d[31]),
      "+f"(d[32]), "+f"(d[33]), "+f"(d[34]), "+f"(d[35]), "+f"(d[36]), "+f"(d[37]), "+f"(d[38]), "+f"(d[39])
      : "r"(a[0]), "r"(a[1]), "r"(a[2]), "r"(a[3]), "l"(db));
  }
};
template <> struct WG<96> {
  static __device__ __forceinline__ void rs(float* d, const uint32_t* a, uint64_t db) {
    asm volatile("{\n.reg .pred p;\nsetp.ne.b32 p, 1, 0;\nwgmma.mma_async.sync.aligned.m64n96k16.f32.bf16.bf16 {"
      "%0, %1, %2, %3, %4, %5, %6, %7, %8, %9, %10, %11, %12, %13, %14, %15, "
      "%16, %17, %18, %19, %20, %21, %22, %23, %24, %25, %26, %27, %28, %29, %30, %31, "
      "%32, %33, %34, %35, %36, %37, %38, %39, %40, %41, %42, %43, %44, %45, %46, %47"
      "}, {%48, %49, %50, %51}, %52, p, 1, 1, 0;\n}\n"
      :
      "+f"(d[0]), "+f"(d[1]), "+f"(d[2]), "+f"(d[3]), "+f"(d[4]), "+f"(d[5]), "+f"(d[6]), "+f"(d[7]),
      "+f"(d[8]), "+f"(d[9]), "+f"(d[10]), "+f"(d[11]), "+f"(d[12]), "+f"(d[13]), "+f"(d[14]), "+f"(d[15]),
      "+f"(d[16]), "+f"(d[17]), "+f"(d[18]), "+f"(d[19]), "+f"(d[20]), "+f"(d[21]), "+f"(d[22]), "+f"(d[23]),
      "+f"(d[24]), "+f"(d[25]), "+f"(d[26]), "+f"(d[27]), "+f"(d[28]), "+f"(d[29]), "+f"(d[30]), "+f"(d[31]),
      "+f"(d[32]), "+f"(d[33]), "+f"(d[34]), "+f"(d[35]), "+f"(d[36]), "+f"(d[37]), "+f"(d[38]), "+f"(d[39]),
      "+f"(d[40]), "+f"(d[41]), "+f"(d[42]), "+f"(d[43]), "+f"(d[44]), "+f"(d[45]), "+f"(d[46]), "+f"(d[47])
      : "r"(a[0]), "r"(a[1]), "r"(a[2]), "r"(a[3]), "l"(db));
  }
};
template <> struct WG<112> {
  static __device__ __forceinline__ void rs(float* d, const uint32_t* a, uint64_t db) {
    asm volatile("{\n.reg .pred p;\nsetp.ne.b32 p, 1, 0;\nwgmma.mma_async.sync.aligned.m64n112k16.f32.bf16.bf16 {"
      "%0, %1, %2, %3, %4, %5, %6, %7, %8, %9, %10, %11, %12, %13, %14, %15, "
      "%16, %17, %18, %19, %20, %21, %22, %23, %24, %25, %26, %27, %28, %29, %30, %31, "
      "%32, %33, %34, %35, %36, %37, %38, %39, %40, %41, %42, %43, %44, %45, %46, %47, "
      "%48, %49, %50, %51, %52, %53, %54, %55"
      "}, {%56, %57, %58, %59}, %60, p, 1, 1, 0;\n}\n"
      :
      "+f"(d[0]), "+f"(d[1]), "+f"(d[2]), "+f"(d[3]), "+f"(d[4]), "+f"(d[5]), "+f"(d[6]), "+f"(d[7]),
      "+f"(d[8]), "+f"(d[9]), "+f"(d[10]), "+f"(d[11]), "+f"(d[12]), "+f"(d[13]), "+f"(d[14]), "+f"(d[15]),
      "+f"(d[16]), "+f"(d[17]), "+f"(d[18]), "+f"(d[19]), "+f"(d[20]), "+f"(d[21]), "+f"(d[22]), "+f"(d[23]),
      "+f"(d[24]), "+f"(d[25]), "+f"(d[26]), "+f"(d[27]), "+f"(d[28]), "+f"(d[29]), "+f"(d[30]), "+f"(d[31]),
      "+f"(d[32]), "+f"(d[33]), "+f"(d[34]), "+f"(d[35]), "+f"(d[36]), "+f"(d[37]), "+f"(d[38]), "+f"(d[39]),
      "+f"(d[40]), "+f"(d[41]), "+f"(d[42]), "+f"(d[43]), "+f"(d[44]), "+f"(d[45]), "+f"(d[46]), "+f"(d[47]),
      "+f"(d[48]), "+f"(d[49]), "+f"(d[50]), "+f"(d[51]), "+f"(d[52]), "+f"(d[53]), "+f"(d[54]), "+f"(d[55])
      : "r"(a[0]), "r"(a[1]), "r"(a[2]), "r"(a[3]), "l"(db));
  }
};
template <> struct WG<128> {
  static __device__ __forceinline__ void rs(float* d, const uint32_t* a, uint64_t db) {
    asm volatile("{\n.reg .pred p;\nsetp.ne.b32 p, 1, 0;\nwgmma.mma_async.sync.aligned.m64n128k16.f32.bf16.bf16 {"
      "%0, %1, %2, %3, %4, %5, %6, %7, %8, %9, %10, %11, %12, %13, %14, %15, "
      "%16, %17, %18, %19, %20, %21, %22, %23, %24, %25, %26, %27, %28, %29, %30, %31, "
      "%32, %33, %34, %35, %36, %37, %38, %39, %40, %41, %42, %43, %44, %45, %46, %47, "
      "%48, %49, %50, %51, %52, %53, %54, %55, %56, %57, %58, %59, %60, %61, %62, %63"
      "}, {%64, %65, %66, %67}, %68, p, 1, 1, 0;\n}\n"
      :
      "+f"(d[0]), "+f"(d[1]), "+f"(d[2]), "+f"(d[3]), "+f"(d[4]), "+f"(d[5]), "+f"(d[6]), "+f"(d[7]),
      "+f"(d[8]), "+f"(d[9]), "+f"(d[10]), "+f"(d[11]), "+f"(d[12]), "+f"(d[13]), "+f"(d[14]), "+f"(d[15]),
      "+f"(d[16]), "+f"(d[17]), "+f"(d[18]), "+f"(d[19]), "+f"(d[20]), "+f"(d[21]), "+f"(d[22]), "+f"(d[23]),
      "+f"(d[24]), "+f"(d[25]), "+f"(d[26]), "+f"(d[27]), "+f"(d[28]), "+f"(d[29]), "+f"(d[30]), "+f"(d[31]),
      "+f"(d[32]), "+f"(d[33]), "+f"(d[34]), "+f"(d[35]), "+f"(d[36]), "+f"(d[37]), "+f"(d[38]), "+f"(d[39]),
      "+f"(d[40]), "+f"(d[41]), "+f"(d[42]), "+f"(d[43]), "+f"(d[44]), "+f"(d[45]), "+f"(d[46]), "+f"(d[47]),
      "+f"(d[48]), "+f"(d[49]), "+f"(d[50]), "+f"(d[51]), "+f"(d[52]), "+f"(d[53]), "+f"(d[54]), "+f"(d[55]),
      "+f"(d[56]), "+f"(d[57]), "+f"(d[58]), "+f"(d[59]), "+f"(d[60]), "+f"(d[61]), "+f"(d[62]), "+f"(d[63])
      : "r"(a[0]), "r"(a[1]), "r"(a[2]), "r"(a[3]), "l"(db));
  }
};
template <> struct WG<160> {
  static __device__ __forceinline__ void ss(float* d, uint64_t da, uint64_t db, int sd) {
    asm volatile("{\n.reg .pred p;\nsetp.ne.b32 p, %82, 0;\nwgmma.mma_async.sync.aligned.m64n160k16.f32.bf16.bf16 {"
      "%0, %1, %2, %3, %4, %5, %6, %7, %8, %9, %10, %11, %12, %13, %14, %15, "
      "%16, %17, %18, %19, %20, %21, %22, %23, %24, %25, %26, %27, %28, %29, %30, %31, "
      "%32, %33, %34, %35, %36, %37, %38, %39, %40, %41, %42, %43, %44, %45, %46, %47, "
      "%48, %49, %50, %51, %52, %53, %54, %55, %56, %57, %58, %59, %60, %61, %62, %63, "
      "%64, %65, %66, %67, %68, %69, %70, %71, %72, %73, %74, %75, %76, %77, %78, %79"
      "}, %80, %81, p, 1, 1, 0, 1;\n}\n"
      :
      "+f"(d[0]), "+f"(d[1]), "+f"(d[2]), "+f"(d[3]), "+f"(d[4]), "+f"(d[5]), "+f"(d[6]), "+f"(d[7]),
      "+f"(d[8]), "+f"(d[9]), "+f"(d[10]), "+f"(d[11]), "+f"(d[12]), "+f"(d[13]), "+f"(d[14]), "+f"(d[15]),
      "+f"(d[16]), "+f"(d[17]), "+f"(d[18]), "+f"(d[19]), "+f"(d[20]), "+f"(d[21]), "+f"(d[22]), "+f"(d[23]),
      "+f"(d[24]), "+f"(d[25]), "+f"(d[26]), "+f"(d[27]), "+f"(d[28]), "+f"(d[29]), "+f"(d[30]), "+f"(d[31]),
      "+f"(d[32]), "+f"(d[33]), "+f"(d[34]), "+f"(d[35]), "+f"(d[36]), "+f"(d[37]), "+f"(d[38]), "+f"(d[39]),
      "+f"(d[40]), "+f"(d[41]), "+f"(d[42]), "+f"(d[43]), "+f"(d[44]), "+f"(d[45]), "+f"(d[46]), "+f"(d[47]),
      "+f"(d[48]), "+f"(d[49]), "+f"(d[50]), "+f"(d[51]), "+f"(d[52]), "+f"(d[53]), "+f"(d[54]), "+f"(d[55]),
      "+f"(d[56]), "+f"(d[57]), "+f"(d[58]), "+f"(d[59]), "+f"(d[60]), "+f"(d[61]), "+f"(d[62]), "+f"(d[63]),
      "+f"(d[64]), "+f"(d[65]), "+f"(d[66]), "+f"(d[67]), "+f"(d[68]), "+f"(d[69]), "+f"(d[70]), "+f"(d[71]),
      "+f"(d[72]), "+f"(d[73]), "+f"(d[74]), "+f"(d[75]), "+f"(d[76]), "+f"(d[77]), "+f"(d[78]), "+f"(d[79])
      : "l"(da), "l"(db), "r"(sd));
  }
};
template <> struct WG<192> {
  static __device__ __forceinline__ void ss(float* d, uint64_t da, uint64_t db, int sd) {
    asm volatile("{\n.reg .pred p;\nsetp.ne.b32 p, %98, 0;\nwgmma.mma_async.sync.aligned.m64n192k16.f32.bf16.bf16 {"
      "%0, %1, %2, %3, %4, %5, %6, %7, %8, %9, %10, %11, %12, %13, %14, %15, "
      "%16, %17, %18, %19, %20, %21, %22, %23, %24, %25, %26, %27, %28, %29, %30, %31, "
      "%32, %33, %34, %35, %36, %37, %38, %39, %40, %41, %42, %43, %44, %45, %46, %47, "
      "%48, %49, %50, %51, %52, %53, %54, %55, %56, %57, %58, %59, %60, %61, %62, %63, "
      "%64, %65, %66, %67, %68, %69, %70, %71, %72, %73, %74, %75, %76, %77, %78, %79, "
      "%80, %81, %82, %83, %84, %85, %86, %87, %88, %89, %90, %91, %92, %93, %94, %95"
      "}, %96, %97, p, 1, 1, 0, 1;\n}\n"
      :
      "+f"(d[0]), "+f"(d[1]), "+f"(d[2]), "+f"(d[3]), "+f"(d[4]), "+f"(d[5]), "+f"(d[6]), "+f"(d[7]),
      "+f"(d[8]), "+f"(d[9]), "+f"(d[10]), "+f"(d[11]), "+f"(d[12]), "+f"(d[13]), "+f"(d[14]), "+f"(d[15]),
      "+f"(d[16]), "+f"(d[17]), "+f"(d[18]), "+f"(d[19]), "+f"(d[20]), "+f"(d[21]), "+f"(d[22]), "+f"(d[23]),
      "+f"(d[24]), "+f"(d[25]), "+f"(d[26]), "+f"(d[27]), "+f"(d[28]), "+f"(d[29]), "+f"(d[30]), "+f"(d[31]),
      "+f"(d[32]), "+f"(d[33]), "+f"(d[34]), "+f"(d[35]), "+f"(d[36]), "+f"(d[37]), "+f"(d[38]), "+f"(d[39]),
      "+f"(d[40]), "+f"(d[41]), "+f"(d[42]), "+f"(d[43]), "+f"(d[44]), "+f"(d[45]), "+f"(d[46]), "+f"(d[47]),
      "+f"(d[48]), "+f"(d[49]), "+f"(d[50]), "+f"(d[51]), "+f"(d[52]), "+f"(d[53]), "+f"(d[54]), "+f"(d[55]),
      "+f"(d[56]), "+f"(d[57]), "+f"(d[58]), "+f"(d[59]), "+f"(d[60]), "+f"(d[61]), "+f"(d[62]), "+f"(d[63]),
      "+f"(d[64]), "+f"(d[65]), "+f"(d[66]), "+f"(d[67]), "+f"(d[68]), "+f"(d[69]), "+f"(d[70]), "+f"(d[71]),
      "+f"(d[72]), "+f"(d[73]), "+f"(d[74]), "+f"(d[75]), "+f"(d[76]), "+f"(d[77]), "+f"(d[78]), "+f"(d[79]),
      "+f"(d[80]), "+f"(d[81]), "+f"(d[82]), "+f"(d[83]), "+f"(d[84]), "+f"(d[85]), "+f"(d[86]), "+f"(d[87]),
      "+f"(d[88]), "+f"(d[89]), "+f"(d[90]), "+f"(d[91]), "+f"(d[92]), "+f"(d[93]), "+f"(d[94]), "+f"(d[95])
      : "l"(da), "l"(db), "r"(sd));
  }
};

#define DB 0
#define STAG -1
#define STAG_N 2
#define HBOTH 1
#define WO_LATE -1
#define SE_AT 5
#define WO_GATE 3
#define HSPLIT 1
#define HOLD_AT 33
#define LL_AT 4
#define KV_T0 2300
#define ST_YIELD 1
#define HP0 3500
#define HPD 450
#define RAMP 1
#define LEAD 2
#define WSP_N 16
#define EARLY 0
#define CPIN 1
#define CW0 0
#define PFT 1
#define WSP_D 600
#define D1 4
#define D2 4
#define D3 0
#define NSLEEP 32
#define G1_LATE 0
#define NPRE 1

namespace {

constexpr int kS = 2048, kD = 640, kF = 1536;
constexpr int NA = 10, NA2 = 9, NB = 5;
constexpr int A_SLOT = 8192, B_SLOT = 24576;
constexpr int OFF_A = 0;
constexpr int OFF_B = OFF_A + NA * A_SLOT;
constexpr int XB_PL = 2112;
constexpr int CV_KE = 4224, CV_KO = CV_KE + 4160;
constexpr int CV_SZ = CV_KO + 4160;
constexpr int OFF_CV = OFF_B + NB * B_SLOT;
constexpr int OFF_CS = OFF_CV + 2 * CV_SZ;
constexpr int OFF_XS = OFF_CS + 1536;
constexpr int OFF_BAR = OFF_XS + 512;
constexpr int BAR_AF = OFF_BAR, BAR_ST = BAR_AF + 8 * NA, BAR_XF = BAR_ST + 16, BAR_KV = BAR_XF + 16;
constexpr int BAR_BF = OFF_BAR + 128, BAR_G2 = BAR_BF + 8 * (NB + 1), BAR_XS = BAR_G2 + 8, BAR_KU = BAR_XS + 8, BAR_ZP = BAR_KU + 40, BAR_HOLD = BAR_ZP + 8, BAR_WO = BAR_HOLD + 8;
constexpr int BAR_AE = OFF_BAR + 256, BAR_BE = BAR_AE + 8 * NA;
constexpr int BAR_YT = BAR_KU + 24;
constexpr int BAR_HR = BAR_AE + 72;
constexpr int BAR_GO = BAR_XS, BAR_H1 = BAR_ST;
constexpr int BAR_YL = BAR_KU + 16;
constexpr int OFF_TAG = OFF_CS - 32;
constexpr int OFF_BIAS = OFF_BAR + 384;
constexpr int SMEM_BYTES = OFF_BIAS + 128;
static_assert(SMEM_BYTES <= 232448, "smem");
constexpr int NB_WGA = 1, NB_WGC = 2, NB_G1 = 3, NB_WO = 4, NB_CD = 5, NB_Z = 6, NB_WGB = 7;

constexpr int CNT_Z = 0, CNT_Y = 1, CNT_KV = 32, CNT_WO = 36;
struct Scratch {
  uint8_t kvx[kD * 4096];
  uint8_t z2[4 * 32 * 24576];
  uint8_t h[32 * 12 * 8192];
  uint8_t wo[4 * 12 * 20480];
  uint8_t y[896 * 4096];
  uint4 xstat[kS];
  uint4 zstat[kS * 4];
  uint2 colsum[kF];
  uint32_t cnt[2 * 32];
  uint32_t hflag[32 * 64];
  uint32_t epoch[136];
};
__device__ __align__(1024) Scratch g_scr;
#define STAMP(i)
#define STAMP2(i)
#define STAMPW(i)

struct Params {
  Scratch* scr;
  int by_smid;
  const __nv_bfloat16 *k, *v, *shift, *ssmk, *ssmD, *wsp, *bsp, *wout;
  __nv_bfloat16* out;
  CUtensorMap tmX, tmW, tmWsp, tmY, tmKV;
};

__device__ __forceinline__ uint64_t mkdesc(uint32_t addr, uint32_t lbo, uint32_t sbo, uint32_t swz) {
  return (uint64_t)((addr & 0x3FFFF) >> 4) | ((uint64_t)(lbo >> 4) << 16) | ((uint64_t)(sbo >> 4) << 32) | ((uint64_t)swz << 62);
}
#define WG_FENCE() asm volatile("wgmma.fence.sync.aligned;" ::: "memory")
#define WG_COMMIT() asm volatile("wgmma.commit_group.sync.aligned;" ::: "memory")
#define WG_WAIT(n) asm volatile("wgmma.wait_group.sync.aligned %0;" ::"n"(n) : "memory")
template <int N> __device__ __forceinline__ void acc_fence(float* d) {
#pragma unroll
  for (int i = 0; i < N; i++) asm volatile("" : "+f"(d[i])::"memory");
}
__device__ __forceinline__ void mbar_init(uint32_t bar, int cnt) { asm volatile("mbarrier.init.shared::cta.b64 [%0], %1;" ::"r"(bar), "r"(cnt) : "memory"); }
__device__ __forceinline__ void mbar_expect(uint32_t bar, uint32_t bytes) { asm volatile("mbarrier.arrive.expect_tx.shared::cta.b64 _, [%0], %1;" ::"r"(bar), "r"(bytes) : "memory"); }
__device__ __forceinline__ void mbar_arrive(uint32_t bar) { asm volatile("mbarrier.arrive.shared::cta.b64 _, [%0];" ::"r"(bar) : "memory"); }
__device__ __forceinline__ void mbar_arrive_if(uint32_t bar, bool c) {
  asm volatile("{\n.reg .pred p;\nsetp.ne.u32 p, %1, 0;\n@p mbarrier.arrive.shared::cta.b64 _, [%0];\n}\n" ::"r"(bar), "r"((uint32_t)c) : "memory");
}
__device__ __forceinline__ bool mbar_try(uint32_t bar, uint32_t parity) {
  uint32_t ok;
  asm volatile("{\n.reg .pred p;\nmbarrier.try_wait.parity.shared::cta.b64 p, [%1], %2;\nselp.u32 %0, 1, 0, p;\n}\n" : "=r"(ok) : "r"(bar), "r"(parity) : "memory");
  return ok;
}
__device__ __forceinline__ bool mbar_test(uint32_t bar, uint32_t parity) {
  uint32_t ok;
  asm volatile("{\n.reg .pred p;\nmbarrier.test_wait.parity.shared::cta.b64 p, [%1], %2;\nselp.u32 %0, 1, 0, p;\n}\n" : "=r"(ok) : "r"(bar), "r"(parity) : "memory");
  return ok;
}
__device__ __forceinline__ void die() { asm volatile("st.volatile.global.u32 [%0], %1;" ::"l"(0ull), "r"(0) : "memory"); }
__device__ __forceinline__ void spin_guard(uint32_t& n) { if (++n == (1u << 22)) die(); }
__device__ __forceinline__ void mbar_wait(uint32_t bar, uint32_t parity) {
  uint32_t t0 = 0;
#pragma unroll 1
  while (!mbar_try(bar, parity)) spin_guard(t0);
}
__device__ __forceinline__ void mbar_wait2(uint32_t b0, uint32_t p0, uint32_t b1, uint32_t p1) {
  uint32_t t0 = 0;
#pragma unroll 1
  while (true) {
    const bool r0 = mbar_try(b0, p0), r1 = mbar_try(b1, p1);
    if (r0 && r1) break;
    spin_guard(t0);
  }
}
__device__ __forceinline__ int tid_now() { int v; asm volatile("mov.u32 %0, %%tid.x;" : "=r"(v)); return v & 127; }
__device__ __forceinline__ bool elect_one() {
  uint32_t p;
  asm volatile("{\n.reg .pred P;\nelect.sync _|P, 0xffffffff;\nselp.u32 %0, 1, 0, P;\n}\n" : "=r"(p));
  return p;
}
__device__ __forceinline__ void bar_sync(int id, int n) { asm volatile("bar.sync %0, %1;" ::"r"(id), "r"(n) : "memory"); }
__device__ __forceinline__ void bar_arrive(int id, int n) { asm volatile("bar.arrive %0, %1;" ::"r"(id), "r"(n) : "memory"); }
__device__ __forceinline__ void fence_async_smem() { asm volatile("fence.proxy.async.shared::cta;" ::: "memory"); }
__device__ __forceinline__ void bulk_g2s(uint32_t dst, const void* src, uint32_t bytes, uint32_t bar) {
  asm volatile("cp.async.bulk.shared::cluster.global.mbarrier::complete_tx::bytes [%0], [%1], %2, [%3];" ::"r"(dst), "l"(src), "r"(bytes), "r"(bar) : "memory");
}
__device__ __forceinline__ void bulk_s2g(void* dst, uint32_t src, uint32_t bytes) {
  asm volatile("cp.async.bulk.global.shared::cta.bulk_group [%0], [%1], %2;" ::"l"(dst), "r"(src), "r"(bytes) : "memory");
}
__device__ __forceinline__ void tma2d(uint32_t dst, const CUtensorMap* m, int c0, int c1, uint32_t bar) {
  asm volatile("cp.async.bulk.tensor.2d.shared::cluster.global.mbarrier::complete_tx::bytes [%0], [%1, {%3, %4}], [%2];" ::"r"(dst), "l"(m), "r"(bar), "r"(c0), "r"(c1) : "memory");
}
__device__ __forceinline__ void tma_rows(uint32_t dst, const CUtensorMap* m, int c0, int rb, uint32_t bar) {
  asm volatile("cp.async.bulk.tensor.5d.shared::cluster.global.mbarrier::complete_tx::bytes [%0], [%1, {%3, %4, %4, %4, %5}], [%2];" ::"r"(dst), "l"(m), "r"(bar), "r"(c0), "r"(0), "r"(rb * 2) : "memory");
}
__device__ __forceinline__ int row_grp(int w, int half) { return (w >> 1) * 4 + (w & 1) + 2 * half; }
__device__ __forceinline__ void tma3d(uint32_t dst, const CUtensorMap* m, int c0, int c1, int c2, uint32_t bar) {
  asm volatile("cp.async.bulk.tensor.3d.shared::cluster.global.mbarrier::complete_tx::bytes [%0], [%1, {%3, %4, %5}], [%2];" ::"r"(dst), "l"(m), "r"(bar), "r"(c0), "r"(c1), "r"(c2) : "memory");
}
__device__ __forceinline__ void st_release(uint32_t* p, uint32_t v) { asm volatile("st.release.gpu.global.u32 [%0], %1;" ::"l"(p), "r"(v) : "memory"); }
__device__ __forceinline__ uint4 ld_ll4(const void* p) {
  uint64_t a, b;
  asm volatile("ld.relaxed.gpu.global.v2.u64 {%0,%1}, [%2];" : "=l"(a), "=l"(b) : "l"(p) : "memory");
  return make_uint4((uint32_t)a, (uint32_t)(a >> 32), (uint32_t)b, (uint32_t)(b >> 32));
}
__device__ __forceinline__ void st_ll4(void* p, uint32_t a, uint32_t b, uint32_t c, uint32_t d) {
  asm volatile("st.relaxed.gpu.global.v2.u64 [%0], {%1,%2};" ::"l"(p), "l"(a | ((uint64_t)b << 32)), "l"(c | ((uint64_t)d << 32)) : "memory");
}
__device__ __forceinline__ void st_ll2(void* p, uint32_t a, uint32_t b) { asm volatile("st.relaxed.gpu.global.u64 [%0], %1;" ::"l"(p), "l"(a | ((uint64_t)b << 32)) : "memory"); }
__device__ __forceinline__ void wgmma_colsum(float* d, uint64_t da, uint64_t db) {
  asm volatile("{\n.reg .pred p;\nsetp.ne.b32 p, 1, 0;\nwgmma.mma_async.sync.aligned.m64n8k16.f32.bf16.bf16 {%0, %1, %2, %3}, %4, %5, p, 1, 1, 1, 0;\n}\n"
               : "+f"(d[0]), "+f"(d[1]), "+f"(d[2]), "+f"(d[3]) : "l"(da), "l"(db));
}
__device__ __forceinline__ void prefetch_l2(const void* p) { asm volatile("prefetch.global.L2 [%0];" ::"l"(p)); }
__device__ __forceinline__ void pace(uint32_t& t, uint32_t dt) {
  t += dt;
  while ((int32_t)((uint32_t)clock() - t) < 0) { if (NSLEEP) __nanosleep(NSLEEP); }
}
__device__ __forceinline__ void red_relaxed(uint32_t* p) { asm volatile("red.relaxed.gpu.global.add.u32 [%0], 1;" ::"l"(p) : "memory"); }
__device__ __forceinline__ void red_release(uint32_t* p) { asm volatile("red.release.gpu.global.add.u32 [%0], 1;" ::"l"(p) : "memory"); }
__device__ __forceinline__ uint4 ldg4(const void* p) { uint4 v; asm volatile("ld.global.v4.u32 {%0,%1,%2,%3}, [%4];" : "=r"(v.x), "=r"(v.y), "=r"(v.z), "=r"(v.w) : "l"(p) : "memory"); return v; }
__device__ __forceinline__ uint32_t ldg1(const void* p) { uint32_t v; asm volatile("ld.global.u32 %0, [%1];" : "=r"(v) : "l"(p) : "memory"); return v; }
__device__ __forceinline__ void stg4_if(void* p, uint32_t a, uint32_t b, uint32_t c, uint32_t d, bool on) {
  asm volatile("{\n.reg .pred p;\nsetp.ne.u32 p, %5, 0;\n@p st.global.v4.u32 [%0], {%1,%2,%3,%4};\n}\n" ::"l"(p), "r"(a), "r"(b), "r"(c), "r"(d), "r"((uint32_t)on) : "memory");
}
template <int OFF> __device__ __forceinline__ uint32_t lds32(uint32_t a) { uint32_t v; asm volatile("ld.shared.u32 %0, [%1+%2];" : "=r"(v) : "r"(a), "n"(OFF)); return v; }
__device__ __forceinline__ uint4 lds128(uint32_t a) { uint4 v; asm volatile("ld.shared.v4.u32 {%0,%1,%2,%3}, [%4];" : "=r"(v.x), "=r"(v.y), "=r"(v.z), "=r"(v.w) : "r"(a) : "memory"); return v; }
__device__ __forceinline__ float2 lds64f(uint32_t a) { float2 v; asm volatile("ld.shared.v2.f32 {%0,%1}, [%2];" : "=f"(v.x), "=f"(v.y) : "r"(a) : "memory"); return v; }
__device__ __forceinline__ void sts64f(uint32_t a, float x, float y) { asm volatile("st.shared.v2.f32 [%0], {%1,%2};" ::"r"(a), "f"(x), "f"(y) : "memory"); }
__device__ __forceinline__ void sts32(uint32_t a, uint32_t x) { asm volatile("st.shared.u32 [%0], %1;" ::"r"(a), "r"(x) : "memory"); }
__device__ __forceinline__ void sts128(uint32_t a, uint32_t x, uint32_t y, uint32_t z, uint32_t w) { asm volatile("st.shared.v4.u32 [%0], {%1,%2,%3,%4};" ::"r"(a), "r"(x), "r"(y), "r"(z), "r"(w) : "memory"); }
__device__ __forceinline__ void stsm4(uint32_t a, uint32_t r0, uint32_t r1, uint32_t r2, uint32_t r3) {
  asm volatile("stmatrix.sync.aligned.m8n8.x4.shared.b16 [%0], {%1,%2,%3,%4};" ::"r"(a), "r"(r0), "r"(r1), "r"(r2), "r"(r3) : "memory");
}
__device__ __forceinline__ void stsm4t(uint32_t a, uint32_t r0, uint32_t r1, uint32_t r2, uint32_t r3) {
  asm volatile("stmatrix.sync.aligned.m8n8.x4.trans.shared.b16 [%0], {%1,%2,%3,%4};" ::"r"(a), "r"(r0), "r"(r1), "r"(r2), "r"(r3) : "memory");
}
__device__ __forceinline__ void ldsm4t(uint32_t* r, uint32_t a) {
  asm volatile("ldmatrix.sync.aligned.m8n8.x4.trans.shared.b16 {%0,%1,%2,%3}, [%4];" : "=r"(r[0]), "=r"(r[1]), "=r"(r[2]), "=r"(r[3]) : "r"(a) : "memory");
}
__device__ __forceinline__ uint32_t pack2(float lo, float hi) { uint32_t r; asm("cvt.rn.bf16x2.f32 %0, %1, %2;" : "=r"(r) : "f"(hi), "f"(lo)); return r; }
__device__ __forceinline__ float bf_lo(uint32_t u) { return __uint_as_float(u << 16); }
__device__ __forceinline__ float bf_hi(uint32_t u) { return __uint_as_float(u & 0xffff0000u); }
__device__ __forceinline__ float tanh_fast(float x) { float y; asm("tanh.approx.f32 %0, %1;" : "=f"(y) : "f"(x)); return y; }
__device__ __forceinline__ uint32_t hmul2(uint32_t a, uint32_t b) { uint32_t r; asm("mul.rn.bf16x2 %0, %1, %2;" : "=r"(r) : "r"(a), "r"(b)); return r; }
__device__ __forceinline__ uint32_t hfma2(uint32_t a, uint32_t b, uint32_t c) { uint32_t r; asm("fma.rn.bf16x2 %0, %1, %2, %3;" : "=r"(r) : "r"(a), "r"(b), "r"(c)); return r; }
__device__ __forceinline__ uint32_t prmt(uint32_t a, uint32_t b, uint32_t s) { return __byte_perm(a, b, s); }

__device__ __forceinline__ uint32_t ld_relaxed(const uint32_t* p) { uint32_t v; asm volatile("ld.relaxed.gpu.global.u32 %0, [%1];" : "=r"(v) : "l"(p) : "memory"); return v; }
__device__ __forceinline__ void acquire_fence() { asm volatile("fence.acquire.gpu;\nfence.proxy.async.global;" ::: "memory"); }
__device__ __forceinline__ uint32_t load_epoch(const Params& p, int idx, int lane) { return ld_relaxed(&p.scr->epoch[idx + (((lane * lane) & 3) == 2 ? 1 : 0)]); }
__device__ __forceinline__ void poll_counter(const uint32_t* cnt, uint32_t target) {
  uint32_t t0 = 0;
#pragma unroll 1
  while (!__all_sync(0xffffffff, ld_relaxed(cnt) == target)) spin_guard(t0);
  acquire_fence();
}

__device__ __forceinline__ int g3_block(int cb, int it) {
  const int j = it < 6 ? it - 3 : (it - 6) >> 1;
  return it < 3 ? cb * 3 + it : (j + (j >= cb)) * 3 + (it < 6 ? 0 : 1 + (it & 1));
}
__device__ __forceinline__ void reset_sector(uint32_t* f) { st_ll4(f, 0, 0, 0, 0); st_ll4(f + 4, 0, 0, 0, 0); }

template <int N, bool A_SWZ, int B_MODE, int DEPTH, class Hook, class Mid>
__device__ __forceinline__ void gemm_loop(float* d, uint32_t sb, int nkb, int sa, int pa, int b0, uint32_t boff, int relA, int relB, int tid, Hook hook, Mid mid) {
  constexpr uint32_t A_STEP = A_SWZ ? 2 : 128;
  constexpr uint32_t B_STEP = B_MODE == 0 ? 128 : (B_MODE == 1 ? 384 : 320);
  const uint64_t da0 = A_SWZ ? mkdesc(sb + OFF_A, 16, 1024, 1) : mkdesc(sb + OFF_A, 1024, 128, 0);
  const uint64_t db0 = B_MODE == 0 ? mkdesc(sb + OFF_B + boff, 8192, 1024, 1) : mkdesc(sb + OFF_B + boff, B_MODE == 1 ? 3072 : 2560, 128, 0);
  constexpr int MODA = B_MODE == 0 ? NA : NA2;
  constexpr int MODB = B_MODE == 2 ? 6 : NB;
  int sbk = b0 % MODB, pb = (b0 / MODB) & 1;
  auto boffs = [](int s_) { return B_MODE == 2 ? (s_ == 5 ? 0 : s_ + 1) * (20480 >> 4) : s_ * (B_SLOT >> 4); };
  uint32_t rel = 0;
  uint64_t da = da0 + sa * (A_SLOT >> 4), db = db0 + boffs(sbk);
  const bool doR = tid < 2 ? tid < relA : tid - 2 < relB;
  mbar_wait2(sb + BAR_AF + 8 * sa, pa, sb + BAR_BF + 8 * sbk, pb);
  if constexpr (DEPTH == 0) {
    acc_fence<N / 2>(d);
#pragma unroll 1
    for (int it = 0; it < nkb; it++) {
      WG_FENCE();
#pragma unroll
      for (int j = 0; j < 4; j++) WG<N>::ss(d, da + j * A_STEP, db + j * B_STEP, 1);
      WG_COMMIT();
      const uint32_t prel = rel;
      rel = sb + BAR_AE + 8 * (tid < 2 ? sa : sbk + NA);
      if (++sa == MODA) { sa = 0; pa ^= 1; }
      if (++sbk == MODB) { sbk = 0; pb ^= 1; }
      da = da0 + sa * (A_SLOT >> 4); db = db0 + boffs(sbk);
      const bool r0 = mbar_test(sb + BAR_AF + 8 * sa, pa), r1 = mbar_test(sb + BAR_BF + 8 * sbk, pb);
      WG_WAIT(1);
      mbar_arrive_if(prel, doR && it != 0);
      mid(it);
      if (it + 1 < nkb && !(r0 && r1)) mbar_wait2(sb + BAR_AF + 8 * sa, pa, sb + BAR_BF + 8 * sbk, pb);
    }
  } else
#pragma unroll 1
  for (int it = 0; it < nkb; it++) {
    WG_FENCE();
    WG<N>::ss(d, da, db, 1);
    const uint32_t prel = rel;
    rel = sb + BAR_AE + 8 * (tid < 2 ? sa : sbk + NA);
    if (++sa == MODA) { sa = 0; pa ^= 1; }
    if (++sbk == MODB) { sbk = 0; pb ^= 1; }
    if (DEPTH == 1) { WG_COMMIT(); WG_WAIT(1); }
    WG<N>::ss(d, da + A_STEP, db + B_STEP, 1);
    WG_COMMIT();
    WG_WAIT(1);
    if (EARLY == 1) mbar_arrive_if(prel, doR && it != 0);
    WG<N>::ss(d, da + 2 * A_STEP, db + 2 * B_STEP, 1);
    if (DEPTH == 1) WG_COMMIT();
    if (EARLY != 1) mbar_arrive_if(prel, doR && it != 0);
    const bool r0 = mbar_test(sb + BAR_AF + 8 * sa, pa), r1 = mbar_test(sb + BAR_BF + 8 * sbk, pb);
    const uint64_t da3 = da + 3 * A_STEP, db3 = db + 3 * B_STEP;
    da = da0 + sa * (A_SLOT >> 4); db = db0 + boffs(sbk);
    if (DEPTH == 1) WG_WAIT(1);
    WG<N>::ss(d, da3, db3, 1);
    WG_COMMIT();
    mid(it);
    if (it + 1 < nkb) {
      if (!(r0 && r1)) {
        mbar_wait2(sb + BAR_AF + 8 * sa, pa, sb + BAR_BF + 8 * sbk, pb);
      }
    }
    if (DEPTH == 2) WG_WAIT(1);
  }
  hook();
  WG_WAIT(0);
  acc_fence<N / 2>(d);
  mbar_arrive_if(rel, doR);
}

__device__ __forceinline__ void gelu_tile(const float* d, uint32_t* z, float* st, uint32_t cs_addr, float2 s0, float2 s1) {
  const float kA = 0.7978845608028654f, kB = 0.7978845608028654f * 0.044715f;
  const float c1a = kA * s0.y, c3a = kB * s0.y * s0.y * s0.y, ma = -s0.x;
  const float c1b = kA * s1.y, c3b = kB * s1.y * s1.y * s1.y, mb = -s1.x;
  float acc[8];
#pragma unroll
  for (int i = 0; i < 8; i++) acc[i] = 0.f;
#pragma unroll
  for (int j = 0; j < 24; j++) {
    const float2 cs = lds64f(cs_addr + j * 32);
    float r[4];
#pragma unroll
    for (int e = 0; e < 4; e++) {
      const float c = (e & 1) ? cs.y : cs.x;
      const float v = fmaf(e < 2 ? ma : mb, c, d[4 * j + e]);
      const float a = v * fmaf(v * v, e < 2 ? c3a : c3b, e < 2 ? c1a : c1b);
      r[e] = fmaf(v, tanh_fast(a), v);
      acc[e] += r[e];
      acc[4 + e] = fmaf(r[e], r[e], acc[4 + e]);
    }
    z[2 * j] = pack2(r[0], r[1]);
    z[2 * j + 1] = pack2(r[2], r[3]);
  }
  st[0] = acc[0] + acc[1]; st[1] = acc[4] + acc[5]; st[2] = acc[2] + acc[3]; st[3] = acc[6] + acc[7];
}

template <int Q> __device__ __forceinline__ void conv_load(uint32_t* a, uint32_t ab) {
  a[0] = lds32<512 * Q>(ab);       a[1] = lds32<512 * Q + 256>(ab);  a[2] = lds32<512 * Q + 16>(ab);   a[3] = lds32<512 * Q + 272>(ab);
  a[4] = lds32<512 * Q + 32>(ab);  a[5] = lds32<512 * Q + 288>(ab);  a[6] = lds32<512 * Q + 48>(ab);   a[7] = lds32<512 * Q + 304>(ab);
  a[8] = lds32<512 * Q + 64>(ab);  a[9] = lds32<512 * Q + 320>(ab);  a[10] = lds32<512 * Q + 80>(ab);  a[11] = lds32<512 * Q + 336>(ab);
  a[12] = lds32<512 * Q + 96>(ab); a[13] = lds32<512 * Q + 352>(ab); a[14] = lds32<512 * Q + 112>(ab); a[15] = lds32<512 * Q + 368>(ab);
}
template <int Q, int L> __device__ __forceinline__ void conv_step(float* d, uint32_t (*a)[16], uint32_t ab, uint64_t db) {
  WG_FENCE();
#pragma unroll
  for (int s = 0; s < 4; s++) WG<128 - 16 * Q>::rs(d, a[Q] + 4 * s, db + s + 16 * Q);
  WG_COMMIT();
  if (CPIN) WG_WAIT(1);
  if (L >= 0) conv_load<(L >= 0 ? L : 0)>(a[L >= 0 ? L : 0], ab);
  if (CW0 || Q == 0) WG_WAIT(0);
}

__device__ __forceinline__ int seg_col(int cb, int h) { return (cb >> 1) * 320 + (cb & 1) * 32 + h * 64; }
__device__ __forceinline__ void final_load_x(uint32_t (*xw)[10], uint32_t xt, int cb, int h, int w, int lane) {
  const int g = lane >> 2, t = lane & 3, cc = seg_col(cb, h) >> 3;
  const int c0 = cc + t, c1 = c0 + 24, c2 = cc + 16 - 6 * h + (t >> 1);
  const uint32_t r0 = xt + (w * 16 + g) * 128;
#pragma unroll
  for (int r = 0; r < 2; r++) {
    const uint4 u = lds128(r0 + r * 1024 + (c0 >> 3) * A_SLOT + (((c0 ^ g) & 7) << 4)), v = lds128(r0 + r * 1024 + (c1 >> 3) * A_SLOT + (((c1 ^ g) & 7) << 4));
    const float2 z = lds64f(r0 + r * 1024 + (c2 >> 3) * A_SLOT + (((c2 ^ g) & 7) << 4) + (t & 1) * 8);
    xw[r][0] = u.x; xw[r][1] = u.y; xw[r][2] = u.z; xw[r][3] = u.w;
    xw[r][4] = v.x; xw[r][5] = v.y; xw[r][6] = v.z; xw[r][7] = v.w;
    xw[r][8] = __float_as_uint(z.x); xw[r][9] = __float_as_uint(z.y);
  }
}
__device__ __forceinline__ void final_s_early(uint32_t (*sw)[10], const uint32_t (*xw)[10], uint32_t ya, float2 s0, float2 s1) {
  const uint32_t r2[2] = {pack2(s0.y, s0.y), pack2(s1.y, s1.y)};
  const float na = -s0.x * bf_lo(r2[0]), nb = -s1.x * bf_lo(r2[1]);
  const uint32_t n2[2] = {pack2(na, na), pack2(nb, nb)};
#pragma unroll
  for (int j = 0; j < 10; j += 2) {
    uint32_t y[4];
    if (j < 4 || j == 8) ldsm4t(y, ya + (j < 4 ? j : 4) * 1024);
#pragma unroll
    for (int e = 0; e < 4; e++) {
      const uint32_t xn = hfma2(xw[e & 1][j + (e >> 1)], r2[e & 1], n2[e & 1]);
      sw[e & 1][j + (e >> 1)] = (j < 4 || j == 8) ? hmul2(xn, y[e]) : xn;
    }
  }
}
__device__ __forceinline__ bool final_late(uint32_t* y, uint32_t ya) {
  ldsm4t(y, ya + 6144);
  ldsm4t(y + 4, ya + 8192);
  uint32_t zero = 0;
#pragma unroll
  for (int e = 0; e < 8; e++) zero |= (y[e] - 0x00010001u) & ~y[e];
  return (zero & 0x80008000u) == 0;
}
__device__ __forceinline__ bool bar_all(int id, int n, bool c) {
  uint32_t r;
  asm volatile("{\n.reg .pred p, q;\nsetp.ne.u32 p, %3, 0;\nbar.red.and.pred q, %1, %2, p;\nselp.u32 %0, 1, 0, q;\n}\n" : "=r"(r) : "r"(id), "r"(n), "r"((uint32_t)c) : "memory");
  return r;
}
__device__ __forceinline__ void final_out(const float* d, const uint32_t (*xw)[10], const uint32_t (*sw)[10], float ra, float rb, __nv_bfloat16* o0, int h, int t) {
  const float ca = 0.25f * ra, cb = 0.25f * rb;
  uint32_t o[2][10];
#pragma unroll
  for (int j = 0; j < 10; j++) {
#pragma unroll
    for (int r = 0; r < 2; r++) {
      const float h0 = d[4 * j + 2 * r] * (r ? cb : ca), h1 = d[4 * j + 2 * r + 1] * (r ? cb : ca);
      o[r][j] = hfma2(pack2(fmaf(h0, tanh_fast(h0), h0), fmaf(h1, tanh_fast(h1), h1)), sw[r][j], xw[r][j]);
      __nv_bfloat16* q = o0 + r * 16 * kD;
      if (j == 3) stg4_if(q + t * 8, o[r][0], o[r][1], o[r][2], o[r][3], true);
      if (j == 7) stg4_if(q + 192 + t * 8, o[r][4], o[r][5], o[r][6], o[r][7], true);
      if (j == 9) asm volatile("st.global.v2.u32 [%0], {%1,%2};" ::"l"(q + 128 - 48 * h + t * 4), "r"(o[r][8]), "r"(o[r][9]) : "memory");
    }
  }
}

struct Taps { uint4 r0, r1; uint32_t n0, n1, dd; };
__device__ __forceinline__ void load_taps(Taps& k, const Params& p, int ch, int tid) {
  const uint4* kp = (const uint4*)(p.ssmk + (size_t)ch * kS);
  k.r0 = ldg4(kp + tid); k.r1 = ldg4(kp + 128 + tid);
  k.n0 = ldg1(kp + tid + 1); k.n1 = tid < 127 ? ldg1(kp + 129 + tid) : 0u;
  k.dd = __bfloat16_as_ushort(p.ssmD[ch]);
}
__device__ __forceinline__ void load_convx(const Params& p, uint32_t cv, uint32_t bar, int ch) {
  mbar_expect(bar, 4096);
  bulk_g2s(cv, p.scr->kvx + (size_t)ch * 4096, 2048, bar);
  bulk_g2s(cv + XB_PL, p.scr->kvx + (size_t)ch * 4096 + 2048, 2048, bar);
}
#define CW 3
#define CSTAMP(j)
__device__ __forceinline__ void zero_pads(uint32_t cv, int lane) {
  if (lane < 8) sts128(cv + (lane >> 2) * XB_PL + 2048 + (lane & 3) * 16, 0, 0, 0, 0);
  else if (lane < 12) sts128(cv + ((lane & 2) ? CV_KO : CV_KE) + (lane & 1) * 16, 0, 0, 0, 0);
  fence_async_smem();
  __syncwarp();
}
__device__ __forceinline__ int y_row(int c, uint32_t par) {
  const int hf = c >= 320, cc = c - hf * 320, u = cc >> 6, cb = hf * 2 + ((cc >> 5) & 1);
  if (u == 2) return cb * 96 + ((cc >> 4) & 1) * 48 + 32 + (cc & 1) + ((cc >> 1) & 1) * 8 + ((cc >> 2) & 3) * 2;
  return (u < 2 ? cb * 96 + u * 48 : 384 + par * 256 + cb * 64 + (u - 3) * 32) + (cc & 1) + ((cc >> 1) & 3) * 8 + ((cc >> 3) & 3) * 2;
}
__device__ __forceinline__ void y_store(const Params& p, uint32_t sb, int h, int ch, uint32_t par) {
  uint8_t* dst = p.scr->y + (size_t)y_row(ch, par) * 4096;
  if (elect_one()) {
    bulk_s2g(dst, sb + OFF_A + 9 * A_SLOT + h * 4096, 4096);
    asm volatile("cp.async.bulk.commit_group;\ncp.async.bulk.wait_group 0;" ::: "memory");
  }
  __syncwarp();
}
__device__ __forceinline__ void conv_service(const Params& p, uint32_t sb, int h, int ch) {
  bar_sync(NB_WGA + 8 + h, 160);
  if (elect_one()) load_convx(p, sb + OFF_CV + (1 - h) * CV_SZ, sb + BAR_XF + 8 * h, ch + 128);
  bar_sync(NB_WGA + 8 + h, 160);
  y_store(p, sb, h, ch, 0);
}
__device__ __forceinline__ uint32_t y_tile(int h) { return OFF_CV + (1 - h) * 13312; }
__device__ __forceinline__ void load_late_y(const Params& p, uint32_t sb, int h, int rb, int cb, uint32_t par) {
  mbar_expect(sb + BAR_YL + 16 * h, 4096);
  tma2d(sb + y_tile(h) + 6144, &p.tmY, rb * 64, 384 + par * 256 + cb * 64 + h * 32, sb + BAR_YL + 16 * h);
  tma2d(sb + y_tile(h) + 8192, &p.tmY, rb * 64, 400 + par * 256 + cb * 64 + h * 32, sb + BAR_YL + 16 * h);
}
__device__ __forceinline__ void held_service(const Params& p, uint32_t sb, int h, int ch, int rb, int cb, uint32_t tag, int lane) {
#pragma unroll 1
  for (int i = 0; i < 8; i++) sts128(sb + OFF_A + 9 * A_SLOT + h * 4096 + i * 512 + lane * 16, 0, 0, 0, 0);
  fence_async_smem();
  __syncwarp();
  y_store(p, sb, h, ch, ~tag & 1);
  mbar_wait(sb + BAR_YT, 1);
  acquire_fence();
  bar_sync(NB_WGA + 8 + h, 160);
  bar_sync(NB_WGA + 8 + h, 160);
  uint8_t* dst = p.scr->y + (size_t)y_row(ch, tag & 1) * 4096;
  if (elect_one()) {
    bulk_s2g(dst, sb + OFF_A + 9 * A_SLOT + h * 4096, 4096);
    asm volatile("cp.async.bulk.commit_group;" ::: "memory");
    mbar_expect(sb + BAR_XF + 8 * h, 6144);
#pragma unroll 1
    for (int i = 0; i < 3; i++) tma2d(sb + y_tile(h) + i * 2048, &p.tmY, rb * 64, cb * 96 + h * 48 + i * 16, sb + BAR_XF + 8 * h);
  }
  mbar_wait(sb + BAR_AE + 8 * (LL_AT - 1), 1);
  if (elect_one()) { load_late_y(p, sb, h, rb, cb, tag & 1); asm volatile("cp.async.bulk.wait_group 0;" ::: "memory"); }
}
__device__ __forceinline__ void conv_worker(const Params& p, Taps& k, uint32_t cv, uint32_t yb0,
                                            uint32_t xbar, int nbar, int ch0, int n, uint32_t holdbar, int w, int lane,
                                            int tid, int st0, int rb, int cb) {
  const int g = lane >> 2, t = lane & 3, w0 = w & 1, w1 = w >> 1;
  const uint32_t ab = cv + ((g & 1) ? CV_KE : CV_KO) + 32 + 2 * (64 * w0 + 8 * w1 + ((g - 15) & ~1) + 2 * t);
  const uint32_t scA = cv + (w1 ? CV_KO : CV_KE) + 32, scB = scA + 2048;
  const int dl = (t >> 1) ^ 1;
  if (n == 2) mbar_wait(xbar, 0);
  STAMPW(st0 + 3);
#pragma unroll 1
  for (int i = 0; i < n; i++) {
    if (tid == 0) {
      k.r0.x = (k.r0.x & 0xffff0000u) | (pack2(bf_lo(k.r0.x) + bf_lo(k.dd), 0.f) & 0xffffu);
      sts32(cv + CV_KO + 28, k.r0.x << 16);
    }
    sts128(cv + CV_KE + 32 + tid * 16, k.r0.x, k.r0.y, k.r0.z, k.r0.w);
    sts128(cv + CV_KO + 32 + tid * 16, prmt(k.r0.x, k.r0.y, 0x5432), prmt(k.r0.y, k.r0.z, 0x5432), prmt(k.r0.z, k.r0.w, 0x5432), prmt(k.r0.w, k.n0, 0x5432));
    sts128(cv + CV_KE + 2080 + tid * 16, k.r1.x, k.r1.y, k.r1.z, k.r1.w);
    sts128(cv + CV_KO + 2080 + tid * 16, prmt(k.r1.x, k.r1.y, 0x5432), prmt(k.r1.y, k.r1.z, 0x5432), prmt(k.r1.z, k.r1.w, 0x5432), prmt(k.r1.w, k.n1, 0x5432));
    if (i + 1 < n) load_taps(k, p, ch0 + (i + 1) * 128, tid);
    bar_sync(nbar, 128);
    CSTAMP(0);
    const uint64_t db = mkdesc(cv + (i & 0x1000), XB_PL, 128, 0);
    float d[64];
    uint32_t a[8][16];
    conv_load<7>(a[7], ab); conv_load<6>(a[6], ab); conv_load<5>(a[5], ab); conv_load<4>(a[4], ab);
#pragma unroll
    for (int j = 0; j < 64; j++) d[j] = 0.f;
    mbar_wait(xbar, i & 1);
    if (i + 1 == n) {
      if (STAG >= 0 && n == STAG_N) bar_sync(NB_G1, 256);
      else mbar_wait(holdbar, 1);
    }
    CSTAMP(1);
    const bool lead = i + 1 == n && n != STAG_N;
    conv_step<7, -1>(d, a, ab, db); conv_step<6, -1>(d, a, ab, db); conv_step<5, -1>(d, a, ab, db); conv_step<4, 3>(d, a, ab, db);
    if (STAG == 4 && lead) bar_arrive(NB_G1, 256);
    conv_step<3, 2>(d, a, ab, db);
    if (STAG == 3 && lead) bar_arrive(NB_G1, 256);
    conv_step<2, 1>(d, a, ab, db);
    if (STAG == 2 && lead) bar_arrive(NB_G1, 256);
    conv_step<1, 0>(d, a, ab, db);
    if (STAG == 1 && lead) bar_arrive(NB_G1, 256);
    conv_step<0, -1>(d, a, ab, db);
    if (STAG == 0 && lead) bar_arrive(NB_G1, 256);
    acc_fence<64>(d);
    CSTAMP(2);
    bar_sync(nbar + 8, 160);
    float E[16][2];
#pragma unroll
    for (int j = 0; j < 15; j++) { E[j][0] = d[4 * j] + d[4 * j + 6]; E[j][1] = d[4 * j + 1] + d[4 * j + 7]; }
    E[15][0] = d[60]; E[15][1] = d[61];
    if (w0 == 0) {
#pragma unroll
      for (int j = 8; j < 16; j++) sts64f(scA + (j - 8) * 256 + lane * 8, E[j][0], E[j][1]);
    } else {
      const uint32_t a = scB - dl * 256 + (lane ^ 2) * 8;
#pragma unroll
      for (int j = 1; j < 8; j++) sts64f(a + j * 256, E[j][0], E[j][1]);
      sts64f(scB + (dl ? 7 * 256 : 0) + (lane ^ 2) * 8, dl ? E[8][0] : E[0][0], dl ? E[8][1] : E[0][1]);
    }
    bar_sync(nbar, 128);
    CSTAMP(3);
    uint32_t pk[8];
    if (w0 == 0) {
#pragma unroll
      for (int j = 0; j < 8; j++) { const float2 v = lds64f(scB + j * 256 + lane * 8); pk[j] = pack2(E[j][0] + v.x, E[j][1] + v.y); }
    } else {
      const uint32_t a0 = scA - dl * 256 + (lane ^ 2) * 8;
#pragma unroll
      for (int j = 9; j < 16; j++) { const float2 v = lds64f(a0 + (j - 8) * 256); pk[j - 8] = pack2(E[j][0] + v.x, E[j][1] + v.y); }
      const float2 v = lds64f(scA + (dl ? 7 * 256 : 0) + (lane ^ 2) * 8);
      pk[0] = pack2((dl ? 0.f : E[8][0]) + v.x, (dl ? 0.f : E[8][1]) + v.y);
    }
    CSTAMP(4);
    if (i + 1 == n) {
#pragma unroll
      for (int j = 0; j < 8; j++) pk[j] = ~pk[j];
    }
    const uint32_t yb = yb0 + 32 * ((w0 ? 35 : 95) - lane) + 16 * w1;
    stsm4t((w0 && lane < 4) ? yb - 1024 : yb + 1024, pk[0], pk[1], pk[2], pk[3]);
    stsm4t(yb, pk[4], pk[5], pk[6], pk[7]);
    fence_async_smem();
    bar_sync(nbar + 8, 160);
    CSTAMP(5);
    STAMPW(st0 + i);
    if (n == 2 && i == 0) {
      const int u = (tid >> 3) % 5, kg = rb * 3 + (tid < 120 ? (tid >> 3) / 5 : 0), c = u < 4 ? (u >> 1) * 10 + (u & 1) * 4 : 8, o2 = u < 4 ? 2 : 10;
      const uint4* wp = (const uint4*)p.wout + (uint32_t)((kg * 8 + (tid & 7)) * (kD / 8) + (seg_col(cb, 0) >> 3) + (u < 4 ? (u >> 1) * 8 + (u & 1) * 24 : 16));
      const uint4 w0 = ldg4(wp), w1 = ldg4(wp + 1), w2 = ldg4(wp + 2), w3 = ldg4(wp + 3);
      uint8_t* dst = p.scr->wo + (uint32_t)(cb * (12 * 20480) + kg * 2560 + c * 128 + (tid & 7) * 16);
      const bool f = u < 4, on = tid < 120;
      stg4_if(dst, w0.x, f ? w1.x : w0.z, f ? w2.x : w1.x, f ? w3.x : w1.z, on);
      stg4_if(dst + 128, w0.y, f ? w1.y : w0.w, f ? w2.y : w1.y, f ? w3.y : w1.w, on);
      stg4_if(dst + o2 * 128, f ? w0.z : w2.x, f ? w1.z : w2.z, f ? w2.z : w3.x, w3.z, on);
      stg4_if(dst + o2 * 128 + 128, f ? w0.w : w2.y, f ? w1.w : w2.w, f ? w2.w : w3.y, w3.w, on);
      bar_arrive(NB_WO, 160);
    }
  }
}

struct KvRegs { uint32_t k[11], v[8]; uint4 sh; };
__device__ __forceinline__ void kv_load(KvRegs& q, const __nv_bfloat16* kp, const __nv_bfloat16* vp, const __nv_bfloat16* sp, bool halo) {
#pragma unroll
  for (int i = 0; i < 11; i++) q.k[i] = (i >= 3 || halo) ? ldg1(kp + i * kD) : 0u;
#pragma unroll
  for (int i = 0; i < 8; i++) q.v[i] = ldg1(vp + i * kD);
  q.sh = ldg4(sp);
}
__device__ __forceinline__ void kv_unit(const KvRegs& q, uint32_t oa) {
  const uint32_t w0 = prmt(q.sh.x, q.sh.z, 0x5410), w1 = prmt(q.sh.x, q.sh.z, 0x7632), w2 = prmt(q.sh.y, q.sh.w, 0x5410), w3 = prmt(q.sh.y, q.sh.w, 0x7632);
  uint32_t r[8];
#pragma unroll
  for (int i = 0; i < 8; i++) r[i] = hmul2(hfma2(q.k[i + 3], w0, hfma2(q.k[i + 2], w1, hfma2(q.k[i + 1], w2, hmul2(q.k[i], w3)))), q.v[i]);
  sts128(oa, prmt(r[7], r[6], 0x5410), prmt(r[5], r[4], 0x5410), prmt(r[3], r[2], 0x5410), prmt(r[1], r[0], 0x5410));
  sts128(oa + 2048, prmt(r[7], r[6], 0x7632), prmt(r[5], r[4], 0x7632), prmt(r[3], r[2], 0x7632), prmt(r[1], r[0], 0x7632));
}

__device__ __forceinline__ void helper_cta(const Params& p, uint32_t sb, int cb, int warp, int lane) {
  constexpr int NS = 9, ONES = NS * B_SLOT, BF = ONES + 256, BE = BF + 8 * NS;
  if (warp < NS && elect_one()) {
    mbar_init(sb + BF + 8 * warp, 1); mbar_init(sb + BE + 8 * warp, 1);
    fence_async_smem();
    if (warp == 0) { mbar_expect(sb + BF, B_SLOT); tma3d(sb, &p.tmW, 0, 0, 12 + cb * 3, sb + BF); }
  }
  if (warp == 15) { sts32(sb + ONES + lane * 4, 0x3f803f80u); sts32(sb + ONES + 128 + lane * 4, 0x3f803f80u); fence_async_smem(); }
  __syncthreads();
  if (warp == 4) {
    int s = 1, ph = 1;
    uint32_t tp = clock() + HP0;
#pragma unroll 1
    for (int it = 1; it < 20; it++) {
      if (HPD && it >= 10) pace(tp, HPD);
      mbar_wait(sb + BE + 8 * s, ph);
      if (elect_one()) { mbar_expect(sb + BF + 8 * s, B_SLOT); tma3d(sb + s * B_SLOT, &p.tmW, 0, (it < 10 ? it : it - 10) * 64, (it < 10 ? 12 : 0) + cb * 3, sb + BF + 8 * s); }
      if (++s == NS) { s = 0; ph ^= 1; }
    }
  } else if (warp < 4) {
    const uint32_t tag = load_epoch(p, 128 + cb, lane) + 1;
    const uint64_t db = mkdesc(sb + ONES, 128, 128, 0);
    uint2* dst = p.scr->colsum + cb * 192 + warp * 16 + (lane >> 2);
    if ((lane & 3) == 0) {
#pragma unroll 1
      for (int j = 0; j < 12; j++) st_ll2(dst + (j < 6 ? 768 : 0) + ((j % 6) >> 1) * 64 + (j & 1) * 8, 0, 0);
    }
    int s = 0, ph = 0;
#pragma unroll 1
    for (int part = 0; part < 2; part++) {
      float d[12];
#pragma unroll
      for (int i = 0; i < 12; i++) d[i] = 0.f;
#pragma unroll 1
      for (int it = 0; it < 10; it++) {
        mbar_wait(sb + BF + 8 * s, ph);
        const uint64_t da = mkdesc(sb + s * B_SLOT, 8192, 1024, 1);
        WG_FENCE();
#pragma unroll
        for (int j = 0; j < 12; j++) wgmma_colsum(d + 4 * (j % 3), da + (j % 3) * 512 + (j / 3) * 128, db);
        WG_COMMIT();
        WG_WAIT(1);
        mbar_arrive_if(sb + BE + 8 * (s == 0 ? NS - 1 : s - 1), threadIdx.x == 0 && (it | part) != 0);
        if (++s == NS) { s = 0; ph ^= 1; }
      }
      WG_WAIT(0);
      acc_fence<12>(d);
      if ((lane & 3) == 0) {
#pragma unroll
        for (int j = 0; j < 6; j++) st_ll2(dst + (part ? 0 : 768) + (j >> 1) * 64 + (j & 1) * 8, __float_as_uint(d[2 * j]), tag);
      }
      STAMPW(1 + part);
    }
    if (threadIdx.x == 0) *(volatile uint32_t*)&p.scr->epoch[128 + cb] = tag;
  }
}

__global__ void __launch_bounds__(512, 1) fused_kernel(const __grid_constant__ Params p) {
  extern __shared__ __align__(1024) uint8_t smem[];
  const int warp = __shfl_sync(0xffffffff, (int)(threadIdx.x >> 5), 0);
  const int lane = threadIdx.x & 31, tid = threadIdx.x & 127;
  const uint32_t sb = __shfl_sync(0xffffffff, (uint32_t)__cvta_generic_to_shared(smem), 0);
  const uint32_t tstart = clock();
  if (elect_one()) {
    if (warp < 5) asm volatile("prefetch.tensormap [%0];" ::"l"(&p.tmX + warp) : "memory");
    mbar_init(sb + OFF_BAR + 8 * warp, 1); mbar_init(sb + OFF_BAR + 128 + 8 * warp, 1); mbar_init(sb + OFF_BAR + 256 + 8 * warp, 2);
    asm volatile("fence.mbarrier_init.release.cluster;" ::: "memory");
  }
  int b = blockIdx.x;
  if (p.by_smid) asm volatile("mov.u32 %0, %%smid;" : "=r"(b));
  b = __shfl_sync(0xffffffff, b, 0);
  const int tp = b >> 1, t7 = (tp - 32) / 7;
  const int lin = tp < 32 ? ((tp & 7) ? (tp & 7) * 16 : 8) + (tp >> 3) * 2 + (b & 1)
                          : (tp < 60 ? (tp - 31 - t7 * 7) * 16 + 8 + t7 * 2 + (b & 1) : (tp < 62 ? -1 : b - 124));
  const int hcb = b & 3;
  if (lin < 0) { helper_cta(p, sb, hcb, warp, lane); return; }
  const int cb = ((lin >> 4) & 1) * 2 + ((lin >> 1) & 1), rb = (lin >> 5) * 8 + ((lin >> 2) & 3) * 2 + (lin & 1);
  const int chb = (cb >> 1) * 320 + rb * 2 + (cb & 1);
  if (elect_one()) {
    if (warp < NPRE) {
      mbar_expect(sb + BAR_AF + 8 * warp, A_SLOT);
      tma_rows(sb + OFF_A + warp * A_SLOT, &p.tmX, warp * 64, rb, sb + BAR_AF + 8 * warp);
      mbar_expect(sb + BAR_BF + 8 * warp, B_SLOT);
      tma3d(sb + OFF_B + warp * B_SLOT, &p.tmW, 0, warp * 64, 12 + cb * 3, sb + BAR_BF + 8 * warp);
    }
  }
  if (warp == 1) STAMP(31);
  if (sb & 1023) die();
  __syncthreads();

  if (warp >= 12) {
    asm volatile("setmaxnreg.dec.sync.aligned.u32 32;");
    const uint32_t epoch = load_epoch(p, lin, lane);
    if (warp == 12) {
#pragma unroll 1
      for (int i = NPRE; i < NA; i++) {
        if (elect_one()) {
          mbar_expect(sb + BAR_AF + 8 * i, A_SLOT);
          tma_rows(sb + OFF_A + i * A_SLOT, &p.tmX, i * 64, rb, sb + BAR_AF + 8 * i);
          if (i < NB) { mbar_expect(sb + BAR_BF + 8 * i, B_SLOT); tma3d(sb + OFF_B + i * B_SLOT, &p.tmW, 0, i * 64, 12 + cb * 3, sb + BAR_BF + 8 * i); }
        }
      }
      if (elect_one()) { reset_sector(&p.scr->hflag[rb * 64 + cb * 8]); reset_sector(&p.scr->hflag[rb * 64 + 32 + cb * 8]); }
      STAMP(32);
      uint32_t kvt;
      {
        const int tb = rb * 2 + (cb & 1);
        kvt = __shfl_sync(0xffffffff, (ld_relaxed(p.scr->cnt + CNT_KV + (cb >> 1)) & ~63u) + 64, 0);
        {
          uint32_t tp = tstart;
          pace(tp, KV_T0);
          mbar_arrive_if(sb + BAR_KV + 8, lane == 0);
        }
        if (ST_YIELD) mbar_wait2(sb + BAR_XS, 0, sb + BAR_ST, 0);
#pragma unroll 1
        for (int u = 0; u < 5; u++) {
          mbar_wait(sb + BAR_KU + 8 * u, 0);
          fence_async_smem();
          if (elect_one()) {
            asm volatile("cp.async.bulk.tensor.3d.global.shared::cta.bulk_group [%0, {%2, %3, %4}], [%1];\ncp.async.bulk.commit_group;" ::"l"(&p.tmKV),
                         "r"(sb + OFF_CV + CV_SZ + (u < 3 ? u : u - 3) * 4096), "r"((63 - tb) * 16), "r"((cb >> 1) * 160 + u * 32), "r"(0) : "memory");
            if (u == 1 || u == 4) asm volatile("cp.async.bulk.wait_group 0;" ::: "memory");
            if (u == 1) { mbar_arrive(sb + BAR_KU); red_release(p.scr->cnt + CNT_KV + (cb >> 1)); }
          }
          __syncwarp();
          if (u == 1) {
            STAMP(35);
            if (PFT) { const char* q = (const char*)p.ssmk + chb * 4096 + lane * 128; prefetch_l2(q); prefetch_l2(q + 64 * 4096); }
          }
        }
        zero_pads(sb + OFF_CV + CV_SZ, lane);
        if (elect_one()) { mbar_arrive(sb + BAR_KU + 8); red_release(p.scr->cnt + CNT_KV + 2 + (cb >> 1)); }
        STAMP(30);
        if (lane < 24) {
          const char* r = (const char*)p.wout + (rb * 24 + lane) * (kD * 2) + (cb >> 1) * 640 + (cb & 1) * 384;
          prefetch_l2(r); prefetch_l2(r + 128); prefetch_l2(r + 256 - (cb & 1) * 384);
        }
      }
      poll_counter(p.scr->cnt + CNT_KV + 2 + (cb >> 1), kvt);
      if (elect_one()) mbar_arrive(sb + BAR_KV);
      STAMP(34);
      {
        const char* q = (const char*)p.wsp + (rb * 64 + cb * 16 + (lane >> 1)) * (kS * 2) + (lane & 1) * 128;
        uint32_t tp = clock();
#pragma unroll 1
        for (int i = LEAD / 2; i < WSP_N; i++) {
          prefetch_l2(q + i * 256);
          pace(tp, WSP_D);
        }
      }
      int s, ph = 1;
      const uint32_t tag = epoch + 1;
      mbar_wait(sb + BAR_G2, 0);
      if (elect_one()) {
        bulk_s2g(p.scr->h + (size_t)(rb * 12 + cb * 3) * A_SLOT, sb + OFF_A + 5 * A_SLOT, HSPLIT ? A_SLOT : 3 * A_SLOT);
        asm volatile("cp.async.bulk.commit_group;\ncp.async.bulk.wait_group 0;" ::: "memory");
        mbar_arrive(sb + BAR_HR);
        if (!HSPLIT) mbar_arrive(sb + BAR_HR);
        st_release(&p.scr->hflag[rb * 64 + cb * 8], tag);
      }
      __syncwarp();
      STAMP(20);
      s = 8;
      uint32_t seen = 0, t0 = 0;
#pragma unroll 1
      for (int it = 3; it < 12; it++) {
        if (it == 3 || (HSPLIT && !HBOTH && it == 6)) {
          const uint32_t m = HSPLIT && HBOTH ? 0xff : (it == 3 ? 0x0f : 0xf0);
#pragma unroll 1
          while ((seen & m) != m) { seen = __ballot_sync(0xffffffff, ld_relaxed(p.scr->hflag + rb * 64 + (lane & 7) * 8) == tag); spin_guard(t0); }
          acquire_fence();
          STAMP(it == 3 ? 37 : 39);
        }
        if (it == 9) mbar_wait(sb + BAR_HR, 1);
        mbar_wait(sb + BAR_AE + 8 * s, ph);
        if (elect_one()) { mbar_expect(sb + BAR_AF + 8 * s, A_SLOT); bulk_g2s(sb + OFF_A + s * A_SLOT, p.scr->h + (size_t)(rb * 12 + g3_block(cb, it)) * A_SLOT, A_SLOT, sb + BAR_AF + 8 * s); }
        if (++s == NA2) { s = 0; ph ^= 1; }
      }
      STAMP(21);
    } else if (warp == 13) {
      const uint32_t ztarget = __shfl_sync(0xffffffff, ld_relaxed(p.scr->cnt + CNT_Z), 0);
      int s = 0, ph = 0;
#pragma unroll 1
      for (int it = NB; it < 20; it++) {
        mbar_wait(sb + BAR_BE + 8 * s, ph);
        if (elect_one()) { mbar_expect(sb + BAR_BF + 8 * s, B_SLOT); tma3d(sb + OFF_B + s * B_SLOT, &p.tmW, 0, (it < 10 ? it : it - 10) * 64, (it < 10 ? 12 : 0) + cb * 3, sb + BAR_BF + 8 * s); }
        STAMP2(32 + it);
        if (++s == NB) { s = 0; ph ^= 1; }
      }
      mbar_wait(sb + BAR_KU + 16, 0);
#pragma unroll 1
      for (int i = 0; i < LEAD; i++) {
        mbar_wait(sb + BAR_AE + 8 * i, 0);
        if (elect_one()) { mbar_expect(sb + BAR_AF + 8 * i, A_SLOT); tma_rows(sb + OFF_A + i * A_SLOT, &p.tmWsp, i * 64, rb, sb + BAR_AF + 8 * i); }
      }
      mbar_wait(sb + BAR_ZP, 0);
      poll_counter(p.scr->cnt + CNT_Z, (ztarget & ~127u) + 128);
      STAMP(22);
      int sa = LEAD, pa = 0, ia = LEAD;
#pragma unroll 1
      for (int it = 0; it < 32; it++) {
        mbar_wait2(sb + BAR_BE + 8 * s, ph, sb + BAR_AE + 8 * sa, pa);
        if (elect_one()) {
          mbar_expect(sb + BAR_BF + 8 * s, B_SLOT);
          bulk_g2s(sb + OFF_B + s * B_SLOT, p.scr->z2 + (size_t)(cb * 32 + it) * B_SLOT, B_SLOT, sb + BAR_BF + 8 * s);
        }
#pragma unroll 1
        for (int j = (it < RAMP ? 0 : (it == 4 ? 1 + RAMP : 1)); j > 0 && ia < 32; j--, ia++) {
          if (it == 4) mbar_wait(sb + BAR_AE + 8 * sa, pa);
          if (elect_one()) { mbar_expect(sb + BAR_AF + 8 * sa, A_SLOT); tma_rows(sb + OFF_A + sa * A_SLOT, &p.tmWsp, ia * 64, rb, sb + BAR_AF + 8 * sa); }
          if (++sa == NA2) { sa = 0; pa ^= 1; }
        }
        STAMP2(52 + it);
        if (++s == NB) { s = 0; ph ^= 1; }
      }
      mbar_wait(sb + BAR_WO, 0);
      acquire_fence();
#pragma unroll 1
      for (int it = 0; it < 12; it++) {
        if (HSPLIT && it == 3) {
          mbar_wait(sb + BAR_H1, 1);
          if (elect_one()) {
            bulk_s2g(p.scr->h + (size_t)(rb * 12 + cb * 3 + 1) * A_SLOT, sb + OFF_A + 6 * A_SLOT, 2 * A_SLOT);
            asm volatile("cp.async.bulk.commit_group;\ncp.async.bulk.wait_group 0;" ::: "memory");
            mbar_arrive(sb + BAR_HR);
          }
        }
        if (HSPLIT && it == WO_GATE) { if (elect_one()) st_release(&p.scr->hflag[rb * 64 + 32 + cb * 8], epoch + 1); STAMP(24); }
        if (it == WO_LATE) mbar_wait(sb + BAR_AF + 64, 0);
        if (it < 6) mbar_wait(sb + BAR_BE + 8 * ((0x110443 >> (4 * it)) & 7), it < 3 ? 1 : 0);
        else mbar_wait(sb + BAR_BE + 8 * s, ph);
        if (elect_one()) {
          mbar_expect(sb + BAR_BF + 8 * s, 20480);
          bulk_g2s(sb + OFF_B + (s == 5 ? 0 : s + 1) * 20480, p.scr->wo + (size_t)(cb * 12 + g3_block(cb, it)) * 20480, 20480, sb + BAR_BF + 8 * s);
        }
        STAMP2(84 + it);
        if (++s == 6) { s = 0; ph ^= 1; }
      }
    } else if (warp == 14) {
      const uint32_t tag = epoch + 1;
      uint32_t t0 = 0;
      mbar_wait(sb + BAR_AF + 8 * (NA - 1), 0);
#pragma unroll 1
      for (int part = 0; part < 2; part++) {
#pragma unroll 1
        while (true) {
          bool ok = true;
#pragma unroll
          for (int i = 0; i < 3; i++) {
            const uint4 v = ld_ll4(&p.scr->colsum[(part ? 0 : 768) + cb * 192 + i * 64 + lane * 2]);
            ok = ok && v.y == tag && v.w == tag;
            sts64f(sb + OFF_CS + part * 768 + i * 256 + lane * 8, __uint_as_float(v.x), __uint_as_float(v.z));
          }
          if (__all_sync(0xffffffff, ok)) break;
          spin_guard(t0);
        }
        __syncwarp();
        if (lane == 0) mbar_arrive(sb + BAR_ST + 8 * part);
        if (part == 0) STAMP(27);
      }
      STAMP(38);
      bar_sync(NB_Z, 160);
      if (elect_one()) {
        bulk_s2g(p.scr->z2 + (size_t)(cb * 32 + rb) * B_SLOT, sb + OFF_A + LEAD * A_SLOT, B_SLOT);
        asm volatile("cp.async.bulk.commit_group;\ncp.async.bulk.wait_group 0;" ::: "memory");
        red_release(p.scr->cnt + CNT_Z);
        mbar_arrive(sb + BAR_ZP);
      }
      STAMP(28);
      mbar_wait2(sb + BAR_KV, 0, sb + BAR_AE + 72, 0);
      acquire_fence();
      conv_service(p, sb, 0, chb + 64);
      bar_sync(NB_WO, 160);
      bar_sync(NB_CD, 64);
      if (elect_one()) { red_release(p.scr->cnt + CNT_WO + cb); red_relaxed(p.scr->cnt + CNT_Y + (cb >> 1)); }
      STAMP(49);
      poll_counter(p.scr->cnt + CNT_WO + cb, tag * 32);
      if (elect_one()) mbar_arrive(sb + BAR_WO);
      STAMP(46);
      held_service(p, sb, 0, chb + 192, rb, cb, tag, lane);
    } else {
      const uint32_t tag = epoch + 1;
      sts32(sb + OFF_BIAS + lane * 4, ldg1(p.bsp + rb * 64 + row_grp(lane >> 3, (lane >> 2) & 1) * 8 + (lane & 3) * 2));
      if (lane < 2) sts32(sb + OFF_TAG + lane * 4, lane ? 0 : tag);
      uint32_t t0 = 0;
      mbar_wait(sb + BAR_AF + 8 * (NA - 1), 0);
#pragma unroll 1
      while (true) {
        const uint4 u = ld_ll4(&p.scr->xstat[rb * 64 + lane]), v = ld_ll4(&p.scr->xstat[rb * 64 + 32 + lane]);
        sts64f(sb + OFF_XS + lane * 8, __uint_as_float(u.x), __uint_as_float(u.z));
        sts64f(sb + OFF_XS + 256 + lane * 8, __uint_as_float(v.x), __uint_as_float(v.z));
        if (__all_sync(0xffffffff, u.y == tag && u.w == tag && v.y == tag && v.w == tag)) break;
        spin_guard(t0);
      }
      STAMP(26);
      __syncwarp();
      if (lane == 0) mbar_arrive(sb + BAR_XS);
      mbar_wait(sb + BAR_KU + 16, 0);
      poll_counter(p.scr->cnt + CNT_KV + (cb >> 1), tag * 64);
      if (elect_one()) load_convx(p, sb + OFF_CV, sb + BAR_XF + 8, chb);
      mbar_wait(sb + BAR_KU + 8, 1);
      if (elect_one()) load_convx(p, sb + OFF_CV + CV_SZ, sb + BAR_XF, chb + 64);
      STAMP(48);
      mbar_wait2(sb + BAR_KV, 0, sb + BAR_AE + 72, 0);
      acquire_fence();
#pragma unroll 1
      for (int i = 0; i < 2; i++) conv_service(p, sb, 1, chb + i * 128);
      bar_arrive(NB_CD, 64);
      mbar_wait(sb + BAR_WO, 0);
      poll_counter(p.scr->cnt + CNT_Y + (cb >> 1), tag * 64);
      STAMP(47);
      if (elect_one()) mbar_arrive(sb + BAR_YT);
      held_service(p, sb, 1, chb + 256, rb, cb, tag, lane);
      if (lane == 0) *(volatile uint32_t*)&p.scr->epoch[lin] = tag;
      STAMP(23);
    }
  } else {
    if (warp == 7) STAMP(36);
    const int wg = warp >> 2, w = warp & 3, g = lane >> 2, t = lane & 3;
    Taps k;
    uint32_t xw[2][10];
    if (wg == 2) {
      asm volatile("setmaxnreg.inc.sync.aligned.u32 160;");
      const int tb = rb * 2 + (cb & 1), c0 = (cb >> 1) * 320;
      const uint32_t cv = sb + OFF_CV + CV_SZ;
      if (w == 0) zero_pads(sb + OFF_CV, lane);
      mbar_wait(sb + BAR_KV + 8, 0);
      const int t0 = tb * 32 + w * 8;
      const __nv_bfloat16* kp = p.k + (size_t)(t0 - 3) * kD + c0 + lane * 2;
      const __nv_bfloat16* vp = p.v + (size_t)t0 * kD + c0 + lane * 2;
      const __nv_bfloat16* sp = p.shift + (c0 + lane * 2) * 4;
      const uint32_t oa = cv + ((3 - w) & 1) * 1024 + lane * 32 + ((((3 - w) >> 1) ^ (lane >> 2)) & 1) * 16;
#pragma unroll 1
      for (int r = 0; r < 2; r++) {
        KvRegs n0, n1, n2;
        kv_load(n0, kp + r * 128, vp + r * 128, sp + r * 512, t0 > 0);
        kv_load(n1, kp + r * 128 + 64, vp + r * 128 + 64, sp + r * 512 + 256, t0 > 0);
        if (r) kv_load(n2, kp + 256, vp + 256, sp + 1024, t0 > 0);
        kv_unit(n0, oa + r * 8192);
        bar_sync(NB_WGC, 128);
        mbar_arrive_if(sb + BAR_KU + 16 * r, tid == 0);
        if (r) mbar_wait(sb + BAR_KU, 1);
        kv_unit(n1, oa + (r ? 0 : 4096));
        bar_sync(NB_WGC, 128);
        mbar_arrive_if(sb + BAR_KU + 16 * r + 8, tid == 0);
        if (r) {
          kv_unit(n2, oa + 4096);
          bar_sync(NB_WGC, 128);
          mbar_arrive_if(sb + BAR_KU + 32, tid == 0);
        } else {
          mbar_wait(sb + BAR_AF + 8 * ((cb >> 1) * 5 + 1), 0);
          mbar_wait2(sb + BAR_AF + 8 * ((cb >> 1) * 5 + 2), 0, sb + BAR_AF + 8 * ((cb >> 1) * 5 + 4), 0);
          final_load_x(xw, sb + OFF_A, cb, 1, w, lane);
        }
      }
      STAMPW(13);
      load_taps(k, p, chb, tid);
    } else {
      float d[96];
      if (wg == 0) { if (t < 2) st_ll4(&p.scr->zstat[rb * 256 + cb * 64 + w * 16 + g + t * 8], 0, 0, 0, 0); }
      else if ((tid & 7) == 0) st_ll4(&p.scr->xstat[rb * 64 + cb * 16 + (tid >> 3)], 0, 0, 0, 0);
      {
        #pragma unroll
        for (int i = 0; i < 96; i++) d[i] = 0.f;
        {
          if (__builtin_expect(wg == 1, 0)) {
            const int tid = tid_now();
            const uint32_t epoch = load_epoch(p, lin, lane);
            float s = 0.f, q = 0.f;
#pragma unroll 1
            for (int i = 0; i < 10; i++) {
              mbar_wait(sb + BAR_AF + 8 * i, 0);
              const uint4 x4 = lds128(sb + OFF_A + i * A_SLOT + cb * 2048 + tid * 16);
              const uint32_t u[4] = {x4.x, x4.y, x4.z, x4.w};
#pragma unroll
              for (int e = 0; e < 4; e++) { const float a = bf_lo(u[e]), c = bf_hi(u[e]); s += a + c; q = fmaf(a, a, q); q = fmaf(c, c, q); }
            }
#pragma unroll
            for (int o = 1; o <= 4; o <<= 1) { s += __shfl_xor_sync(0xffffffff, s, o); q += __shfl_xor_sync(0xffffffff, q, o); }
            const float m = s * (1.f / kD);
            const float r = rsqrtf(fmaxf(fmaf(-m, m, q * (1.f / kD)), 0.f) + 1e-5f);
            if ((tid & 7) == 0) st_ll4(&p.scr->xstat[rb * 64 + cb * 16 + (tid >> 3)], __float_as_uint(m), epoch + 1, __float_as_uint(r), epoch + 1);
            STAMPW(12);
            bar_sync(NB_G1, 256);
          }
          gemm_loop<192, true, 0, D1>(d, sb, 10, 0, 0, 0, 0, wg, 2, tid_now(), [&]() { if (!G1_LATE && wg == 0) bar_arrive(NB_G1, 256); }, [](int) {});
          asm volatile("setmaxnreg.inc.sync.aligned.u32 160;");
          STAMPW(wg ? 14 : 1);
          mbar_wait2(sb + BAR_XS, 0, sb + BAR_ST + 8 * wg, 0);
        }
        const int t1 = tid_now();
        const uint32_t xa1 = sb + OFF_XS + (w * 16 + ((t1 & 31) >> 2)) * 8;
        const float2 s0 = lds64f(xa1), s1 = lds64f(xa1 + 64);
        uint32_t z[48];
        float st[4];
        gelu_tile(d, z, st, sb + OFF_CS + wg * 768 + (t1 & 3) * 8, s0, s1);
        const int tid = tid_now(), lane = tid & 31, g = lane >> 2, t = lane & 3;
        if (wg == 1) {
          uint32_t bra, brb;
          asm volatile("ld.shared.u16 %0, [%1];" : "=r"(bra) : "r"(sb + OFF_BIAS + (w * 16 + g) * 2));
          asm volatile("ld.shared.u16 %0, [%1+16];" : "=r"(brb) : "r"(sb + OFF_BIAS + (w * 16 + g) * 2));
#pragma unroll
          for (int j = 0; j < 96; j++) d[j] = bf_lo((j & 2) ? brb : bra);
          STAMPW(15);
          gemm_loop<192, true, 1, D2>(d, sb, 32, 0, 1, 20, 0, 2, 2, tid, [&]() { if (HOLD_AT < 32) mbar_arrive_if(sb + BAR_GO, tid == 0); }, [](int) {});
          if (HOLD_AT == 32) mbar_arrive_if(sb + BAR_GO, tid == 0);
          STAMPW(16);
          const int t2 = tid_now(), l2 = t2 & 31;
          const uint32_t ha = sb + OFF_A + 5 * A_SLOT + (l2 >> 4) * 1024 + (2 * w + ((l2 >> 3) & 1)) * 128 + (l2 & 7) * 16;
#pragma unroll
          for (int j = 0; j < 24; j += 2) {
#pragma unroll
            for (int e = 0; e < 4; e++) z[2 * j + e] = hmul2(z[2 * j + e], pack2(d[4 * j + 2 * e], d[4 * j + 2 * e + 1]));
            stsm4(ha + j * 1024, z[2 * j], z[2 * j + 1], z[2 * j + 2], z[2 * j + 3]);
            if (HSPLIT && j == 6) {
              fence_async_smem();
              bar_sync(NB_WGB, 128);
              mbar_arrive_if(sb + BAR_G2, t2 == 0);
            }
          }
          fence_async_smem();
          bar_sync(NB_WGB, 128);
          mbar_arrive_if(sb + BAR_AF + 8 * (t2 == 3 ? ((HSPLIT ? BAR_H1 : BAR_G2) - BAR_AF) / 8 : (t2 == 4 ? (BAR_GO - BAR_AF) / 8 : 5 + t2)), t2 < (HOLD_AT == 33 ? 5 : 4));
          STAMPW(17);
          {
            float e[80];
#pragma unroll
            for (int j = 0; j < 80; j++) e[j] = 0.f;
            gemm_loop<160, false, 2, DB>(e, sb, 12, 5, 0, 2, 0, 2, 2, tid_now(), []() {}, [](int) {});
            STAMPW(10);
            const int t3 = tid_now();
#pragma unroll
            for (int j = 0; j < 10; j++) {
              sts128(sb + OFF_A + j * 2048 + t3 * 16, pack2(e[8 * j], e[8 * j + 1]), pack2(e[8 * j + 2], e[8 * j + 3]), pack2(e[8 * j + 4], e[8 * j + 5]),
                     pack2(e[8 * j + 6], e[8 * j + 7]));
              if (j == 4) bar_arrive(NB_WO, 256);
            }
            bar_arrive(NB_Z, 256);
            STAMPW(45);
          }
          return;
        }
        float sa = st[0], qa = st[1], sbb = st[2], qb = st[3];
#pragma unroll
        for (int o = 1; o <= 2; o <<= 1) {
          sa += __shfl_xor_sync(0xffffffff, sa, o); qa += __shfl_xor_sync(0xffffffff, qa, o);
          sbb += __shfl_xor_sync(0xffffffff, sbb, o); qb += __shfl_xor_sync(0xffffffff, qb, o);
        }
        const uint32_t tag = lds32<0>(sb + OFF_TAG);
        if (t < 2) st_ll4(&p.scr->zstat[rb * 256 + cb * 64 + w * 16 + g + t * 8], __float_as_uint(t ? sbb : sa), tag, __float_as_uint(t ? qb : qa), tag);
        if (G1_LATE) bar_arrive(NB_G1, 256);
        STAMPW(2);
        const float ca = 0.5f * s0.y, cbb = 0.5f * s1.y;
        {
          const uint4* zs = &p.scr->zstat[rb * 256 + t * 64 + w * 16 + g];
          uint4 u0 = ld_ll4(zs), u1 = ld_ll4(zs + 8);
          final_load_x(xw, sb + OFF_A, cb, 0, w, lane);
          fence_async_smem();
          bar_sync(NB_WGA, 128);
          mbar_arrive_if(sb + BAR_AE + 8 * tid, tid < NA);
          uint32_t t0 = 0;
#pragma unroll 1
          while (!__all_sync(0xffffffff, u0.y == tag && u0.w == tag && u1.y == tag && u1.w == tag)) {
            spin_guard(t0);
            u0 = ld_ll4(zs); u1 = ld_ll4(zs + 8);
          }
          sa = __uint_as_float(u0.x); qa = __uint_as_float(u0.z); sbb = __uint_as_float(u1.x); qb = __uint_as_float(u1.z);
          STAMPW(3);
        }
#pragma unroll
        for (int o = 1; o <= 2; o <<= 1) {
          sa += __shfl_xor_sync(0xffffffff, sa, o); qa += __shfl_xor_sync(0xffffffff, qa, o);
          sbb += __shfl_xor_sync(0xffffffff, sbb, o); qb += __shfl_xor_sync(0xffffffff, qb, o);
        }
        const float inv = 1.f / 768.f;
        const float ma = sa * inv, mb = sbb * inv;
        const float ra = ca * rsqrtf(fmaf(fmaxf(fmaf(-ma, ma, qa * inv), 0.f), ca * ca, 1e-5f));
        const float rb_ = cbb * rsqrtf(fmaf(fmaxf(fmaf(-mb, mb, qb * inv), 0.f), cbb * cbb, 1e-5f));
        const uint32_t ra2 = pack2(ra, ra), rb2 = pack2(rb_, rb_);
        const float na = -ma * bf_lo(ra2), nb = -mb * bf_lo(rb2);
        {
          const uint32_t n2a = pack2(na, na), n2b = pack2(nb, nb);
          const uint32_t za = sb + OFF_A + LEAD * A_SLOT + row_grp(w, (lane >> 3) & 1) * 3072 + (lane >> 4) * 128 + (lane & 7) * 16;
          mbar_wait2(sb + BAR_AE + 8 * (LEAD + 2), 0, sb + BAR_KU + 16, 0);
#pragma unroll
          for (int j = 0; j < 24; j += 2)
            stsm4(za + j * 128, hfma2(z[2 * j], ra2, n2a), hfma2(z[2 * j + 1], rb2, n2b), hfma2(z[2 * j + 2], ra2, n2a), hfma2(z[2 * j + 3], rb2, n2b));
          fence_async_smem();
        }
      }
      bar_arrive(NB_Z, 160);
      {
        const uint32_t zero = lds32<0>(sb + OFF_TAG + 4);
#pragma unroll
        for (int i = 0; i < 20; i++) xw[i / 10][i % 10] |= zero;
      }
      load_taps(k, p, chb + 64, tid_now());
      STAMPW(4);
    }
    const int h = wg >> 1;
    {
    const int tid = tid_now(), lane = tid & 31;
    conv_worker(p, k, sb + OFF_CV + (1 - h) * CV_SZ, sb + OFF_A + 9 * A_SLOT + h * 4096, sb + BAR_XF + 8 * h, NB_WGA + h,
                chb + (h ? 0 : 64), 2 + h, sb + BAR_GO, w, lane, tid, h ? 40 : 5, rb, cb);
    {
      const int t3 = tid_now(), l3 = t3 & 31;
      const uint32_t xs_addr = sb + OFF_XS + (w * 16 + (l3 >> 2)) * 8;
      const float2 s0 = lds64f(xs_addr), s1 = lds64f(xs_addr + 64);
      const uint32_t ya = sb + y_tile(h) + ((l3 >> 4) * 8 + (l3 & 7)) * 128 + ((row_grp(w, (l3 >> 3) & 1) ^ (l3 & 7)) << 4);
      uint32_t sw[2][10];
      mbar_wait(sb + BAR_XF + 8 * h, h);
      final_s_early(sw, xw, ya, s0, s1);
      uint32_t ph = 1, t0 = 0, y[8];
#pragma unroll 1
      while (true) {
        mbar_wait(sb + BAR_YL + 16 * h, ph);
        if (bar_all(NB_WGA + h, 128, final_late(y, ya))) break;
        spin_guard(t0);
        ph ^= 1;
        if (t3 == 0) load_late_y(p, sb, h, rb, cb, lds32<0>(sb + OFF_TAG) & 1);
      }
#pragma unroll
      for (int e = 0; e < 8; e++) sw[e & 1][4 + (e >> 1)] = hmul2(sw[e & 1][4 + (e >> 1)], ~y[e]);
      __nv_bfloat16* o0 = p.out + (size_t)(rb * 64 + row_grp(w, 0) * 8 + (l3 >> 2)) * kD + seg_col(cb, h);
      STAMPW(h ? 44 : 9);
      bar_sync(h ? NB_Z : NB_WO, 256);
      float d[40];
#pragma unroll
      for (int j = 0; j < 5; j++) {
        const uint4 v = lds128(sb + OFF_A + (h * 5 + j) * 2048 + t3 * 16);
        d[8 * j] = bf_lo(v.x); d[8 * j + 1] = bf_hi(v.x); d[8 * j + 2] = bf_lo(v.y); d[8 * j + 3] = bf_hi(v.y);
        d[8 * j + 4] = bf_lo(v.z); d[8 * j + 5] = bf_hi(v.z); d[8 * j + 6] = bf_lo(v.w); d[8 * j + 7] = bf_hi(v.w);
      }
      final_out(d, xw, sw, s0.y, s1.y, o0, h, l3 & 3);
    }
    }
  }
}

typedef CUresult (*EncodeFn)(CUtensorMap*, CUtensorMapDataType, cuuint32_t, void*, const cuuint64_t*, const cuuint64_t*, const cuuint32_t*,
                             const cuuint32_t*, CUtensorMapInterleave, CUtensorMapSwizzle, CUtensorMapL2promotion, CUtensorMapFloatOOBfill);

void encode(EncodeFn fn, CUtensorMap* m, const void* ptr, int rank, const cuuint64_t* dims, const cuuint64_t* strides, const cuuint32_t* box,
            CUtensorMapSwizzle swz = CU_TENSOR_MAP_SWIZZLE_128B) {
  const cuuint32_t es[5] = {1, 1, 1, 1, 1};
  fn(m, CU_TENSOR_MAP_DATA_TYPE_BFLOAT16, rank, const_cast<void*>(ptr), dims, strides, box, es, CU_TENSOR_MAP_INTERLEAVE_NONE,
     swz, CU_TENSOR_MAP_L2_PROMOTION_L2_128B, CU_TENSOR_MAP_FLOAT_OOB_FILL_NONE);
}

}

extern "C" void kernel_launch(void* const* d_in, const int* in_sizes, int n_in, void* d_out, int out_size) {
  (void)in_sizes; (void)n_in; (void)out_size;
  static EncodeFn enc = nullptr;
  static Scratch* scr = nullptr;
  static int sms = 0;
  if (!enc) {
    void* fn = nullptr;
    cudaDriverEntryPointQueryResult qr;
    cudaGetDriverEntryPoint("cuTensorMapEncodeTiled", &fn, cudaEnableDefault, &qr);
    enc = (EncodeFn)fn;
    cudaFuncSetAttribute(fused_kernel, cudaFuncAttributeMaxDynamicSharedMemorySize, SMEM_BYTES);
    cudaGetSymbolAddress((void**)&scr, g_scr);
    int dev = 0;
    cudaGetDevice(&dev);
    cudaDeviceGetAttribute(&sms, cudaDevAttrMultiProcessorCount, dev);
  }
  Params p;
  p.scr = scr;
  p.by_smid = sms == 132;
  p.k = (const __nv_bfloat16*)d_in[1];
  p.v = (const __nv_bfloat16*)d_in[2];
  p.shift = (const __nv_bfloat16*)d_in[3];
  p.ssmk = (const __nv_bfloat16*)d_in[4];
  p.ssmD = (const __nv_bfloat16*)d_in[5];
  p.wsp = (const __nv_bfloat16*)d_in[8];
  p.bsp = (const __nv_bfloat16*)d_in[9];
  p.wout = (const __nv_bfloat16*)d_in[10];
  p.out = (__nv_bfloat16*)d_out;
  for (int i = 0; i < 2; i++) {
    const cuuint64_t n = i ? kS : kD, dims[5] = {n, 8, 2, 2, kS / 32}, st[4] = {n * 2, n * 32, n * 16, n * 64};
    const cuuint32_t box[5] = {64, 8, 2, 2, 2};
    encode(enc, i ? &p.tmWsp : &p.tmX, d_in[i ? 8 : 0], 5, dims, st, box);
  }
  {
    const cuuint64_t dims[3] = {64, kD, kF / 64}, st[2] = {kF * 2, 128};
    const cuuint32_t box[3] = {64, 64, 3};
    encode(enc, &p.tmW, d_in[7], 3, dims, st, box);
  }
  {
    const cuuint64_t dims[2] = {kS, 896}, st[1] = {kS * 2};
    const cuuint32_t box[2] = {64, 16};
    encode(enc, &p.tmY, scr->y, 2, dims, st, box);
  }
  {
    const cuuint64_t dims[3] = {1024, kD / 2, 4}, st[2] = {8192, 2048};
    const cuuint32_t box[3] = {16, 32, 4};
    encode(enc, &p.tmKV, scr->kvx, 3, dims, st, box, CU_TENSOR_MAP_SWIZZLE_32B);
  }
  fused_kernel<<<132, 512, SMEM_BYTES, cudaStreamPerThread>>>(p);
}
```

```cpp
#include <cuda_runtime.h>
#include <cuda.h>
#include <cuda_bf16.h>
#include <stdint.h>

template <int N> struct WG;
template <> struct WG<16> {
  static __device__ __forceinline__ void rs(float* d, const uint32_t* a, uint64_t db) {
    asm volatile("{\n.reg .pred p;\nsetp.ne.b32 p, 1, 0;\nwgmma.mma_async.sync.aligned.m64n16k16.f32.bf16.bf16 {"
      "%0, %1, %2, %3, %4, %5, %6, %7"
      "}, {%8, %9, %10, %11}, %12, p, 1, 1, 0;\n}\n"
      :
      "+f"(d[0]), "+f"(d[1]), "+f"(d[2]), "+f"(d[3]), "+f"(d[4]), "+f"(d[5]), "+f"(d[6]), "+f"(d[7])
      : "r"(a[0]), "r"(a[1]), "r"(a[2]), "r"(a[3]), "l"(db));
  }
};
template <> struct WG<32> {
  static __device__ __forceinline__ void rs(float* d, const uint32_t* a, uint64_t db) {
    asm volatile("{\n.reg .pred p;\nsetp.ne.b32 p, 1, 0;\nwgmma.mma_async.sync.aligned.m64n32k16.f32.bf16.bf16 {"
      "%0, %1, %2, %3, %4, %5, %6, %7, %8, %9, %10, %11, %12, %13, %14, %15"
      "}, {%16, %17, %18, %19}, %20, p, 1, 1, 0;\n}\n"
      :
      "+f"(d[0]), "+f"(d[1]), "+f"(d[2]), "+f"(d[3]), "+f"(d[4]), "+f"(d[5]), "+f"(d[6]), "+f"(d[7]),
      "+f"(d[8]), "+f"(d[9]), "+f"(d[10]), "+f"(d[11]), "+f"(d[12]), "+f"(d[13]), "+f"(d[14]), "+f"(d[15])
      : "r"(a[0]), "r"(a[1]), "r"(a[2]), "r"(a[3]), "l"(db));
  }
};
template <> struct WG<48> {
  static __device__ __forceinline__ void rs(float* d, const uint32_t* a, uint64_t db) {
    asm volatile("{\n.reg .pred p;\nsetp.ne.b32 p, 1, 0;\nwgmma.mma_async.sync.aligned.m64n48k16.f32.bf16.bf16 {"
      "%0, %1, %2, %3, %4, %5, %6, %7, %8, %9, %10, %11, %12, %13, %14, %15, "
      "%16, %17, %18, %19, %20, %21, %22, %23"
      "}, {%24, %25, %26, %27}, %28, p, 1, 1, 0;\n}\n"
      :
      "+f"(d[0]), "+f"(d[1]), "+f"(d[2]), "+f"(d[3]), "+f"(d[4]), "+f"(d[5]), "+f"(d[6]), "+f"(d[7]),
      "+f"(d[8]), "+f"(d[9]), "+f"(d[10]), "+f"(d[11]), "+f"(d[12]), "+f"(d[13]), "+f"(d[14]), "+f"(d[15]),
      "+f"(d[16]), "+f"(d[17]), "+f"(d[18]), "+f"(d[19]), "+f"(d[20]), "+f"(d[21]), "+f"(d[22]), "+f"(d[23])
      : "r"(a[0]), "r"(a[1]), "r"(a[2]), "r"(a[3]), "l"(db));
  }
};
template <> struct WG<64> {
  static __device__ __forceinline__ void rs(float* d, const uint32_t* a, uint64_t db) {
    asm volatile("{\n.reg .pred p;\nsetp.ne.b32 p, 1, 0;\nwgmma.mma_async.sync.aligned.m64n64k16.f32.bf16.bf16 {"
      "%0, %1, %2, %3, %4, %5, %6, %7, %8, %9, %10, %11, %12, %13, %14, %15, "
      "%16, %17, %18, %19, %20, %21, %22, %23, %24, %25, %26, %27, %28, %29, %30, %31"
      "}, {%32, %33, %34, %35}, %36, p, 1, 1, 0;\n}\n"
      :
      "+f"(d[0]), "+f"(d[1]), "+f"(d[2]), "+f"(d[3]), "+f"(d[4]), "+f"(d[5]), "+f"(d[6]), "+f"(d[7]),
      "+f"(d[8]), "+f"(d[9]), "+f"(d[10]), "+f"(d[11]), "+f"(d[12]), "+f"(d[13]), "+f"(d[14]), "+f"(d[15]),
      "+f"(d[16]), "+f"(d[17]), "+f"(d[18]), "+f"(d[19]), "+f"(d[20]), "+f"(d[21]), "+f"(d[22]), "+f"(d[23]),
      "+f"(d[24]), "+f"(d[25]), "+f"(d[26]), "+f"(d[27]), "+f"(d[28]), "+f"(d[29]), "+f"(d[30]), "+f"(d[31])
      : "r"(a[0]), "r"(a[1]), "r"(a[2]), "r"(a[3]), "l"(db));
  }
};
template <> struct WG<80> {
  static __device__ __forceinline__ void rs(float* d, const uint32_t* a, uint64_t db) {
    asm volatile("{\n.reg .pred p;\nsetp.ne.b32 p, 1, 0;\nwgmma.mma_async.sync.aligned.m64n80k16.f32.bf16.bf16 {"
      "%0, %1, %2, %3, %4, %5, %6, %7, %8, %9, %10, %11, %12, %13, %14, %15, "
      "%16, %17, %18, %19, %20, %21, %22, %23, %24, %25, %26, %27, %28, %29, %30, %31, "
      "%32, %33, %34, %35, %36, %37, %38, %39"
      "}, {%40, %41, %42, %43}, %44, p, 1, 1, 0;\n}\n"
      :
      "+f"(d[0]), "+f"(d[1]), "+f"(d[2]), "+f"(d[3]), "+f"(d[4]), "+f"(d[5]), "+f"(d[6]), "+f"(d[7]),
      "+f"(d[8]), "+f"(d[9]), "+f"(d[10]), "+f"(d[11]), "+f"(d[12]), "+f"(d[13]), "+f"(d[14]), "+f"(d[15]),
      "+f"(d[16]), "+f"(d[17]), "+f"(d[18]), "+f"(d[19]), "+f"(d[20]), "+f"(d[21]), "+f"(d[22]), "+f"(d[23]),
      "+f"(d[24]), "+f"(d[25]), "+f"(d[26]), "+f"(d[27]), "+f"(d[28]), "+f"(d[29]), "+f"(d[30]), "+f"(d[31]),
      "+f"(d[32]), "+f"(d[33]), "+f"(d[34]), "+f"(d[35]), "+f"(d[36]), "+f"(d[37]), "+f"(d[38]), "+f"(d[39])
      : "r"(a[0]), "r"(a[1]), "r"(a[2]), "r"(a[3]), "l"(db));
  }
};
template <> struct WG<96> {
  static __device__ __forceinline__ void rs(float* d, const uint32_t* a, uint64_t db) {
    asm volatile("{\n.reg .pred p;\nsetp.ne.b32 p, 1, 0;\nwgmma.mma_async.sync.aligned.m64n96k16.f32.bf16.bf16 {"
      "%0, %1, %2, %3, %4, %5, %6, %7, %8, %9, %10, %11, %12, %13, %14, %15, "
      "%16, %17, %18, %19, %20, %21, %22, %23, %24, %25, %26, %27, %28, %29, %30, %31, "
      "%32, %33, %34, %35, %36, %37, %38, %39, %40, %41, %42, %43, %44, %45, %46, %47"
      "}, {%48, %49, %50, %51}, %52, p, 1, 1, 0;\n}\n"
      :
      "+f"(d[0]), "+f"(d[1]), "+f"(d[2]), "+f"(d[3]), "+f"(d[4]), "+f"(d[5]), "+f"(d[6]), "+f"(d[7]),
      "+f"(d[8]), "+f"(d[9]), "+f"(d[10]), "+f"(d[11]), "+f"(d[12]), "+f"(d[13]), "+f"(d[14]), "+f"(d[15]),
      "+f"(d[16]), "+f"(d[17]), "+f"(d[18]), "+f"(d[19]), "+f"(d[20]), "+f"(d[21]), "+f"(d[22]), "+f"(d[23]),
      "+f"(d[24]), "+f"(d[25]), "+f"(d[26]), "+f"(d[27]), "+f"(d[28]), "+f"(d[29]), "+f"(d[30]), "+f"(d[31]),
      "+f"(d[32]), "+f"(d[33]), "+f"(d[34]), "+f"(d[35]), "+f"(d[36]), "+f"(d[37]), "+f"(d[38]), "+f"(d[39]),
      "+f"(d[40]), "+f"(d[41]), "+f"(d[42]), "+f"(d[43]), "+f"(d[44]), "+f"(d[45]), "+f"(d[46]), "+f"(d[47])
      : "r"(a[0]), "r"(a[1]), "r"(a[2]), "r"(a[3]), "l"(db));
  }
};
template <> struct WG<112> {
  static __device__ __forceinline__ void rs(float* d, const uint32_t* a, uint64_t db) {
    asm volatile("{\n.reg .pred p;\nsetp.ne.b32 p, 1, 0;\nwgmma.mma_async.sync.aligned.m64n112k16.f32.bf16.bf16 {"
      "%0, %1, %2, %3, %4, %5, %6, %7, %8, %9, %10, %11, %12, %13, %14, %15, "
      "%16, %17, %18, %19, %20, %21, %22, %23, %24, %25, %26, %27, %28, %29, %30, %31, "
      "%32, %33, %34, %35, %36, %37, %38, %39, %40, %41, %42, %43, %44, %45, %46, %47, "
      "%48, %49, %50, %51, %52, %53, %54, %55"
      "}, {%56, %57, %58, %59}, %60, p, 1, 1, 0;\n}\n"
      :
      "+f"(d[0]), "+f"(d[1]), "+f"(d[2]), "+f"(d[3]), "+f"(d[4]), "+f"(d[5]), "+f"(d[6]), "+f"(d[7]),
      "+f"(d[8]), "+f"(d[9]), "+f"(d[10]), "+f"(d[11]), "+f"(d[12]), "+f"(d[13]), "+f"(d[14]), "+f"(d[15]),
      "+f"(d[16]), "+f"(d[17]), "+f"(d[18]), "+f"(d[19]), "+f"(d[20]), "+f"(d[21]), "+f"(d[22]), "+f"(d[23]),
      "+f"(d[24]), "+f"(d[25]), "+f"(d[26]), "+f"(d[27]), "+f"(d[28]), "+f"(d[29]), "+f"(d[30]), "+f"(d[31]),
      "+f"(d[32]), "+f"(d[33]), "+f"(d[34]), "+f"(d[35]), "+f"(d[36]), "+f"(d[37]), "+f"(d[38]), "+f"(d[39]),
      "+f"(d[40]), "+f"(d[41]), "+f"(d[42]), "+f"(d[43]), "+f"(d[44]), "+f"(d[45]), "+f"(d[46]), "+f"(d[47]),
      "+f"(d[48]), "+f"(d[49]), "+f"(d[50]), "+f"(d[51]), "+f"(d[52]), "+f"(d[53]), "+f"(d[54]), "+f"(d[55])
      : "r"(a[0]), "r"(a[1]), "r"(a[2]), "r"(a[3]), "l"(db));
  }
};
template <> struct WG<128> {
  static __device__ __forceinline__ void rs(float* d, const uint32_t* a, uint64_t db) {
    asm volatile("{\n.reg .pred p;\nsetp.ne.b32 p, 1, 0;\nwgmma.mma_async.sync.aligned.m64n128k16.f32.bf16.bf16 {"
      "%0, %1, %2, %3, %4, %5, %6, %7, %8, %9, %10, %11, %12, %13, %14, %15, "
      "%16, %17, %18, %19, %20, %21, %22, %23, %24, %25, %26, %27, %28, %29, %30, %31, "
      "%32, %33, %34, %35, %36, %37, %38, %39, %40, %41, %42, %43, %44, %45, %46, %47, "
      "%48, %49, %50, %51, %52, %53, %54, %55, %56, %57, %58, %59, %60, %61, %62, %63"
      "}, {%64, %65, %66, %67}, %68, p, 1, 1, 0;\n}\n"
      :
      "+f"(d[0]), "+f"(d[1]), "+f"(d[2]), "+f"(d[3]), "+f"(d[4]), "+f"(d[5]), "+f"(d[6]), "+f"(d[7]),
      "+f"(d[8]), "+f"(d[9]), "+f"(d[10]), "+f"(d[11]), "+f"(d[12]), "+f"(d[13]), "+f"(d[14]), "+f"(d[15]),
      "+f"(d[16]), "+f"(d[17]), "+f"(d[18]), "+f"(d[19]), "+f"(d[20]), "+f"(d[21]), "+f"(d[22]), "+f"(d[23]),
      "+f"(d[24]), "+f"(d[25]), "+f"(d[26]), "+f"(d[27]), "+f"(d[28]), "+f"(d[29]), "+f"(d[30]), "+f"(d[31]),
      "+f"(d[32]), "+f"(d[33]), "+f"(d[34]), "+f"(d[35]), "+f"(d[36]), "+f"(d[37]), "+f"(d[38]), "+f"(d[39]),
      "+f"(d[40]), "+f"(d[41]), "+f"(d[42]), "+f"(d[43]), "+f"(d[44]), "+f"(d[45]), "+f"(d[46]), "+f"(d[47]),
      "+f"(d[48]), "+f"(d[49]), "+f"(d[50]), "+f"(d[51]), "+f"(d[52]), "+f"(d[53]), "+f"(d[54]), "+f"(d[55]),
      "+f"(d[56]), "+f"(d[57]), "+f"(d[58]), "+f"(d[59]), "+f"(d[60]), "+f"(d[61]), "+f"(d[62]), "+f"(d[63])
      : "r"(a[0]), "r"(a[1]), "r"(a[2]), "r"(a[3]), "l"(db));
  }
};
template <> struct WG<160> {
  static __device__ __forceinline__ void ss(float* d, uint64_t da, uint64_t db, int sd) {
    asm volatile("{\n.reg .pred p;\nsetp.ne.b32 p, %82, 0;\nwgmma.mma_async.sync.aligned.m64n160k16.f32.bf16.bf16 {"
      "%0, %1, %2, %3, %4, %5, %6, %7, %8, %9, %10, %11, %12, %13, %14, %15, "
      "%16, %17, %18, %19, %20, %21, %22, %23, %24, %25, %26, %27, %28, %29, %30, %31, "
      "%32, %33, %34, %35, %36, %37, %38, %39, %40, %41, %42, %43, %44, %45, %46, %47, "
      "%48, %49, %50, %51, %52, %53, %54, %55, %56, %57, %58, %59, %60, %61, %62, %63, "
      "%64, %65, %66, %67, %68, %69, %70, %71, %72, %73, %74, %75, %76, %77, %78, %79"
      "}, %80, %81, p, 1, 1, 0, 1;\n}\n"
      :
      "+f"(d[0]), "+f"(d[1]), "+f"(d[2]), "+f"(d[3]), "+f"(d[4]), "+f"(d[5]), "+f"(d[6]), "+f"(d[7]),
      "+f"(d[8]), "+f"(d[9]), "+f"(d[10]), "+f"(d[11]), "+f"(d[12]), "+f"(d[13]), "+f"(d[14]), "+f"(d[15]),
      "+f"(d[16]), "+f"(d[17]), "+f"(d[18]), "+f"(d[19]), "+f"(d[20]), "+f"(d[21]), "+f"(d[22]), "+f"(d[23]),
      "+f"(d[24]), "+f"(d[25]), "+f"(d[26]), "+f"(d[27]), "+f"(d[28]), "+f"(d[29]), "+f"(d[30]), "+f"(d[31]),
      "+f"(d[32]), "+f"(d[33]), "+f"(d[34]), "+f"(d[35]), "+f"(d[36]), "+f"(d[37]), "+f"(d[38]), "+f"(d[39]),
      "+f"(d[40]), "+f"(d[41]), "+f"(d[42]), "+f"(d[43]), "+f"(d[44]), "+f"(d[45]), "+f"(d[46]), "+f"(d[47]),
      "+f"(d[48]), "+f"(d[49]), "+f"(d[50]), "+f"(d[51]), "+f"(d[52]), "+f"(d[53]), "+f"(d[54]), "+f"(d[55]),
      "+f"(d[56]), "+f"(d[57]), "+f"(d[58]), "+f"(d[59]), "+f"(d[60]), "+f"(d[61]), "+f"(d[62]), "+f"(d[63]),
      "+f"(d[64]), "+f"(d[65]), "+f"(d[66]), "+f"(d[67]), "+f"(d[68]), "+f"(d[69]), "+f"(d[70]), "+f"(d[71]),
      "+f"(d[72]), "+f"(d[73]), "+f"(d[74]), "+f"(d[75]), "+f"(d[76]), "+f"(d[77]), "+f"(d[78]), "+f"(d[79])
      : "l"(da), "l"(db), "r"(sd));
  }
};
template <> struct WG<192> {
  static __device__ __forceinline__ void ss(float* d, uint64_t da, uint64_t db, int sd) {
    asm volatile("{\n.reg .pred p;\nsetp.ne.b32 p, %98, 0;\nwgmma.mma_async.sync.aligned.m64n192k16.f32.bf16.bf16 {"
      "%0, %1, %2, %3, %4, %5, %6, %7, %8, %9, %10, %11, %12, %13, %14, %15, "
      "%16, %17, %18, %19, %20, %21, %22, %23, %24, %25, %26, %27, %28, %29, %30, %31, "
      "%32, %33, %34, %35, %36, %37, %38, %39, %40, %41, %42, %43, %44, %45, %46, %47, "
      "%48, %49, %50, %51, %52, %53, %54, %55, %56, %57, %58, %59, %60, %61, %62, %63, "
      "%64, %65, %66, %67, %68, %69, %70, %71, %72, %73, %74, %75, %76, %77, %78, %79, "
      "%80, %81, %82, %83, %84, %85, %86, %87, %88, %89, %90, %91, %92, %93, %94, %95"
      "}, %96, %97, p, 1, 1, 0, 1;\n}\n"
      :
      "+f"(d[0]), "+f"(d[1]), "+f"(d[2]), "+f"(d[3]), "+f"(d[4]), "+f"(d[5]), "+f"(d[6]), "+f"(d[7]),
      "+f"(d[8]), "+f"(d[9]), "+f"(d[10]), "+f"(d[11]), "+f"(d[12]), "+f"(d[13]), "+f"(d[14]), "+f"(d[15]),
      "+f"(d[16]), "+f"(d[17]), "+f"(d[18]), "+f"(d[19]), "+f"(d[20]), "+f"(d[21]), "+f"(d[22]), "+f"(d[23]),
      "+f"(d[24]), "+f"(d[25]), "+f"(d[26]), "+f"(d[27]), "+f"(d[28]), "+f"(d[29]), "+f"(d[30]), "+f"(d[31]),
      "+f"(d[32]), "+f"(d[33]), "+f"(d[34]), "+f"(d[35]), "+f"(d[36]), "+f"(d[37]), "+f"(d[38]), "+f"(d[39]),
      "+f"(d[40]), "+f"(d[41]), "+f"(d[42]), "+f"(d[43]), "+f"(d[44]), "+f"(d[45]), "+f"(d[46]), "+f"(d[47]),
      "+f"(d[48]), "+f"(d[49]), "+f"(d[50]), "+f"(d[51]), "+f"(d[52]), "+f"(d[53]), "+f"(d[54]), "+f"(d[55]),
      "+f"(d[56]), "+f"(d[57]), "+f"(d[58]), "+f"(d[59]), "+f"(d[60]), "+f"(d[61]), "+f"(d[62]), "+f"(d[63]),
      "+f"(d[64]), "+f"(d[65]), "+f"(d[66]), "+f"(d[67]), "+f"(d[68]), "+f"(d[69]), "+f"(d[70]), "+f"(d[71]),
      "+f"(d[72]), "+f"(d[73]), "+f"(d[74]), "+f"(d[75]), "+f"(d[76]), "+f"(d[77]), "+f"(d[78]), "+f"(d[79]),
      "+f"(d[80]), "+f"(d[81]), "+f"(d[82]), "+f"(d[83]), "+f"(d[84]), "+f"(d[85]), "+f"(d[86]), "+f"(d[87]),
      "+f"(d[88]), "+f"(d[89]), "+f"(d[90]), "+f"(d[91]), "+f"(d[92]), "+f"(d[93]), "+f"(d[94]), "+f"(d[95])
      : "l"(da), "l"(db), "r"(sd));
  }
};

#define HGRP 3
#define HPACE 200
#define DB 0
#define STAG -1
#define STAG_N 2
#define WO_LATE -1
#define SE_AT 5
#define H1_AT 6
#define WO_GATE H1_AT
#define HSPLIT 0
#define HOLD_AT 33
#define LL_AT 4
#define KV_T0 2300
#define ST_YIELD 1
#define HP0 3500
#define HPD 450
#define RAMP 1
#define LEAD 2
#define WSP_N 16
#define EARLY 0
#define CPIN 1
#define CW0 0
#define PFT 1
#define WSP_D 600
#define D1 4
#define D2 4
#define D3 0
#define NSLEEP 32
#define G1_LATE 0
#define NPRE 1

namespace {

constexpr int kS = 2048, kD = 640, kF = 1536;
constexpr int NA = 10, NA2 = 9, NB = 5;
constexpr int A_SLOT = 8192, B_SLOT = 24576;
constexpr int OFF_A = 0;
constexpr int OFF_B = OFF_A + NA * A_SLOT;
constexpr int XB_PL = 2112;
constexpr int CV_KE = 4224, CV_KO = CV_KE + 4160;
constexpr int CV_SZ = CV_KO + 4160;
constexpr int OFF_CV = OFF_B + NB * B_SLOT;
constexpr int OFF_CS = OFF_CV + 2 * CV_SZ;
constexpr int OFF_XS = OFF_CS + 1536;
constexpr int OFF_BAR = OFF_XS + 512;
constexpr int BAR_AF = OFF_BAR, BAR_ST = BAR_AF + 8 * NA, BAR_XF = BAR_ST + 16, BAR_KV = BAR_XF + 16;
constexpr int BAR_BF = OFF_BAR + 128, BAR_G2 = BAR_BF + 8 * (NB + 1), BAR_XS = BAR_G2 + 8, BAR_KU = BAR_XS + 8, BAR_ZP = BAR_KU + 40, BAR_HOLD = BAR_ZP + 8, BAR_WO = BAR_HOLD + 8;
constexpr int BAR_AE = OFF_BAR + 256, BAR_BE = BAR_AE + 8 * NA;
constexpr int BAR_YT = BAR_KU + 24;
constexpr int BAR_HR = BAR_AE + 72;
constexpr int BAR_GO = BAR_XS, BAR_H1 = BAR_ST;
constexpr int BAR_YL = BAR_KU + 16;
constexpr int OFF_TAG = OFF_CS - 32;
constexpr int OFF_BIAS = OFF_BAR + 384;
constexpr int SMEM_BYTES = OFF_BIAS + 128;
static_assert(SMEM_BYTES <= 232448, "smem");
constexpr int NB_WGA = 1, NB_WGC = 2, NB_G1 = 3, NB_WO = 4, NB_CD = 5, NB_Z = 6, NB_WGB = 7;

constexpr int CNT_Z = 0, CNT_Y = 1, CNT_KV = 32, CNT_WO = 36;
struct Scratch {
  uint8_t kvx[kD * 4096];
  uint8_t z2[4 * 32 * 24576];
  uint8_t h[32 * 12 * 8192];
  uint8_t wo[4 * 12 * 20480];
  uint8_t y[896 * 4096];
  uint4 xstat[kS];
  uint4 zstat[kS * 4];
  uint2 colsum[kF];
  uint32_t cnt[2 * 32];
  uint32_t hcnt[32 * 32];
  uint32_t epoch[136];
};
__device__ __align__(1024) Scratch g_scr;
#define STAMP(i)
#define STAMP2(i)
#define STAMPW(i)

struct Params {
  Scratch* scr;
  int by_smid;
  const __nv_bfloat16 *k, *v, *shift, *ssmk, *ssmD, *wsp, *bsp, *wout;
  __nv_bfloat16* out;
  CUtensorMap tmX, tmW, tmWsp, tmY, tmKV;
};

__device__ __forceinline__ uint64_t mkdesc(uint32_t addr, uint32_t lbo, uint32_t sbo, uint32_t swz) {
  return (uint64_t)((addr & 0x3FFFF) >> 4) | ((uint64_t)(lbo >> 4) << 16) | ((uint64_t)(sbo >> 4) << 32) | ((uint64_t)swz << 62);
}
#define WG_FENCE() asm volatile("wgmma.fence.sync.aligned;" ::: "memory")
#define WG_COMMIT() asm volatile("wgmma.commit_group.sync.aligned;" ::: "memory")
#define WG_WAIT(n) asm volatile("wgmma.wait_group.sync.aligned %0;" ::"n"(n) : "memory")
template <int N> __device__ __forceinline__ void acc_fence(float* d) {
#pragma unroll
  for (int i = 0; i < N; i++) asm volatile("" : "+f"(d[i])::"memory");
}
__device__ __forceinline__ void mbar_init(uint32_t bar, int cnt) { asm volatile("mbarrier.init.shared::cta.b64 [%0], %1;" ::"r"(bar), "r"(cnt) : "memory"); }
__device__ __forceinline__ void mbar_expect(uint32_t bar, uint32_t bytes) { asm volatile("mbarrier.arrive.expect_tx.shared::cta.b64 _, [%0], %1;" ::"r"(bar), "r"(bytes) : "memory"); }
__device__ __forceinline__ void mbar_arrive(uint32_t bar) { asm volatile("mbarrier.arrive.shared::cta.b64 _, [%0];" ::"r"(bar) : "memory"); }
__device__ __forceinline__ void mbar_arrive_if(uint32_t bar, bool c) {
  asm volatile("{\n.reg .pred p;\nsetp.ne.u32 p, %1, 0;\n@p mbarrier.arrive.shared::cta.b64 _, [%0];\n}\n" ::"r"(bar), "r"((uint32_t)c) : "memory");
}
__device__ __forceinline__ void mbar_expect_if(uint32_t bar, uint32_t bytes, bool c) {
  asm volatile("{\n.reg .pred p;\nsetp.ne.u32 p, %2, 0;\n@p mbarrier.arrive.expect_tx.shared::cta.b64 _, [%0], %1;\n}\n" ::"r"(bar), "r"(bytes), "r"((uint32_t)c) : "memory");
}
__device__ __forceinline__ bool mbar_try(uint32_t bar, uint32_t parity) {
  uint32_t ok;
  asm volatile("{\n.reg .pred p;\nmbarrier.try_wait.parity.shared::cta.b64 p, [%1], %2;\nselp.u32 %0, 1, 0, p;\n}\n" : "=r"(ok) : "r"(bar), "r"(parity) : "memory");
  return ok;
}
__device__ __forceinline__ bool mbar_test(uint32_t bar, uint32_t parity) {
  uint32_t ok;
  asm volatile("{\n.reg .pred p;\nmbarrier.test_wait.parity.shared::cta.b64 p, [%1], %2;\nselp.u32 %0, 1, 0, p;\n}\n" : "=r"(ok) : "r"(bar), "r"(parity) : "memory");
  return ok;
}
__device__ __forceinline__ void die() { asm volatile("st.volatile.global.u32 [%0], %1;" ::"l"(0ull), "r"(0) : "memory"); }
__device__ __forceinline__ void spin_guard(uint32_t& n) { if (++n == (1u << 22)) die(); }
__device__ __forceinline__ void mbar_wait(uint32_t bar, uint32_t parity) {
  uint32_t t0 = 0;
#pragma unroll 1
  while (!mbar_try(bar, parity)) spin_guard(t0);
}
__device__ __forceinline__ void mbar_wait2(uint32_t b0, uint32_t p0, uint32_t b1, uint32_t p1) {
  uint32_t t0 = 0;
#pragma unroll 1
  while (true) {
    const bool r0 = mbar_try(b0, p0), r1 = mbar_try(b1, p1);
    if (r0 && r1) break;
    spin_guard(t0);
  }
}
__device__ __forceinline__ int tid_now() { int v; asm volatile("mov.u32 %0, %%tid.x;" : "=r"(v)); return v & 127; }
__device__ __forceinline__ bool elect_one() {
  uint32_t p;
  asm volatile("{\n.reg .pred P;\nelect.sync _|P, 0xffffffff;\nselp.u32 %0, 1, 0, P;\n}\n" : "=r"(p));
  return p;
}
__device__ __forceinline__ void bar_sync(int id, int n) { asm volatile("bar.sync %0, %1;" ::"r"(id), "r"(n) : "memory"); }
__device__ __forceinline__ void bar_arrive(int id, int n) { asm volatile("bar.arrive %0, %1;" ::"r"(id), "r"(n) : "memory"); }
__device__ __forceinline__ void fence_async_smem() { asm volatile("fence.proxy.async.shared::cta;" ::: "memory"); }
__device__ __forceinline__ void bulk_g2s(uint32_t dst, const void* src, uint32_t bytes, uint32_t bar) {
  asm volatile("cp.async.bulk.shared::cluster.global.mbarrier::complete_tx::bytes [%0], [%1], %2, [%3];" ::"r"(dst), "l"(src), "r"(bytes), "r"(bar) : "memory");
}
__device__ __forceinline__ void bulk_s2g(void* dst, uint32_t src, uint32_t bytes) {
  asm volatile("cp.async.bulk.global.shared::cta.bulk_group [%0], [%1], %2;" ::"l"(dst), "r"(src), "r"(bytes) : "memory");
}
__device__ __forceinline__ void tma2d(uint32_t dst, const CUtensorMap* m, int c0, int c1, uint32_t bar) {
  asm volatile("cp.async.bulk.tensor.2d.shared::cluster.global.mbarrier::complete_tx::bytes [%0], [%1, {%3, %4}], [%2];" ::"r"(dst), "l"(m), "r"(bar), "r"(c0), "r"(c1) : "memory");
}
__device__ __forceinline__ void tma_rows(uint32_t dst, const CUtensorMap* m, int c0, int rb, uint32_t bar) {
  asm volatile("cp.async.bulk.tensor.5d.shared::cluster.global.mbarrier::complete_tx::bytes [%0], [%1, {%3, %4, %4, %4, %5}], [%2];" ::"r"(dst), "l"(m), "r"(bar), "r"(c0), "r"(0), "r"(rb * 2) : "memory");
}
__device__ __forceinline__ int row_grp(int w, int half) { return (w >> 1) * 4 + (w & 1) + 2 * half; }
__device__ __forceinline__ void tma3d(uint32_t dst, const CUtensorMap* m, int c0, int c1, int c2, uint32_t bar) {
  asm volatile("cp.async.bulk.tensor.3d.shared::cluster.global.mbarrier::complete_tx::bytes [%0], [%1, {%3, %4, %5}], [%2];" ::"r"(dst), "l"(m), "r"(bar), "r"(c0), "r"(c1), "r"(c2) : "memory");
}
__device__ __forceinline__ uint4 ld_ll4(const void* p) {
  uint64_t a, b;
  asm volatile("ld.relaxed.gpu.global.v2.u64 {%0,%1}, [%2];" : "=l"(a), "=l"(b) : "l"(p) : "memory");
  return make_uint4((uint32_t)a, (uint32_t)(a >> 32), (uint32_t)b, (uint32_t)(b >> 32));
}
__device__ __forceinline__ void st_ll4(void* p, uint32_t a, uint32_t b, uint32_t c, uint32_t d) {
  asm volatile("st.relaxed.gpu.global.v2.u64 [%0], {%1,%2};" ::"l"(p), "l"(a | ((uint64_t)b << 32)), "l"(c | ((uint64_t)d << 32)) : "memory");
}
__device__ __forceinline__ void st_ll2(void* p, uint32_t a, uint32_t b) { asm volatile("st.relaxed.gpu.global.u64 [%0], %1;" ::"l"(p), "l"(a | ((uint64_t)b << 32)) : "memory"); }
__device__ __forceinline__ void wgmma_colsum(float* d, uint64_t da, uint64_t db) {
  asm volatile("{\n.reg .pred p;\nsetp.ne.b32 p, 1, 0;\nwgmma.mma_async.sync.aligned.m64n8k16.f32.bf16.bf16 {%0, %1, %2, %3}, %4, %5, p, 1, 1, 1, 0;\n}\n"
               : "+f"(d[0]), "+f"(d[1]), "+f"(d[2]), "+f"(d[3]) : "l"(da), "l"(db));
}
__device__ __forceinline__ void prefetch_l2(const void* p) { asm volatile("prefetch.global.L2 [%0];" ::"l"(p)); }
__device__ __forceinline__ void pace(uint32_t& t, uint32_t dt) {
  t += dt;
  while ((int32_t)((uint32_t)clock() - t) < 0) { if (NSLEEP) __nanosleep(NSLEEP); }
}
__device__ __forceinline__ void red_relaxed(uint32_t* p) { asm volatile("red.relaxed.gpu.global.add.u32 [%0], 1;" ::"l"(p) : "memory"); }
__device__ __forceinline__ void red_release(uint32_t* p) { asm volatile("red.release.gpu.global.add.u32 [%0], 1;" ::"l"(p) : "memory"); }
__device__ __forceinline__ uint4 ldg4(const void* p) { uint4 v; asm volatile("ld.global.v4.u32 {%0,%1,%2,%3}, [%4];" : "=r"(v.x), "=r"(v.y), "=r"(v.z), "=r"(v.w) : "l"(p) : "memory"); return v; }
__device__ __forceinline__ uint32_t ldg1(const void* p) { uint32_t v; asm volatile("ld.global.u32 %0, [%1];" : "=r"(v) : "l"(p) : "memory"); return v; }
__device__ __forceinline__ void stg4_if(void* p, uint32_t a, uint32_t b, uint32_t c, uint32_t d, bool on) {
  asm volatile("{\n.reg .pred p;\nsetp.ne.u32 p, %5, 0;\n@p st.global.v4.u32 [%0], {%1,%2,%3,%4};\n}\n" ::"l"(p), "r"(a), "r"(b), "r"(c), "r"(d), "r"((uint32_t)on) : "memory");
}
template <int OFF> __device__ __forceinline__ uint32_t lds32(uint32_t a) { uint32_t v; asm volatile("ld.shared.u32 %0, [%1+%2];" : "=r"(v) : "r"(a), "n"(OFF)); return v; }
__device__ __forceinline__ uint4 lds128(uint32_t a) { uint4 v; asm volatile("ld.shared.v4.u32 {%0,%1,%2,%3}, [%4];" : "=r"(v.x), "=r"(v.y), "=r"(v.z), "=r"(v.w) : "r"(a) : "memory"); return v; }
__device__ __forceinline__ float2 lds64f(uint32_t a) { float2 v; asm volatile("ld.shared.v2.f32 {%0,%1}, [%2];" : "=f"(v.x), "=f"(v.y) : "r"(a) : "memory"); return v; }
__device__ __forceinline__ void sts64f(uint32_t a, float x, float y) { asm volatile("st.shared.v2.f32 [%0], {%1,%2};" ::"r"(a), "f"(x), "f"(y) : "memory"); }
__device__ __forceinline__ void sts32(uint32_t a, uint32_t x) { asm volatile("st.shared.u32 [%0], %1;" ::"r"(a), "r"(x) : "memory"); }
__device__ __forceinline__ void sts128(uint32_t a, uint32_t x, uint32_t y, uint32_t z, uint32_t w) { asm volatile("st.shared.v4.u32 [%0], {%1,%2,%3,%4};" ::"r"(a), "r"(x), "r"(y), "r"(z), "r"(w) : "memory"); }
__device__ __forceinline__ void stsm4(uint32_t a, uint32_t r0, uint32_t r1, uint32_t r2, uint32_t r3) {
  asm volatile("stmatrix.sync.aligned.m8n8.x4.shared.b16 [%0], {%1,%2,%3,%4};" ::"r"(a), "r"(r0), "r"(r1), "r"(r2), "r"(r3) : "memory");
}
__device__ __forceinline__ void stsm4t(uint32_t a, uint32_t r0, uint32_t r1, uint32_t r2, uint32_t r3) {
  asm volatile("stmatrix.sync.aligned.m8n8.x4.trans.shared.b16 [%0], {%1,%2,%3,%4};" ::"r"(a), "r"(r0), "r"(r1), "r"(r2), "r"(r3) : "memory");
}
__device__ __forceinline__ void ldsm4t(uint32_t* r, uint32_t a) {
  asm volatile("ldmatrix.sync.aligned.m8n8.x4.trans.shared.b16 {%0,%1,%2,%3}, [%4];" : "=r"(r[0]), "=r"(r[1]), "=r"(r[2]), "=r"(r[3]) : "r"(a) : "memory");
}
__device__ __forceinline__ uint32_t pack2(float lo, float hi) { uint32_t r; asm("cvt.rn.bf16x2.f32 %0, %1, %2;" : "=r"(r) : "f"(hi), "f"(lo)); return r; }
__device__ __forceinline__ float bf_lo(uint32_t u) { return __uint_as_float(u << 16); }
__device__ __forceinline__ float bf_hi(uint32_t u) { return __uint_as_float(u & 0xffff0000u); }
__device__ __forceinline__ float tanh_fast(float x) { float y; asm("tanh.approx.f32 %0, %1;" : "=f"(y) : "f"(x)); return y; }
__device__ __forceinline__ uint32_t hmul2(uint32_t a, uint32_t b) { uint32_t r; asm("mul.rn.bf16x2 %0, %1, %2;" : "=r"(r) : "r"(a), "r"(b)); return r; }
__device__ __forceinline__ uint32_t hfma2(uint32_t a, uint32_t b, uint32_t c) { uint32_t r; asm("fma.rn.bf16x2 %0, %1, %2, %3;" : "=r"(r) : "r"(a), "r"(b), "r"(c)); return r; }
__device__ __forceinline__ uint32_t prmt(uint32_t a, uint32_t b, uint32_t s) { return __byte_perm(a, b, s); }

__device__ __forceinline__ uint32_t ld_relaxed(const uint32_t* p) { uint32_t v; asm volatile("ld.relaxed.gpu.global.u32 %0, [%1];" : "=r"(v) : "l"(p) : "memory"); return v; }
__device__ __forceinline__ void acquire_fence() { asm volatile("fence.acquire.gpu;\nfence.proxy.async.global;" ::: "memory"); }
__device__ __forceinline__ uint32_t load_epoch(const Params& p, int idx, int lane) { return ld_relaxed(&p.scr->epoch[idx + (((lane * lane) & 3) == 2 ? 1 : 0)]); }
__device__ __forceinline__ void poll_counter(const uint32_t* cnt, uint32_t target) {
  uint32_t t0 = 0;
#pragma unroll 1
  while (!__all_sync(0xffffffff, ld_relaxed(cnt) == target)) spin_guard(t0);
  acquire_fence();
}

__device__ __forceinline__ int g3_block(int cb, int it) { return it < 3 ? cb * 3 + it : (it - 3 < cb * 3 ? it - 3 : it); }

template <int N, bool A_SWZ, int B_MODE, int DEPTH, class Hook, class Mid>
__device__ __forceinline__ void gemm_loop(float* d, uint32_t sb, int nkb, int sa, int pa, int b0, uint32_t boff, int relA, int relB, int tid, Hook hook, Mid mid) {
  constexpr uint32_t A_STEP = A_SWZ ? 2 : 128;
  constexpr uint32_t B_STEP = B_MODE == 0 ? 128 : (B_MODE == 1 ? 384 : 320);
  const uint64_t da0 = A_SWZ ? mkdesc(sb + OFF_A, 16, 1024, 1) : mkdesc(sb + OFF_A, 1024, 128, 0);
  const uint64_t db0 = B_MODE == 0 ? mkdesc(sb + OFF_B + boff, 8192, 1024, 1) : mkdesc(sb + OFF_B + boff, B_MODE == 1 ? 3072 : 2560, 128, 0);
  constexpr int MODA = B_MODE == 0 ? NA : NA2;
  constexpr int MODB = B_MODE == 2 ? 6 : NB;
  int sbk = b0 % MODB, pb = (b0 / MODB) & 1;
  auto boffs = [](int s_) { return B_MODE == 2 ? (s_ == 5 ? 0 : s_ + 1) * (20480 >> 4) : s_ * (B_SLOT >> 4); };
  uint32_t rel = 0;
  uint64_t da = da0 + sa * (A_SLOT >> 4), db = db0 + boffs(sbk);
  const bool doR = tid < 2 ? tid < relA : tid - 2 < relB;
  mbar_wait2(sb + BAR_AF + 8 * sa, pa, sb + BAR_BF + 8 * sbk, pb);
  if constexpr (DEPTH == 0) {
    acc_fence<N / 2>(d);
#pragma unroll 1
    for (int it = 0; it < nkb; it++) {
      WG_FENCE();
#pragma unroll
      for (int j = 0; j < 4; j++) WG<N>::ss(d, da + j * A_STEP, db + j * B_STEP, 1);
      WG_COMMIT();
      const uint32_t prel = rel;
      rel = sb + BAR_AE + 8 * (tid < 2 ? sa : sbk + NA);
      if (++sa == MODA) { sa = 0; pa ^= 1; }
      if (++sbk == MODB) { sbk = 0; pb ^= 1; }
      da = da0 + sa * (A_SLOT >> 4); db = db0 + boffs(sbk);
      const bool r0 = mbar_test(sb + BAR_AF + 8 * sa, pa), r1 = mbar_test(sb + BAR_BF + 8 * sbk, pb);
      WG_WAIT(1);
      mbar_arrive_if(prel, doR && prel != 0);
      if (it == 2) {
        WG_WAIT(0);
        mbar_expect_if(sb + BAR_AF + 8 * (tid == 8 ? 8 : tid), A_SLOT, tid < 9);
        mbar_arrive_if(rel, doR);
        rel = 0;
      }
      mid(it);
      if (it + 1 < nkb && !(r0 && r1)) {
        mbar_wait2(sb + BAR_AF + 8 * sa, pa, sb + BAR_BF + 8 * sbk, pb);
      }
    }
  } else
#pragma unroll 1
  for (int it = 0; it < nkb; it++) {
    WG_FENCE();
    WG<N>::ss(d, da, db, 1);
    const uint32_t prel = rel;
    rel = sb + BAR_AE + 8 * (tid < 2 ? sa : sbk + NA);
    if (++sa == MODA) { sa = 0; pa ^= 1; }
    if (++sbk == MODB) { sbk = 0; pb ^= 1; }
    if (DEPTH == 1) { WG_COMMIT(); WG_WAIT(1); }
    WG<N>::ss(d, da + A_STEP, db + B_STEP, 1);
    WG_COMMIT();
    WG_WAIT(1);
    if (EARLY == 1) mbar_arrive_if(prel, doR && it != 0);
    WG<N>::ss(d, da + 2 * A_STEP, db + 2 * B_STEP, 1);
    if (DEPTH == 1) WG_COMMIT();
    if (EARLY != 1) mbar_arrive_if(prel, doR && it != 0);
    const bool r0 = mbar_test(sb + BAR_AF + 8 * sa, pa), r1 = mbar_test(sb + BAR_BF + 8 * sbk, pb);
    const uint64_t da3 = da + 3 * A_STEP, db3 = db + 3 * B_STEP;
    da = da0 + sa * (A_SLOT >> 4); db = db0 + boffs(sbk);
    if (DEPTH == 1) WG_WAIT(1);
    WG<N>::ss(d, da3, db3, 1);
    WG_COMMIT();
    mid(it);
    if (it + 1 < nkb) {
      if (!(r0 && r1)) {
        mbar_wait2(sb + BAR_AF + 8 * sa, pa, sb + BAR_BF + 8 * sbk, pb);
      }
    }
    if (DEPTH == 2) WG_WAIT(1);
  }
  hook();
  WG_WAIT(0);
  acc_fence<N / 2>(d);
  mbar_arrive_if(rel, doR);
}

__device__ __forceinline__ void gelu_tile(const float* d, uint32_t* z, float* st, uint32_t cs_addr, float2 s0, float2 s1) {
  const float kA = 0.7978845608028654f, kB = 0.7978845608028654f * 0.044715f;
  const float c1a = kA * s0.y, c3a = kB * s0.y * s0.y * s0.y, ma = -s0.x;
  const float c1b = kA * s1.y, c3b = kB * s1.y * s1.y * s1.y, mb = -s1.x;
  float acc[8];
#pragma unroll
  for (int i = 0; i < 8; i++) acc[i] = 0.f;
#pragma unroll
  for (int j = 0; j < 24; j++) {
    const float2 cs = lds64f(cs_addr + j * 32);
    float r[4];
#pragma unroll
    for (int e = 0; e < 4; e++) {
      const float c = (e & 1) ? cs.y : cs.x;
      const float v = fmaf(e < 2 ? ma : mb, c, d[4 * j + e]);
      const float a = v * fmaf(v * v, e < 2 ? c3a : c3b, e < 2 ? c1a : c1b);
      r[e] = fmaf(v, tanh_fast(a), v);
      acc[e] += r[e];
      acc[4 + e] = fmaf(r[e], r[e], acc[4 + e]);
    }
    z[2 * j] = pack2(r[0], r[1]);
    z[2 * j + 1] = pack2(r[2], r[3]);
  }
  st[0] = acc[0] + acc[1]; st[1] = acc[4] + acc[5]; st[2] = acc[2] + acc[3]; st[3] = acc[6] + acc[7];
}

template <int Q> __device__ __forceinline__ void conv_load(uint32_t* a, uint32_t ab) {
  a[0] = lds32<512 * Q>(ab);       a[1] = lds32<512 * Q + 256>(ab);  a[2] = lds32<512 * Q + 16>(ab);   a[3] = lds32<512 * Q + 272>(ab);
  a[4] = lds32<512 * Q + 32>(ab);  a[5] = lds32<512 * Q + 288>(ab);  a[6] = lds32<512 * Q + 48>(ab);   a[7] = lds32<512 * Q + 304>(ab);
  a[8] = lds32<512 * Q + 64>(ab);  a[9] = lds32<512 * Q + 320>(ab);  a[10] = lds32<512 * Q + 80>(ab);  a[11] = lds32<512 * Q + 336>(ab);
  a[12] = lds32<512 * Q + 96>(ab); a[13] = lds32<512 * Q + 352>(ab); a[14] = lds32<512 * Q + 112>(ab); a[15] = lds32<512 * Q + 368>(ab);
}
template <int Q, int L> __device__ __forceinline__ void conv_step(float* d, uint32_t (*a)[16], uint32_t ab, uint64_t db) {
  WG_FENCE();
#pragma unroll
  for (int s = 0; s < 4; s++) WG<128 - 16 * Q>::rs(d, a[Q] + 4 * s, db + s + 16 * Q);
  WG_COMMIT();
  if (CPIN) WG_WAIT(1);
  if (L >= 0) conv_load<(L >= 0 ? L : 0)>(a[L >= 0 ? L : 0], ab);
  if (CW0 || Q == 0) WG_WAIT(0);
}

__device__ __forceinline__ int seg_col(int cb, int h) { return (cb >> 1) * 320 + (cb & 1) * 32 + h * 64; }
__device__ __forceinline__ void final_load_x(uint32_t (*xw)[10], uint32_t xt, int cb, int h, int w, int lane) {
  const int g = lane >> 2, t = lane & 3, cc = seg_col(cb, h) >> 3;
  const int c0 = cc + t, c1 = c0 + 24, c2 = cc + 16 - 6 * h + (t >> 1);
  const uint32_t r0 = xt + (w * 16 + g) * 128;
#pragma unroll
  for (int r = 0; r < 2; r++) {
    const uint4 u = lds128(r0 + r * 1024 + (c0 >> 3) * A_SLOT + (((c0 ^ g) & 7) << 4)), v = lds128(r0 + r * 1024 + (c1 >> 3) * A_SLOT + (((c1 ^ g) & 7) << 4));
    const float2 z = lds64f(r0 + r * 1024 + (c2 >> 3) * A_SLOT + (((c2 ^ g) & 7) << 4) + (t & 1) * 8);
    xw[r][0] = u.x; xw[r][1] = u.y; xw[r][2] = u.z; xw[r][3] = u.w;
    xw[r][4] = v.x; xw[r][5] = v.y; xw[r][6] = v.z; xw[r][7] = v.w;
    xw[r][8] = __float_as_uint(z.x); xw[r][9] = __float_as_uint(z.y);
  }
}
__device__ __forceinline__ void final_s_early(uint32_t (*sw)[10], const uint32_t (*xw)[10], uint32_t ya, float2 s0, float2 s1) {
  const uint32_t r2[2] = {pack2(s0.y, s0.y), pack2(s1.y, s1.y)};
  const float na = -s0.x * bf_lo(r2[0]), nb = -s1.x * bf_lo(r2[1]);
  const uint32_t n2[2] = {pack2(na, na), pack2(nb, nb)};
#pragma unroll
  for (int j = 0; j < 10; j += 2) {
    uint32_t y[4];
    if (j < 4 || j == 8) ldsm4t(y, ya + (j < 4 ? j : 4) * 1024);
#pragma unroll
    for (int e = 0; e < 4; e++) {
      const uint32_t xn = hfma2(xw[e & 1][j + (e >> 1)], r2[e & 1], n2[e & 1]);
      sw[e & 1][j + (e >> 1)] = (j < 4 || j == 8) ? hmul2(xn, y[e]) : xn;
    }
  }
}
__device__ __forceinline__ bool final_late(uint32_t* y, uint32_t ya) {
  ldsm4t(y, ya + 6144);
  ldsm4t(y + 4, ya + 8192);
  uint32_t zero = 0;
#pragma unroll
  for (int e = 0; e < 8; e++) zero |= (y[e] - 0x00010001u) & ~y[e];
  return (zero & 0x80008000u) == 0;
}
__device__ __forceinline__ bool bar_all(int id, int n, bool c) {
  uint32_t r;
  asm volatile("{\n.reg .pred p, q;\nsetp.ne.u32 p, %3, 0;\nbar.red.and.pred q, %1, %2, p;\nselp.u32 %0, 1, 0, q;\n}\n" : "=r"(r) : "r"(id), "r"(n), "r"((uint32_t)c) : "memory");
  return r;
}
__device__ __forceinline__ void final_out(const float* d, const uint32_t (*xw)[10], const uint32_t (*sw)[10], float ra, float rb, __nv_bfloat16* o0, int h, int t) {
  const float ca = 0.25f * ra, cb = 0.25f * rb;
  uint32_t o[2][10];
#pragma unroll
  for (int j = 0; j < 10; j++) {
#pragma unroll
    for (int r = 0; r < 2; r++) {
      const float h0 = d[4 * j + 2 * r] * (r ? cb : ca), h1 = d[4 * j + 2 * r + 1] * (r ? cb : ca);
      o[r][j] = hfma2(pack2(fmaf(h0, tanh_fast(h0), h0), fmaf(h1, tanh_fast(h1), h1)), sw[r][j], xw[r][j]);
      __nv_bfloat16* q = o0 + r * 16 * kD;
      if (j == 3) stg4_if(q + t * 8, o[r][0], o[r][1], o[r][2], o[r][3], true);
      if (j == 7) stg4_if(q + 192 + t * 8, o[r][4], o[r][5], o[r][6], o[r][7], true);
      if (j == 9) asm volatile("st.global.v2.u32 [%0], {%1,%2};" ::"l"(q + 128 - 48 * h + t * 4), "r"(o[r][8]), "r"(o[r][9]) : "memory");
    }
  }
}

struct Taps { uint4 r0, r1; uint32_t n0, n1, dd; };
__device__ __forceinline__ void load_taps(Taps& k, const Params& p, int ch, int tid) {
  const uint4* kp = (const uint4*)(p.ssmk + (size_t)ch * kS);
  k.r0 = ldg4(kp + tid); k.r1 = ldg4(kp + 128 + tid);
  k.n0 = ldg1(kp + tid + 1); k.n1 = tid < 127 ? ldg1(kp + 129 + tid) : 0u;
  k.dd = __bfloat16_as_ushort(p.ssmD[ch]);
}
__device__ __forceinline__ void load_convx(const Params& p, uint32_t cv, uint32_t bar, int ch) {
  mbar_expect(bar, 4096);
  bulk_g2s(cv, p.scr->kvx + (size_t)ch * 4096, 2048, bar);
  bulk_g2s(cv + XB_PL, p.scr->kvx + (size_t)ch * 4096 + 2048, 2048, bar);
}
#define CW 3
#define CSTAMP(j)
__device__ __forceinline__ void zero_pads(uint32_t cv, int lane) {
  if (lane < 8) sts128(cv + (lane >> 2) * XB_PL + 2048 + (lane & 3) * 16, 0, 0, 0, 0);
  else if (lane < 12) sts128(cv + ((lane & 2) ? CV_KO : CV_KE) + (lane & 1) * 16, 0, 0, 0, 0);
  fence_async_smem();
  __syncwarp();
}
__device__ __forceinline__ int y_row(int c, uint32_t par) {
  const int hf = c >= 320, cc = c - hf * 320, u = cc >> 6, cb = hf * 2 + ((cc >> 5) & 1);
  if (u == 2) return cb * 96 + ((cc >> 4) & 1) * 48 + 32 + (cc & 1) + ((cc >> 1) & 1) * 8 + ((cc >> 2) & 3) * 2;
  return (u < 2 ? cb * 96 + u * 48 : 384 + par * 256 + cb * 64 + (u - 3) * 32) + (cc & 1) + ((cc >> 1) & 3) * 8 + ((cc >> 3) & 3) * 2;
}
__device__ __forceinline__ void y_store(const Params& p, uint32_t sb, int h, int ch, uint32_t par) {
  uint8_t* dst = p.scr->y + (size_t)y_row(ch, par) * 4096;
  if (elect_one()) {
    bulk_s2g(dst, sb + OFF_A + 9 * A_SLOT + h * 4096, 4096);
    asm volatile("cp.async.bulk.commit_group;\ncp.async.bulk.wait_group 0;" ::: "memory");
  }
  __syncwarp();
}
__device__ __forceinline__ void conv_service(const Params& p, uint32_t sb, int h, int ch) {
  bar_sync(NB_WGA + 8 + h, 160);
  if (elect_one()) load_convx(p, sb + OFF_CV + (1 - h) * CV_SZ, sb + BAR_XF + 8 * h, ch + 128);
  bar_sync(NB_WGA + 8 + h, 160);
  y_store(p, sb, h, ch, 0);
}
__device__ __forceinline__ uint32_t y_tile(int h) { return OFF_CV + (1 - h) * 13312; }
__device__ __forceinline__ void load_late_y(const Params& p, uint32_t sb, int h, int rb, int cb, uint32_t par) {
  mbar_expect(sb + BAR_YL + 16 * h, 4096);
  tma2d(sb + y_tile(h) + 6144, &p.tmY, rb * 64, 384 + par * 256 + cb * 64 + h * 32, sb + BAR_YL + 16 * h);
  tma2d(sb + y_tile(h) + 8192, &p.tmY, rb * 64, 400 + par * 256 + cb * 64 + h * 32, sb + BAR_YL + 16 * h);
}
__device__ __forceinline__ void held_service(const Params& p, uint32_t sb, int h, int ch, int rb, int cb, uint32_t tag, int lane) {
#pragma unroll 1
  for (int i = 0; i < 8; i++) sts128(sb + OFF_A + 9 * A_SLOT + h * 4096 + i * 512 + lane * 16, 0, 0, 0, 0);
  fence_async_smem();
  __syncwarp();
  y_store(p, sb, h, ch, ~tag & 1);
  mbar_wait(sb + BAR_YT, 1);
  acquire_fence();
  bar_sync(NB_WGA + 8 + h, 160);
  bar_sync(NB_WGA + 8 + h, 160);
  uint8_t* dst = p.scr->y + (size_t)y_row(ch, tag & 1) * 4096;
  if (elect_one()) {
    bulk_s2g(dst, sb + OFF_A + 9 * A_SLOT + h * 4096, 4096);
    asm volatile("cp.async.bulk.commit_group;" ::: "memory");
    mbar_expect(sb + BAR_XF + 8 * h, 6144);
#pragma unroll 1
    for (int i = 0; i < 3; i++) tma2d(sb + y_tile(h) + i * 2048, &p.tmY, rb * 64, cb * 96 + h * 48 + i * 16, sb + BAR_XF + 8 * h);
  }
  mbar_wait(sb + BAR_AE + 8 * (LL_AT - 1), 1);
  if (elect_one()) { load_late_y(p, sb, h, rb, cb, tag & 1); asm volatile("cp.async.bulk.wait_group 0;" ::: "memory"); }
}
__device__ __forceinline__ void conv_worker(const Params& p, Taps& k, uint32_t cv, uint32_t yb0,
                                            uint32_t xbar, int nbar, int ch0, int n, uint32_t holdbar, int w, int lane,
                                            int tid, int st0, int rb, int cb) {
  const int g = lane >> 2, t = lane & 3, w0 = w & 1, w1 = w >> 1;
  const uint32_t ab = cv + ((g & 1) ? CV_KE : CV_KO) + 32 + 2 * (64 * w0 + 8 * w1 + ((g - 15) & ~1) + 2 * t);
  const uint32_t scA = cv + (w1 ? CV_KO : CV_KE) + 32, scB = scA + 2048;
  const int dl = (t >> 1) ^ 1;
  if (n == 2) mbar_wait(xbar, 0);
  STAMPW(st0 + 3);
#pragma unroll 1
  for (int i = 0; i < n; i++) {
    if (tid == 0) {
      k.r0.x = (k.r0.x & 0xffff0000u) | (pack2(bf_lo(k.r0.x) + bf_lo(k.dd), 0.f) & 0xffffu);
      sts32(cv + CV_KO + 28, k.r0.x << 16);
    }
    sts128(cv + CV_KE + 32 + tid * 16, k.r0.x, k.r0.y, k.r0.z, k.r0.w);
    sts128(cv + CV_KO + 32 + tid * 16, prmt(k.r0.x, k.r0.y, 0x5432), prmt(k.r0.y, k.r0.z, 0x5432), prmt(k.r0.z, k.r0.w, 0x5432), prmt(k.r0.w, k.n0, 0x5432));
    sts128(cv + CV_KE + 2080 + tid * 16, k.r1.x, k.r1.y, k.r1.z, k.r1.w);
    sts128(cv + CV_KO + 2080 + tid * 16, prmt(k.r1.x, k.r1.y, 0x5432), prmt(k.r1.y, k.r1.z, 0x5432), prmt(k.r1.z, k.r1.w, 0x5432), prmt(k.r1.w, k.n1, 0x5432));
    if (i + 1 < n) load_taps(k, p, ch0 + (i + 1) * 128, tid);
    bar_sync(nbar, 128);
    CSTAMP(0);
    const uint64_t db = mkdesc(cv + (i & 0x1000), XB_PL, 128, 0);
    float d[64];
    uint32_t a[8][16];
    conv_load<7>(a[7], ab); conv_load<6>(a[6], ab); conv_load<5>(a[5], ab); conv_load<4>(a[4], ab);
#pragma unroll
    for (int j = 0; j < 64; j++) d[j] = 0.f;
    mbar_wait(xbar, i & 1);
    if (i + 1 == n) {
      if (STAG >= 0 && n == STAG_N) bar_sync(NB_G1, 256);
      else mbar_wait(holdbar, 1);
    }
    CSTAMP(1);
    const bool lead = i + 1 == n && n != STAG_N;
    conv_step<7, -1>(d, a, ab, db); conv_step<6, -1>(d, a, ab, db); conv_step<5, -1>(d, a, ab, db); conv_step<4, 3>(d, a, ab, db);
    if (STAG == 4 && lead) bar_arrive(NB_G1, 256);
    conv_step<3, 2>(d, a, ab, db);
    if (STAG == 3 && lead) bar_arrive(NB_G1, 256);
    conv_step<2, 1>(d, a, ab, db);
    if (STAG == 2 && lead) bar_arrive(NB_G1, 256);
    conv_step<1, 0>(d, a, ab, db);
    if (STAG == 1 && lead) bar_arrive(NB_G1, 256);
    conv_step<0, -1>(d, a, ab, db);
    if (STAG == 0 && lead) bar_arrive(NB_G1, 256);
    acc_fence<64>(d);
    CSTAMP(2);
    bar_sync(nbar + 8, 160);
    float E[16][2];
#pragma unroll
    for (int j = 0; j < 15; j++) { E[j][0] = d[4 * j] + d[4 * j + 6]; E[j][1] = d[4 * j + 1] + d[4 * j + 7]; }
    E[15][0] = d[60]; E[15][1] = d[61];
    if (w0 == 0) {
#pragma unroll
      for (int j = 8; j < 16; j++) sts64f(scA + (j - 8) * 256 + lane * 8, E[j][0], E[j][1]);
    } else {
      const uint32_t a = scB - dl * 256 + (lane ^ 2) * 8;
#pragma unroll
      for (int j = 1; j < 8; j++) sts64f(a + j * 256, E[j][0], E[j][1]);
      sts64f(scB + (dl ? 7 * 256 : 0) + (lane ^ 2) * 8, dl ? E[8][0] : E[0][0], dl ? E[8][1] : E[0][1]);
    }
    bar_sync(nbar, 128);
    CSTAMP(3);
    uint32_t pk[8];
    if (w0 == 0) {
#pragma unroll
      for (int j = 0; j < 8; j++) { const float2 v = lds64f(scB + j * 256 + lane * 8); pk[j] = pack2(E[j][0] + v.x, E[j][1] + v.y); }
    } else {
      const uint32_t a0 = scA - dl * 256 + (lane ^ 2) * 8;
#pragma unroll
      for (int j = 9; j < 16; j++) { const float2 v = lds64f(a0 + (j - 8) * 256); pk[j - 8] = pack2(E[j][0] + v.x, E[j][1] + v.y); }
      const float2 v = lds64f(scA + (dl ? 7 * 256 : 0) + (lane ^ 2) * 8);
      pk[0] = pack2((dl ? 0.f : E[8][0]) + v.x, (dl ? 0.f : E[8][1]) + v.y);
    }
    CSTAMP(4);
    if (i + 1 == n) {
#pragma unroll
      for (int j = 0; j < 8; j++) pk[j] = ~pk[j];
    }
    const uint32_t yb = yb0 + 32 * ((w0 ? 35 : 95) - lane) + 16 * w1;
    stsm4t((w0 && lane < 4) ? yb - 1024 : yb + 1024, pk[0], pk[1], pk[2], pk[3]);
    stsm4t(yb, pk[4], pk[5], pk[6], pk[7]);
    fence_async_smem();
    bar_sync(nbar + 8, 160);
    CSTAMP(5);
    STAMPW(st0 + i);
    if (n == 2 && i == 0) {
      const int u = (tid >> 3) % 5, kg = rb * 3 + (tid < 120 ? (tid >> 3) / 5 : 0), c = u < 4 ? (u >> 1) * 10 + (u & 1) * 4 : 8, o2 = u < 4 ? 2 : 10;
      const uint4* wp = (const uint4*)p.wout + (uint32_t)((kg * 8 + (tid & 7)) * (kD / 8) + (seg_col(cb, 0) >> 3) + (u < 4 ? (u >> 1) * 8 + (u & 1) * 24 : 16));
      const uint4 w0 = ldg4(wp), w1 = ldg4(wp + 1), w2 = ldg4(wp + 2), w3 = ldg4(wp + 3);
      uint8_t* dst = p.scr->wo + (uint32_t)(cb * (12 * 20480) + kg * 2560 + c * 128 + (tid & 7) * 16);
      const bool f = u < 4, on = tid < 120;
      stg4_if(dst, w0.x, f ? w1.x : w0.z, f ? w2.x : w1.x, f ? w3.x : w1.z, on);
      stg4_if(dst + 128, w0.y, f ? w1.y : w0.w, f ? w2.y : w1.y, f ? w3.y : w1.w, on);
      stg4_if(dst + o2 * 128, f ? w0.z : w2.x, f ? w1.z : w2.z, f ? w2.z : w3.x, w3.z, on);
      stg4_if(dst + o2 * 128 + 128, f ? w0.w : w2.y, f ? w1.w : w2.w, f ? w2.w : w3.y, w3.w, on);
      bar_arrive(NB_WO, 160);
    }
  }
}

struct KvRegs { uint32_t k[11], v[8]; uint4 sh; };
__device__ __forceinline__ void kv_load(KvRegs& q, const __nv_bfloat16* kp, const __nv_bfloat16* vp, const __nv_bfloat16* sp, bool halo) {
#pragma unroll
  for (int i = 0; i < 11; i++) q.k[i] = (i >= 3 || halo) ? ldg1(kp + i * kD) : 0u;
#pragma unroll
  for (int i = 0; i < 8; i++) q.v[i] = ldg1(vp + i * kD);
  q.sh = ldg4(sp);
}
__device__ __forceinline__ void kv_unit(const KvRegs& q, uint32_t oa) {
  const uint32_t w0 = prmt(q.sh.x, q.sh.z, 0x5410), w1 = prmt(q.sh.x, q.sh.z, 0x7632), w2 = prmt(q.sh.y, q.sh.w, 0x5410), w3 = prmt(q.sh.y, q.sh.w, 0x7632);
  uint32_t r[8];
#pragma unroll
  for (int i = 0; i < 8; i++) r[i] = hmul2(hfma2(q.k[i + 3], w0, hfma2(q.k[i + 2], w1, hfma2(q.k[i + 1], w2, hmul2(q.k[i], w3)))), q.v[i]);
  sts128(oa, prmt(r[7], r[6], 0x5410), prmt(r[5], r[4], 0x5410), prmt(r[3], r[2], 0x5410), prmt(r[1], r[0], 0x5410));
  sts128(oa + 2048, prmt(r[7], r[6], 0x7632), prmt(r[5], r[4], 0x7632), prmt(r[3], r[2], 0x7632), prmt(r[1], r[0], 0x7632));
}

__device__ __forceinline__ void helper_cta(const Params& p, uint32_t sb, int cb, int warp, int lane) {
  constexpr int NS = 9, ONES = NS * B_SLOT, BF = ONES + 256, BE = BF + 8 * NS;
  if (warp < NS && elect_one()) {
    mbar_init(sb + BF + 8 * warp, 1); mbar_init(sb + BE + 8 * warp, 1);
    fence_async_smem();
    if (warp == 0) { mbar_expect(sb + BF, B_SLOT); tma3d(sb, &p.tmW, 0, 0, 12 + cb * 3, sb + BF); }
  }
  if (warp == 15) { sts32(sb + ONES + lane * 4, 0x3f803f80u); sts32(sb + ONES + 128 + lane * 4, 0x3f803f80u); fence_async_smem(); }
  __syncthreads();
  if (warp == 4) {
    int s = 1, ph = 1;
    uint32_t tp = clock() + HP0;
#pragma unroll 1
    for (int it = 1; it < 20; it++) {
      if (HPD && it >= 10) pace(tp, HPD);
      mbar_wait(sb + BE + 8 * s, ph);
      if (elect_one()) { mbar_expect(sb + BF + 8 * s, B_SLOT); tma3d(sb + s * B_SLOT, &p.tmW, 0, (it < 10 ? it : it - 10) * 64, (it < 10 ? 12 : 0) + cb * 3, sb + BF + 8 * s); }
      if (++s == NS) { s = 0; ph ^= 1; }
    }
  } else if (warp < 4) {
    const uint32_t tag = load_epoch(p, 128 + cb, lane) + 1;
    const uint64_t db = mkdesc(sb + ONES, 128, 128, 0);
    uint2* dst = p.scr->colsum + cb * 192 + warp * 16 + (lane >> 2);
    if ((lane & 3) == 0) {
#pragma unroll 1
      for (int j = 0; j < 12; j++) st_ll2(dst + (j < 6 ? 768 : 0) + ((j % 6) >> 1) * 64 + (j & 1) * 8, 0, 0);
    }
    int s = 0, ph = 0;
#pragma unroll 1
    for (int part = 0; part < 2; part++) {
      float d[12];
#pragma unroll
      for (int i = 0; i < 12; i++) d[i] = 0.f;
#pragma unroll 1
      for (int it = 0; it < 10; it++) {
        mbar_wait(sb + BF + 8 * s, ph);
        const uint64_t da = mkdesc(sb + s * B_SLOT, 8192, 1024, 1);
        WG_FENCE();
#pragma unroll
        for (int j = 0; j < 12; j++) wgmma_colsum(d + 4 * (j % 3), da + (j % 3) * 512 + (j / 3) * 128, db);
        WG_COMMIT();
        WG_WAIT(1);
        mbar_arrive_if(sb + BE + 8 * (s == 0 ? NS - 1 : s - 1), threadIdx.x == 0 && (it | part) != 0);
        if (++s == NS) { s = 0; ph ^= 1; }
      }
      WG_WAIT(0);
      acc_fence<12>(d);
      if ((lane & 3) == 0) {
#pragma unroll
        for (int j = 0; j < 6; j++) st_ll2(dst + (part ? 0 : 768) + (j >> 1) * 64 + (j & 1) * 8, __float_as_uint(d[2 * j]), tag);
      }
      STAMPW(1 + part);
    }
    if (threadIdx.x == 0) *(volatile uint32_t*)&p.scr->epoch[128 + cb] = tag;
  }
}

__global__ void __launch_bounds__(512, 1) fused_kernel(const __grid_constant__ Params p) {
  extern __shared__ __align__(1024) uint8_t smem[];
  const int warp = __shfl_sync(0xffffffff, (int)(threadIdx.x >> 5), 0);
  const int lane = threadIdx.x & 31, tid = threadIdx.x & 127;
  const uint32_t sb = __shfl_sync(0xffffffff, (uint32_t)__cvta_generic_to_shared(smem), 0);
  const uint32_t tstart = clock();
  if (elect_one()) {
    if (warp < 5) asm volatile("prefetch.tensormap [%0];" ::"l"(&p.tmX + warp) : "memory");
    mbar_init(sb + OFF_BAR + 8 * warp, 1); mbar_init(sb + OFF_BAR + 128 + 8 * warp, 1); mbar_init(sb + OFF_BAR + 256 + 8 * warp, 2);
    asm volatile("fence.mbarrier_init.release.cluster;" ::: "memory");
  }
  int b = blockIdx.x;
  if (p.by_smid) asm volatile("mov.u32 %0, %%smid;" : "=r"(b));
  b = __shfl_sync(0xffffffff, b, 0);
  const int tp = b >> 1, t7 = (tp - 32) / 7;
  const int lin = tp < 32 ? ((tp & 7) ? (tp & 7) * 16 : 8) + (tp >> 3) * 2 + (b & 1)
                          : (tp < 60 ? (tp - 31 - t7 * 7) * 16 + 8 + t7 * 2 + (b & 1) : (tp < 62 ? -1 : b - 124));
  const int hcb = b & 3;
  if (lin < 0) { helper_cta(p, sb, hcb, warp, lane); return; }
  const int cb = ((lin >> 4) & 1) * 2 + ((lin >> 1) & 1), rb = (lin >> 5) * 8 + ((lin >> 2) & 3) * 2 + (lin & 1);
  const int chb = (cb >> 1) * 320 + rb * 2 + (cb & 1);
  if (elect_one()) {
    if (warp < NPRE) {
      mbar_expect(sb + BAR_AF + 8 * warp, A_SLOT);
      tma_rows(sb + OFF_A + warp * A_SLOT, &p.tmX, warp * 64, rb, sb + BAR_AF + 8 * warp);
      mbar_expect(sb + BAR_BF + 8 * warp, B_SLOT);
      tma3d(sb + OFF_B + warp * B_SLOT, &p.tmW, 0, warp * 64, 12 + cb * 3, sb + BAR_BF + 8 * warp);
    }
  }
  if (warp == 1) STAMP(31);
  if (sb & 1023) die();
  __syncthreads();

  if (warp >= 12) {
    asm volatile("setmaxnreg.dec.sync.aligned.u32 32;");
    const uint32_t epoch = load_epoch(p, lin, lane);
    if (warp == 12) {
#pragma unroll 1
      for (int i = NPRE; i < NA; i++) {
        if (elect_one()) {
          mbar_expect(sb + BAR_AF + 8 * i, A_SLOT);
          tma_rows(sb + OFF_A + i * A_SLOT, &p.tmX, i * 64, rb, sb + BAR_AF + 8 * i);
          if (i < NB) { mbar_expect(sb + BAR_BF + 8 * i, B_SLOT); tma3d(sb + OFF_B + i * B_SLOT, &p.tmW, 0, i * 64, 12 + cb * 3, sb + BAR_BF + 8 * i); }
        }
      }
      STAMP(32);
      uint32_t kvt;
      {
        const int tb = rb * 2 + (cb & 1);
        kvt = __shfl_sync(0xffffffff, (ld_relaxed(p.scr->cnt + CNT_KV + (cb >> 1)) & ~63u) + 64, 0);
        {
          uint32_t tp = tstart;
          pace(tp, KV_T0);
          mbar_arrive_if(sb + BAR_KV + 8, lane == 0);
        }
        if (ST_YIELD) mbar_wait2(sb + BAR_XS, 0, sb + BAR_ST, 0);
#pragma unroll 1
        for (int u = 0; u < 5; u++) {
          mbar_wait(sb + BAR_KU + 8 * u, 0);
          fence_async_smem();
          if (elect_one()) {
            asm volatile("cp.async.bulk.tensor.3d.global.shared::cta.bulk_group [%0, {%2, %3, %4}], [%1];\ncp.async.bulk.commit_group;" ::"l"(&p.tmKV),
                         "r"(sb + OFF_CV + CV_SZ + (u < 3 ? u : u - 3) * 4096), "r"((63 - tb) * 16), "r"((cb >> 1) * 160 + u * 32), "r"(0) : "memory");
            if (u == 1 || u == 4) asm volatile("cp.async.bulk.wait_group 0;" ::: "memory");
            if (u == 1) { mbar_arrive(sb + BAR_KU); red_release(p.scr->cnt + CNT_KV + (cb >> 1)); }
          }
          __syncwarp();
          if (u == 1) {
            STAMP(35);
            if (PFT) { const char* q = (const char*)p.ssmk + chb * 4096 + lane * 128; prefetch_l2(q); prefetch_l2(q + 64 * 4096); }
          }
        }
        zero_pads(sb + OFF_CV + CV_SZ, lane);
        if (elect_one()) { mbar_arrive(sb + BAR_KU + 8); red_release(p.scr->cnt + CNT_KV + 2 + (cb >> 1)); }
        STAMP(30);
        if (lane < 24) {
          const char* r = (const char*)p.wout + (rb * 24 + lane) * (kD * 2) + (cb >> 1) * 640 + (cb & 1) * 384;
          prefetch_l2(r); prefetch_l2(r + 128); prefetch_l2(r + 256 - (cb & 1) * 384);
        }
      }
      poll_counter(p.scr->cnt + CNT_KV + 2 + (cb >> 1), kvt);
      if (elect_one()) mbar_arrive(sb + BAR_KV);
      STAMP(34);
      {
        const char* q = (const char*)p.wsp + (rb * 64 + cb * 16 + (lane >> 1)) * (kS * 2) + (lane & 1) * 128;
        uint32_t tp = clock();
#pragma unroll 1
        for (int i = LEAD / 2; i < WSP_N; i++) {
          prefetch_l2(q + i * 256);
          pace(tp, WSP_D);
        }
      }
      const uint32_t tag = epoch + 1;
      mbar_wait(sb + BAR_G2, 0);
      if (elect_one()) {
        bulk_s2g(p.scr->h + (size_t)(rb * 12 + cb * 3) * A_SLOT, sb + OFF_A + 5 * A_SLOT, HSPLIT ? A_SLOT : 3 * A_SLOT);
        asm volatile("cp.async.bulk.commit_group;\ncp.async.bulk.wait_group 0;" ::: "memory");
        mbar_arrive(sb + BAR_HR);
        if (!HSPLIT) mbar_arrive(sb + BAR_HR);
        red_release(&p.scr->hcnt[(rb >> HGRP) * 32]);
      }
      __syncwarp();
      STAMP(20);
      mbar_wait2(sb + BAR_HR, 1, sb + BAR_AE + 56, 0);
      STAMP(39);
      poll_counter(&p.scr->hcnt[(rb >> HGRP) * 32], tag * ((HSPLIT ? 8 : 4) << HGRP));
      STAMP(37);
      if (elect_one()) {
        uint32_t tp = clock();
#pragma unroll 1
        for (int it = 3; it < 12; it++) {
          if (HPACE && it > 3) { tp += HPACE; while ((int32_t)((uint32_t)clock() - tp) < 0) {} }
          bulk_g2s(sb + OFF_A + ((it + 5) % 9) * A_SLOT, p.scr->h + (size_t)(rb * 12 + g3_block(cb, it)) * A_SLOT, A_SLOT, sb + BAR_AF + 8 * ((it + 5) % 9));
        }
      }
      STAMP(21);
    } else if (warp == 13) {
      const uint32_t ztarget = __shfl_sync(0xffffffff, ld_relaxed(p.scr->cnt + CNT_Z), 0);
      int s = 0, ph = 0;
#pragma unroll 1
      for (int it = NB; it < 20; it++) {
        mbar_wait(sb + BAR_BE + 8 * s, ph);
        if (elect_one()) { mbar_expect(sb + BAR_BF + 8 * s, B_SLOT); tma3d(sb + OFF_B + s * B_SLOT, &p.tmW, 0, (it < 10 ? it : it - 10) * 64, (it < 10 ? 12 : 0) + cb * 3, sb + BAR_BF + 8 * s); }
        STAMP2(32 + it);
        if (++s == NB) { s = 0; ph ^= 1; }
      }
      mbar_wait(sb + BAR_KU + 16, 0);
#pragma unroll 1
      for (int i = 0; i < LEAD; i++) {
        mbar_wait(sb + BAR_AE + 8 * i, 0);
        if (elect_one()) { mbar_expect(sb + BAR_AF + 8 * i, A_SLOT); tma_rows(sb + OFF_A + i * A_SLOT, &p.tmWsp, i * 64, rb, sb + BAR_AF + 8 * i); }
      }
      mbar_wait(sb + BAR_ZP, 0);
      poll_counter(p.scr->cnt + CNT_Z, (ztarget & ~127u) + 128);
      STAMP(22);
      int sa = LEAD, pa = 0, ia = LEAD;
#pragma unroll 1
      for (int it = 0; it < 32; it++) {
        mbar_wait2(sb + BAR_BE + 8 * s, ph, sb + BAR_AE + 8 * sa, pa);
        if (elect_one()) {
          mbar_expect(sb + BAR_BF + 8 * s, B_SLOT);
          bulk_g2s(sb + OFF_B + s * B_SLOT, p.scr->z2 + (size_t)(cb * 32 + it) * B_SLOT, B_SLOT, sb + BAR_BF + 8 * s);
        }
#pragma unroll 1
        for (int j = (it < RAMP ? 0 : (it == 4 ? 1 + RAMP : 1)); j > 0 && ia < 32; j--, ia++) {
          if (it == 4) mbar_wait(sb + BAR_AE + 8 * sa, pa);
          if (elect_one()) { mbar_expect(sb + BAR_AF + 8 * sa, A_SLOT); tma_rows(sb + OFF_A + sa * A_SLOT, &p.tmWsp, ia * 64, rb, sb + BAR_AF + 8 * sa); }
          if (++sa == NA2) { sa = 0; pa ^= 1; }
        }
        STAMP2(52 + it);
        if (++s == NB) { s = 0; ph ^= 1; }
      }
      mbar_wait(sb + BAR_WO, 0);
      acquire_fence();
#pragma unroll 1
      for (int it = 0; it < 12; it++) {
        if (HSPLIT && it == H1_AT) {
          mbar_wait(sb + BAR_H1, 1);
          if (elect_one()) {
            bulk_s2g(p.scr->h + (size_t)(rb * 12 + cb * 3 + 1) * A_SLOT, sb + OFF_A + 6 * A_SLOT, 2 * A_SLOT);
            asm volatile("cp.async.bulk.commit_group;\ncp.async.bulk.wait_group 0;" ::: "memory");
            mbar_arrive(sb + BAR_HR);
          }
        }
        if (HSPLIT && it == WO_GATE) { if (elect_one()) red_release(&p.scr->hcnt[(rb >> HGRP) * 32]); STAMP(24); }
        if (it == WO_LATE) mbar_wait(sb + BAR_AF + 64, 0);
        if (it < 6) mbar_wait(sb + BAR_BE + 8 * ((0x110443 >> (4 * it)) & 7), it < 3 ? 1 : 0);
        else mbar_wait(sb + BAR_BE + 8 * s, ph);
        if (elect_one()) {
          mbar_expect(sb + BAR_BF + 8 * s, 20480);
          bulk_g2s(sb + OFF_B + (s == 5 ? 0 : s + 1) * 20480, p.scr->wo + (size_t)(cb * 12 + g3_block(cb, it)) * 20480, 20480, sb + BAR_BF + 8 * s);
        }
        STAMP2(84 + it);
        if (++s == 6) { s = 0; ph ^= 1; }
      }
    } else if (warp == 14) {
      const uint32_t tag = epoch + 1;
      uint32_t t0 = 0;
      mbar_wait(sb + BAR_AF + 8 * (NA - 1), 0);
#pragma unroll 1
      for (int part = 0; part < 2; part++) {
#pragma unroll 1
        while (true) {
          bool ok = true;
#pragma unroll
          for (int i = 0; i < 3; i++) {
            const uint4 v = ld_ll4(&p.scr->colsum[(part ? 0 : 768) + cb * 192 + i * 64 + lane * 2]);
            ok = ok && v.y == tag && v.w == tag;
            sts64f(sb + OFF_CS + part * 768 + i * 256 + lane * 8, __uint_as_float(v.x), __uint_as_float(v.z));
          }
          if (__all_sync(0xffffffff, ok)) break;
          spin_guard(t0);
        }
        __syncwarp();
        if (lane == 0) mbar_arrive(sb + BAR_ST + 8 * part);
        if (part == 0) STAMP(27);
      }
      STAMP(38);
      bar_sync(NB_Z, 160);
      if (elect_one()) {
        bulk_s2g(p.scr->z2 + (size_t)(cb * 32 + rb) * B_SLOT, sb + OFF_A + LEAD * A_SLOT, B_SLOT);
        asm volatile("cp.async.bulk.commit_group;\ncp.async.bulk.wait_group 0;" ::: "memory");
        red_release(p.scr->cnt + CNT_Z);
        mbar_arrive(sb + BAR_ZP);
      }
      STAMP(28);
      mbar_wait2(sb + BAR_KV, 0, sb + BAR_AE + 72, 0);
      acquire_fence();
      conv_service(p, sb, 0, chb + 64);
      bar_sync(NB_WO, 160);
      bar_sync(NB_CD, 64);
      if (elect_one()) { red_release(p.scr->cnt + CNT_WO + cb); red_relaxed(p.scr->cnt + CNT_Y + (cb >> 1)); }
      STAMP(49);
      poll_counter(p.scr->cnt + CNT_WO + cb, tag * 32);
      if (elect_one()) mbar_arrive(sb + BAR_WO);
      STAMP(46);
      held_service(p, sb, 0, chb + 192, rb, cb, tag, lane);
    } else {
      const uint32_t tag = epoch + 1;
      sts32(sb + OFF_BIAS + lane * 4, ldg1(p.bsp + rb * 64 + row_grp(lane >> 3, (lane >> 2) & 1) * 8 + (lane & 3) * 2));
      if (lane < 2) sts32(sb + OFF_TAG + lane * 4, lane ? 0 : tag);
      uint32_t t0 = 0;
      mbar_wait(sb + BAR_AF + 8 * (NA - 1), 0);
#pragma unroll 1
      while (true) {
        const uint4 u = ld_ll4(&p.scr->xstat[rb * 64 + lane]), v = ld_ll4(&p.scr->xstat[rb * 64 + 32 + lane]);
        sts64f(sb + OFF_XS + lane * 8, __uint_as_float(u.x), __uint_as_float(u.z));
        sts64f(sb + OFF_XS + 256 + lane * 8, __uint_as_float(v.x), __uint_as_float(v.z));
        if (__all_sync(0xffffffff, u.y == tag && u.w == tag && v.y == tag && v.w == tag)) break;
        spin_guard(t0);
      }
      STAMP(26);
      __syncwarp();
      if (lane == 0) mbar_arrive(sb + BAR_XS);
      mbar_wait(sb + BAR_KU + 16, 0);
      poll_counter(p.scr->cnt + CNT_KV + (cb >> 1), tag * 64);
      if (elect_one()) load_convx(p, sb + OFF_CV, sb + BAR_XF + 8, chb);
      mbar_wait(sb + BAR_KU + 8, 1);
      if (elect_one()) load_convx(p, sb + OFF_CV + CV_SZ, sb + BAR_XF, chb + 64);
      STAMP(48);
      mbar_wait2(sb + BAR_KV, 0, sb + BAR_AE + 72, 0);
      acquire_fence();
#pragma unroll 1
      for (int i = 0; i < 2; i++) conv_service(p, sb, 1, chb + i * 128);
      bar_arrive(NB_CD, 64);
      mbar_wait(sb + BAR_WO, 0);
      poll_counter(p.scr->cnt + CNT_Y + (cb >> 1), tag * 64);
      STAMP(47);
      if (elect_one()) mbar_arrive(sb + BAR_YT);
      held_service(p, sb, 1, chb + 256, rb, cb, tag, lane);
      if (lane == 0) *(volatile uint32_t*)&p.scr->epoch[lin] = tag;
      STAMP(23);
    }
  } else {
    if (warp == 7) STAMP(36);
    const int wg = warp >> 2, w = warp & 3, g = lane >> 2, t = lane & 3;
    Taps k;
    uint32_t xw[2][10];
    if (wg == 2) {
      asm volatile("setmaxnreg.inc.sync.aligned.u32 160;");
      const int tb = rb * 2 + (cb & 1), c0 = (cb >> 1) * 320;
      const uint32_t cv = sb + OFF_CV + CV_SZ;
      if (w == 0) zero_pads(sb + OFF_CV, lane);
      mbar_wait(sb + BAR_KV + 8, 0);
      const int t0 = tb * 32 + w * 8;
      const __nv_bfloat16* kp = p.k + (size_t)(t0 - 3) * kD + c0 + lane * 2;
      const __nv_bfloat16* vp = p.v + (size_t)t0 * kD + c0 + lane * 2;
      const __nv_bfloat16* sp = p.shift + (c0 + lane * 2) * 4;
      const uint32_t oa = cv + ((3 - w) & 1) * 1024 + lane * 32 + ((((3 - w) >> 1) ^ (lane >> 2)) & 1) * 16;
#pragma unroll 1
      for (int r = 0; r < 2; r++) {
        KvRegs n0, n1, n2;
        kv_load(n0, kp + r * 128, vp + r * 128, sp + r * 512, t0 > 0);
        kv_load(n1, kp + r * 128 + 64, vp + r * 128 + 64, sp + r * 512 + 256, t0 > 0);
        if (r) kv_load(n2, kp + 256, vp + 256, sp + 1024, t0 > 0);
        kv_unit(n0, oa + r * 8192);
        bar_sync(NB_WGC, 128);
        mbar_arrive_if(sb + BAR_KU + 16 * r, tid == 0);
        if (r) mbar_wait(sb + BAR_KU, 1);
        kv_unit(n1, oa + (r ? 0 : 4096));
        bar_sync(NB_WGC, 128);
        mbar_arrive_if(sb + BAR_KU + 16 * r + 8, tid == 0);
        if (r) {
          kv_unit(n2, oa + 4096);
          bar_sync(NB_WGC, 128);
          mbar_arrive_if(sb + BAR_KU + 32, tid == 0);
        } else {
          mbar_wait(sb + BAR_AF + 8 * ((cb >> 1) * 5 + 1), 0);
          mbar_wait2(sb + BAR_AF + 8 * ((cb >> 1) * 5 + 2), 0, sb + BAR_AF + 8 * ((cb >> 1) * 5 + 4), 0);
          final_load_x(xw, sb + OFF_A, cb, 1, w, lane);
        }
      }
      STAMPW(13);
      load_taps(k, p, chb, tid);
    } else {
      float d[96];
      if (wg == 0) { if (t < 2) st_ll4(&p.scr->zstat[rb * 256 + cb * 64 + w * 16 + g + t * 8], 0, 0, 0, 0); }
      else if ((tid & 7) == 0) st_ll4(&p.scr->xstat[rb * 64 + cb * 16 + (tid >> 3)], 0, 0, 0, 0);
      {
        #pragma unroll
        for (int i = 0; i < 96; i++) d[i] = 0.f;
        {
          if (__builtin_expect(wg == 1, 0)) {
            const int tid = tid_now();
            const uint32_t epoch = load_epoch(p, lin, lane);
            float s = 0.f, q = 0.f;
#pragma unroll 1
            for (int i = 0; i < 10; i++) {
              mbar_wait(sb + BAR_AF + 8 * i, 0);
              const uint4 x4 = lds128(sb + OFF_A + i * A_SLOT + cb * 2048 + tid * 16);
              const uint32_t u[4] = {x4.x, x4.y, x4.z, x4.w};
#pragma unroll
              for (int e = 0; e < 4; e++) { const float a = bf_lo(u[e]), c = bf_hi(u[e]); s += a + c; q = fmaf(a, a, q); q = fmaf(c, c, q); }
            }
#pragma unroll
            for (int o = 1; o <= 4; o <<= 1) { s += __shfl_xor_sync(0xffffffff, s, o); q += __shfl_xor_sync(0xffffffff, q, o); }
            const float m = s * (1.f / kD);
            const float r = rsqrtf(fmaxf(fmaf(-m, m, q * (1.f / kD)), 0.f) + 1e-5f);
            if ((tid & 7) == 0) st_ll4(&p.scr->xstat[rb * 64 + cb * 16 + (tid >> 3)], __float_as_uint(m), epoch + 1, __float_as_uint(r), epoch + 1);
            STAMPW(12);
            bar_sync(NB_G1, 256);
          }
          gemm_loop<192, true, 0, D1>(d, sb, 10, 0, 0, 0, 0, wg, 2, tid_now(), [&]() { if (!G1_LATE && wg == 0) bar_arrive(NB_G1, 256); }, [](int) {});
          asm volatile("setmaxnreg.inc.sync.aligned.u32 160;");
          STAMPW(wg ? 14 : 1);
          mbar_wait2(sb + BAR_XS, 0, sb + BAR_ST + 8 * wg, 0);
        }
        const int t1 = tid_now();
        const uint32_t xa1 = sb + OFF_XS + (w * 16 + ((t1 & 31) >> 2)) * 8;
        const float2 s0 = lds64f(xa1), s1 = lds64f(xa1 + 64);
        uint32_t z[48];
        float st[4];
        gelu_tile(d, z, st, sb + OFF_CS + wg * 768 + (t1 & 3) * 8, s0, s1);
        const int tid = tid_now(), lane = tid & 31, g = lane >> 2, t = lane & 3;
        if (wg == 1) {
          uint32_t bra, brb;
          asm volatile("ld.shared.u16 %0, [%1];" : "=r"(bra) : "r"(sb + OFF_BIAS + (w * 16 + g) * 2));
          asm volatile("ld.shared.u16 %0, [%1+16];" : "=r"(brb) : "r"(sb + OFF_BIAS + (w * 16 + g) * 2));
#pragma unroll
          for (int j = 0; j < 96; j++) d[j] = bf_lo((j & 2) ? brb : bra);
          STAMPW(15);
          gemm_loop<192, true, 1, D2>(d, sb, 32, 0, 1, 20, 0, 2, 2, tid, [&]() { if (HOLD_AT < 32) mbar_arrive_if(sb + BAR_GO, tid == 0); }, [](int) {});
          if (HOLD_AT == 32) mbar_arrive_if(sb + BAR_GO, tid == 0);
          STAMPW(16);
          const int t2 = tid_now(), l2 = t2 & 31;
          const uint32_t ha = sb + OFF_A + 5 * A_SLOT + (l2 >> 4) * 1024 + (2 * w + ((l2 >> 3) & 1)) * 128 + (l2 & 7) * 16;
#pragma unroll
          for (int j = 0; j < 24; j += 2) {
#pragma unroll
            for (int e = 0; e < 4; e++) z[2 * j + e] = hmul2(z[2 * j + e], pack2(d[4 * j + 2 * e], d[4 * j + 2 * e + 1]));
            stsm4(ha + j * 1024, z[2 * j], z[2 * j + 1], z[2 * j + 2], z[2 * j + 3]);
            if (HSPLIT && j == 6) {
              fence_async_smem();
              bar_sync(NB_WGB, 128);
              mbar_arrive_if(sb + BAR_G2, t2 == 0);
            }
          }
          fence_async_smem();
          bar_sync(NB_WGB, 128);
          mbar_arrive_if(sb + BAR_AF + 8 * (t2 == 3 ? ((HSPLIT ? BAR_H1 : BAR_G2) - BAR_AF) / 8 : (t2 == 4 ? (BAR_GO - BAR_AF) / 8 : 5 + t2)), t2 < (HOLD_AT == 33 ? 5 : 4));
          STAMPW(17);
          {
            float e[80];
#pragma unroll
            for (int j = 0; j < 80; j++) e[j] = 0.f;
            gemm_loop<160, false, 2, DB>(e, sb, 12, 5, 0, 2, 0, 2, 2, tid_now(), []() {}, [](int) {});
            STAMPW(10);
            const int t3 = tid_now();
#pragma unroll
            for (int j = 0; j < 10; j++) {
              sts128(sb + OFF_A + j * 2048 + t3 * 16, pack2(e[8 * j], e[8 * j + 1]), pack2(e[8 * j + 2], e[8 * j + 3]), pack2(e[8 * j + 4], e[8 * j + 5]),
                     pack2(e[8 * j + 6], e[8 * j + 7]));
              if (j == 4) bar_arrive(NB_WO, 256);
            }
            bar_arrive(NB_Z, 256);
            STAMPW(45);
          }
          return;
        }
        float sa = st[0], qa = st[1], sbb = st[2], qb = st[3];
#pragma unroll
        for (int o = 1; o <= 2; o <<= 1) {
          sa += __shfl_xor_sync(0xffffffff, sa, o); qa += __shfl_xor_sync(0xffffffff, qa, o);
          sbb += __shfl_xor_sync(0xffffffff, sbb, o); qb += __shfl_xor_sync(0xffffffff, qb, o);
        }
        const uint32_t tag = lds32<0>(sb + OFF_TAG);
        if (t < 2) st_ll4(&p.scr->zstat[rb * 256 + cb * 64 + w * 16 + g + t * 8], __float_as_uint(t ? sbb : sa), tag, __float_as_uint(t ? qb : qa), tag);
        if (G1_LATE) bar_arrive(NB_G1, 256);
        STAMPW(2);
        const float ca = 0.5f * s0.y, cbb = 0.5f * s1.y;
        {
          const uint4* zs = &p.scr->zstat[rb * 256 + t * 64 + w * 16 + g];
          uint4 u0 = ld_ll4(zs), u1 = ld_ll4(zs + 8);
          final_load_x(xw, sb + OFF_A, cb, 0, w, lane);
          fence_async_smem();
          bar_sync(NB_WGA, 128);
          mbar_arrive_if(sb + BAR_AE + 8 * tid, tid < NA);
          uint32_t t0 = 0;
#pragma unroll 1
          while (!__all_sync(0xffffffff, u0.y == tag && u0.w == tag && u1.y == tag && u1.w == tag)) {
            spin_guard(t0);
            u0 = ld_ll4(zs); u1 = ld_ll4(zs + 8);
          }
          sa = __uint_as_float(u0.x); qa = __uint_as_float(u0.z); sbb = __uint_as_float(u1.x); qb = __uint_as_float(u1.z);
          STAMPW(3);
        }
#pragma unroll
        for (int o = 1; o <= 2; o <<= 1) {
          sa += __shfl_xor_sync(0xffffffff, sa, o); qa += __shfl_xor_sync(0xffffffff, qa, o);
          sbb += __shfl_xor_sync(0xffffffff, sbb, o); qb += __shfl_xor_sync(0xffffffff, qb, o);
        }
        const float inv = 1.f / 768.f;
        const float ma = sa * inv, mb = sbb * inv;
        const float ra = ca * rsqrtf(fmaf(fmaxf(fmaf(-ma, ma, qa * inv), 0.f), ca * ca, 1e-5f));
        const float rb_ = cbb * rsqrtf(fmaf(fmaxf(fmaf(-mb, mb, qb * inv), 0.f), cbb * cbb, 1e-5f));
        const uint32_t ra2 = pack2(ra, ra), rb2 = pack2(rb_, rb_);
        const float na = -ma * bf_lo(ra2), nb = -mb * bf_lo(rb2);
        {
          const uint32_t n2a = pack2(na, na), n2b = pack2(nb, nb);
          const uint32_t za = sb + OFF_A + LEAD * A_SLOT + row_grp(w, (lane >> 3) & 1) * 3072 + (lane >> 4) * 128 + (lane & 7) * 16;
          mbar_wait2(sb + BAR_AE + 8 * (LEAD + 2), 0, sb + BAR_KU + 16, 0);
#pragma unroll
          for (int j = 0; j < 24; j += 2)
            stsm4(za + j * 128, hfma2(z[2 * j], ra2, n2a), hfma2(z[2 * j + 1], rb2, n2b), hfma2(z[2 * j + 2], ra2, n2a), hfma2(z[2 * j + 3], rb2, n2b));
          fence_async_smem();
        }
      }
      bar_arrive(NB_Z, 160);
      {
        const uint32_t zero = lds32<0>(sb + OFF_TAG + 4);
#pragma unroll
        for (int i = 0; i < 20; i++) xw[i / 10][i % 10] |= zero;
      }
      load_taps(k, p, chb + 64, tid_now());
      STAMPW(4);
    }
    const int h = wg >> 1;
    {
    const int tid = tid_now(), lane = tid & 31;
    conv_worker(p, k, sb + OFF_CV + (1 - h) * CV_SZ, sb + OFF_A + 9 * A_SLOT + h * 4096, sb + BAR_XF + 8 * h, NB_WGA + h,
                chb + (h ? 0 : 64), 2 + h, sb + BAR_GO, w, lane, tid, h ? 40 : 5, rb, cb);
    {
      const int t3 = tid_now(), l3 = t3 & 31;
      const uint32_t xs_addr = sb + OFF_XS + (w * 16 + (l3 >> 2)) * 8;
      const float2 s0 = lds64f(xs_addr), s1 = lds64f(xs_addr + 64);
      const uint32_t ya = sb + y_tile(h) + ((l3 >> 4) * 8 + (l3 & 7)) * 128 + ((row_grp(w, (l3 >> 3) & 1) ^ (l3 & 7)) << 4);
      uint32_t sw[2][10];
      mbar_wait(sb + BAR_XF + 8 * h, h);
      final_s_early(sw, xw, ya, s0, s1);
      uint32_t ph = 1, t0 = 0, y[8];
#pragma unroll 1
      while (true) {
        mbar_wait(sb + BAR_YL + 16 * h, ph);
        if (bar_all(NB_WGA + h, 128, final_late(y, ya))) break;
        spin_guard(t0);
        ph ^= 1;
        if (t3 == 0) load_late_y(p, sb, h, rb, cb, lds32<0>(sb + OFF_TAG) & 1);
      }
#pragma unroll
      for (int e = 0; e < 8; e++) sw[e & 1][4 + (e >> 1)] = hmul2(sw[e & 1][4 + (e >> 1)], ~y[e]);
      __nv_bfloat16* o0 = p.out + (size_t)(rb * 64 + row_grp(w, 0) * 8 + (l3 >> 2)) * kD + seg_col(cb, h);
      STAMPW(h ? 44 : 9);
      bar_sync(h ? NB_Z : NB_WO, 256);
      float d[40];
#pragma unroll
      for (int j = 0; j < 5; j++) {
        const uint4 v = lds128(sb + OFF_A + (h * 5 + j) * 2048 + t3 * 16);
        d[8 * j] = bf_lo(v.x); d[8 * j + 1] = bf_hi(v.x); d[8 * j + 2] = bf_lo(v.y); d[8 * j + 3] = bf_hi(v.y);
        d[8 * j + 4] = bf_lo(v.z); d[8 * j + 5] = bf_hi(v.z); d[8 * j + 6] = bf_lo(v.w); d[8 * j + 7] = bf_hi(v.w);
      }
      final_out(d, xw, sw, s0.y, s1.y, o0, h, l3 & 3);
    }
    }
  }
}

typedef CUresult (*EncodeFn)(CUtensorMap*, CUtensorMapDataType, cuuint32_t, void*, const cuuint64_t*, const cuuint64_t*, const cuuint32_t*,
                             const cuuint32_t*, CUtensorMapInterleave, CUtensorMapSwizzle, CUtensorMapL2promotion, CUtensorMapFloatOOBfill);

void encode(EncodeFn fn, CUtensorMap* m, const void* ptr, int rank, const cuuint64_t* dims, const cuuint64_t* strides, const cuuint32_t* box,
            CUtensorMapSwizzle swz = CU_TENSOR_MAP_SWIZZLE_128B) {
  const cuuint32_t es[5] = {1, 1, 1, 1, 1};
  fn(m, CU_TENSOR_MAP_DATA_TYPE_BFLOAT16, rank, const_cast<void*>(ptr), dims, strides, box, es, CU_TENSOR_MAP_INTERLEAVE_NONE,
     swz, CU_TENSOR_MAP_L2_PROMOTION_L2_128B, CU_TENSOR_MAP_FLOAT_OOB_FILL_NONE);
}

}

extern "C" void kernel_launch(void* const* d_in, const int* in_sizes, int n_in, void* d_out, int out_size) {
  (void)in_sizes; (void)n_in; (void)out_size;
  static EncodeFn enc = nullptr;
  static Scratch* scr = nullptr;
  static int sms = 0;
  if (!enc) {
    void* fn = nullptr;
    cudaDriverEntryPointQueryResult qr;
    cudaGetDriverEntryPoint("cuTensorMapEncodeTiled", &fn, cudaEnableDefault, &qr);
    enc = (EncodeFn)fn;
    cudaFuncSetAttribute(fused_kernel, cudaFuncAttributeMaxDynamicSharedMemorySize, SMEM_BYTES);
    cudaGetSymbolAddress((void**)&scr, g_scr);
    int dev = 0;
    cudaGetDevice(&dev);
    cudaDeviceGetAttribute(&sms, cudaDevAttrMultiProcessorCount, dev);
  }
  Params p;
  p.scr = scr;
  p.by_smid = sms == 132;
  p.k = (const __nv_bfloat16*)d_in[1];
  p.v = (const __nv_bfloat16*)d_in[2];
  p.shift = (const __nv_bfloat16*)d_in[3];
  p.ssmk = (const __nv_bfloat16*)d_in[4];
  p.ssmD = (const __nv_bfloat16*)d_in[5];
  p.wsp = (const __nv_bfloat16*)d_in[8];
  p.bsp = (const __nv_bfloat16*)d_in[9];
  p.wout = (const __nv_bfloat16*)d_in[10];
  p.out = (__nv_bfloat16*)d_out;
  for (int i = 0; i < 2; i++) {
    const cuuint64_t n = i ? kS : kD, dims[5] = {n, 8, 2, 2, kS / 32}, st[4] = {n * 2, n * 32, n * 16, n * 64};
    const cuuint32_t box[5] = {64, 8, 2, 2, 2};
    encode(enc, i ? &p.tmWsp : &p.tmX, d_in[i ? 8 : 0], 5, dims, st, box);
  }
  {
    const cuuint64_t dims[3] = {64, kD, kF / 64}, st[2] = {kF * 2, 128};
    const cuuint32_t box[3] = {64, 64, 3};
    encode(enc, &p.tmW, d_in[7], 3, dims, st, box);
  }
  {
    const cuuint64_t dims[2] = {kS, 896}, st[1] = {kS * 2};
    const cuuint32_t box[2] = {64, 16};
    encode(enc, &p.tmY, scr->y, 2, dims, st, box);
  }
  {
    const cuuint64_t dims[3] = {1024, kD / 2, 4}, st[2] = {8192, 2048};
    const cuuint32_t box[3] = {16, 32, 4};
    encode(enc, &p.tmKV, scr->kvx, 3, dims, st, box, CU_TENSOR_MAP_SWIZZLE_32B);
  }
  fused_kernel<<<132, 512, SMEM_BYTES, cudaStreamPerThread>>>(p);
}
```

```cpp
#include <cuda_runtime.h>
#include <cuda.h>
#include <cuda_bf16.h>
#include <stdint.h>

template <int N> struct WG;
template <> struct WG<16> {
  static __device__ __forceinline__ void rs(float* d, const uint32_t* a, uint64_t db) {
    asm volatile("{\n.reg .pred p;\nsetp.ne.b32 p, 1, 0;\nwgmma.mma_async.sync.aligned.m64n16k16.f32.bf16.bf16 {"
      "%0, %1, %2, %3, %4, %5, %6, %7"
      "}, {%8, %9, %10, %11}, %12, p, 1, 1, 0;\n}\n"
      :
      "+f"(d[0]), "+f"(d[1]), "+f"(d[2]), "+f"(d[3]), "+f"(d[4]), "+f"(d[5]), "+f"(d[6]), "+f"(d[7])
      : "r"(a[0]), "r"(a[1]), "r"(a[2]), "r"(a[3]), "l"(db));
  }
};
template <> struct WG<32> {
  static __device__ __forceinline__ void rs(float* d, const uint32_t* a, uint64_t db) {
    asm volatile("{\n.reg .pred p;\nsetp.ne.b32 p, 1, 0;\nwgmma.mma_async.sync.aligned.m64n32k16.f32.bf16.bf16 {"
      "%0, %1, %2, %3, %4, %5, %6, %7, %8, %9, %10, %11, %12, %13, %14, %15"
      "}, {%16, %17, %18, %19}, %20, p, 1, 1, 0;\n}\n"
      :
      "+f"(d[0]), "+f"(d[1]), "+f"(d[2]), "+f"(d[3]), "+f"(d[4]), "+f"(d[5]), "+f"(d[6]), "+f"(d[7]),
      "+f"(d[8]), "+f"(d[9]), "+f"(d[10]), "+f"(d[11]), "+f"(d[12]), "+f"(d[13]), "+f"(d[14]), "+f"(d[15])
      : "r"(a[0]), "r"(a[1]), "r"(a[2]), "r"(a[3]), "l"(db));
  }
};
template <> struct WG<48> {
  static __device__ __forceinline__ void rs(float* d, const uint32_t* a, uint64_t db) {
    asm volatile("{\n.reg .pred p;\nsetp.ne.b32 p, 1, 0;\nwgmma.mma_async.sync.aligned.m64n48k16.f32.bf16.bf16 {"
      "%0, %1, %2, %3, %4, %5, %6, %7, %8, %9, %10, %11, %12, %13, %14, %15, "
      "%16, %17, %18, %19, %20, %21, %22, %23"
      "}, {%24, %25, %26, %27}, %28, p, 1, 1, 0;\n}\n"
      :
      "+f"(d[0]), "+f"(d[1]), "+f"(d[2]), "+f"(d[3]), "+f"(d[4]), "+f"(d[5]), "+f"(d[6]), "+f"(d[7]),
      "+f"(d[8]), "+f"(d[9]), "+f"(d[10]), "+f"(d[11]), "+f"(d[12]), "+f"(d[13]), "+f"(d[14]), "+f"(d[15]),
      "+f"(d[16]), "+f"(d[17]), "+f"(d[18]), "+f"(d[19]), "+f"(d[20]), "+f"(d[21]), "+f"(d[22]), "+f"(d[23])
      : "r"(a[0]), "r"(a[1]), "r"(a[2]), "r"(a[3]), "l"(db));
  }
};
template <> struct WG<64> {
  static __device__ __forceinline__ void rs(float* d, const uint32_t* a, uint64_t db) {
    asm volatile("{\n.reg .pred p;\nsetp.ne.b32 p, 1, 0;\nwgmma.mma_async.sync.aligned.m64n64k16.f32.bf16.bf16 {"
      "%0, %1, %2, %3, %4, %5, %6, %7, %8, %9, %10, %11, %12, %13, %14, %15, "
      "%16, %17, %18, %19, %20, %21, %22, %23, %24, %25, %26, %27, %28, %29, %30, %31"
      "}, {%32, %33, %34, %35}, %36, p, 1, 1, 0;\n}\n"
      :
      "+f"(d[0]), "+f"(d[1]), "+f"(d[2]), "+f"(d[3]), "+f"(d[4]), "+f"(d[5]), "+f"(d[6]), "+f"(d[7]),
      "+f"(d[8]), "+f"(d[9]), "+f"(d[10]), "+f"(d[11]), "+f"(d[12]), "+f"(d[13]), "+f"(d[14]), "+f"(d[15]),
      "+f"(d[16]), "+f"(d[17]), "+f"(d[18]), "+f"(d[19]), "+f"(d[20]), "+f"(d[21]), "+f"(d[22]), "+f"(d[23]),
      "+f"(d[24]), "+f"(d[25]), "+f"(d[26]), "+f"(d[27]), "+f"(d[28]), "+f"(d[29]), "+f"(d[30]), "+f"(d[31])
      : "r"(a[0]), "r"(a[1]), "r"(a[2]), "r"(a[3]), "l"(db));
  }
};
template <> struct WG<80> {
  static __device__ __forceinline__ void rs(float* d, const uint32_t* a, uint64_t db) {
    asm volatile("{\n.reg .pred p;\nsetp.ne.b32 p, 1, 0;\nwgmma.mma_async.sync.aligned.m64n80k16.f32.bf16.bf16 {"
      "%0, %1, %2, %3, %4, %5, %6, %7, %8, %9, %10, %11, %12, %13, %14, %15, "
      "%16, %17, %18, %19, %20, %21, %22, %23, %24, %25, %26, %27, %28, %29, %30, %31, "
      "%32, %33, %34, %35, %36, %37, %38, %39"
      "}, {%40, %41, %42, %43}, %44, p, 1, 1, 0;\n}\n"
      :
      "+f"(d[0]), "+f"(d[1]), "+f"(d[2]), "+f"(d[3]), "+f"(d[4]), "+f"(d[5]), "+f"(d[6]), "+f"(d[7]),
      "+f"(d[8]), "+f"(d[9]), "+f"(d[10]), "+f"(d[11]), "+f"(d[12]), "+f"(d[13]), "+f"(d[14]), "+f"(d[15]),
      "+f"(d[16]), "+f"(d[17]), "+f"(d[18]), "+f"(d[19]), "+f"(d[20]), "+f"(d[21]), "+f"(d[22]), "+f"(d[23]),
      "+f"(d[24]), "+f"(d[25]), "+f"(d[26]), "+f"(d[27]), "+f"(d[28]), "+f"(d[29]), "+f"(d[30]), "+f"(d[31]),
      "+f"(d[32]), "+f"(d[33]), "+f"(d[34]), "+f"(d[35]), "+f"(d[36]), "+f"(d[37]), "+f"(d[38]), "+f"(d[39])
      : "r"(a[0]), "r"(a[1]), "r"(a[2]), "r"(a[3]), "l"(db));
  }
};
template <> struct WG<96> {
  static __device__ __forceinline__ void rs(float* d, const uint32_t* a, uint64_t db) {
    asm volatile("{\n.reg .pred p;\nsetp.ne.b32 p, 1, 0;\nwgmma.mma_async.sync.aligned.m64n96k16.f32.bf16.bf16 {"
      "%0, %1, %2, %3, %4, %5, %6, %7, %8, %9, %10, %11, %12, %13, %14, %15, "
      "%16, %17, %18, %19, %20, %21, %22, %23, %24, %25, %26, %27, %28, %29, %30, %31, "
      "%32, %33, %34, %35, %36, %37, %38, %39, %40, %41, %42, %43, %44, %45, %46, %47"
      "}, {%48, %49, %50, %51}, %52, p, 1, 1, 0;\n}\n"
      :
      "+f"(d[0]), "+f"(d[1]), "+f"(d[2]), "+f"(d[3]), "+f"(d[4]), "+f"(d[5]), "+f"(d[6]), "+f"(d[7]),
      "+f"(d[8]), "+f"(d[9]), "+f"(d[10]), "+f"(d[11]), "+f"(d[12]), "+f"(d[13]), "+f"(d[14]), "+f"(d[15]),
      "+f"(d[16]), "+f"(d[17]), "+f"(d[18]), "+f"(d[19]), "+f"(d[20]), "+f"(d[21]), "+f"(d[22]), "+f"(d[23]),
      "+f"(d[24]), "+f"(d[25]), "+f"(d[26]), "+f"(d[27]), "+f"(d[28]), "+f"(d[29]), "+f"(d[30]), "+f"(d[31]),
      "+f"(d[32]), "+f"(d[33]), "+f"(d[34]), "+f"(d[35]), "+f"(d[36]), "+f"(d[37]), "+f"(d[38]), "+f"(d[39]),
      "+f"(d[40]), "+f"(d[41]), "+f"(d[42]), "+f"(d[43]), "+f"(d[44]), "+f"(d[45]), "+f"(d[46]), "+f"(d[47])
      : "r"(a[0]), "r"(a[1]), "r"(a[2]), "r"(a[3]), "l"(db));
  }
};
template <> struct WG<112> {
  static __device__ __forceinline__ void rs(float* d, const uint32_t* a, uint64_t db) {
    asm volatile("{\n.reg .pred p;\nsetp.ne.b32 p, 1, 0;\nwgmma.mma_async.sync.aligned.m64n112k16.f32.bf16.bf16 {"
      "%0, %1, %2, %3, %4, %5, %6, %7, %8, %9, %10, %11, %12, %13, %14, %15, "
      "%16, %17, %18, %19, %20, %21, %22, %23, %24, %25, %26, %27, %28, %29, %30, %31, "
      "%32, %33, %34, %35, %36, %37, %38, %39, %40, %41, %42, %43, %44, %45, %46, %47, "
      "%48, %49, %50, %51, %52, %53, %54, %55"
      "}, {%56, %57, %58, %59}, %60, p, 1, 1, 0;\n}\n"
      :
      "+f"(d[0]), "+f"(d[1]), "+f"(d[2]), "+f"(d[3]), "+f"(d[4]), "+f"(d[5]), "+f"(d[6]), "+f"(d[7]),
      "+f"(d[8]), "+f"(d[9]), "+f"(d[10]), "+f"(d[11]), "+f"(d[12]), "+f"(d[13]), "+f"(d[14]), "+f"(d[15]),
      "+f"(d[16]), "+f"(d[17]), "+f"(d[18]), "+f"(d[19]), "+f"(d[20]), "+f"(d[21]), "+f"(d[22]), "+f"(d[23]),
      "+f"(d[24]), "+f"(d[25]), "+f"(d[26]), "+f"(d[27]), "+f"(d[28]), "+f"(d[29]), "+f"(d[30]), "+f"(d[31]),
      "+f"(d[32]), "+f"(d[33]), "+f"(d[34]), "+f"(d[35]), "+f"(d[36]), "+f"(d[37]), "+f"(d[38]), "+f"(d[39]),
      "+f"(d[40]), "+f"(d[41]), "+f"(d[42]), "+f"(d[43]), "+f"(d[44]), "+f"(d[45]), "+f"(d[46]), "+f"(d[47]),
      "+f"(d[48]), "+f"(d[49]), "+f"(d[50]), "+f"(d[51]), "+f"(d[52]), "+f"(d[53]), "+f"(d[54]), "+f"(d[55])
      : "r"(a[0]), "r"(a[1]), "r"(a[2]), "r"(a[3]), "l"(db));
  }
};
template <> struct WG<128> {
  static __device__ __forceinline__ void rs(float* d, const uint32_t* a, uint64_t db) {
    asm volatile("{\n.reg .pred p;\nsetp.ne.b32 p, 1, 0;\nwgmma.mma_async.sync.aligned.m64n128k16.f32.bf16.bf16 {"
      "%0, %1, %2, %3, %4, %5, %6, %7, %8, %9, %10, %11, %12, %13, %14, %15, "
      "%16, %17, %18, %19, %20, %21, %22, %23, %24, %25, %26, %27, %28, %29, %30, %31, "
      "%32, %33, %34, %35, %36, %37, %38, %39, %40, %41, %42, %43, %44, %45, %46, %47, "
      "%48, %49, %50, %51, %52, %53, %54, %55, %56, %57, %58, %59, %60, %61, %62, %63"
      "}, {%64, %65, %66, %67}, %68, p, 1, 1, 0;\n}\n"
      :
      "+f"(d[0]), "+f"(d[1]), "+f"(d[2]), "+f"(d[3]), "+f"(d[4]), "+f"(d[5]), "+f"(d[6]), "+f"(d[7]),
      "+f"(d[8]), "+f"(d[9]), "+f"(d[10]), "+f"(d[11]), "+f"(d[12]), "+f"(d[13]), "+f"(d[14]), "+f"(d[15]),
      "+f"(d[16]), "+f"(d[17]), "+f"(d[18]), "+f"(d[19]), "+f"(d[20]), "+f"(d[21]), "+f"(d[22]), "+f"(d[23]),
      "+f"(d[24]), "+f"(d[25]), "+f"(d[26]), "+f"(d[27]), "+f"(d[28]), "+f"(d[29]), "+f"(d[30]), "+f"(d[31]),
      "+f"(d[32]), "+f"(d[33]), "+f"(d[34]), "+f"(d[35]), "+f"(d[36]), "+f"(d[37]), "+f"(d[38]), "+f"(d[39]),
      "+f"(d[40]), "+f"(d[41]), "+f"(d[42]), "+f"(d[43]), "+f"(d[44]), "+f"(d[45]), "+f"(d[46]), "+f"(d[47]),
      "+f"(d[48]), "+f"(d[49]), "+f"(d[50]), "+f"(d[51]), "+f"(d[52]), "+f"(d[53]), "+f"(d[54]), "+f"(d[55]),
      "+f"(d[56]), "+f"(d[57]), "+f"(d[58]), "+f"(d[59]), "+f"(d[60]), "+f"(d[61]), "+f"(d[62]), "+f"(d[63])
      : "r"(a[0]), "r"(a[1]), "r"(a[2]), "r"(a[3]), "l"(db));
  }
};
template <> struct WG<160> {
  static __device__ __forceinline__ void ss(float* d, uint64_t da, uint64_t db, int sd) {
    asm volatile("{\n.reg .pred p;\nsetp.ne.b32 p, %82, 0;\nwgmma.mma_async.sync.aligned.m64n160k16.f32.bf16.bf16 {"
      "%0, %1, %2, %3, %4, %5, %6, %7, %8, %9, %10, %11, %12, %13, %14, %15, "
      "%16, %17, %18, %19, %20, %21, %22, %23, %24, %25, %26, %27, %28, %29, %30, %31, "
      "%32, %33, %34, %35, %36, %37, %38, %39, %40, %41, %42, %43, %44, %45, %46, %47, "
      "%48, %49, %50, %51, %52, %53, %54, %55, %56, %57, %58, %59, %60, %61, %62, %63, "
      "%64, %65, %66, %67, %68, %69, %70, %71, %72, %73, %74, %75, %76, %77, %78, %79"
      "}, %80, %81, p, 1, 1, 0, 1;\n}\n"
      :
      "+f"(d[0]), "+f"(d[1]), "+f"(d[2]), "+f"(d[3]), "+f"(d[4]), "+f"(d[5]), "+f"(d[6]), "+f"(d[7]),
      "+f"(d[8]), "+f"(d[9]), "+f"(d[10]), "+f"(d[11]), "+f"(d[12]), "+f"(d[13]), "+f"(d[14]), "+f"(d[15]),
      "+f"(d[16]), "+f"(d[17]), "+f"(d[18]), "+f"(d[19]), "+f"(d[20]), "+f"(d[21]), "+f"(d[22]), "+f"(d[23]),
      "+f"(d[24]), "+f"(d[25]), "+f"(d[26]), "+f"(d[27]), "+f"(d[28]), "+f"(d[29]), "+f"(d[30]), "+f"(d[31]),
      "+f"(d[32]), "+f"(d[33]), "+f"(d[34]), "+f"(d[35]), "+f"(d[36]), "+f"(d[37]), "+f"(d[38]), "+f"(d[39]),
      "+f"(d[40]), "+f"(d[41]), "+f"(d[42]), "+f"(d[43]), "+f"(d[44]), "+f"(d[45]), "+f"(d[46]), "+f"(d[47]),
      "+f"(d[48]), "+f"(d[49]), "+f"(d[50]), "+f"(d[51]), "+f"(d[52]), "+f"(d[53]), "+f"(d[54]), "+f"(d[55]),
      "+f"(d[56]), "+f"(d[57]), "+f"(d[58]), "+f"(d[59]), "+f"(d[60]), "+f"(d[61]), "+f"(d[62]), "+f"(d[63]),
      "+f"(d[64]), "+f"(d[65]), "+f"(d[66]), "+f"(d[67]), "+f"(d[68]), "+f"(d[69]), "+f"(d[70]), "+f"(d[71]),
      "+f"(d[72]), "+f"(d[73]), "+f"(d[74]), "+f"(d[75]), "+f"(d[76]), "+f"(d[77]), "+f"(d[78]), "+f"(d[79])
      : "l"(da), "l"(db), "r"(sd));
  }
};
template <> struct WG<192> {
  static __device__ __forceinline__ void ss(float* d, uint64_t da, uint64_t db, int sd) {
    asm volatile("{\n.reg .pred p;\nsetp.ne.b32 p, %98, 0;\nwgmma.mma_async.sync.aligned.m64n192k16.f32.bf16.bf16 {"
      "%0, %1, %2, %3, %4, %5, %6, %7, %8, %9, %10, %11, %12, %13, %14, %15, "
      "%16, %17, %18, %19, %20, %21, %22, %23, %24, %25, %26, %27, %28, %29, %30, %31, "
      "%32, %33, %34, %35, %36, %37, %38, %39, %40, %41, %42, %43, %44, %45, %46, %47, "
      "%48, %49, %50, %51, %52, %53, %54, %55, %56, %57, %58, %59, %60, %61, %62, %63, "
      "%64, %65, %66, %67, %68, %69, %70, %71, %72, %73, %74, %75, %76, %77, %78, %79, "
      "%80, %81, %82, %83, %84, %85, %86, %87, %88, %89, %90, %91, %92, %93, %94, %95"
      "}, %96, %97, p, 1, 1, 0, 1;\n}\n"
      :
      "+f"(d[0]), "+f"(d[1]), "+f"(d[2]), "+f"(d[3]), "+f"(d[4]), "+f"(d[5]), "+f"(d[6]), "+f"(d[7]),
      "+f"(d[8]), "+f"(d[9]), "+f"(d[10]), "+f"(d[11]), "+f"(d[12]), "+f"(d[13]), "+f"(d[14]), "+f"(d[15]),
      "+f"(d[16]), "+f"(d[17]), "+f"(d[18]), "+f"(d[19]), "+f"(d[20]), "+f"(d[21]), "+f"(d[22]), "+f"(d[23]),
      "+f"(d[24]), "+f"(d[25]), "+f"(d[26]), "+f"(d[27]), "+f"(d[28]), "+f"(d[29]), "+f"(d[30]), "+f"(d[31]),
      "+f"(d[32]), "+f"(d[33]), "+f"(d[34]), "+f"(d[35]), "+f"(d[36]), "+f"(d[37]), "+f"(d[38]), "+f"(d[39]),
      "+f"(d[40]), "+f"(d[41]), "+f"(d[42]), "+f"(d[43]), "+f"(d[44]), "+f"(d[45]), "+f"(d[46]), "+f"(d[47]),
      "+f"(d[48]), "+f"(d[49]), "+f"(d[50]), "+f"(d[51]), "+f"(d[52]), "+f"(d[53]), "+f"(d[54]), "+f"(d[55]),
      "+f"(d[56]), "+f"(d[57]), "+f"(d[58]), "+f"(d[59]), "+f"(d[60]), "+f"(d[61]), "+f"(d[62]), "+f"(d[63]),
      "+f"(d[64]), "+f"(d[65]), "+f"(d[66]), "+f"(d[67]), "+f"(d[68]), "+f"(d[69]), "+f"(d[70]), "+f"(d[71]),
      "+f"(d[72]), "+f"(d[73]), "+f"(d[74]), "+f"(d[75]), "+f"(d[76]), "+f"(d[77]), "+f"(d[78]), "+f"(d[79]),
      "+f"(d[80]), "+f"(d[81]), "+f"(d[82]), "+f"(d[83]), "+f"(d[84]), "+f"(d[85]), "+f"(d[86]), "+f"(d[87]),
      "+f"(d[88]), "+f"(d[89]), "+f"(d[90]), "+f"(d[91]), "+f"(d[92]), "+f"(d[93]), "+f"(d[94]), "+f"(d[95])
      : "l"(da), "l"(db), "r"(sd));
  }
  static __device__ __forceinline__ void rst(float* d, const uint32_t* a, uint64_t db) {
    asm volatile("{\n.reg .pred p;\nsetp.ne.b32 p, 1, 0;\nwgmma.mma_async.sync.aligned.m64n192k16.f32.bf16.bf16 {"
      "%0, %1, %2, %3, %4, %5, %6, %7, %8, %9, %10, %11, %12, %13, %14, %15, "
      "%16, %17, %18, %19, %20, %21, %22, %23, %24, %25, %26, %27, %28, %29, %30, %31, "
      "%32, %33, %34, %35, %36, %37, %38, %39, %40, %41, %42, %43, %44, %45, %46, %47, "
      "%48, %49, %50, %51, %52, %53, %54, %55, %56, %57, %58, %59, %60, %61, %62, %63, "
      "%64, %65, %66, %67, %68, %69, %70, %71, %72, %73, %74, %75, %76, %77, %78, %79, "
      "%80, %81, %82, %83, %84, %85, %86, %87, %88, %89, %90, %91, %92, %93, %94, %95"
      "}, {%96, %97, %98, %99}, %100, p, 1, 1, 1;\n}\n"
      :
      "+f"(d[0]), "+f"(d[1]), "+f"(d[2]), "+f"(d[3]), "+f"(d[4]), "+f"(d[5]), "+f"(d[6]), "+f"(d[7]),
      "+f"(d[8]), "+f"(d[9]), "+f"(d[10]), "+f"(d[11]), "+f"(d[12]), "+f"(d[13]), "+f"(d[14]), "+f"(d[15]),
      "+f"(d[16]), "+f"(d[17]), "+f"(d[18]), "+f"(d[19]), "+f"(d[20]), "+f"(d[21]), "+f"(d[22]), "+f"(d[23]),
      "+f"(d[24]), "+f"(d[25]), "+f"(d[26]), "+f"(d[27]), "+f"(d[28]), "+f"(d[29]), "+f"(d[30]), "+f"(d[31]),
      "+f"(d[32]), "+f"(d[33]), "+f"(d[34]), "+f"(d[35]), "+f"(d[36]), "+f"(d[37]), "+f"(d[38]), "+f"(d[39]),
      "+f"(d[40]), "+f"(d[41]), "+f"(d[42]), "+f"(d[43]), "+f"(d[44]), "+f"(d[45]), "+f"(d[46]), "+f"(d[47]),
      "+f"(d[48]), "+f"(d[49]), "+f"(d[50]), "+f"(d[51]), "+f"(d[52]), "+f"(d[53]), "+f"(d[54]), "+f"(d[55]),
      "+f"(d[56]), "+f"(d[57]), "+f"(d[58]), "+f"(d[59]), "+f"(d[60]), "+f"(d[61]), "+f"(d[62]), "+f"(d[63]),
      "+f"(d[64]), "+f"(d[65]), "+f"(d[66]), "+f"(d[67]), "+f"(d[68]), "+f"(d[69]), "+f"(d[70]), "+f"(d[71]),
      "+f"(d[72]), "+f"(d[73]), "+f"(d[74]), "+f"(d[75]), "+f"(d[76]), "+f"(d[77]), "+f"(d[78]), "+f"(d[79]),
      "+f"(d[80]), "+f"(d[81]), "+f"(d[82]), "+f"(d[83]), "+f"(d[84]), "+f"(d[85]), "+f"(d[86]), "+f"(d[87]),
      "+f"(d[88]), "+f"(d[89]), "+f"(d[90]), "+f"(d[91]), "+f"(d[92]), "+f"(d[93]), "+f"(d[94]), "+f"(d[95])
      : "r"(a[0]), "r"(a[1]), "r"(a[2]), "r"(a[3]), "l"(db));
  }
};

#define ZQ_N 2
#define CFENCE 1
#define Z1_AT 4
#define G1_AT 1
#define HGRP 3
#define HPACE 200
#define DB 0
#define HOLD_AT 33
#define LL_AT 4
#define KV_T0 2300
#define ST_YIELD 1
#define HP0 3500
#define HPD 450
#define RAMP 1
#define LEAD 2
#define WSP_N 16
#define EARLY 0
#define CPIN 1
#define CW0 0
#define PFT 1
#define WSP_D 600
#define D1 4
#define D2 4
#define NSLEEP 32

namespace {

constexpr int kS = 2048, kD = 640, kF = 1536;
constexpr int NA = 10, NA2 = 9, NB = 5;
constexpr int A_SLOT = 8192, B_SLOT = 24576;
constexpr int OFF_A = 0;
constexpr int OFF_B = OFF_A + NA * A_SLOT;
constexpr int XB_PL = 2112;
constexpr int CV_KE = 4224, CV_KO = CV_KE + 4160;
constexpr int CV_SZ = CV_KO + 4160;
constexpr int OFF_CV = OFF_B + NB * B_SLOT;
constexpr int OFF_CS = OFF_CV + 2 * CV_SZ;
constexpr int OFF_BIAS = OFF_CS + 1536;
constexpr int OFF_XS = OFF_BIAS + 128;
constexpr int OFF_BAR = OFF_XS + 512;
constexpr int BAR_AF = OFF_BAR, BAR_ST = BAR_AF + 8 * NA, BAR_XF = BAR_ST + 16, BAR_KV = BAR_XF + 16;
constexpr int BAR_BF = OFF_BAR + 128, BAR_G2 = BAR_BF + 8 * (NB + 1), BAR_XS = BAR_G2 + 8, BAR_KU = BAR_XS + 8, BAR_ZP = BAR_KU + 40, BAR_HOLD = BAR_ZP + 8, BAR_WO = BAR_HOLD + 8;
constexpr int BAR_AE = OFF_BAR + 256, BAR_BE = BAR_AE + 8 * NA;
constexpr int BAR_YT = BAR_KU + 24;
constexpr int BAR_GO = BAR_XS;
constexpr int BAR_YL = BAR_KU + 16;
constexpr int OFF_TAG = OFF_CS - 32;
constexpr int SMEM_BYTES = OFF_BAR + 384;
static_assert(SMEM_BYTES <= 232448, "smem");
constexpr int NB_WGA = 1, NB_WGC = 2, NB_G1 = 3, NB_WO = 4, NB_CD = 5, NB_Z = 6, NB_WGB = 7;

constexpr int CNT_Z = 0, CNT_Y = 1, CNT_Z1 = 3, CNT_KV = 32, CNT_WO = 36;
struct Scratch {
  uint8_t kvx[kD * 4096];
  uint8_t z2[4 * 32 * 24576];
  uint8_t h[32 * 12 * 8192];
  uint8_t wo[4 * 12 * 20480];
  uint8_t y[896 * 4096];
  uint4 xstat[kS];
  uint4 zstat[kS * 4];
  uint2 colsum[kF];
  uint32_t cnt[2 * 32];
  uint32_t hcnt[32 * 32];
  uint32_t epoch[136];
};
__device__ __align__(1024) Scratch g_scr;
#define STAMP(i)
#define STAMP2(i)
#define STAMPW(i)

struct Params {
  Scratch* scr;
  int by_smid;
  const __nv_bfloat16 *k, *v, *shift, *ssmk, *ssmD, *wsp, *bsp, *wout;
  __nv_bfloat16* out;
  CUtensorMap tmX, tmW, tmWsp, tmY, tmKV;
};

__device__ __forceinline__ uint64_t mkdesc(uint32_t addr, uint32_t lbo, uint32_t sbo, uint32_t swz) {
  return (uint64_t)((addr & 0x3FFFF) >> 4) | ((uint64_t)(lbo >> 4) << 16) | ((uint64_t)(sbo >> 4) << 32) | ((uint64_t)swz << 62);
}
#define WG_FENCE() asm volatile("wgmma.fence.sync.aligned;" ::: "memory")
#define WG_COMMIT() asm volatile("wgmma.commit_group.sync.aligned;" ::: "memory")
#define WG_WAIT(n) asm volatile("wgmma.wait_group.sync.aligned %0;" ::"n"(n) : "memory")
template <int N> __device__ __forceinline__ void acc_fence(float* d) {
#pragma unroll
  for (int i = 0; i < N; i++) asm volatile("" : "+f"(d[i])::"memory");
}
__device__ __forceinline__ void mbar_init(uint32_t bar, int cnt) { asm volatile("mbarrier.init.shared::cta.b64 [%0], %1;" ::"r"(bar), "r"(cnt) : "memory"); }
__device__ __forceinline__ void mbar_expect(uint32_t bar, uint32_t bytes) { asm volatile("mbarrier.arrive.expect_tx.shared::cta.b64 _, [%0], %1;" ::"r"(bar), "r"(bytes) : "memory"); }
__device__ __forceinline__ void mbar_arrive(uint32_t bar) { asm volatile("mbarrier.arrive.shared::cta.b64 _, [%0];" ::"r"(bar) : "memory"); }
__device__ __forceinline__ void mbar_arrive_if(uint32_t bar, bool c) {
  asm volatile("{\n.reg .pred p;\nsetp.ne.u32 p, %1, 0;\n@p mbarrier.arrive.shared::cta.b64 _, [%0];\n}\n" ::"r"(bar), "r"((uint32_t)c) : "memory");
}
__device__ __forceinline__ void mbar_expect_if(uint32_t bar, uint32_t bytes, bool c) {
  asm volatile("{\n.reg .pred p;\nsetp.ne.u32 p, %2, 0;\n@p mbarrier.arrive.expect_tx.shared::cta.b64 _, [%0], %1;\n}\n" ::"r"(bar), "r"(bytes), "r"((uint32_t)c) : "memory");
}
__device__ __forceinline__ bool mbar_try(uint32_t bar, uint32_t parity) {
  uint32_t ok;
  asm volatile("{\n.reg .pred p;\nmbarrier.try_wait.parity.shared::cta.b64 p, [%1], %2;\nselp.u32 %0, 1, 0, p;\n}\n" : "=r"(ok) : "r"(bar), "r"(parity) : "memory");
  return ok;
}
__device__ __forceinline__ bool mbar_test(uint32_t bar, uint32_t parity) {
  uint32_t ok;
  asm volatile("{\n.reg .pred p;\nmbarrier.test_wait.parity.shared::cta.b64 p, [%1], %2;\nselp.u32 %0, 1, 0, p;\n}\n" : "=r"(ok) : "r"(bar), "r"(parity) : "memory");
  return ok;
}
__device__ __forceinline__ void die() { asm volatile("st.volatile.global.u32 [%0], %1;" ::"l"(0ull), "r"(0) : "memory"); }
__device__ __forceinline__ void spin_guard(uint32_t& n) { if (++n == (1u << 22)) die(); }
__device__ __forceinline__ void mbar_wait(uint32_t bar, uint32_t parity) {
  uint32_t t0 = 0;
#pragma unroll 1
  while (!mbar_try(bar, parity)) spin_guard(t0);
}
__device__ __forceinline__ void mbar_wait2(uint32_t b0, uint32_t p0, uint32_t b1, uint32_t p1) {
  uint32_t t0 = 0;
#pragma unroll 1
  while (true) {
    const bool r0 = mbar_try(b0, p0), r1 = mbar_try(b1, p1);
    if (r0 && r1) break;
    spin_guard(t0);
  }
}
__device__ __forceinline__ int tid_now() { int v; asm volatile("mov.u32 %0, %%tid.x;" : "=r"(v)); return v & 127; }
__device__ __forceinline__ bool elect_one() {
  uint32_t p;
  asm volatile("{\n.reg .pred P;\nelect.sync _|P, 0xffffffff;\nselp.u32 %0, 1, 0, P;\n}\n" : "=r"(p));
  return p;
}
__device__ __forceinline__ void bar_sync(int id, int n) { asm volatile("bar.sync %0, %1;" ::"r"(id), "r"(n) : "memory"); }
__device__ __forceinline__ void bar_arrive(int id, int n) { asm volatile("bar.arrive %0, %1;" ::"r"(id), "r"(n) : "memory"); }
__device__ __forceinline__ void fence_async_smem() { asm volatile("fence.proxy.async.shared::cta;" ::: "memory"); }
__device__ __forceinline__ void bulk_g2s(uint32_t dst, const void* src, uint32_t bytes, uint32_t bar) {
  asm volatile("cp.async.bulk.shared::cluster.global.mbarrier::complete_tx::bytes [%0], [%1], %2, [%3];" ::"r"(dst), "l"(src), "r"(bytes), "r"(bar) : "memory");
}
__device__ __forceinline__ void bulk_s2g(void* dst, uint32_t src, uint32_t bytes) {
  asm volatile("cp.async.bulk.global.shared::cta.bulk_group [%0], [%1], %2;" ::"l"(dst), "r"(src), "r"(bytes) : "memory");
}
__device__ __forceinline__ void tma2d(uint32_t dst, const CUtensorMap* m, int c0, int c1, uint32_t bar) {
  asm volatile("cp.async.bulk.tensor.2d.shared::cluster.global.mbarrier::complete_tx::bytes [%0], [%1, {%3, %4}], [%2];" ::"r"(dst), "l"(m), "r"(bar), "r"(c0), "r"(c1) : "memory");
}
__device__ __forceinline__ void tma3d(uint32_t dst, const CUtensorMap* m, int c0, int c1, int c2, uint32_t bar) {
  asm volatile("cp.async.bulk.tensor.3d.shared::cluster.global.mbarrier::complete_tx::bytes [%0], [%1, {%3, %4, %5}], [%2];" ::"r"(dst), "l"(m), "r"(bar), "r"(c0), "r"(c1), "r"(c2) : "memory");
}
__device__ __forceinline__ void tma_rows(uint32_t dst, const CUtensorMap* m, int c0, int rb, uint32_t bar) { tma3d(dst, m, c0, rb * 16, 0, bar); }
__device__ __forceinline__ uint4 ld_ll4(const void* p) {
  uint64_t a, b;
  asm volatile("ld.relaxed.gpu.global.v2.u64 {%0,%1}, [%2];" : "=l"(a), "=l"(b) : "l"(p) : "memory");
  return make_uint4((uint32_t)a, (uint32_t)(a >> 32), (uint32_t)b, (uint32_t)(b >> 32));
}
__device__ __forceinline__ void st_ll4(void* p, uint32_t a, uint32_t b, uint32_t c, uint32_t d) {
  asm volatile("st.relaxed.gpu.global.v2.u64 [%0], {%1,%2};" ::"l"(p), "l"(a | ((uint64_t)b << 32)), "l"(c | ((uint64_t)d << 32)) : "memory");
}
__device__ __forceinline__ void st_ll2(void* p, uint32_t a, uint32_t b) { asm volatile("st.relaxed.gpu.global.u64 [%0], %1;" ::"l"(p), "l"(a | ((uint64_t)b << 32)) : "memory"); }
__device__ __forceinline__ void wgmma_colsum(float* d, uint64_t da, uint64_t db) {
  asm volatile("{\n.reg .pred p;\nsetp.ne.b32 p, 1, 0;\nwgmma.mma_async.sync.aligned.m64n8k16.f32.bf16.bf16 {%0, %1, %2, %3}, %4, %5, p, 1, 1, 1, 0;\n}\n"
               : "+f"(d[0]), "+f"(d[1]), "+f"(d[2]), "+f"(d[3]) : "l"(da), "l"(db));
}
__device__ __forceinline__ void prefetch_l2(const void* p) { asm volatile("prefetch.global.L2 [%0];" ::"l"(p)); }
__device__ __forceinline__ void pace(uint32_t& t, uint32_t dt) {
  t += dt;
  while ((int32_t)((uint32_t)clock() - t) < 0) { if (NSLEEP) __nanosleep(NSLEEP); }
}
__device__ __forceinline__ void red_relaxed(uint32_t* p) { asm volatile("red.relaxed.gpu.global.add.u32 [%0], 1;" ::"l"(p) : "memory"); }
__device__ __forceinline__ void red_release(uint32_t* p) { asm volatile("red.release.gpu.global.add.u32 [%0], 1;" ::"l"(p) : "memory"); }
__device__ __forceinline__ uint4 ldg4(const void* p) { uint4 v; asm volatile("ld.global.v4.u32 {%0,%1,%2,%3}, [%4];" : "=r"(v.x), "=r"(v.y), "=r"(v.z), "=r"(v.w) : "l"(p) : "memory"); return v; }
__device__ __forceinline__ uint32_t ldg1(const void* p) { uint32_t v; asm volatile("ld.global.u32 %0, [%1];" : "=r"(v) : "l"(p) : "memory"); return v; }
__device__ __forceinline__ void stg4_if(void* p, uint32_t a, uint32_t b, uint32_t c, uint32_t d, bool on) {
  asm volatile("{\n.reg .pred p;\nsetp.ne.u32 p, %5, 0;\n@p st.global.v4.u32 [%0], {%1,%2,%3,%4};\n}\n" ::"l"(p), "r"(a), "r"(b), "r"(c), "r"(d), "r"((uint32_t)on) : "memory");
}
template <int OFF> __device__ __forceinline__ uint32_t lds32(uint32_t a) { uint32_t v; asm volatile("ld.shared.u32 %0, [%1+%2];" : "=r"(v) : "r"(a), "n"(OFF)); return v; }
__device__ __forceinline__ uint4 lds128(uint32_t a) { uint4 v; asm volatile("ld.shared.v4.u32 {%0,%1,%2,%3}, [%4];" : "=r"(v.x), "=r"(v.y), "=r"(v.z), "=r"(v.w) : "r"(a) : "memory"); return v; }
__device__ __forceinline__ float2 lds64f(uint32_t a) { float2 v; asm volatile("ld.shared.v2.f32 {%0,%1}, [%2];" : "=f"(v.x), "=f"(v.y) : "r"(a) : "memory"); return v; }
__device__ __forceinline__ void sts64f(uint32_t a, float x, float y) { asm volatile("st.shared.v2.f32 [%0], {%1,%2};" ::"r"(a), "f"(x), "f"(y) : "memory"); }
__device__ __forceinline__ void sts32(uint32_t a, uint32_t x) { asm volatile("st.shared.u32 [%0], %1;" ::"r"(a), "r"(x) : "memory"); }
__device__ __forceinline__ void sts128(uint32_t a, uint32_t x, uint32_t y, uint32_t z, uint32_t w) { asm volatile("st.shared.v4.u32 [%0], {%1,%2,%3,%4};" ::"r"(a), "r"(x), "r"(y), "r"(z), "r"(w) : "memory"); }
__device__ __forceinline__ void stsm4(uint32_t a, uint32_t r0, uint32_t r1, uint32_t r2, uint32_t r3) {
  asm volatile("stmatrix.sync.aligned.m8n8.x4.shared.b16 [%0], {%1,%2,%3,%4};" ::"r"(a), "r"(r0), "r"(r1), "r"(r2), "r"(r3) : "memory");
}
__device__ __forceinline__ void stsm4t(uint32_t a, uint32_t r0, uint32_t r1, uint32_t r2, uint32_t r3) {
  asm volatile("stmatrix.sync.aligned.m8n8.x4.trans.shared.b16 [%0], {%1,%2,%3,%4};" ::"r"(a), "r"(r0), "r"(r1), "r"(r2), "r"(r3) : "memory");
}
__device__ __forceinline__ void ldsm4t(uint32_t* r, uint32_t a) {
  asm volatile("ldmatrix.sync.aligned.m8n8.x4.trans.shared.b16 {%0,%1,%2,%3}, [%4];" : "=r"(r[0]), "=r"(r[1]), "=r"(r[2]), "=r"(r[3]) : "r"(a) : "memory");
}
__device__ __forceinline__ uint32_t pack2(float lo, float hi) { uint32_t r; asm("cvt.rn.bf16x2.f32 %0, %1, %2;" : "=r"(r) : "f"(hi), "f"(lo)); return r; }
__device__ __forceinline__ float bf_lo(uint32_t u) { return __uint_as_float(u << 16); }
__device__ __forceinline__ float bf_hi(uint32_t u) { return __uint_as_float(u & 0xffff0000u); }
__device__ __forceinline__ float tanh_fast(float x) { float y; asm("tanh.approx.f32 %0, %1;" : "=f"(y) : "f"(x)); return y; }
__device__ __forceinline__ uint32_t hmul2(uint32_t a, uint32_t b) { uint32_t r; asm("mul.rn.bf16x2 %0, %1, %2;" : "=r"(r) : "r"(a), "r"(b)); return r; }
__device__ __forceinline__ uint32_t hfma2(uint32_t a, uint32_t b, uint32_t c) { uint32_t r; asm("fma.rn.bf16x2 %0, %1, %2, %3;" : "=r"(r) : "r"(a), "r"(b), "r"(c)); return r; }
__device__ __forceinline__ uint32_t prmt(uint32_t a, uint32_t b, uint32_t s) { return __byte_perm(a, b, s); }

__device__ __forceinline__ uint32_t ld_relaxed(const uint32_t* p) { uint32_t v; asm volatile("ld.relaxed.gpu.global.u32 %0, [%1];" : "=r"(v) : "l"(p) : "memory"); return v; }
__device__ __forceinline__ void acquire_fence() { asm volatile("fence.acquire.gpu;\nfence.proxy.async.global;" ::: "memory"); }
__device__ __forceinline__ uint32_t load_epoch(const Params& p, int idx, int lane) { return ld_relaxed(&p.scr->epoch[idx + (((lane * lane) & 3) == 2 ? 1 : 0)]); }
__device__ __forceinline__ void poll_counter(const uint32_t* cnt, uint32_t target) {
  uint32_t t0 = 0;
#pragma unroll 1
  while (!__all_sync(0xffffffff, ld_relaxed(cnt) == target)) spin_guard(t0);
  acquire_fence();
}

__device__ __forceinline__ int g3_block(int cb, int it) { return it < 3 ? cb * 3 + it : (it - 3 < cb * 3 ? it - 3 : it); }

template <int N, bool A_SWZ, int B_MODE, int DEPTH, class Hook, class Mid>
__device__ __forceinline__ void gemm_loop(float* d, uint32_t sb, int nkb, int sa, int pa, int b0, uint32_t boff, int relA, int relB, int tid, Hook hook, Mid mid) {
  constexpr uint32_t A_STEP = A_SWZ ? 2 : 128;
  constexpr uint32_t B_STEP = B_MODE == 0 ? 128 : (B_MODE == 1 ? 384 : 320);
  const uint64_t da0 = A_SWZ ? mkdesc(sb + OFF_A, 16, 1024, 1) : mkdesc(sb + OFF_A, 1024, 128, 0);
  const uint64_t db0 = B_MODE == 0 ? mkdesc(sb + OFF_B + boff, 8192, 1024, 1) : mkdesc(sb + OFF_B + boff, B_MODE == 1 ? 3072 : 2560, 128, 0);
  constexpr int MODA = B_MODE == 0 ? NA : NA2;
  constexpr int MODB = B_MODE == 2 ? 6 : NB;
  int sbk = b0 % MODB, pb = (b0 / MODB) & 1;
  auto boffs = [](int s_) { return B_MODE == 2 ? (s_ == 5 ? 0 : s_ + 1) * (20480 >> 4) : s_ * (B_SLOT >> 4); };
  uint32_t rel = 0;
  uint64_t da = da0 + sa * (A_SLOT >> 4), db = db0 + boffs(sbk);
  const bool doR = tid < 2 ? tid < relA : tid - 2 < relB;
  mbar_wait2(sb + BAR_AF + 8 * sa, pa, sb + BAR_BF + 8 * sbk, pb);
  if constexpr (DEPTH == 0) {
    acc_fence<N / 2>(d);
#pragma unroll 1
    for (int it = 0; it < nkb; it++) {
      WG_FENCE();
#pragma unroll
      for (int j = 0; j < 4; j++) WG<N>::ss(d, da + j * A_STEP, db + j * B_STEP, 1);
      WG_COMMIT();
      const uint32_t prel = rel;
      rel = sb + BAR_AE + 8 * (tid < 2 ? sa : sbk + NA);
      if (++sa == MODA) { sa = 0; pa ^= 1; }
      if (++sbk == MODB) { sbk = 0; pb ^= 1; }
      da = da0 + sa * (A_SLOT >> 4); db = db0 + boffs(sbk);
      const bool r0 = mbar_test(sb + BAR_AF + 8 * sa, pa), r1 = mbar_test(sb + BAR_BF + 8 * sbk, pb);
      WG_WAIT(1);
      mbar_arrive_if(prel, doR && prel != 0);
      if (it == 2) {
        WG_WAIT(0);
        mbar_expect_if(sb + BAR_AF + 8 * (tid == 8 ? 8 : tid), A_SLOT, tid < 9);
        mbar_arrive_if(rel, doR);
        rel = 0;
      }
      mid(it);
      if (it + 1 < nkb && !(r0 && r1)) {
        mbar_wait2(sb + BAR_AF + 8 * sa, pa, sb + BAR_BF + 8 * sbk, pb);
      }
    }
  } else
#pragma unroll 1
  for (int it = 0; it < nkb; it++) {
    WG_FENCE();
    WG<N>::ss(d, da, db, 1);
    const uint32_t prel = rel;
    rel = sb + BAR_AE + 8 * (tid < 2 ? sa : sbk + NA);
    if (++sa == MODA) { sa = 0; pa ^= 1; }
    if (++sbk == MODB) { sbk = 0; pb ^= 1; }
    if (DEPTH == 1) { WG_COMMIT(); WG_WAIT(1); }
    WG<N>::ss(d, da + A_STEP, db + B_STEP, 1);
    WG_COMMIT();
    WG_WAIT(1);
    if (EARLY == 1) mbar_arrive_if(prel, doR && it != 0);
    WG<N>::ss(d, da + 2 * A_STEP, db + 2 * B_STEP, 1);
    if (DEPTH == 1) WG_COMMIT();
    if (EARLY != 1) mbar_arrive_if(prel, doR && it != 0);
    const bool r0 = mbar_test(sb + BAR_AF + 8 * sa, pa), r1 = mbar_test(sb + BAR_BF + 8 * sbk, pb);
    const uint64_t da3 = da + 3 * A_STEP, db3 = db + 3 * B_STEP;
    da = da0 + sa * (A_SLOT >> 4); db = db0 + boffs(sbk);
    if (DEPTH == 1) WG_WAIT(1);
    WG<N>::ss(d, da3, db3, 1);
    WG_COMMIT();
    mid(it);
    if (it + 1 < nkb) {
      if (!(r0 && r1)) {
        mbar_wait2(sb + BAR_AF + 8 * sa, pa, sb + BAR_BF + 8 * sbk, pb);
      }
    }
    if (DEPTH == 2) WG_WAIT(1);
  }
  hook();
  WG_WAIT(0);
  acc_fence<N / 2>(d);
  mbar_arrive_if(rel, doR);
}

__device__ __forceinline__ void fold_mean(float* d, uint32_t cs, float ma, float mb, int t) {
  const uint32_t ha = pack2(-ma, -ma), hb = pack2(-mb, -mb);
  const float la = -ma - bf_lo(ha), lb = -mb - bf_lo(hb);
  const uint32_t a[4] = {t ? 0u : ha, t ? 0u : hb, t ? 0u : pack2(la, la), t ? 0u : pack2(lb, lb)};
  WG_FENCE();
  WG<192>::rst(d, a, mkdesc(cs, 0, 32, 0));
  WG_COMMIT();
}
__device__ __forceinline__ void gelu_tile(const float* d, uint32_t* z, float* st, float ra, float rb) {
  const float kA = 0.7978845608028654f, kB = 0.7978845608028654f * 0.044715f;
  const float c1a = kA * ra, c3a = kB * ra * ra * ra, c1b = kA * rb, c3b = kB * rb * rb * rb;
  float acc[8];
#pragma unroll
  for (int i = 0; i < 8; i++) acc[i] = 0.f;
#pragma unroll
  for (int j = 0; j < 24; j++) {
    float r[4];
#pragma unroll
    for (int e = 0; e < 4; e++) {
      const float v = d[4 * j + e];
      const float a = v * fmaf(v * v, e < 2 ? c3a : c3b, e < 2 ? c1a : c1b);
      r[e] = fmaf(v, tanh_fast(a), v);
      acc[e] += r[e];
      acc[4 + e] = fmaf(r[e], r[e], acc[4 + e]);
    }
    z[2 * j] = pack2(r[0], r[1]);
    z[2 * j + 1] = pack2(r[2], r[3]);
  }
  st[0] = acc[0] + acc[1]; st[1] = acc[4] + acc[5]; st[2] = acc[2] + acc[3]; st[3] = acc[6] + acc[7];
}

template <int Q> __device__ __forceinline__ void conv_load(uint32_t* a, uint32_t ab) {
  a[0] = lds32<512 * Q>(ab);       a[1] = lds32<512 * Q + 256>(ab);  a[2] = lds32<512 * Q + 16>(ab);   a[3] = lds32<512 * Q + 272>(ab);
  a[4] = lds32<512 * Q + 32>(ab);  a[5] = lds32<512 * Q + 288>(ab);  a[6] = lds32<512 * Q + 48>(ab);   a[7] = lds32<512 * Q + 304>(ab);
  a[8] = lds32<512 * Q + 64>(ab);  a[9] = lds32<512 * Q + 320>(ab);  a[10] = lds32<512 * Q + 80>(ab);  a[11] = lds32<512 * Q + 336>(ab);
  a[12] = lds32<512 * Q + 96>(ab); a[13] = lds32<512 * Q + 352>(ab); a[14] = lds32<512 * Q + 112>(ab); a[15] = lds32<512 * Q + 368>(ab);
}
template <int Q, int L> __device__ __forceinline__ void conv_step(float* d, uint32_t (*a)[16], uint32_t ab, uint64_t db) {
  WG_FENCE();
#pragma unroll
  for (int s = 0; s < 4; s++) WG<128 - 16 * Q>::rs(d, a[Q] + 4 * s, db + s + 16 * Q);
  WG_COMMIT();
  if (CPIN) WG_WAIT(1);
  if (L >= 0) conv_load<(L >= 0 ? L : 0)>(a[L >= 0 ? L : 0], ab);
  if (CW0 || Q == 0) WG_WAIT(0);
}

__device__ __forceinline__ int seg_col(int cb, int h) { return (cb >> 1) * 320 + (cb & 1) * 32 + h * 64; }
__device__ __forceinline__ void final_load_x(uint32_t (*xw)[10], uint32_t xt, int cb, int h, int w, int lane) {
  const int g = lane >> 2, t = lane & 3, cc = seg_col(cb, h) >> 3;
  const int c0 = cc + t, c1 = c0 + 24, c2 = cc + 16 - 6 * h + (t >> 1);
  const uint32_t r0 = xt + (w * 16 + g) * 128;
#pragma unroll
  for (int r = 0; r < 2; r++) {
    const uint4 u = lds128(r0 + r * 1024 + (c0 >> 3) * A_SLOT + (((c0 ^ g) & 7) << 4)), v = lds128(r0 + r * 1024 + (c1 >> 3) * A_SLOT + (((c1 ^ g) & 7) << 4));
    const float2 z = lds64f(r0 + r * 1024 + (c2 >> 3) * A_SLOT + (((c2 ^ g) & 7) << 4) + (t & 1) * 8);
    xw[r][0] = u.x; xw[r][1] = u.y; xw[r][2] = u.z; xw[r][3] = u.w;
    xw[r][4] = v.x; xw[r][5] = v.y; xw[r][6] = v.z; xw[r][7] = v.w;
    xw[r][8] = __float_as_uint(z.x); xw[r][9] = __float_as_uint(z.y);
  }
}
__device__ __forceinline__ void final_s_early(uint32_t (*sw)[10], const uint32_t (*xw)[10], uint32_t ya, float2 s0, float2 s1) {
  const uint32_t r2[2] = {pack2(s0.y, s0.y), pack2(s1.y, s1.y)};
  const float na = -s0.x * bf_lo(r2[0]), nb = -s1.x * bf_lo(r2[1]);
  const uint32_t n2[2] = {pack2(na, na), pack2(nb, nb)};
#pragma unroll
  for (int j = 0; j < 10; j += 2) {
    uint32_t y[4];
    if (j < 4 || j == 8) ldsm4t(y, ya + (j < 4 ? j : 4) * 1024);
#pragma unroll
    for (int e = 0; e < 4; e++) {
      const uint32_t xn = hfma2(xw[e & 1][j + (e >> 1)], r2[e & 1], n2[e & 1]);
      sw[e & 1][j + (e >> 1)] = (j < 4 || j == 8) ? hmul2(xn, y[e]) : xn;
    }
  }
}
__device__ __forceinline__ bool final_late(uint32_t* y, uint32_t ya) {
  ldsm4t(y, ya + 6144);
  ldsm4t(y + 4, ya + 8192);
  uint32_t zero = 0;
#pragma unroll
  for (int e = 0; e < 8; e++) zero |= (y[e] - 0x00010001u) & ~y[e];
  return (zero & 0x80008000u) == 0;
}
__device__ __forceinline__ bool bar_all(int id, int n, bool c) {
  uint32_t r;
  asm volatile("{\n.reg .pred p, q;\nsetp.ne.u32 p, %3, 0;\nbar.red.and.pred q, %1, %2, p;\nselp.u32 %0, 1, 0, q;\n}\n" : "=r"(r) : "r"(id), "r"(n), "r"((uint32_t)c) : "memory");
  return r;
}
__device__ __forceinline__ void final_out(const float* d, const uint32_t (*xw)[10], const uint32_t (*sw)[10], float ra, float rb, __nv_bfloat16* o0, int h, int t) {
  const float ca = 0.25f * ra, cb = 0.25f * rb;
  uint32_t o[2][10];
#pragma unroll
  for (int j = 0; j < 10; j++) {
#pragma unroll
    for (int r = 0; r < 2; r++) {
      const float h0 = d[4 * j + 2 * r] * (r ? cb : ca), h1 = d[4 * j + 2 * r + 1] * (r ? cb : ca);
      o[r][j] = hfma2(pack2(fmaf(h0, tanh_fast(h0), h0), fmaf(h1, tanh_fast(h1), h1)), sw[r][j], xw[r][j]);
      __nv_bfloat16* q = o0 + r * 8 * kD;
      if (j == 3) stg4_if(q + t * 8, o[r][0], o[r][1], o[r][2], o[r][3], true);
      if (j == 7) stg4_if(q + 192 + t * 8, o[r][4], o[r][5], o[r][6], o[r][7], true);
      if (j == 9) asm volatile("st.global.v2.u32 [%0], {%1,%2};" ::"l"(q + 128 - 48 * h + t * 4), "r"(o[r][8]), "r"(o[r][9]) : "memory");
    }
  }
}

struct Taps { uint4 r0, r1; uint32_t n0, n1, dd; };
__device__ __forceinline__ void load_taps(Taps& k, const Params& p, int ch, int tid) {
  const uint4* kp = (const uint4*)(p.ssmk + (size_t)ch * kS);
  k.r0 = ldg4(kp + tid); k.r1 = ldg4(kp + 128 + tid);
  k.n0 = ldg1(kp + tid + 1); k.n1 = tid < 127 ? ldg1(kp + 129 + tid) : 0u;
  k.dd = __bfloat16_as_ushort(p.ssmD[ch]);
}
__device__ __forceinline__ void load_convx(const Params& p, uint32_t cv, uint32_t bar, int ch) {
  mbar_expect(bar, 4096);
  bulk_g2s(cv, p.scr->kvx + (size_t)ch * 4096, 2048, bar);
  bulk_g2s(cv + XB_PL, p.scr->kvx + (size_t)ch * 4096 + 2048, 2048, bar);
}
#define CW 3
#define CSTAMP(j)
__device__ __forceinline__ void zero_pads(uint32_t cv, int lane) {
  if (lane < 8) sts128(cv + (lane >> 2) * XB_PL + 2048 + (lane & 3) * 16, 0, 0, 0, 0);
  else if (lane < 12) sts128(cv + ((lane & 2) ? CV_KO : CV_KE) + (lane & 1) * 16, 0, 0, 0, 0);
  fence_async_smem();
  __syncwarp();
}
__device__ __forceinline__ int y_row(int c, uint32_t par) {
  const int hf = c >= 320, cc = c - hf * 320, u = cc >> 6, cb = hf * 2 + ((cc >> 5) & 1);
  if (u == 2) return cb * 96 + ((cc >> 4) & 1) * 48 + 32 + (cc & 1) + ((cc >> 1) & 1) * 8 + ((cc >> 2) & 3) * 2;
  return (u < 2 ? cb * 96 + u * 48 : 384 + par * 256 + cb * 64 + (u - 3) * 32) + (cc & 1) + ((cc >> 1) & 3) * 8 + ((cc >> 3) & 3) * 2;
}
__device__ __forceinline__ void y_store(const Params& p, uint32_t sb, int h, int ch, uint32_t par) {
  uint8_t* dst = p.scr->y + (size_t)y_row(ch, par) * 4096;
  if (elect_one()) {
    bulk_s2g(dst, sb + OFF_A + 9 * A_SLOT + h * 4096, 4096);
    asm volatile("cp.async.bulk.commit_group;\ncp.async.bulk.wait_group 0;" ::: "memory");
  }
  __syncwarp();
}
__device__ __forceinline__ void conv_service(const Params& p, uint32_t sb, int h, int ch, bool first) {
  bar_sync(NB_WGA + 8 + h, 160);
  const bool now = !first || __all_sync(0xffffffff, mbar_test(sb + BAR_KV, 0));
  if (now) { acquire_fence(); if (elect_one()) load_convx(p, sb + OFF_CV + (1 - h) * CV_SZ, sb + BAR_XF + 8 * h, ch + 128); }
  bar_sync(NB_WGA + 8 + h, 160);
  y_store(p, sb, h, ch, 0);
  if (!now) {
    mbar_wait(sb + BAR_KV, 0);
    acquire_fence();
    if (elect_one()) load_convx(p, sb + OFF_CV + (1 - h) * CV_SZ, sb + BAR_XF + 8 * h, ch + 128);
  }
}
__device__ __forceinline__ uint32_t y_tile(int h) { return OFF_CV + (1 - h) * 13312; }
__device__ __forceinline__ void load_late_y(const Params& p, uint32_t sb, int h, int rb, int cb, uint32_t par) {
  mbar_expect(sb + BAR_YL + 16 * h, 4096);
  tma2d(sb + y_tile(h) + 6144, &p.tmY, rb * 64, 384 + par * 256 + cb * 64 + h * 32, sb + BAR_YL + 16 * h);
  tma2d(sb + y_tile(h) + 8192, &p.tmY, rb * 64, 400 + par * 256 + cb * 64 + h * 32, sb + BAR_YL + 16 * h);
}
__device__ __forceinline__ void held_service(const Params& p, uint32_t sb, int h, int ch, int rb, int cb, uint32_t tag, int lane) {
#pragma unroll 1
  for (int i = 0; i < 8; i++) sts128(sb + OFF_A + 9 * A_SLOT + h * 4096 + i * 512 + lane * 16, 0, 0, 0, 0);
  fence_async_smem();
  __syncwarp();
  y_store(p, sb, h, ch, ~tag & 1);
  mbar_wait(sb + BAR_YT, 1);
  acquire_fence();
  bar_sync(NB_WGA + 8 + h, 160);
  bar_sync(NB_WGA + 8 + h, 160);
  uint8_t* dst = p.scr->y + (size_t)y_row(ch, tag & 1) * 4096;
  if (elect_one()) {
    bulk_s2g(dst, sb + OFF_A + 9 * A_SLOT + h * 4096, 4096);
    asm volatile("cp.async.bulk.commit_group;" ::: "memory");
    mbar_expect(sb + BAR_XF + 8 * h, 6144);
#pragma unroll 1
    for (int i = 0; i < 3; i++) tma2d(sb + y_tile(h) + i * 2048, &p.tmY, rb * 64, cb * 96 + h * 48 + i * 16, sb + BAR_XF + 8 * h);
  }
  mbar_wait(sb + BAR_AE + 8 * (LL_AT - 1), 1);
  if (elect_one()) { load_late_y(p, sb, h, rb, cb, tag & 1); asm volatile("cp.async.bulk.wait_group 0;" ::: "memory"); }
}
__device__ __forceinline__ void conv_worker(const Params& p, Taps& k, uint32_t cv, uint32_t yb0,
                                            uint32_t xbar, int nbar, int ch0, int n, uint32_t holdbar, int w, int lane,
                                            int tid, int st0, int rb, int cb) {
  const int g = lane >> 2, t = lane & 3, w0 = w & 1, w1 = w >> 1;
  const uint32_t ab = cv + ((g & 1) ? CV_KE : CV_KO) + 32 + 2 * (64 * w0 + 8 * w1 + ((g - 15) & ~1) + 2 * t);
  const uint32_t scA = cv + (w1 ? CV_KO : CV_KE) + 32, scB = scA + 2048;
  const int dl = (t >> 1) ^ 1;
  if (n == 2) mbar_wait(xbar, 0);
  STAMPW(st0 + 3);
#pragma unroll 1
  for (int i = 0; i < n; i++) {
    if (tid == 0) {
      k.r0.x = (k.r0.x & 0xffff0000u) | (pack2(bf_lo(k.r0.x) + bf_lo(k.dd), 0.f) & 0xffffu);
      sts32(cv + CV_KO + 28, k.r0.x << 16);
    }
    sts128(cv + CV_KE + 32 + tid * 16, k.r0.x, k.r0.y, k.r0.z, k.r0.w);
    sts128(cv + CV_KO + 32 + tid * 16, prmt(k.r0.x, k.r0.y, 0x5432), prmt(k.r0.y, k.r0.z, 0x5432), prmt(k.r0.z, k.r0.w, 0x5432), prmt(k.r0.w, k.n0, 0x5432));
    sts128(cv + CV_KE + 2080 + tid * 16, k.r1.x, k.r1.y, k.r1.z, k.r1.w);
    sts128(cv + CV_KO + 2080 + tid * 16, prmt(k.r1.x, k.r1.y, 0x5432), prmt(k.r1.y, k.r1.z, 0x5432), prmt(k.r1.z, k.r1.w, 0x5432), prmt(k.r1.w, k.n1, 0x5432));
    if (i + 1 < n) load_taps(k, p, ch0 + (i + 1) * 128, tid);
    bar_sync(nbar, 128);
    CSTAMP(0);
    const uint64_t db = mkdesc(cv + (i & 0x1000), XB_PL, 128, 0);
    float d[64];
    uint32_t a[8][16];
    conv_load<7>(a[7], ab); conv_load<6>(a[6], ab); conv_load<5>(a[5], ab); conv_load<4>(a[4], ab);
#pragma unroll
    for (int j = 0; j < 64; j++) d[j] = 0.f;
    mbar_wait(xbar, i & 1);
    if (i + 1 == n) mbar_wait(holdbar, 1);
    CSTAMP(1);
    conv_step<7, -1>(d, a, ab, db); conv_step<6, -1>(d, a, ab, db); conv_step<5, -1>(d, a, ab, db); conv_step<4, 3>(d, a, ab, db);
    conv_step<3, 2>(d, a, ab, db);
    conv_step<2, 1>(d, a, ab, db);
    conv_step<1, 0>(d, a, ab, db);
    conv_step<0, -1>(d, a, ab, db);
    acc_fence<64>(d);
    CSTAMP(2);
    bar_sync(nbar + 8, 160);
    float E[16][2];
#pragma unroll
    for (int j = 0; j < 15; j++) { E[j][0] = d[4 * j] + d[4 * j + 6]; E[j][1] = d[4 * j + 1] + d[4 * j + 7]; }
    E[15][0] = d[60]; E[15][1] = d[61];
    if (w0 == 0) {
#pragma unroll
      for (int j = 8; j < 16; j++) sts64f(scA + (j - 8) * 256 + lane * 8, E[j][0], E[j][1]);
    } else {
      const uint32_t a = scB - dl * 256 + (lane ^ 2) * 8;
#pragma unroll
      for (int j = 1; j < 8; j++) sts64f(a + j * 256, E[j][0], E[j][1]);
      sts64f(scB + (dl ? 7 * 256 : 0) + (lane ^ 2) * 8, dl ? E[8][0] : E[0][0], dl ? E[8][1] : E[0][1]);
    }
    bar_sync(nbar, 128);
    CSTAMP(3);
    uint32_t pk[8];
    if (w0 == 0) {
#pragma unroll
      for (int j = 0; j < 8; j++) { const float2 v = lds64f(scB + j * 256 + lane * 8); pk[j] = pack2(E[j][0] + v.x, E[j][1] + v.y); }
    } else {
      const uint32_t a0 = scA - dl * 256 + (lane ^ 2) * 8;
#pragma unroll
      for (int j = 9; j < 16; j++) { const float2 v = lds64f(a0 + (j - 8) * 256); pk[j - 8] = pack2(E[j][0] + v.x, E[j][1] + v.y); }
      const float2 v = lds64f(scA + (dl ? 7 * 256 : 0) + (lane ^ 2) * 8);
      pk[0] = pack2((dl ? 0.f : E[8][0]) + v.x, (dl ? 0.f : E[8][1]) + v.y);
    }
    CSTAMP(4);
    if (i + 1 == n) {
#pragma unroll
      for (int j = 0; j < 8; j++) pk[j] = ~pk[j];
    }
    const int c1 = (w0 ? 35 : 95) - lane, c0 = (w0 && lane < 4) ? c1 - 32 : c1 + 32;
    stsm4t(yb0 + 128 * (c0 & 31) + (((2 * (c0 >> 5) + w1) ^ (c0 & 7)) << 4), pk[0], pk[1], pk[2], pk[3]);
    stsm4t(yb0 + 128 * (c1 & 31) + (((2 * (c1 >> 5) + w1) ^ (c1 & 7)) << 4), pk[4], pk[5], pk[6], pk[7]);
    fence_async_smem();
    bar_sync(nbar + 8, 160);
    CSTAMP(5);
    STAMPW(st0 + i);
    if (n == 2 && i == 0) {
      const int u = (tid >> 3) % 5, kg = rb * 3 + (tid < 120 ? (tid >> 3) / 5 : 0), c = u < 4 ? (u >> 1) * 10 + (u & 1) * 4 : 8, o2 = u < 4 ? 2 : 10;
      const uint4* wp = (const uint4*)p.wout + (uint32_t)((kg * 8 + (tid & 7)) * (kD / 8) + (seg_col(cb, 0) >> 3) + (u < 4 ? (u >> 1) * 8 + (u & 1) * 24 : 16));
      const uint4 w0 = ldg4(wp), w1 = ldg4(wp + 1), w2 = ldg4(wp + 2), w3 = ldg4(wp + 3);
      uint8_t* dst = p.scr->wo + (uint32_t)(cb * (12 * 20480) + kg * 2560 + c * 128 + (tid & 7) * 16);
      const bool f = u < 4, on = tid < 120;
      stg4_if(dst, w0.x, f ? w1.x : w0.z, f ? w2.x : w1.x, f ? w3.x : w1.z, on);
      stg4_if(dst + 128, w0.y, f ? w1.y : w0.w, f ? w2.y : w1.y, f ? w3.y : w1.w, on);
      stg4_if(dst + o2 * 128, f ? w0.z : w2.x, f ? w1.z : w2.z, f ? w2.z : w3.x, w3.z, on);
      stg4_if(dst + o2 * 128 + 128, f ? w0.w : w2.y, f ? w1.w : w2.w, f ? w2.w : w3.y, w3.w, on);
      bar_arrive(NB_WO, 160);
    }
  }
}

struct KvRegs { uint32_t k[11], v[8]; uint4 sh; };
__device__ __forceinline__ void kv_load(KvRegs& q, const __nv_bfloat16* kp, const __nv_bfloat16* vp, const __nv_bfloat16* sp, bool halo) {
#pragma unroll
  for (int i = 0; i < 11; i++) q.k[i] = (i >= 3 || halo) ? ldg1(kp + i * kD) : 0u;
#pragma unroll
  for (int i = 0; i < 8; i++) q.v[i] = ldg1(vp + i * kD);
  q.sh = ldg4(sp);
}
__device__ __forceinline__ void kv_unit(const KvRegs& q, uint32_t oa) {
  const uint32_t w0 = prmt(q.sh.x, q.sh.z, 0x5410), w1 = prmt(q.sh.x, q.sh.z, 0x7632), w2 = prmt(q.sh.y, q.sh.w, 0x5410), w3 = prmt(q.sh.y, q.sh.w, 0x7632);
  uint32_t r[8];
#pragma unroll
  for (int i = 0; i < 8; i++) r[i] = hmul2(hfma2(q.k[i + 3], w0, hfma2(q.k[i + 2], w1, hfma2(q.k[i + 1], w2, hmul2(q.k[i], w3)))), q.v[i]);
  sts128(oa, prmt(r[7], r[6], 0x5410), prmt(r[5], r[4], 0x5410), prmt(r[3], r[2], 0x5410), prmt(r[1], r[0], 0x5410));
  sts128(oa + 2048, prmt(r[7], r[6], 0x7632), prmt(r[5], r[4], 0x7632), prmt(r[3], r[2], 0x7632), prmt(r[1], r[0], 0x7632));
}

__device__ __forceinline__ void helper_cta(const Params& p, uint32_t sb, int cb, int warp, int lane) {
  constexpr int NS = 9, ONES = NS * B_SLOT, BF = ONES + 256, BE = BF + 8 * NS;
  if (warp < NS && elect_one()) {
    mbar_init(sb + BF + 8 * warp, 1); mbar_init(sb + BE + 8 * warp, 1);
    fence_async_smem();
    if (warp == 0) { mbar_expect(sb + BF, B_SLOT); tma3d(sb, &p.tmW, 0, 0, 12 + cb * 3, sb + BF); }
  }
  if (warp == 15) { sts32(sb + ONES + lane * 4, 0x3f803f80u); sts32(sb + ONES + 128 + lane * 4, 0x3f803f80u); fence_async_smem(); }
  __syncthreads();
  if (warp == 4) {
    int s = 1, ph = 1;
    uint32_t tp = clock() + HP0;
#pragma unroll 1
    for (int it = 1; it < 20; it++) {
      if (HPD && it >= 10) pace(tp, HPD);
      mbar_wait(sb + BE + 8 * s, ph);
      if (elect_one()) { mbar_expect(sb + BF + 8 * s, B_SLOT); tma3d(sb + s * B_SLOT, &p.tmW, 0, (it < 10 ? it : it - 10) * 64, (it < 10 ? 12 : 0) + cb * 3, sb + BF + 8 * s); }
      if (++s == NS) { s = 0; ph ^= 1; }
    }
  } else if (warp < 4) {
    const uint32_t tag = load_epoch(p, 128 + cb, lane) + 1;
    const uint64_t db = mkdesc(sb + ONES, 128, 128, 0);
    uint2* dst = p.scr->colsum + cb * 192 + warp * 16 + (lane >> 2);
    if ((lane & 3) == 0) {
#pragma unroll 1
      for (int j = 0; j < 12; j++) st_ll2(dst + (j < 6 ? 768 : 0) + ((j % 6) >> 1) * 64 + (j & 1) * 8, 0, 0);
    }
    int s = 0, ph = 0;
#pragma unroll 1
    for (int part = 0; part < 2; part++) {
      float d[12];
#pragma unroll
      for (int i = 0; i < 12; i++) d[i] = 0.f;
#pragma unroll 1
      for (int it = 0; it < 10; it++) {
        mbar_wait(sb + BF + 8 * s, ph);
        const uint64_t da = mkdesc(sb + s * B_SLOT, 8192, 1024, 1);
        WG_FENCE();
#pragma unroll
        for (int j = 0; j < 12; j++) wgmma_colsum(d + 4 * (j % 3), da + (j % 3) * 512 + (j / 3) * 128, db);
        WG_COMMIT();
        WG_WAIT(1);
        mbar_arrive_if(sb + BE + 8 * (s == 0 ? NS - 1 : s - 1), threadIdx.x == 0 && (it | part) != 0);
        if (++s == NS) { s = 0; ph ^= 1; }
      }
      WG_WAIT(0);
      acc_fence<12>(d);
      if ((lane & 3) == 0) {
#pragma unroll
        for (int j = 0; j < 6; j++) st_ll2(dst + (part ? 0 : 768) + (j >> 1) * 64 + (j & 1) * 8, __float_as_uint(d[2 * j]), tag);
      }
      STAMPW(1 + part);
    }
    if (threadIdx.x == 0) *(volatile uint32_t*)&p.scr->epoch[128 + cb] = tag;
  }
}

__global__ void __launch_bounds__(512, 1) fused_kernel(const __grid_constant__ Params p) {
  extern __shared__ __align__(1024) uint8_t smem[];
  const int warp = __shfl_sync(0xffffffff, (int)(threadIdx.x >> 5), 0);
  const int lane = threadIdx.x & 31, tid = threadIdx.x & 127;
  const uint32_t sb = __shfl_sync(0xffffffff, (uint32_t)__cvta_generic_to_shared(smem), 0);
  const uint32_t tstart = clock();
  if (elect_one()) {
    if (warp < 5) asm volatile("prefetch.tensormap [%0];" ::"l"(&p.tmX + warp) : "memory");
    mbar_init(sb + OFF_BAR + 8 * warp, 1); mbar_init(sb + OFF_BAR + 128 + 8 * warp, 1); mbar_init(sb + OFF_BAR + 256 + 8 * warp, 2);
    asm volatile("fence.mbarrier_init.release.cluster;" ::: "memory");
  }
  int b = blockIdx.x;
  if (p.by_smid) asm volatile("mov.u32 %0, %%smid;" : "=r"(b));
  b = __shfl_sync(0xffffffff, b, 0);
  const int tp = b >> 1, t7 = (tp - 32) / 7;
  const int lin = tp < 32 ? ((tp & 7) ? (tp & 7) * 16 : 8) + (tp >> 3) * 2 + (b & 1)
                          : (tp < 60 ? (tp - 31 - t7 * 7) * 16 + 8 + t7 * 2 + (b & 1) : (tp < 62 ? -1 : b - 124));
  const int hcb = b & 3;
  if (lin < 0) { helper_cta(p, sb, hcb, warp, lane); return; }
  const int cb = ((lin >> 4) & 1) * 2 + ((lin >> 1) & 1), rb = (lin >> 5) * 8 + ((lin >> 2) & 3) * 2 + (lin & 1);
  const int chb = (cb >> 1) * 320 + rb * 2 + (cb & 1);
  if (warp == 0 && elect_one()) {
    mbar_expect(sb + BAR_AF, A_SLOT);
    tma_rows(sb + OFF_A, &p.tmX, 0, rb, sb + BAR_AF);
    mbar_expect(sb + BAR_BF, B_SLOT);
    tma3d(sb + OFF_B, &p.tmW, 0, 0, 12 + cb * 3, sb + BAR_BF);
  }
  if (warp == 1) STAMP(31);
  if (sb & 1023) die();
  __syncthreads();

  if (warp >= 12) {
    asm volatile("setmaxnreg.dec.sync.aligned.u32 32;");
    const uint32_t epoch = load_epoch(p, lin, lane);
    if (warp == 12) {
#pragma unroll 1
      for (int i = 1; i < NA; i++) {
        if (elect_one()) {
          mbar_expect(sb + BAR_AF + 8 * i, A_SLOT);
          tma_rows(sb + OFF_A + i * A_SLOT, &p.tmX, i * 64, rb, sb + BAR_AF + 8 * i);
          if (i < NB) { mbar_expect(sb + BAR_BF + 8 * i, B_SLOT); tma3d(sb + OFF_B + i * B_SLOT, &p.tmW, 0, i * 64, 12 + cb * 3, sb + BAR_BF + 8 * i); }
        }
      }
      STAMP(32);
      uint32_t kvt;
      {
        const int tb = rb * 2 + (cb & 1);
        kvt = __shfl_sync(0xffffffff, (ld_relaxed(p.scr->cnt + CNT_KV + (cb >> 1)) & ~63u) + 64, 0);
        {
          uint32_t tp = tstart;
          pace(tp, KV_T0);
          mbar_arrive_if(sb + BAR_KV + 8, lane == 0);
        }
        if (ST_YIELD) mbar_wait2(sb + BAR_XS, 0, sb + BAR_ST, 0);
#pragma unroll 1
        for (int u = 0; u < 5; u++) {
          mbar_wait(sb + BAR_KU + 8 * u, 0);
          fence_async_smem();
          if (elect_one()) {
            asm volatile("cp.async.bulk.tensor.3d.global.shared::cta.bulk_group [%0, {%2, %3, %4}], [%1];\ncp.async.bulk.commit_group;" ::"l"(&p.tmKV),
                         "r"(sb + OFF_CV + CV_SZ + (u < 3 ? u : u - 3) * 4096), "r"((63 - tb) * 16), "r"((cb >> 1) * 160 + u * 32), "r"(0) : "memory");
            if (u == 1 || u == 4) asm volatile("cp.async.bulk.wait_group 0;" ::: "memory");
            if (u == 1) { mbar_arrive(sb + BAR_KU); red_release(p.scr->cnt + CNT_KV + (cb >> 1)); }
          }
          __syncwarp();
          if (u == 1) {
            STAMP(35);
            if (PFT) { const char* q = (const char*)p.ssmk + chb * 4096 + lane * 128; prefetch_l2(q); prefetch_l2(q + 64 * 4096); }
          }
        }
        zero_pads(sb + OFF_CV + CV_SZ, lane);
        if (elect_one()) { mbar_arrive(sb + BAR_KU + 8); red_release(p.scr->cnt + CNT_KV + 2 + (cb >> 1)); }
        STAMP(30);
        if (lane < 24) {
          const char* r = (const char*)p.wout + (rb * 24 + lane) * (kD * 2) + (cb >> 1) * 640 + (cb & 1) * 384;
          prefetch_l2(r); prefetch_l2(r + 128); prefetch_l2(r + 256 - (cb & 1) * 384);
        }
      }
      poll_counter(p.scr->cnt + CNT_KV + 2 + (cb >> 1), kvt);
      if (elect_one()) mbar_arrive(sb + BAR_KV);
      STAMP(34);
      {
        const char* q = (const char*)p.wsp + (cb * 512 + rb * 16 + (lane >> 1)) * (kS * 2) + (lane & 1) * 128;
        uint32_t tp = clock();
#pragma unroll 1
        for (int i = LEAD / 2; i < WSP_N; i++) {
          prefetch_l2(q + i * 256);
          if (ZQ_N < 4 && i == Z1_AT) {
            poll_counter(p.scr->cnt + CNT_Z1, (epoch + 1) * 128);
            if (elect_one()) mbar_arrive(sb + BAR_ZP);
            STAMP(24);
          }
          pace(tp, WSP_D);
        }
      }
      const uint32_t tag = epoch + 1;
      mbar_wait(sb + BAR_G2, 0);
      if (elect_one()) {
        bulk_s2g(p.scr->h + (size_t)(rb * 12 + cb * 3) * A_SLOT, sb + OFF_A + 5 * A_SLOT, 3 * A_SLOT);
        asm volatile("cp.async.bulk.commit_group;\ncp.async.bulk.wait_group 0;" ::: "memory");
        red_release(&p.scr->hcnt[(rb >> HGRP) * 32]);
      }
      __syncwarp();
      STAMP(20);
      mbar_wait(sb + BAR_AE + 56, 0);
      STAMP(39);
      poll_counter(&p.scr->hcnt[(rb >> HGRP) * 32], tag * (4 << HGRP));
      STAMP(37);
      if (elect_one()) {
        uint32_t tp = clock();
#pragma unroll 1
        for (int it = 3; it < 12; it++) {
          if (HPACE && it > 3) { tp += HPACE; while ((int32_t)((uint32_t)clock() - tp) < 0) {} }
          bulk_g2s(sb + OFF_A + ((it + 5) % 9) * A_SLOT, p.scr->h + (size_t)(rb * 12 + g3_block(cb, it)) * A_SLOT, A_SLOT, sb + BAR_AF + 8 * ((it + 5) % 9));
        }
      }
      STAMP(21);
    } else if (warp == 13) {
      const uint32_t ztarget = __shfl_sync(0xffffffff, ld_relaxed(p.scr->cnt + CNT_Z), 0);
      int s = 0, ph = 0;
#pragma unroll 1
      for (int it = NB; it < 20; it++) {
        mbar_wait(sb + BAR_BE + 8 * s, ph);
        if (elect_one()) { mbar_expect(sb + BAR_BF + 8 * s, B_SLOT); tma3d(sb + OFF_B + s * B_SLOT, &p.tmW, 0, (it < 10 ? it : it - 10) * 64, (it < 10 ? 12 : 0) + cb * 3, sb + BAR_BF + 8 * s); }
        STAMP2(32 + it);
        if (++s == NB) { s = 0; ph ^= 1; }
      }
      mbar_wait(sb + BAR_KU + 16, 0);
#pragma unroll 1
      for (int i = 0; i < LEAD; i++) {
        mbar_wait(sb + BAR_AE + 8 * i, 0);
        if (elect_one()) { mbar_expect(sb + BAR_AF + 8 * i, A_SLOT); tma_rows(sb + OFF_A + i * A_SLOT, &p.tmWsp, i * 64, rb, sb + BAR_AF + 8 * i); }
      }
      mbar_wait(sb + BAR_ZP, 0);
      poll_counter(p.scr->cnt + CNT_Z, (ztarget & ~127u) + 128);
      STAMP(22);
      int sa = LEAD, pa = 0, ia = LEAD;
#pragma unroll 1
      for (int it = 0; it < 32; it++) {
        if (ZQ_N < 4 && it == 8 * ZQ_N) { mbar_wait(sb + BAR_ZP, 1); acquire_fence(); }
        mbar_wait2(sb + BAR_BE + 8 * s, ph, sb + BAR_AE + 8 * sa, pa);
        if (elect_one()) {
          mbar_expect(sb + BAR_BF + 8 * s, B_SLOT);
          bulk_g2s(sb + OFF_B + s * B_SLOT, p.scr->z2 + (size_t)(cb * 32 + it) * B_SLOT, B_SLOT, sb + BAR_BF + 8 * s);
        }
#pragma unroll 1
        for (int j = (it < RAMP ? 0 : (it == 4 ? 1 + RAMP : 1)); j > 0 && ia < 32; j--, ia++) {
          if (it == 4) mbar_wait(sb + BAR_AE + 8 * sa, pa);
          if (elect_one()) { mbar_expect(sb + BAR_AF + 8 * sa, A_SLOT); tma_rows(sb + OFF_A + sa * A_SLOT, &p.tmWsp, ia * 64, rb, sb + BAR_AF + 8 * sa); }
          if (++sa == NA2) { sa = 0; pa ^= 1; }
        }
        STAMP2(52 + it);
        if (++s == NB) { s = 0; ph ^= 1; }
      }
      mbar_wait(sb + BAR_WO, 0);
      acquire_fence();
#pragma unroll 1
      for (int it = 0; it < 12; it++) {
        if (it < 6) mbar_wait(sb + BAR_BE + 8 * ((0x110443 >> (4 * it)) & 7), it < 3 ? 1 : 0);
        else mbar_wait(sb + BAR_BE + 8 * s, ph);
        if (elect_one()) {
          mbar_expect(sb + BAR_BF + 8 * s, 20480);
          bulk_g2s(sb + OFF_B + (s == 5 ? 0 : s + 1) * 20480, p.scr->wo + (size_t)(cb * 12 + g3_block(cb, it)) * 20480, 20480, sb + BAR_BF + 8 * s);
        }
        STAMP2(84 + it);
        if (++s == 6) { s = 0; ph ^= 1; }
      }
    } else if (warp == 14) {
      const uint32_t tag = epoch + 1;
      uint32_t t0 = 0;
      mbar_wait(sb + BAR_AF + 8 * (NA - 1), 0);
#pragma unroll 1
      for (int part = 0; part < 2; part++) {
        uint4 v[3];
#pragma unroll 1
        while (true) {
          bool ok = true;
#pragma unroll
          for (int i = 0; i < 3; i++) {
            v[i] = ld_ll4(&p.scr->colsum[(part ? 0 : 768) + cb * 192 + i * 64 + lane * 2]);
            ok = ok && v[i].y == tag && v[i].w == tag;
          }
          if (__all_sync(0xffffffff, ok)) break;
          spin_guard(t0);
        }
#pragma unroll
        for (int i = 0; i < 3; i++) {
          const uint32_t hi = pack2(__uint_as_float(v[i].x), __uint_as_float(v[i].z)), ca = sb + OFF_CS + (1 - part) * 768 + i * 256 + (lane >> 2) * 32 + (lane & 3) * 4;
          sts32(ca, hi);
          sts32(ca + 16, pack2(__uint_as_float(v[i].x) - bf_lo(hi), __uint_as_float(v[i].z) - bf_hi(hi)));
        }
        if (!CFENCE) fence_async_smem();
        __syncwarp();
        if (lane == 0) mbar_arrive(sb + BAR_ST + 8 * part);
        if (part == 0) STAMP(27);
      }
      STAMP(38);
      bar_sync(NB_Z, 160);
      if (elect_one()) {
        uint8_t* dst = p.scr->z2 + (size_t)(cb * 32 + (rb >> 2)) * B_SLOT + (rb & 3) * 6144;
#pragma unroll 1
        for (int q = 0; q < ZQ_N; q++) bulk_s2g(dst + q * 8 * B_SLOT, sb + OFF_A + LEAD * A_SLOT + q * 6144, 6144);
        asm volatile("cp.async.bulk.commit_group;\ncp.async.bulk.wait_group 0;" ::: "memory");
        red_release(p.scr->cnt + CNT_Z);
#pragma unroll 1
        for (int q = ZQ_N; q < 4; q++) bulk_s2g(dst + q * 8 * B_SLOT, sb + OFF_A + LEAD * A_SLOT + q * 6144, 6144);
        asm volatile("cp.async.bulk.commit_group;\ncp.async.bulk.wait_group 0;" ::: "memory");
        mbar_arrive(sb + BAR_ZP);
        if (ZQ_N < 4) red_release(p.scr->cnt + CNT_Z1);
      }
      STAMP(28);
      mbar_wait(sb + BAR_AE + 72, 0);
      conv_service(p, sb, 0, chb + 64, true);
      bar_sync(NB_WO, 160);
      bar_sync(NB_CD, 64);
      if (elect_one()) { red_release(p.scr->cnt + CNT_WO + cb); red_relaxed(p.scr->cnt + CNT_Y + (cb >> 1)); }
      STAMP(49);
      poll_counter(p.scr->cnt + CNT_WO + cb, tag * 32);
      if (elect_one()) mbar_arrive(sb + BAR_WO);
      STAMP(46);
      held_service(p, sb, 0, chb + 192, rb, cb, tag, lane);
    } else {
      const uint32_t tag = epoch + 1;
      sts32(sb + OFF_BIAS + lane * 4, ldg1(p.bsp + (lane >> 3) * 512 + rb * 16 + (lane & 7) * 2));
      if (lane < 2) sts32(sb + OFF_TAG + lane * 4, lane ? 0 : tag);
      fence_async_smem();
      uint32_t t0 = 0;
      mbar_wait(sb + BAR_AF + 8 * (NA - 1), 0);
#pragma unroll 1
      while (true) {
        const uint4 u = ld_ll4(&p.scr->xstat[rb * 64 + lane]), v = ld_ll4(&p.scr->xstat[rb * 64 + 32 + lane]);
        sts64f(sb + OFF_XS + lane * 8, __uint_as_float(u.x), __uint_as_float(u.z));
        sts64f(sb + OFF_XS + 256 + lane * 8, __uint_as_float(v.x), __uint_as_float(v.z));
        if (__all_sync(0xffffffff, u.y == tag && u.w == tag && v.y == tag && v.w == tag)) break;
        spin_guard(t0);
      }
      STAMP(26);
      __syncwarp();
      if (lane == 0) mbar_arrive(sb + BAR_XS);
      mbar_wait(sb + BAR_KU + 16, 0);
      poll_counter(p.scr->cnt + CNT_KV + (cb >> 1), tag * 64);
      if (elect_one()) load_convx(p, sb + OFF_CV, sb + BAR_XF + 8, chb);
      mbar_wait(sb + BAR_KU + 8, 1);
      if (elect_one()) load_convx(p, sb + OFF_CV + CV_SZ, sb + BAR_XF, chb + 64);
      STAMP(48);
      mbar_wait(sb + BAR_AE + 72, 0);
#pragma unroll 1
      for (int i = 0; i < 2; i++) conv_service(p, sb, 1, chb + i * 128, i == 0);
      bar_arrive(NB_CD, 64);
      mbar_wait(sb + BAR_WO, 0);
      poll_counter(p.scr->cnt + CNT_Y + (cb >> 1), tag * 64);
      STAMP(47);
      if (elect_one()) mbar_arrive(sb + BAR_YT);
      held_service(p, sb, 1, chb + 256, rb, cb, tag, lane);
      if (lane == 0) *(volatile uint32_t*)&p.scr->epoch[lin] = tag;
      STAMP(23);
    }
  } else {
    if (warp == 7) STAMP(36);
    const int wg = warp >> 2, w = warp & 3, g = lane >> 2, t = lane & 3;
    Taps k;
    uint32_t xw[2][10];
    if (wg == 2) {
      asm volatile("setmaxnreg.inc.sync.aligned.u32 160;");
      const int tb = rb * 2 + (cb & 1), c0 = (cb >> 1) * 320;
      const uint32_t cv = sb + OFF_CV + CV_SZ;
      if (w == 0) zero_pads(sb + OFF_CV, lane);
      mbar_wait(sb + BAR_KV + 8, 0);
      const int t0 = tb * 32 + w * 8;
      const __nv_bfloat16* kp = p.k + (size_t)(t0 - 3) * kD + c0 + lane * 2;
      const __nv_bfloat16* vp = p.v + (size_t)t0 * kD + c0 + lane * 2;
      const __nv_bfloat16* sp = p.shift + (c0 + lane * 2) * 4;
      const uint32_t oa = cv + ((3 - w) & 1) * 1024 + lane * 32 + ((((3 - w) >> 1) ^ (lane >> 2)) & 1) * 16;
#pragma unroll 1
      for (int r = 0; r < 2; r++) {
        KvRegs n0, n1, n2;
        kv_load(n0, kp + r * 128, vp + r * 128, sp + r * 512, t0 > 0);
        kv_load(n1, kp + r * 128 + 64, vp + r * 128 + 64, sp + r * 512 + 256, t0 > 0);
        if (r) kv_load(n2, kp + 256, vp + 256, sp + 1024, t0 > 0);
        kv_unit(n0, oa + r * 8192);
        bar_sync(NB_WGC, 128);
        mbar_arrive_if(sb + BAR_KU + 16 * r, tid == 0);
        if (r) mbar_wait(sb + BAR_KU, 1);
        kv_unit(n1, oa + (r ? 0 : 4096));
        bar_sync(NB_WGC, 128);
        mbar_arrive_if(sb + BAR_KU + 16 * r + 8, tid == 0);
        if (r) {
          kv_unit(n2, oa + 4096);
          bar_sync(NB_WGC, 128);
          mbar_arrive_if(sb + BAR_KU + 32, tid == 0);
        } else {
          mbar_wait(sb + BAR_AF + 8 * ((cb >> 1) * 5 + 1), 0);
          mbar_wait2(sb + BAR_AF + 8 * ((cb >> 1) * 5 + 2), 0, sb + BAR_AF + 8 * ((cb >> 1) * 5 + 4), 0);
          final_load_x(xw, sb + OFF_A, cb, 1, w, lane);
        }
      }
      STAMPW(13);
      load_taps(k, p, chb, tid);
    } else {
      float d[96];
      if (wg == 0) { if (t < 2) st_ll4(&p.scr->zstat[rb * 256 + cb * 64 + w * 16 + g + t * 8], 0, 0, 0, 0); }
      else if ((tid & 7) == 0) st_ll4(&p.scr->xstat[rb * 64 + cb * 16 + (tid >> 3)], 0, 0, 0, 0);
      {
        #pragma unroll
        for (int i = 0; i < 96; i++) d[i] = 0.f;
        {
          if (__builtin_expect(wg == 1, 0)) {
            const int tid = tid_now();
            const uint32_t epoch = load_epoch(p, lin, lane);
            float s = 0.f, q = 0.f;
#pragma unroll 1
            for (int i = 0; i < 10; i++) {
              mbar_wait(sb + BAR_AF + 8 * i, 0);
              const uint4 x4 = lds128(sb + OFF_A + i * A_SLOT + cb * 2048 + tid * 16);
              const uint32_t u[4] = {x4.x, x4.y, x4.z, x4.w};
#pragma unroll
              for (int e = 0; e < 4; e++) { const float a = bf_lo(u[e]), c = bf_hi(u[e]); s += a + c; q = fmaf(a, a, q); q = fmaf(c, c, q); }
            }
#pragma unroll
            for (int o = 1; o <= 4; o <<= 1) { s += __shfl_xor_sync(0xffffffff, s, o); q += __shfl_xor_sync(0xffffffff, q, o); }
            const float m = s * (1.f / kD);
            const float r = rsqrtf(fmaxf(fmaf(-m, m, q * (1.f / kD)), 0.f) + 1e-5f);
            if ((tid & 7) == 0) st_ll4(&p.scr->xstat[rb * 64 + cb * 16 + (tid >> 3)], __float_as_uint(m), epoch + 1, __float_as_uint(r), epoch + 1);
            STAMPW(12);
            bar_sync(NB_G1, 256);
          }
          gemm_loop<192, true, 0, D1>(d, sb, 10, 0, 0, 0, 0, wg, 2, tid_now(), [&]() { if (G1_AT == 0 && wg == 0) bar_arrive(NB_G1, 256); }, [](int) {});
          asm volatile("setmaxnreg.inc.sync.aligned.u32 160;");
          STAMPW(wg ? 14 : 1);
          mbar_wait2(sb + BAR_XS, 0, sb + BAR_ST + 8 * wg, 0);
        }
        const int t1 = tid_now();
        const uint32_t xa1 = sb + OFF_XS + (w * 16 + ((t1 & 31) >> 2)) * 8;
        const float2 s0 = lds64f(xa1), s1 = lds64f(xa1 + 64);
        uint32_t z[48];
        float st[4];
        if (CFENCE) fence_async_smem();
        fold_mean(d, sb + OFF_CS + (1 - wg) * 768, s0.x, s1.x, t1 & 3);
        if (G1_AT == 1 && wg == 0) bar_arrive(NB_G1, 256);
        WG_WAIT(0);
        acc_fence<96>(d);
        gelu_tile(d, z, st, s0.y, s1.y);
        const int tid = tid_now(), lane = tid & 31, g = lane >> 2, t = lane & 3;
        if (wg == 1) {
          uint32_t bra, brb;
          asm volatile("ld.shared.u16 %0, [%1];" : "=r"(bra) : "r"(sb + OFF_BIAS + (w * 16 + g) * 2));
          asm volatile("ld.shared.u16 %0, [%1+16];" : "=r"(brb) : "r"(sb + OFF_BIAS + (w * 16 + g) * 2));
#pragma unroll
          for (int j = 0; j < 96; j++) d[j] = bf_lo((j & 2) ? brb : bra);
          STAMPW(15);
          gemm_loop<192, true, 1, D2>(d, sb, 32, 0, 1, 20, 0, 2, 2, tid, [&]() { if (HOLD_AT < 32) mbar_arrive_if(sb + BAR_GO, tid == 0); }, [](int) {});
          if (HOLD_AT == 32) mbar_arrive_if(sb + BAR_GO, tid == 0);
          STAMPW(16);
          const int t2 = tid_now(), l2 = t2 & 31;
          const uint32_t ha = sb + OFF_A + 5 * A_SLOT + (l2 >> 4) * 1024 + (2 * w + ((l2 >> 3) & 1)) * 128 + (l2 & 7) * 16;
#pragma unroll
          for (int j = 0; j < 24; j += 2) {
#pragma unroll
            for (int e = 0; e < 4; e++) z[2 * j + e] = hmul2(z[2 * j + e], pack2(d[4 * j + 2 * e], d[4 * j + 2 * e + 1]));
            stsm4(ha + j * 1024, z[2 * j], z[2 * j + 1], z[2 * j + 2], z[2 * j + 3]);
          }
          fence_async_smem();
          bar_sync(NB_WGB, 128);
          mbar_arrive_if(sb + BAR_AF + 8 * (t2 == 3 ? (BAR_G2 - BAR_AF) / 8 : (t2 == 4 ? (BAR_GO - BAR_AF) / 8 : 5 + t2)), t2 < (HOLD_AT == 33 ? 5 : 4));
          STAMPW(17);
          {
            float e[80];
#pragma unroll
            for (int j = 0; j < 80; j++) e[j] = 0.f;
            gemm_loop<160, false, 2, DB>(e, sb, 12, 5, 0, 2, 0, 2, 2, tid_now(), []() {}, [](int) {});
            STAMPW(10);
            const int t3 = tid_now();
#pragma unroll
            for (int j = 0; j < 10; j++) {
              sts128(sb + OFF_A + j * 2048 + t3 * 16, pack2(e[8 * j], e[8 * j + 1]), pack2(e[8 * j + 2], e[8 * j + 3]), pack2(e[8 * j + 4], e[8 * j + 5]),
                     pack2(e[8 * j + 6], e[8 * j + 7]));
              if (j == 4) bar_arrive(NB_WO, 256);
            }
            bar_arrive(NB_Z, 256);
            STAMPW(45);
          }
          return;
        }
        float sa = st[0], qa = st[1], sbb = st[2], qb = st[3];
#pragma unroll
        for (int o = 1; o <= 2; o <<= 1) {
          sa += __shfl_xor_sync(0xffffffff, sa, o); qa += __shfl_xor_sync(0xffffffff, qa, o);
          sbb += __shfl_xor_sync(0xffffffff, sbb, o); qb += __shfl_xor_sync(0xffffffff, qb, o);
        }
        const uint32_t tag = lds32<0>(sb + OFF_TAG);
        if (t < 2) st_ll4(&p.scr->zstat[rb * 256 + cb * 64 + w * 16 + g + t * 8], __float_as_uint(t ? sbb : sa), tag, __float_as_uint(t ? qb : qa), tag);
        STAMPW(2);
        const float ca = 0.5f * s0.y, cbb = 0.5f * s1.y;
        {
          const uint4* zs = &p.scr->zstat[rb * 256 + t * 64 + w * 16 + g];
          uint4 u0 = ld_ll4(zs), u1 = ld_ll4(zs + 8);
          final_load_x(xw, sb + OFF_A, cb, 0, w, lane);
          fence_async_smem();
          bar_sync(NB_WGA, 128);
          mbar_arrive_if(sb + BAR_AE + 8 * tid, tid < NA);
          uint32_t t0 = 0;
#pragma unroll 1
          while (!__all_sync(0xffffffff, u0.y == tag && u0.w == tag && u1.y == tag && u1.w == tag)) {
            spin_guard(t0);
            u0 = ld_ll4(zs); u1 = ld_ll4(zs + 8);
          }
          sa = __uint_as_float(u0.x); qa = __uint_as_float(u0.z); sbb = __uint_as_float(u1.x); qb = __uint_as_float(u1.z);
          STAMPW(3);
        }
#pragma unroll
        for (int o = 1; o <= 2; o <<= 1) {
          sa += __shfl_xor_sync(0xffffffff, sa, o); qa += __shfl_xor_sync(0xffffffff, qa, o);
          sbb += __shfl_xor_sync(0xffffffff, sbb, o); qb += __shfl_xor_sync(0xffffffff, qb, o);
        }
        const float inv = 1.f / 768.f;
        const float ma = sa * inv, mb = sbb * inv;
        const float ra = ca * rsqrtf(fmaf(fmaxf(fmaf(-ma, ma, qa * inv), 0.f), ca * ca, 1e-5f));
        const float rb_ = cbb * rsqrtf(fmaf(fmaxf(fmaf(-mb, mb, qb * inv), 0.f), cbb * cbb, 1e-5f));
        const uint32_t ra2 = pack2(ra, ra), rb2 = pack2(rb_, rb_);
        const float na = -ma * bf_lo(ra2), nb = -mb * bf_lo(rb2);
        {
          const uint32_t n2a = pack2(na, na), n2b = pack2(nb, nb);
          const uint32_t za = sb + OFF_A + LEAD * A_SLOT + (2 * w + ((lane >> 3) & 1)) * 3072 + (lane >> 4) * 128 + (lane & 7) * 16;
          mbar_wait2(sb + BAR_AE + 8 * (LEAD + 2), 0, sb + BAR_KU + 16, 0);
#pragma unroll
          for (int j = 0; j < 24; j += 2)
            stsm4(za + j * 128, hfma2(z[2 * j], ra2, n2a), hfma2(z[2 * j + 1], rb2, n2b), hfma2(z[2 * j + 2], ra2, n2a), hfma2(z[2 * j + 3], rb2, n2b));
          fence_async_smem();
        }
      }
      bar_arrive(NB_Z, 160);
      {
        const uint32_t zero = lds32<0>(sb + OFF_TAG + 4);
#pragma unroll
        for (int i = 0; i < 20; i++) xw[i / 10][i % 10] |= zero;
      }
      load_taps(k, p, chb + 64, tid_now());
      STAMPW(4);
    }
    const int h = wg >> 1;
    {
    const int tid = tid_now(), lane = tid & 31;
    conv_worker(p, k, sb + OFF_CV + (1 - h) * CV_SZ, sb + OFF_A + 9 * A_SLOT + h * 4096, sb + BAR_XF + 8 * h, NB_WGA + h,
                chb + (h ? 0 : 64), 2 + h, sb + BAR_GO, w, lane, tid, h ? 40 : 5, rb, cb);
    {
      const int t3 = tid_now(), l3 = t3 & 31;
      const uint32_t xs_addr = sb + OFF_XS + (w * 16 + (l3 >> 2)) * 8;
      const float2 s0 = lds64f(xs_addr), s1 = lds64f(xs_addr + 64);
      const uint32_t ya = sb + y_tile(h) + ((l3 >> 4) * 8 + (l3 & 7)) * 128 + (((2 * w + ((l3 >> 3) & 1)) ^ (l3 & 7) ^ (rb & 7)) << 4);
      uint32_t sw[2][10];
      mbar_wait(sb + BAR_XF + 8 * h, h);
      final_s_early(sw, xw, ya, s0, s1);
      uint32_t ph = 1, t0 = 0, y[8];
#pragma unroll 1
      while (true) {
        mbar_wait(sb + BAR_YL + 16 * h, ph);
        if (bar_all(NB_WGA + h, 128, final_late(y, ya))) break;
        spin_guard(t0);
        ph ^= 1;
        if (t3 == 0) load_late_y(p, sb, h, rb, cb, lds32<0>(sb + OFF_TAG) & 1);
      }
#pragma unroll
      for (int e = 0; e < 8; e++) sw[e & 1][4 + (e >> 1)] = hmul2(sw[e & 1][4 + (e >> 1)], ~y[e]);
      __nv_bfloat16* o0 = p.out + (size_t)(w * 512 + rb * 16 + (l3 >> 2)) * kD + seg_col(cb, h);
      STAMPW(h ? 44 : 9);
      bar_sync(h ? NB_Z : NB_WO, 256);
      float d[40];
#pragma unroll
      for (int j = 0; j < 5; j++) {
        const uint4 v = lds128(sb + OFF_A + (h * 5 + j) * 2048 + t3 * 16);
        d[8 * j] = bf_lo(v.x); d[8 * j + 1] = bf_hi(v.x); d[8 * j + 2] = bf_lo(v.y); d[8 * j + 3] = bf_hi(v.y);
        d[8 * j + 4] = bf_lo(v.z); d[8 * j + 5] = bf_hi(v.z); d[8 * j + 6] = bf_lo(v.w); d[8 * j + 7] = bf_hi(v.w);
      }
      final_out(d, xw, sw, s0.y, s1.y, o0, h, l3 & 3);
    }
    }
  }
}

typedef CUresult (*EncodeFn)(CUtensorMap*, CUtensorMapDataType, cuuint32_t, void*, const cuuint64_t*, const cuuint64_t*, const cuuint32_t*,
                             const cuuint32_t*, CUtensorMapInterleave, CUtensorMapSwizzle, CUtensorMapL2promotion, CUtensorMapFloatOOBfill);

void encode(EncodeFn fn, CUtensorMap* m, const void* ptr, int rank, const cuuint64_t* dims, const cuuint64_t* strides, const cuuint32_t* box,
            CUtensorMapSwizzle swz = CU_TENSOR_MAP_SWIZZLE_128B) {
  const cuuint32_t es[3] = {1, 1, 1};
  fn(m, CU_TENSOR_MAP_DATA_TYPE_BFLOAT16, rank, const_cast<void*>(ptr), dims, strides, box, es, CU_TENSOR_MAP_INTERLEAVE_NONE,
     swz, CU_TENSOR_MAP_L2_PROMOTION_L2_128B, CU_TENSOR_MAP_FLOAT_OOB_FILL_NONE);
}

}

extern "C" void kernel_launch(void* const* d_in, const int* in_sizes, int n_in, void* d_out, int out_size) {
  (void)in_sizes; (void)n_in; (void)out_size;
  static EncodeFn enc = nullptr;
  static Scratch* scr = nullptr;
  static int sms = 0;
  if (!enc) {
    void* fn = nullptr;
    cudaDriverEntryPointQueryResult qr;
    cudaGetDriverEntryPoint("cuTensorMapEncodeTiled", &fn, cudaEnableDefault, &qr);
    enc = (EncodeFn)fn;
    cudaFuncSetAttribute(fused_kernel, cudaFuncAttributeMaxDynamicSharedMemorySize, SMEM_BYTES);
    cudaGetSymbolAddress((void**)&scr, g_scr);
    int dev = 0;
    cudaGetDevice(&dev);
    cudaDeviceGetAttribute(&sms, cudaDevAttrMultiProcessorCount, dev);
  }
  Params p;
  p.scr = scr;
  p.by_smid = sms == 132;
  p.k = (const __nv_bfloat16*)d_in[1];
  p.v = (const __nv_bfloat16*)d_in[2];
  p.shift = (const __nv_bfloat16*)d_in[3];
  p.ssmk = (const __nv_bfloat16*)d_in[4];
  p.ssmD = (const __nv_bfloat16*)d_in[5];
  p.wsp = (const __nv_bfloat16*)d_in[8];
  p.bsp = (const __nv_bfloat16*)d_in[9];
  p.wout = (const __nv_bfloat16*)d_in[10];
  p.out = (__nv_bfloat16*)d_out;
  for (int i = 0; i < 2; i++) {
    const cuuint64_t n = i ? kS : kD, dims[3] = {n, 512, 4}, st[2] = {n * 2, n * 1024};
    const cuuint32_t box[3] = {64, 16, 4};
    encode(enc, i ? &p.tmWsp : &p.tmX, d_in[i ? 8 : 0], 3, dims, st, box);
  }
  {
    const cuuint64_t dims[3] = {64, kD, kF / 64}, st[2] = {kF * 2, 128};
    const cuuint32_t box[3] = {64, 64, 3};
    encode(enc, &p.tmW, d_in[7], 3, dims, st, box);
  }
  {
    const cuuint64_t dims[2] = {kS, 896}, st[1] = {kS * 2};
    const cuuint32_t box[2] = {64, 16};
    encode(enc, &p.tmY, scr->y, 2, dims, st, box);
  }
  {
    const cuuint64_t dims[3] = {1024, kD / 2, 4}, st[2] = {8192, 2048};
    const cuuint32_t box[3] = {16, 32, 4};
    encode(enc, &p.tmKV, scr->kvx, 3, dims, st, box, CU_TENSOR_MAP_SWIZZLE_32B);
  }
  fused_kernel<<<132, 512, SMEM_BYTES, cudaStreamPerThread>>>(p);
}
```

```cpp
#include <cuda_runtime.h>
#include <cuda.h>
#include <cuda_bf16.h>
#include <stdint.h>

template <int N> struct WG;
template <> struct WG<16> {
  static __device__ __forceinline__ void rs(float* d, const uint32_t* a, uint64_t db) {
    asm volatile("{\n.reg .pred p;\nsetp.ne.b32 p, 1, 0;\nwgmma.mma_async.sync.aligned.m64n16k16.f32.bf16.bf16 {"
      "%0, %1, %2, %3, %4, %5, %6, %7"
      "}, {%8, %9, %10, %11}, %12, p, 1, 1, 0;\n}\n"
      :
      "+f"(d[0]), "+f"(d[1]), "+f"(d[2]), "+f"(d[3]), "+f"(d[4]), "+f"(d[5]), "+f"(d[6]), "+f"(d[7])
      : "r"(a[0]), "r"(a[1]), "r"(a[2]), "r"(a[3]), "l"(db));
  }
};
template <> struct WG<32> {
  static __device__ __forceinline__ void rs(float* d, const uint32_t* a, uint64_t db) {
    asm volatile("{\n.reg .pred p;\nsetp.ne.b32 p, 1, 0;\nwgmma.mma_async.sync.aligned.m64n32k16.f32.bf16.bf16 {"
      "%0, %1, %2, %3, %4, %5, %6, %7, %8, %9, %10, %11, %12, %13, %14, %15"
      "}, {%16, %17, %18, %19}, %20, p, 1, 1, 0;\n}\n"
      :
      "+f"(d[0]), "+f"(d[1]), "+f"(d[2]), "+f"(d[3]), "+f"(d[4]), "+f"(d[5]), "+f"(d[6]), "+f"(d[7]),
      "+f"(d[8]), "+f"(d[9]), "+f"(d[10]), "+f"(d[11]), "+f"(d[12]), "+f"(d[13]), "+f"(d[14]), "+f"(d[15])
      : "r"(a[0]), "r"(a[1]), "r"(a[2]), "r"(a[3]), "l"(db));
  }
};
template <> struct WG<48> {
  static __device__ __forceinline__ void rs(float* d, const uint32_t* a, uint64_t db) {
    asm volatile("{\n.reg .pred p;\nsetp.ne.b32 p, 1, 0;\nwgmma.mma_async.sync.aligned.m64n48k16.f32.bf16.bf16 {"
      "%0, %1, %2, %3, %4, %5, %6, %7, %8, %9, %10, %11, %12, %13, %14, %15, "
      "%16, %17, %18, %19, %20, %21, %22, %23"
      "}, {%24, %25, %26, %27}, %28, p, 1, 1, 0;\n}\n"
      :
      "+f"(d[0]), "+f"(d[1]), "+f"(d[2]), "+f"(d[3]), "+f"(d[4]), "+f"(d[5]), "+f"(d[6]), "+f"(d[7]),
      "+f"(d[8]), "+f"(d[9]), "+f"(d[10]), "+f"(d[11]), "+f"(d[12]), "+f"(d[13]), "+f"(d[14]), "+f"(d[15]),
      "+f"(d[16]), "+f"(d[17]), "+f"(d[18]), "+f"(d[19]), "+f"(d[20]), "+f"(d[21]), "+f"(d[22]), "+f"(d[23])
      : "r"(a[0]), "r"(a[1]), "r"(a[2]), "r"(a[3]), "l"(db));
  }
};
template <> struct WG<64> {
  static __device__ __forceinline__ void rs(float* d, const uint32_t* a, uint64_t db) {
    asm volatile("{\n.reg .pred p;\nsetp.ne.b32 p, 1, 0;\nwgmma.mma_async.sync.aligned.m64n64k16.f32.bf16.bf16 {"
      "%0, %1, %2, %3, %4, %5, %6, %7, %8, %9, %10, %11, %12, %13, %14, %15, "
      "%16, %17, %18, %19, %20, %21, %22, %23, %24, %25, %26, %27, %28, %29, %30, %31"
      "}, {%32, %33, %34, %35}, %36, p, 1, 1, 0;\n}\n"
      :
      "+f"(d[0]), "+f"(d[1]), "+f"(d[2]), "+f"(d[3]), "+f"(d[4]), "+f"(d[5]), "+f"(d[6]), "+f"(d[7]),
      "+f"(d[8]), "+f"(d[9]), "+f"(d[10]), "+f"(d[11]), "+f"(d[12]), "+f"(d[13]), "+f"(d[14]), "+f"(d[15]),
      "+f"(d[16]), "+f"(d[17]), "+f"(d[18]), "+f"(d[19]), "+f"(d[20]), "+f"(d[21]), "+f"(d[22]), "+f"(d[23]),
      "+f"(d[24]), "+f"(d[25]), "+f"(d[26]), "+f"(d[27]), "+f"(d[28]), "+f"(d[29]), "+f"(d[30]), "+f"(d[31])
      : "r"(a[0]), "r"(a[1]), "r"(a[2]), "r"(a[3]), "l"(db));
  }
};
template <> struct WG<80> {
  static __device__ __forceinline__ void rs(float* d, const uint32_t* a, uint64_t db) {
    asm volatile("{\n.reg .pred p;\nsetp.ne.b32 p, 1, 0;\nwgmma.mma_async.sync.aligned.m64n80k16.f32.bf16.bf16 {"
      "%0, %1, %2, %3, %4, %5, %6, %7, %8, %9, %10, %11, %12, %13, %14, %15, "
      "%16, %17, %18, %19, %20, %21, %22, %23, %24, %25, %26, %27, %28, %29, %30, %31, "
      "%32, %33, %34, %35, %36, %37, %38, %39"
      "}, {%40, %41, %42, %43}, %44, p, 1, 1, 0;\n}\n"
      :
      "+f"(d[0]), "+f"(d[1]), "+f"(d[2]), "+f"(d[3]), "+f"(d[4]), "+f"(d[5]), "+f"(d[6]), "+f"(d[7]),
      "+f"(d[8]), "+f"(d[9]), "+f"(d[10]), "+f"(d[11]), "+f"(d[12]), "+f"(d[13]), "+f"(d[14]), "+f"(d[15]),
      "+f"(d[16]), "+f"(d[17]), "+f"(d[18]), "+f"(d[19]), "+f"(d[20]), "+f"(d[21]), "+f"(d[22]), "+f"(d[23]),
      "+f"(d[24]), "+f"(d[25]), "+f"(d[26]), "+f"(d[27]), "+f"(d[28]), "+f"(d[29]), "+f"(d[30]), "+f"(d[31]),
      "+f"(d[32]), "+f"(d[33]), "+f"(d[34]), "+f"(d[35]), "+f"(d[36]), "+f"(d[37]), "+f"(d[38]), "+f"(d[39])
      : "r"(a[0]), "r"(a[1]), "r"(a[2]), "r"(a[3]), "l"(db));
  }
};
template <> struct WG<96> {
  static __device__ __forceinline__ void rs(float* d, const uint32_t* a, uint64_t db) {
    asm volatile("{\n.reg .pred p;\nsetp.ne.b32 p, 1, 0;\nwgmma.mma_async.sync.aligned.m64n96k16.f32.bf16.bf16 {"
      "%0, %1, %2, %3, %4, %5, %6, %7, %8, %9, %10, %11, %12, %13, %14, %15, "
      "%16, %17, %18, %19, %20, %21, %22, %23, %24, %25, %26, %27, %28, %29, %30, %31, "
      "%32, %33, %34, %35, %36, %37, %38, %39, %40, %41, %42, %43, %44, %45, %46, %47"
      "}, {%48, %49, %50, %51}, %52, p, 1, 1, 0;\n}\n"
      :
      "+f"(d[0]), "+f"(d[1]), "+f"(d[2]), "+f"(d[3]), "+f"(d[4]), "+f"(d[5]), "+f"(d[6]), "+f"(d[7]),
      "+f"(d[8]), "+f"(d[9]), "+f"(d[10]), "+f"(d[11]), "+f"(d[12]), "+f"(d[13]), "+f"(d[14]), "+f"(d[15]),
      "+f"(d[16]), "+f"(d[17]), "+f"(d[18]), "+f"(d[19]), "+f"(d[20]), "+f"(d[21]), "+f"(d[22]), "+f"(d[23]),
      "+f"(d[24]), "+f"(d[25]), "+f"(d[26]), "+f"(d[27]), "+f"(d[28]), "+f"(d[29]), "+f"(d[30]), "+f"(d[31]),
      "+f"(d[32]), "+f"(d[33]), "+f"(d[34]), "+f"(d[35]), "+f"(d[36]), "+f"(d[37]), "+f"(d[38]), "+f"(d[39]),
      "+f"(d[40]), "+f"(d[41]), "+f"(d[42]), "+f"(d[43]), "+f"(d[44]), "+f"(d[45]), "+f"(d[46]), "+f"(d[47])
      : "r"(a[0]), "r"(a[1]), "r"(a[2]), "r"(a[3]), "l"(db));
  }
};
template <> struct WG<112> {
  static __device__ __forceinline__ void rs(float* d, const uint32_t* a, uint64_t db) {
    asm volatile("{\n.reg .pred p;\nsetp.ne.b32 p, 1, 0;\nwgmma.mma_async.sync.aligned.m64n112k16.f32.bf16.bf16 {"
      "%0, %1, %2, %3, %4, %5, %6, %7, %8, %9, %10, %11, %12, %13, %14, %15, "
      "%16, %17, %18, %19, %20, %21, %22, %23, %24, %25, %26, %27, %28, %29, %30, %31, "
      "%32, %33, %34, %35, %36, %37, %38, %39, %40, %41, %42, %43, %44, %45, %46, %47, "
      "%48, %49, %50, %51, %52, %53, %54, %55"
      "}, {%56, %57, %58, %59}, %60, p, 1, 1, 0;\n}\n"
      :
      "+f"(d[0]), "+f"(d[1]), "+f"(d[2]), "+f"(d[3]), "+f"(d[4]), "+f"(d[5]), "+f"(d[6]), "+f"(d[7]),
      "+f"(d[8]), "+f"(d[9]), "+f"(d[10]), "+f"(d[11]), "+f"(d[12]), "+f"(d[13]), "+f"(d[14]), "+f"(d[15]),
      "+f"(d[16]), "+f"(d[17]), "+f"(d[18]), "+f"(d[19]), "+f"(d[20]), "+f"(d[21]), "+f"(d[22]), "+f"(d[23]),
      "+f"(d[24]), "+f"(d[25]), "+f"(d[26]), "+f"(d[27]), "+f"(d[28]), "+f"(d[29]), "+f"(d[30]), "+f"(d[31]),
      "+f"(d[32]), "+f"(d[33]), "+f"(d[34]), "+f"(d[35]), "+f"(d[36]), "+f"(d[37]), "+f"(d[38]), "+f"(d[39]),
      "+f"(d[40]), "+f"(d[41]), "+f"(d[42]), "+f"(d[43]), "+f"(d[44]), "+f"(d[45]), "+f"(d[46]), "+f"(d[47]),
      "+f"(d[48]), "+f"(d[49]), "+f"(d[50]), "+f"(d[51]), "+f"(d[52]), "+f"(d[53]), "+f"(d[54]), "+f"(d[55])
      : "r"(a[0]), "r"(a[1]), "r"(a[2]), "r"(a[3]), "l"(db));
  }
};
template <> struct WG<128> {
  static __device__ __forceinline__ void rs(float* d, const uint32_t* a, uint64_t db) {
    asm volatile("{\n.reg .pred p;\nsetp.ne.b32 p, 1, 0;\nwgmma.mma_async.sync.aligned.m64n128k16.f32.bf16.bf16 {"
      "%0, %1, %2, %3, %4, %5, %6, %7, %8, %9, %10, %11, %12, %13, %14, %15, "
      "%16, %17, %18, %19, %20, %21, %22, %23, %24, %25, %26, %27, %28, %29, %30, %31, "
      "%32, %33, %34, %35, %36, %37, %38, %39, %40, %41, %42, %43, %44, %45, %46, %47, "
      "%48, %49, %50, %51, %52, %53, %54, %55, %56, %57, %58, %59, %60, %61, %62, %63"
      "}, {%64, %65, %66, %67}, %68, p, 1, 1, 0;\n}\n"
      :
      "+f"(d[0]), "+f"(d[1]), "+f"(d[2]), "+f"(d[3]), "+f"(d[4]), "+f"(d[5]), "+f"(d[6]), "+f"(d[7]),
      "+f"(d[8]), "+f"(d[9]), "+f"(d[10]), "+f"(d[11]), "+f"(d[12]), "+f"(d[13]), "+f"(d[14]), "+f"(d[15]),
      "+f"(d[16]), "+f"(d[17]), "+f"(d[18]), "+f"(d[19]), "+f"(d[20]), "+f"(d[21]), "+f"(d[22]), "+f"(d[23]),
      "+f"(d[24]), "+f"(d[25]), "+f"(d[26]), "+f"(d[27]), "+f"(d[28]), "+f"(d[29]), "+f"(d[30]), "+f"(d[31]),
      "+f"(d[32]), "+f"(d[33]), "+f"(d[34]), "+f"(d[35]), "+f"(d[36]), "+f"(d[37]), "+f"(d[38]), "+f"(d[39]),
      "+f"(d[40]), "+f"(d[41]), "+f"(d[42]), "+f"(d[43]), "+f"(d[44]), "+f"(d[45]), "+f"(d[46]), "+f"(d[47]),
      "+f"(d[48]), "+f"(d[49]), "+f"(d[50]), "+f"(d[51]), "+f"(d[52]), "+f"(d[53]), "+f"(d[54]), "+f"(d[55]),
      "+f"(d[56]), "+f"(d[57]), "+f"(d[58]), "+f"(d[59]), "+f"(d[60]), "+f"(d[61]), "+f"(d[62]), "+f"(d[63])
      : "r"(a[0]), "r"(a[1]), "r"(a[2]), "r"(a[3]), "l"(db));
  }
};
template <> struct WG<160> {
  static __device__ __forceinline__ void ss(float* d, uint64_t da, uint64_t db, int sd) {
    asm volatile("{\n.reg .pred p;\nsetp.ne.b32 p, %82, 0;\nwgmma.mma_async.sync.aligned.m64n160k16.f32.bf16.bf16 {"
      "%0, %1, %2, %3, %4, %5, %6, %7, %8, %9, %10, %11, %12, %13, %14, %15, "
      "%16, %17, %18, %19, %20, %21, %22, %23, %24, %25, %26, %27, %28, %29, %30, %31, "
      "%32, %33, %34, %35, %36, %37, %38, %39, %40, %41, %42, %43, %44, %45, %46, %47, "
      "%48, %49, %50, %51, %52, %53, %54, %55, %56, %57, %58, %59, %60, %61, %62, %63, "
      "%64, %65, %66, %67, %68, %69, %70, %71, %72, %73, %74, %75, %76, %77, %78, %79"
      "}, %80, %81, p, 1, 1, 0, 1;\n}\n"
      :
      "+f"(d[0]), "+f"(d[1]), "+f"(d[2]), "+f"(d[3]), "+f"(d[4]), "+f"(d[5]), "+f"(d[6]), "+f"(d[7]),
      "+f"(d[8]), "+f"(d[9]), "+f"(d[10]), "+f"(d[11]), "+f"(d[12]), "+f"(d[13]), "+f"(d[14]), "+f"(d[15]),
      "+f"(d[16]), "+f"(d[17]), "+f"(d[18]), "+f"(d[19]), "+f"(d[20]), "+f"(d[21]), "+f"(d[22]), "+f"(d[23]),
      "+f"(d[24]), "+f"(d[25]), "+f"(d[26]), "+f"(d[27]), "+f"(d[28]), "+f"(d[29]), "+f"(d[30]), "+f"(d[31]),
      "+f"(d[32]), "+f"(d[33]), "+f"(d[34]), "+f"(d[35]), "+f"(d[36]), "+f"(d[37]), "+f"(d[38]), "+f"(d[39]),
      "+f"(d[40]), "+f"(d[41]), "+f"(d[42]), "+f"(d[43]), "+f"(d[44]), "+f"(d[45]), "+f"(d[46]), "+f"(d[47]),
      "+f"(d[48]), "+f"(d[49]), "+f"(d[50]), "+f"(d[51]), "+f"(d[52]), "+f"(d[53]), "+f"(d[54]), "+f"(d[55]),
      "+f"(d[56]), "+f"(d[57]), "+f"(d[58]), "+f"(d[59]), "+f"(d[60]), "+f"(d[61]), "+f"(d[62]), "+f"(d[63]),
      "+f"(d[64]), "+f"(d[65]), "+f"(d[66]), "+f"(d[67]), "+f"(d[68]), "+f"(d[69]), "+f"(d[70]), "+f"(d[71]),
      "+f"(d[72]), "+f"(d[73]), "+f"(d[74]), "+f"(d[75]), "+f"(d[76]), "+f"(d[77]), "+f"(d[78]), "+f"(d[79])
      : "l"(da), "l"(db), "r"(sd));
  }
};
template <> struct WG<192> {
  static __device__ __forceinline__ void ss(float* d, uint64_t da, uint64_t db, int sd) {
    asm volatile("{\n.reg .pred p;\nsetp.ne.b32 p, %98, 0;\nwgmma.mma_async.sync.aligned.m64n192k16.f32.bf16.bf16 {"
      "%0, %1, %2, %3, %4, %5, %6, %7, %8, %9, %10, %11, %12, %13, %14, %15, "
      "%16, %17, %18, %19, %20, %21, %22, %23, %24, %25, %26, %27, %28, %29, %30, %31, "
      "%32, %33, %34, %35, %36, %37, %38, %39, %40, %41, %42, %43, %44, %45, %46, %47, "
      "%48, %49, %50, %51, %52, %53, %54, %55, %56, %57, %58, %59, %60, %61, %62, %63, "
      "%64, %65, %66, %67, %68, %69, %70, %71, %72, %73, %74, %75, %76, %77, %78, %79, "
      "%80, %81, %82, %83, %84, %85, %86, %87, %88, %89, %90, %91, %92, %93, %94, %95"
      "}, %96, %97, p, 1, 1, 0, 1;\n}\n"
      :
      "+f"(d[0]), "+f"(d[1]), "+f"(d[2]), "+f"(d[3]), "+f"(d[4]), "+f"(d[5]), "+f"(d[6]), "+f"(d[7]),
      "+f"(d[8]), "+f"(d[9]), "+f"(d[10]), "+f"(d[11]), "+f"(d[12]), "+f"(d[13]), "+f"(d[14]), "+f"(d[15]),
      "+f"(d[16]), "+f"(d[17]), "+f"(d[18]), "+f"(d[19]), "+f"(d[20]), "+f"(d[21]), "+f"(d[22]), "+f"(d[23]),
      "+f"(d[24]), "+f"(d[25]), "+f"(d[26]), "+f"(d[27]), "+f"(d[28]), "+f"(d[29]), "+f"(d[30]), "+f"(d[31]),
      "+f"(d[32]), "+f"(d[33]), "+f"(d[34]), "+f"(d[35]), "+f"(d[36]), "+f"(d[37]), "+f"(d[38]), "+f"(d[39]),
      "+f"(d[40]), "+f"(d[41]), "+f"(d[42]), "+f"(d[43]), "+f"(d[44]), "+f"(d[45]), "+f"(d[46]), "+f"(d[47]),
      "+f"(d[48]), "+f"(d[49]), "+f"(d[50]), "+f"(d[51]), "+f"(d[52]), "+f"(d[53]), "+f"(d[54]), "+f"(d[55]),
      "+f"(d[56]), "+f"(d[57]), "+f"(d[58]), "+f"(d[59]), "+f"(d[60]), "+f"(d[61]), "+f"(d[62]), "+f"(d[63]),
      "+f"(d[64]), "+f"(d[65]), "+f"(d[66]), "+f"(d[67]), "+f"(d[68]), "+f"(d[69]), "+f"(d[70]), "+f"(d[71]),
      "+f"(d[72]), "+f"(d[73]), "+f"(d[74]), "+f"(d[75]), "+f"(d[76]), "+f"(d[77]), "+f"(d[78]), "+f"(d[79]),
      "+f"(d[80]), "+f"(d[81]), "+f"(d[82]), "+f"(d[83]), "+f"(d[84]), "+f"(d[85]), "+f"(d[86]), "+f"(d[87]),
      "+f"(d[88]), "+f"(d[89]), "+f"(d[90]), "+f"(d[91]), "+f"(d[92]), "+f"(d[93]), "+f"(d[94]), "+f"(d[95])
      : "l"(da), "l"(db), "r"(sd));
  }
  static __device__ __forceinline__ void rst(float* d, const uint32_t* a, uint64_t db) {
    asm volatile("{\n.reg .pred p;\nsetp.ne.b32 p, 1, 0;\nwgmma.mma_async.sync.aligned.m64n192k16.f32.bf16.bf16 {"
      "%0, %1, %2, %3, %4, %5, %6, %7, %8, %9, %10, %11, %12, %13, %14, %15, "
      "%16, %17, %18, %19, %20, %21, %22, %23, %24, %25, %26, %27, %28, %29, %30, %31, "
      "%32, %33, %34, %35, %36, %37, %38, %39, %40, %41, %42, %43, %44, %45, %46, %47, "
      "%48, %49, %50, %51, %52, %53, %54, %55, %56, %57, %58, %59, %60, %61, %62, %63, "
      "%64, %65, %66, %67, %68, %69, %70, %71, %72, %73, %74, %75, %76, %77, %78, %79, "
      "%80, %81, %82, %83, %84, %85, %86, %87, %88, %89, %90, %91, %92, %93, %94, %95"
      "}, {%96, %97, %98, %99}, %100, p, 1, 1, 1;\n}\n"
      :
      "+f"(d[0]), "+f"(d[1]), "+f"(d[2]), "+f"(d[3]), "+f"(d[4]), "+f"(d[5]), "+f"(d[6]), "+f"(d[7]),
      "+f"(d[8]), "+f"(d[9]), "+f"(d[10]), "+f"(d[11]), "+f"(d[12]), "+f"(d[13]), "+f"(d[14]), "+f"(d[15]),
      "+f"(d[16]), "+f"(d[17]), "+f"(d[18]), "+f"(d[19]), "+f"(d[20]), "+f"(d[21]), "+f"(d[22]), "+f"(d[23]),
      "+f"(d[24]), "+f"(d[25]), "+f"(d[26]), "+f"(d[27]), "+f"(d[28]), "+f"(d[29]), "+f"(d[30]), "+f"(d[31]),
      "+f"(d[32]), "+f"(d[33]), "+f"(d[34]), "+f"(d[35]), "+f"(d[36]), "+f"(d[37]), "+f"(d[38]), "+f"(d[39]),
      "+f"(d[40]), "+f"(d[41]), "+f"(d[42]), "+f"(d[43]), "+f"(d[44]), "+f"(d[45]), "+f"(d[46]), "+f"(d[47]),
      "+f"(d[48]), "+f"(d[49]), "+f"(d[50]), "+f"(d[51]), "+f"(d[52]), "+f"(d[53]), "+f"(d[54]), "+f"(d[55]),
      "+f"(d[56]), "+f"(d[57]), "+f"(d[58]), "+f"(d[59]), "+f"(d[60]), "+f"(d[61]), "+f"(d[62]), "+f"(d[63]),
      "+f"(d[64]), "+f"(d[65]), "+f"(d[66]), "+f"(d[67]), "+f"(d[68]), "+f"(d[69]), "+f"(d[70]), "+f"(d[71]),
      "+f"(d[72]), "+f"(d[73]), "+f"(d[74]), "+f"(d[75]), "+f"(d[76]), "+f"(d[77]), "+f"(d[78]), "+f"(d[79]),
      "+f"(d[80]), "+f"(d[81]), "+f"(d[82]), "+f"(d[83]), "+f"(d[84]), "+f"(d[85]), "+f"(d[86]), "+f"(d[87]),
      "+f"(d[88]), "+f"(d[89]), "+f"(d[90]), "+f"(d[91]), "+f"(d[92]), "+f"(d[93]), "+f"(d[94]), "+f"(d[95])
      : "r"(a[0]), "r"(a[1]), "r"(a[2]), "r"(a[3]), "l"(db));
  }
};

#define ZPOLL 0
#define ZQ_N 2
#define CFENCE 1
#define Z1_AT 4
#define G1_AT 1
#define HGRP 3
#define HPACE 200
#define DB 0
#define HOLD_AT 33
#define LL_AT 4
#define KV_T0 2300
#define ST_YIELD 1
#define HP0 3500
#define HPD 450
#define RAMP 1
#define LEAD 2
#define WSP_N 16
#define EARLY 0
#define CPIN 1
#define CW0 0
#define PFT 1
#define WSP_D 600
#define D1 4
#define D2 4
#define NSLEEP 32

namespace {

constexpr int kS = 2048, kD = 640, kF = 1536;
constexpr int NA = 10, NA2 = 9, NB = 5;
constexpr int A_SLOT = 8192, B_SLOT = 24576;
constexpr int OFF_A = 0;
constexpr int OFF_B = OFF_A + NA * A_SLOT;
constexpr int XB_PL = 2112;
constexpr int CV_KE = 4224, CV_KO = CV_KE + 4160;
constexpr int CV_SZ = CV_KO + 4160;
constexpr int OFF_CV = OFF_B + NB * B_SLOT;
constexpr int OFF_CS = OFF_CV + 2 * CV_SZ;
constexpr int OFF_BIAS = OFF_CS + 1536;
constexpr int OFF_XS = OFF_BIAS + 128;
constexpr int OFF_BAR = OFF_XS + 512;
constexpr int BAR_AF = OFF_BAR, BAR_ST = BAR_AF + 8 * NA, BAR_XF = BAR_ST + 16, BAR_KV = BAR_XF + 16;
constexpr int BAR_BF = OFF_BAR + 128, BAR_G2 = BAR_BF + 8 * (NB + 1), BAR_XS = BAR_G2 + 8, BAR_KU = BAR_XS + 8, BAR_ZP = BAR_KU + 40, BAR_HOLD = BAR_ZP + 8, BAR_WO = BAR_HOLD + 8;
constexpr int BAR_AE = OFF_BAR + 256, BAR_BE = BAR_AE + 8 * NA;
constexpr int BAR_YT = BAR_KU + 24;
constexpr int BAR_GO = BAR_XS;
constexpr int BAR_YL = BAR_KU + 16;
constexpr int OFF_TAG = OFF_CS - 32;
constexpr int SMEM_BYTES = OFF_BAR + 384;
static_assert(SMEM_BYTES <= 232448, "smem");
constexpr int NB_WGA = 1, NB_WGC = 2, NB_G1 = 3, NB_WO = 4, NB_CD = 5, NB_Z = 6, NB_WGB = 7;

constexpr int CNT_Z = 0, CNT_Y = 1, CNT_Z1 = 3, CNT_KV = 32, CNT_WO = 36;
struct Scratch {
  uint8_t kvx[kD * 4096];
  uint8_t z2[4 * 32 * 24576];
  uint8_t h[32 * 12 * 8192];
  uint8_t wo[4 * 12 * 20480];
  uint8_t y[896 * 4096];
  uint4 xstat[kS];
  uint2 zstat[kS * 8];
  uint2 colsum[kF];
  uint32_t cnt[2 * 32];
  uint32_t hcnt[32 * 32];
  uint32_t epoch[136];
};
__device__ __align__(1024) Scratch g_scr;
#define STAMP(i)
#define STAMP2(i)
#define STAMPW(i)

struct Params {
  Scratch* scr;
  int by_smid;
  const __nv_bfloat16 *k, *v, *shift, *ssmk, *ssmD, *wsp, *bsp, *wout;
  __nv_bfloat16* out;
  CUtensorMap tmX, tmW, tmWsp, tmY, tmKV;
};

__device__ __forceinline__ uint64_t mkdesc(uint32_t addr, uint32_t lbo, uint32_t sbo, uint32_t swz) {
  return (uint64_t)((addr & 0x3FFFF) >> 4) | ((uint64_t)(lbo >> 4) << 16) | ((uint64_t)(sbo >> 4) << 32) | ((uint64_t)swz << 62);
}
#define WG_FENCE() asm volatile("wgmma.fence.sync.aligned;" ::: "memory")
#define WG_COMMIT() asm volatile("wgmma.commit_group.sync.aligned;" ::: "memory")
#define WG_WAIT(n) asm volatile("wgmma.wait_group.sync.aligned %0;" ::"n"(n) : "memory")
template <int N> __device__ __forceinline__ void acc_fence(float* d) {
#pragma unroll
  for (int i = 0; i < N; i++) asm volatile("" : "+f"(d[i])::"memory");
}
__device__ __forceinline__ void mbar_init(uint32_t bar, int cnt) { asm volatile("mbarrier.init.shared::cta.b64 [%0], %1;" ::"r"(bar), "r"(cnt) : "memory"); }
__device__ __forceinline__ void mbar_expect(uint32_t bar, uint32_t bytes) { asm volatile("mbarrier.arrive.expect_tx.shared::cta.b64 _, [%0], %1;" ::"r"(bar), "r"(bytes) : "memory"); }
__device__ __forceinline__ void mbar_arrive(uint32_t bar) { asm volatile("mbarrier.arrive.shared::cta.b64 _, [%0];" ::"r"(bar) : "memory"); }
__device__ __forceinline__ void mbar_arrive_if(uint32_t bar, bool c) {
  asm volatile("{\n.reg .pred p;\nsetp.ne.u32 p, %1, 0;\n@p mbarrier.arrive.shared::cta.b64 _, [%0];\n}\n" ::"r"(bar), "r"((uint32_t)c) : "memory");
}
__device__ __forceinline__ void mbar_expect_if(uint32_t bar, uint32_t bytes, bool c) {
  asm volatile("{\n.reg .pred p;\nsetp.ne.u32 p, %2, 0;\n@p mbarrier.arrive.expect_tx.shared::cta.b64 _, [%0], %1;\n}\n" ::"r"(bar), "r"(bytes), "r"((uint32_t)c) : "memory");
}
__device__ __forceinline__ bool mbar_try(uint32_t bar, uint32_t parity) {
  uint32_t ok;
  asm volatile("{\n.reg .pred p;\nmbarrier.try_wait.parity.shared::cta.b64 p, [%1], %2;\nselp.u32 %0, 1, 0, p;\n}\n" : "=r"(ok) : "r"(bar), "r"(parity) : "memory");
  return ok;
}
__device__ __forceinline__ bool mbar_test(uint32_t bar, uint32_t parity) {
  uint32_t ok;
  asm volatile("{\n.reg .pred p;\nmbarrier.test_wait.parity.shared::cta.b64 p, [%1], %2;\nselp.u32 %0, 1, 0, p;\n}\n" : "=r"(ok) : "r"(bar), "r"(parity) : "memory");
  return ok;
}
__device__ __forceinline__ void die() { asm volatile("st.volatile.global.u32 [%0], %1;" ::"l"(0ull), "r"(0) : "memory"); }
__device__ __forceinline__ void spin_guard(uint32_t& n) { if (++n == (1u << 22)) die(); }
__device__ __forceinline__ void mbar_wait(uint32_t bar, uint32_t parity) {
  uint32_t t0 = 0;
#pragma unroll 1
  while (!mbar_try(bar, parity)) spin_guard(t0);
}
__device__ __forceinline__ void mbar_wait2(uint32_t b0, uint32_t p0, uint32_t b1, uint32_t p1) {
  uint32_t t0 = 0;
#pragma unroll 1
  while (true) {
    const bool r0 = mbar_try(b0, p0), r1 = mbar_try(b1, p1);
    if (r0 && r1) break;
    spin_guard(t0);
  }
}
__device__ __forceinline__ int tid_now() { int v; asm volatile("mov.u32 %0, %%tid.x;" : "=r"(v)); return v & 127; }
__device__ __forceinline__ bool elect_one() {
  uint32_t p;
  asm volatile("{\n.reg .pred P;\nelect.sync _|P, 0xffffffff;\nselp.u32 %0, 1, 0, P;\n}\n" : "=r"(p));
  return p;
}
__device__ __forceinline__ void bar_sync(int id, int n) { asm volatile("bar.sync %0, %1;" ::"r"(id), "r"(n) : "memory"); }
__device__ __forceinline__ void bar_arrive(int id, int n) { asm volatile("bar.arrive %0, %1;" ::"r"(id), "r"(n) : "memory"); }
__device__ __forceinline__ void fence_async_smem() { asm volatile("fence.proxy.async.shared::cta;" ::: "memory"); }
__device__ __forceinline__ void bulk_g2s(uint32_t dst, const void* src, uint32_t bytes, uint32_t bar) {
  asm volatile("cp.async.bulk.shared::cluster.global.mbarrier::complete_tx::bytes [%0], [%1], %2, [%3];" ::"r"(dst), "l"(src), "r"(bytes), "r"(bar) : "memory");
}
__device__ __forceinline__ void bulk_s2g(void* dst, uint32_t src, uint32_t bytes) {
  asm volatile("cp.async.bulk.global.shared::cta.bulk_group [%0], [%1], %2;" ::"l"(dst), "r"(src), "r"(bytes) : "memory");
}
__device__ __forceinline__ void tma2d(uint32_t dst, const CUtensorMap* m, int c0, int c1, uint32_t bar) {
  asm volatile("cp.async.bulk.tensor.2d.shared::cluster.global.mbarrier::complete_tx::bytes [%0], [%1, {%3, %4}], [%2];" ::"r"(dst), "l"(m), "r"(bar), "r"(c0), "r"(c1) : "memory");
}
__device__ __forceinline__ void tma3d(uint32_t dst, const CUtensorMap* m, int c0, int c1, int c2, uint32_t bar) {
  asm volatile("cp.async.bulk.tensor.3d.shared::cluster.global.mbarrier::complete_tx::bytes [%0], [%1, {%3, %4, %5}], [%2];" ::"r"(dst), "l"(m), "r"(bar), "r"(c0), "r"(c1), "r"(c2) : "memory");
}
__device__ __forceinline__ void tma_rows(uint32_t dst, const CUtensorMap* m, int c0, int rb, uint32_t bar) { tma3d(dst, m, c0, rb * 16, 0, bar); }
__device__ __forceinline__ uint4 ld_ll4(const void* p) {
  uint64_t a, b;
  asm volatile("ld.relaxed.gpu.global.v2.u64 {%0,%1}, [%2];" : "=l"(a), "=l"(b) : "l"(p) : "memory");
  return make_uint4((uint32_t)a, (uint32_t)(a >> 32), (uint32_t)b, (uint32_t)(b >> 32));
}
__device__ __forceinline__ void st_ll4(void* p, uint32_t a, uint32_t b, uint32_t c, uint32_t d) {
  asm volatile("st.relaxed.gpu.global.v2.u64 [%0], {%1,%2};" ::"l"(p), "l"(a | ((uint64_t)b << 32)), "l"(c | ((uint64_t)d << 32)) : "memory");
}
__device__ __forceinline__ void st_ll2(void* p, uint32_t a, uint32_t b) { asm volatile("st.relaxed.gpu.global.u64 [%0], %1;" ::"l"(p), "l"(a | ((uint64_t)b << 32)) : "memory"); }
__device__ __forceinline__ uint2 ld_ll2(const void* p) {
  uint64_t a;
  asm volatile("ld.relaxed.gpu.global.u64 %0, [%1];" : "=l"(a) : "l"(p) : "memory");
  return make_uint2((uint32_t)a, (uint32_t)(a >> 32));
}
__device__ __forceinline__ void wgmma_colsum(float* d, uint64_t da, uint64_t db) {
  asm volatile("{\n.reg .pred p;\nsetp.ne.b32 p, 1, 0;\nwgmma.mma_async.sync.aligned.m64n8k16.f32.bf16.bf16 {%0, %1, %2, %3}, %4, %5, p, 1, 1, 1, 0;\n}\n"
               : "+f"(d[0]), "+f"(d[1]), "+f"(d[2]), "+f"(d[3]) : "l"(da), "l"(db));
}
__device__ __forceinline__ void prefetch_l2(const void* p) { asm volatile("prefetch.global.L2 [%0];" ::"l"(p)); }
__device__ __forceinline__ void pace(uint32_t& t, uint32_t dt) {
  t += dt;
  while ((int32_t)((uint32_t)clock() - t) < 0) { if (NSLEEP) __nanosleep(NSLEEP); }
}
__device__ __forceinline__ void red_relaxed(uint32_t* p) { asm volatile("red.relaxed.gpu.global.add.u32 [%0], 1;" ::"l"(p) : "memory"); }
__device__ __forceinline__ void red_release(uint32_t* p) { asm volatile("red.release.gpu.global.add.u32 [%0], 1;" ::"l"(p) : "memory"); }
__device__ __forceinline__ uint4 ldg4(const void* p) { uint4 v; asm volatile("ld.global.v4.u32 {%0,%1,%2,%3}, [%4];" : "=r"(v.x), "=r"(v.y), "=r"(v.z), "=r"(v.w) : "l"(p) : "memory"); return v; }
__device__ __forceinline__ uint32_t ldg1(const void* p) { uint32_t v; asm volatile("ld.global.u32 %0, [%1];" : "=r"(v) : "l"(p) : "memory"); return v; }
__device__ __forceinline__ void stg4_if(void* p, uint32_t a, uint32_t b, uint32_t c, uint32_t d, bool on) {
  asm volatile("{\n.reg .pred p;\nsetp.ne.u32 p, %5, 0;\n@p st.global.v4.u32 [%0], {%1,%2,%3,%4};\n}\n" ::"l"(p), "r"(a), "r"(b), "r"(c), "r"(d), "r"((uint32_t)on) : "memory");
}
template <int OFF> __device__ __forceinline__ uint32_t lds32(uint32_t a) { uint32_t v; asm volatile("ld.shared.u32 %0, [%1+%2];" : "=r"(v) : "r"(a), "n"(OFF)); return v; }
__device__ __forceinline__ uint4 lds128(uint32_t a) { uint4 v; asm volatile("ld.shared.v4.u32 {%0,%1,%2,%3}, [%4];" : "=r"(v.x), "=r"(v.y), "=r"(v.z), "=r"(v.w) : "r"(a) : "memory"); return v; }
__device__ __forceinline__ float2 lds64f(uint32_t a) { float2 v; asm volatile("ld.shared.v2.f32 {%0,%1}, [%2];" : "=f"(v.x), "=f"(v.y) : "r"(a) : "memory"); return v; }
__device__ __forceinline__ void sts64f(uint32_t a, float x, float y) { asm volatile("st.shared.v2.f32 [%0], {%1,%2};" ::"r"(a), "f"(x), "f"(y) : "memory"); }
__device__ __forceinline__ void sts32(uint32_t a, uint32_t x) { asm volatile("st.shared.u32 [%0], %1;" ::"r"(a), "r"(x) : "memory"); }
__device__ __forceinline__ void sts128(uint32_t a, uint32_t x, uint32_t y, uint32_t z, uint32_t w) { asm volatile("st.shared.v4.u32 [%0], {%1,%2,%3,%4};" ::"r"(a), "r"(x), "r"(y), "r"(z), "r"(w) : "memory"); }
__device__ __forceinline__ void stsm4(uint32_t a, uint32_t r0, uint32_t r1, uint32_t r2, uint32_t r3) {
  asm volatile("stmatrix.sync.aligned.m8n8.x4.shared.b16 [%0], {%1,%2,%3,%4};" ::"r"(a), "r"(r0), "r"(r1), "r"(r2), "r"(r3) : "memory");
}
__device__ __forceinline__ void stsm4t(uint32_t a, uint32_t r0, uint32_t r1, uint32_t r2, uint32_t r3) {
  asm volatile("stmatrix.sync.aligned.m8n8.x4.trans.shared.b16 [%0], {%1,%2,%3,%4};" ::"r"(a), "r"(r0), "r"(r1), "r"(r2), "r"(r3) : "memory");
}
__device__ __forceinline__ void ldsm4t(uint32_t* r, uint32_t a) {
  asm volatile("ldmatrix.sync.aligned.m8n8.x4.trans.shared.b16 {%0,%1,%2,%3}, [%4];" : "=r"(r[0]), "=r"(r[1]), "=r"(r[2]), "=r"(r[3]) : "r"(a) : "memory");
}
__device__ __forceinline__ uint32_t pack2(float lo, float hi) { uint32_t r; asm("cvt.rn.bf16x2.f32 %0, %1, %2;" : "=r"(r) : "f"(hi), "f"(lo)); return r; }
__device__ __forceinline__ float bf_lo(uint32_t u) { return __uint_as_float(u << 16); }
__device__ __forceinline__ float bf_hi(uint32_t u) { return __uint_as_float(u & 0xffff0000u); }
__device__ __forceinline__ float tanh_fast(float x) { float y; asm("tanh.approx.f32 %0, %1;" : "=f"(y) : "f"(x)); return y; }
__device__ __forceinline__ uint32_t hmul2(uint32_t a, uint32_t b) { uint32_t r; asm("mul.rn.bf16x2 %0, %1, %2;" : "=r"(r) : "r"(a), "r"(b)); return r; }
__device__ __forceinline__ uint32_t hfma2(uint32_t a, uint32_t b, uint32_t c) { uint32_t r; asm("fma.rn.bf16x2 %0, %1, %2, %3;" : "=r"(r) : "r"(a), "r"(b), "r"(c)); return r; }
__device__ __forceinline__ uint32_t prmt(uint32_t a, uint32_t b, uint32_t s) { return __byte_perm(a, b, s); }

__device__ __forceinline__ uint32_t ld_relaxed(const uint32_t* p) { uint32_t v; asm volatile("ld.relaxed.gpu.global.u32 %0, [%1];" : "=r"(v) : "l"(p) : "memory"); return v; }
__device__ __forceinline__ void acquire_fence() { asm volatile("fence.acquire.gpu;\nfence.proxy.async.global;" ::: "memory"); }
__device__ __forceinline__ uint32_t load_epoch(const Params& p, int idx, int lane) { return ld_relaxed(&p.scr->epoch[idx + (((lane * lane) & 3) == 2 ? 1 : 0)]); }
__device__ __forceinline__ void poll_counter(const uint32_t* cnt, uint32_t target) {
  uint32_t t0 = 0;
#pragma unroll 1
  while (!__all_sync(0xffffffff, ld_relaxed(cnt) == target)) spin_guard(t0);
  acquire_fence();
}

__device__ __forceinline__ int g3_block(int cb, int it) { return it < 3 ? cb * 3 + it : (it - 3 < cb * 3 ? it - 3 : it); }

template <int N, bool A_SWZ, int B_MODE, int DEPTH, class Hook, class Mid>
__device__ __forceinline__ void gemm_loop(float* d, uint32_t sb, int nkb, int sa, int pa, int b0, uint32_t boff, int relA, int relB, int tid, Hook hook, Mid mid) {
  constexpr uint32_t A_STEP = A_SWZ ? 2 : 128;
  constexpr uint32_t B_STEP = B_MODE == 0 ? 128 : (B_MODE == 1 ? 384 : 320);
  const uint64_t da0 = A_SWZ ? mkdesc(sb + OFF_A, 16, 1024, 1) : mkdesc(sb + OFF_A, 1024, 128, 0);
  const uint64_t db0 = B_MODE == 0 ? mkdesc(sb + OFF_B + boff, 8192, 1024, 1) : mkdesc(sb + OFF_B + boff, B_MODE == 1 ? 3072 : 2560, 128, 0);
  constexpr int MODA = B_MODE == 0 ? NA : NA2;
  constexpr int MODB = B_MODE == 2 ? 6 : NB;
  int sbk = b0 % MODB, pb = (b0 / MODB) & 1;
  auto boffs = [](int s_) { return B_MODE == 2 ? (s_ == 5 ? 0 : s_ + 1) * (20480 >> 4) : s_ * (B_SLOT >> 4); };
  uint32_t rel = 0;
  uint64_t da = da0 + sa * (A_SLOT >> 4), db = db0 + boffs(sbk);
  const bool doR = tid < 2 ? tid < relA : tid - 2 < relB;
  mbar_wait2(sb + BAR_AF + 8 * sa, pa, sb + BAR_BF + 8 * sbk, pb);
  if constexpr (DEPTH == 0) {
    acc_fence<N / 2>(d);
#pragma unroll 1
    for (int it = 0; it < nkb; it++) {
      WG_FENCE();
#pragma unroll
      for (int j = 0; j < 4; j++) WG<N>::ss(d, da + j * A_STEP, db + j * B_STEP, 1);
      WG_COMMIT();
      const uint32_t prel = rel;
      rel = sb + BAR_AE + 8 * (tid < 2 ? sa : sbk + NA);
      if (++sa == MODA) { sa = 0; pa ^= 1; }
      if (++sbk == MODB) { sbk = 0; pb ^= 1; }
      da = da0 + sa * (A_SLOT >> 4); db = db0 + boffs(sbk);
      const bool r0 = mbar_test(sb + BAR_AF + 8 * sa, pa), r1 = mbar_test(sb + BAR_BF + 8 * sbk, pb);
      WG_WAIT(1);
      mbar_arrive_if(prel, doR && prel != 0);
      if (it == 2) {
        WG_WAIT(0);
        mbar_expect_if(sb + BAR_AF + 8 * (tid == 8 ? 8 : tid), A_SLOT, tid < 9);
        mbar_arrive_if(rel, doR);
        rel = 0;
      }
      mid(it);
      if (it + 1 < nkb && !(r0 && r1)) {
        mbar_wait2(sb + BAR_AF + 8 * sa, pa, sb + BAR_BF + 8 * sbk, pb);
      }
    }
  } else
#pragma unroll 1
  for (int it = 0; it < nkb; it++) {
    WG_FENCE();
    WG<N>::ss(d, da, db, 1);
    const uint32_t prel = rel;
    rel = sb + BAR_AE + 8 * (tid < 2 ? sa : sbk + NA);
    if (++sa == MODA) { sa = 0; pa ^= 1; }
    if (++sbk == MODB) { sbk = 0; pb ^= 1; }
    if (DEPTH == 1) { WG_COMMIT(); WG_WAIT(1); }
    WG<N>::ss(d, da + A_STEP, db + B_STEP, 1);
    WG_COMMIT();
    WG_WAIT(1);
    if (EARLY == 1) mbar_arrive_if(prel, doR && it != 0);
    WG<N>::ss(d, da + 2 * A_STEP, db + 2 * B_STEP, 1);
    if (DEPTH == 1) WG_COMMIT();
    if (EARLY != 1) mbar_arrive_if(prel, doR && it != 0);
    const bool r0 = mbar_test(sb + BAR_AF + 8 * sa, pa), r1 = mbar_test(sb + BAR_BF + 8 * sbk, pb);
    const uint64_t da3 = da + 3 * A_STEP, db3 = db + 3 * B_STEP;
    da = da0 + sa * (A_SLOT >> 4); db = db0 + boffs(sbk);
    if (DEPTH == 1) WG_WAIT(1);
    WG<N>::ss(d, da3, db3, 1);
    WG_COMMIT();
    mid(it);
    if (it + 1 < nkb) {
      if (!(r0 && r1)) {
        mbar_wait2(sb + BAR_AF + 8 * sa, pa, sb + BAR_BF + 8 * sbk, pb);
      }
    }
    if (DEPTH == 2) WG_WAIT(1);
  }
  hook();
  WG_WAIT(0);
  acc_fence<N / 2>(d);
  mbar_arrive_if(rel, doR);
}

__device__ __forceinline__ void fold_mean(float* d, uint32_t cs, float ma, float mb, int t) {
  const uint32_t ha = pack2(-ma, -ma), hb = pack2(-mb, -mb);
  const float la = -ma - bf_lo(ha), lb = -mb - bf_lo(hb);
  const uint32_t a[4] = {t ? 0u : ha, t ? 0u : hb, t ? 0u : pack2(la, la), t ? 0u : pack2(lb, lb)};
  WG_FENCE();
  WG<192>::rst(d, a, mkdesc(cs, 0, 32, 0));
  WG_COMMIT();
}
__device__ __forceinline__ void gelu_tile(const float* d, uint32_t* z, float* st, float ra, float rb) {
  const float kA = 0.7978845608028654f, kB = 0.7978845608028654f * 0.044715f;
  const float c1a = kA * ra, c3a = kB * ra * ra * ra, c1b = kA * rb, c3b = kB * rb * rb * rb;
  float acc[8];
#pragma unroll
  for (int i = 0; i < 8; i++) acc[i] = 0.f;
#pragma unroll
  for (int j = 0; j < 24; j++) {
    float r[4];
#pragma unroll
    for (int e = 0; e < 4; e++) {
      const float v = d[4 * j + e];
      const float a = v * fmaf(v * v, e < 2 ? c3a : c3b, e < 2 ? c1a : c1b);
      r[e] = fmaf(v, tanh_fast(a), v);
      acc[e] += r[e];
      acc[4 + e] = fmaf(r[e], r[e], acc[4 + e]);
    }
    z[2 * j] = pack2(r[0], r[1]);
    z[2 * j + 1] = pack2(r[2], r[3]);
  }
  st[0] = acc[0] + acc[1]; st[1] = acc[4] + acc[5]; st[2] = acc[2] + acc[3]; st[3] = acc[6] + acc[7];
}

template <int Q> __device__ __forceinline__ void conv_load(uint32_t* a, uint32_t ab) {
  a[0] = lds32<512 * Q>(ab);       a[1] = lds32<512 * Q + 256>(ab);  a[2] = lds32<512 * Q + 16>(ab);   a[3] = lds32<512 * Q + 272>(ab);
  a[4] = lds32<512 * Q + 32>(ab);  a[5] = lds32<512 * Q + 288>(ab);  a[6] = lds32<512 * Q + 48>(ab);   a[7] = lds32<512 * Q + 304>(ab);
  a[8] = lds32<512 * Q + 64>(ab);  a[9] = lds32<512 * Q + 320>(ab);  a[10] = lds32<512 * Q + 80>(ab);  a[11] = lds32<512 * Q + 336>(ab);
  a[12] = lds32<512 * Q + 96>(ab); a[13] = lds32<512 * Q + 352>(ab); a[14] = lds32<512 * Q + 112>(ab); a[15] = lds32<512 * Q + 368>(ab);
}
template <int Q, int L> __device__ __forceinline__ void conv_step(float* d, uint32_t (*a)[16], uint32_t ab, uint64_t db) {
  WG_FENCE();
#pragma unroll
  for (int s = 0; s < 4; s++) WG<128 - 16 * Q>::rs(d, a[Q] + 4 * s, db + s + 16 * Q);
  WG_COMMIT();
  if (CPIN) WG_WAIT(1);
  if (L >= 0) conv_load<(L >= 0 ? L : 0)>(a[L >= 0 ? L : 0], ab);
  if (CW0 || Q == 0) WG_WAIT(0);
}

__device__ __forceinline__ int seg_col(int cb, int h) { return (cb >> 1) * 320 + (cb & 1) * 32 + h * 64; }
__device__ __forceinline__ void final_load_x(uint32_t (*xw)[10], uint32_t xt, int cb, int h, int w, int lane) {
  const int g = lane >> 2, t = lane & 3, cc = seg_col(cb, h) >> 3;
  const int c0 = cc + t, c1 = c0 + 24, c2 = cc + 16 - 6 * h + (t >> 1);
  const uint32_t r0 = xt + (w * 16 + g) * 128;
#pragma unroll
  for (int r = 0; r < 2; r++) {
    const uint4 u = lds128(r0 + r * 1024 + (c0 >> 3) * A_SLOT + (((c0 ^ g) & 7) << 4)), v = lds128(r0 + r * 1024 + (c1 >> 3) * A_SLOT + (((c1 ^ g) & 7) << 4));
    const float2 z = lds64f(r0 + r * 1024 + (c2 >> 3) * A_SLOT + (((c2 ^ g) & 7) << 4) + (t & 1) * 8);
    xw[r][0] = u.x; xw[r][1] = u.y; xw[r][2] = u.z; xw[r][3] = u.w;
    xw[r][4] = v.x; xw[r][5] = v.y; xw[r][6] = v.z; xw[r][7] = v.w;
    xw[r][8] = __float_as_uint(z.x); xw[r][9] = __float_as_uint(z.y);
  }
}
__device__ __forceinline__ void final_s_early(uint32_t (*sw)[10], const uint32_t (*xw)[10], uint32_t ya, float2 s0, float2 s1) {
  const uint32_t r2[2] = {pack2(s0.y, s0.y), pack2(s1.y, s1.y)};
  const float na = -s0.x * bf_lo(r2[0]), nb = -s1.x * bf_lo(r2[1]);
  const uint32_t n2[2] = {pack2(na, na), pack2(nb, nb)};
#pragma unroll
  for (int j = 0; j < 10; j += 2) {
    uint32_t y[4];
    if (j < 4 || j == 8) ldsm4t(y, ya + (j < 4 ? j : 4) * 1024);
#pragma unroll
    for (int e = 0; e < 4; e++) {
      const uint32_t xn = hfma2(xw[e & 1][j + (e >> 1)], r2[e & 1], n2[e & 1]);
      sw[e & 1][j + (e >> 1)] = (j < 4 || j == 8) ? hmul2(xn, y[e]) : xn;
    }
  }
}
__device__ __forceinline__ bool final_late(uint32_t* y, uint32_t ya) {
  ldsm4t(y, ya + 6144);
  ldsm4t(y + 4, ya + 8192);
  uint32_t zero = 0;
#pragma unroll
  for (int e = 0; e < 8; e++) zero |= (y[e] - 0x00010001u) & ~y[e];
  return (zero & 0x80008000u) == 0;
}
__device__ __forceinline__ bool bar_all(int id, int n, bool c) {
  uint32_t r;
  asm volatile("{\n.reg .pred p, q;\nsetp.ne.u32 p, %3, 0;\nbar.red.and.pred q, %1, %2, p;\nselp.u32 %0, 1, 0, q;\n}\n" : "=r"(r) : "r"(id), "r"(n), "r"((uint32_t)c) : "memory");
  return r;
}
__device__ __forceinline__ void final_out(const float* d, const uint32_t (*xw)[10], const uint32_t (*sw)[10], float ra, float rb, __nv_bfloat16* o0, int h, int t) {
  const float ca = 0.25f * ra, cb = 0.25f * rb;
  uint32_t o[2][10];
#pragma unroll
  for (int j = 0; j < 10; j++) {
#pragma unroll
    for (int r = 0; r < 2; r++) {
      const float h0 = d[4 * j + 2 * r] * (r ? cb : ca), h1 = d[4 * j + 2 * r + 1] * (r ? cb : ca);
      o[r][j] = hfma2(pack2(fmaf(h0, tanh_fast(h0), h0), fmaf(h1, tanh_fast(h1), h1)), sw[r][j], xw[r][j]);
      __nv_bfloat16* q = o0 + r * 8 * kD;
      if (j == 3) stg4_if(q + t * 8, o[r][0], o[r][1], o[r][2], o[r][3], true);
      if (j == 7) stg4_if(q + 192 + t * 8, o[r][4], o[r][5], o[r][6], o[r][7], true);
      if (j == 9) asm volatile("st.global.v2.u32 [%0], {%1,%2};" ::"l"(q + 128 - 48 * h + t * 4), "r"(o[r][8]), "r"(o[r][9]) : "memory");
    }
  }
}

struct Taps { uint4 r0, r1; uint32_t n0, n1, dd; };
__device__ __forceinline__ void load_taps(Taps& k, const Params& p, int ch, int tid) {
  const uint4* kp = (const uint4*)(p.ssmk + (size_t)ch * kS);
  k.r0 = ldg4(kp + tid); k.r1 = ldg4(kp + 128 + tid);
  k.n0 = ldg1(kp + tid + 1); k.n1 = tid < 127 ? ldg1(kp + 129 + tid) : 0u;
  k.dd = __bfloat16_as_ushort(p.ssmD[ch]);
}
__device__ __forceinline__ void load_convx(const Params& p, uint32_t cv, uint32_t bar, int ch) {
  mbar_expect(bar, 4096);
  bulk_g2s(cv, p.scr->kvx + (size_t)ch * 4096, 2048, bar);
  bulk_g2s(cv + XB_PL, p.scr->kvx + (size_t)ch * 4096 + 2048, 2048, bar);
}
#define CW 3
#define CSTAMP(j)
__device__ __forceinline__ void zero_pads(uint32_t cv, int lane) {
  if (lane < 8) sts128(cv + (lane >> 2) * XB_PL + 2048 + (lane & 3) * 16, 0, 0, 0, 0);
  else if (lane < 12) sts128(cv + ((lane & 2) ? CV_KO : CV_KE) + (lane & 1) * 16, 0, 0, 0, 0);
  fence_async_smem();
  __syncwarp();
}
__device__ __forceinline__ int y_row(int c, uint32_t par) {
  const int hf = c >= 320, cc = c - hf * 320, u = cc >> 6, cb = hf * 2 + ((cc >> 5) & 1);
  if (u == 2) return cb * 96 + ((cc >> 4) & 1) * 48 + 32 + (cc & 1) + ((cc >> 1) & 1) * 8 + ((cc >> 2) & 3) * 2;
  return (u < 2 ? cb * 96 + u * 48 : 384 + par * 256 + cb * 64 + (u - 3) * 32) + (cc & 1) + ((cc >> 1) & 3) * 8 + ((cc >> 3) & 3) * 2;
}
__device__ __forceinline__ void y_store(const Params& p, uint32_t sb, int h, int ch, uint32_t par) {
  uint8_t* dst = p.scr->y + (size_t)y_row(ch, par) * 4096;
  if (elect_one()) {
    bulk_s2g(dst, sb + OFF_A + 9 * A_SLOT + h * 4096, 4096);
    asm volatile("cp.async.bulk.commit_group;\ncp.async.bulk.wait_group 0;" ::: "memory");
  }
  __syncwarp();
}
__device__ __forceinline__ void conv_service(const Params& p, uint32_t sb, int h, int ch, bool first) {
  bar_sync(NB_WGA + 8 + h, 160);
  const bool now = !first || __all_sync(0xffffffff, mbar_test(sb + BAR_KV, 0));
  if (now) { acquire_fence(); if (elect_one()) load_convx(p, sb + OFF_CV + (1 - h) * CV_SZ, sb + BAR_XF + 8 * h, ch + 128); }
  bar_sync(NB_WGA + 8 + h, 160);
  y_store(p, sb, h, ch, 0);
  if (!now) {
    mbar_wait(sb + BAR_KV, 0);
    acquire_fence();
    if (elect_one()) load_convx(p, sb + OFF_CV + (1 - h) * CV_SZ, sb + BAR_XF + 8 * h, ch + 128);
  }
}
__device__ __forceinline__ uint32_t y_tile(int h) { return OFF_CV + (1 - h) * 13312; }
__device__ __forceinline__ void load_late_y(const Params& p, uint32_t sb, int h, int rb, int cb, uint32_t par) {
  mbar_expect(sb + BAR_YL + 16 * h, 4096);
  tma2d(sb + y_tile(h) + 6144, &p.tmY, rb * 64, 384 + par * 256 + cb * 64 + h * 32, sb + BAR_YL + 16 * h);
  tma2d(sb + y_tile(h) + 8192, &p.tmY, rb * 64, 400 + par * 256 + cb * 64 + h * 32, sb + BAR_YL + 16 * h);
}
__device__ __forceinline__ void held_service(const Params& p, uint32_t sb, int h, int ch, int rb, int cb, uint32_t tag, int lane) {
#pragma unroll 1
  for (int i = 0; i < 8; i++) sts128(sb + OFF_A + 9 * A_SLOT + h * 4096 + i * 512 + lane * 16, 0, 0, 0, 0);
  fence_async_smem();
  __syncwarp();
  y_store(p, sb, h, ch, ~tag & 1);
  mbar_wait(sb + BAR_YT, 1);
  acquire_fence();
  bar_sync(NB_WGA + 8 + h, 160);
  bar_sync(NB_WGA + 8 + h, 160);
  uint8_t* dst = p.scr->y + (size_t)y_row(ch, tag & 1) * 4096;
  if (elect_one()) {
    bulk_s2g(dst, sb + OFF_A + 9 * A_SLOT + h * 4096, 4096);
    asm volatile("cp.async.bulk.commit_group;" ::: "memory");
    mbar_expect(sb + BAR_XF + 8 * h, 6144);
#pragma unroll 1
    for (int i = 0; i < 3; i++) tma2d(sb + y_tile(h) + i * 2048, &p.tmY, rb * 64, cb * 96 + h * 48 + i * 16, sb + BAR_XF + 8 * h);
  }
  mbar_wait(sb + BAR_AE + 8 * (LL_AT - 1), 1);
  if (elect_one()) { load_late_y(p, sb, h, rb, cb, tag & 1); asm volatile("cp.async.bulk.wait_group 0;" ::: "memory"); }
}
__device__ __forceinline__ void conv_worker(const Params& p, Taps& k, uint32_t cv, uint32_t yb0,
                                            uint32_t xbar, int nbar, int ch0, int n, uint32_t holdbar, int w, int lane,
                                            int tid, int st0, int rb, int cb) {
  const int g = lane >> 2, t = lane & 3, w0 = w & 1, w1 = w >> 1;
  const uint32_t ab = cv + ((g & 1) ? CV_KE : CV_KO) + 32 + 2 * (64 * w0 + 8 * w1 + ((g - 15) & ~1) + 2 * t);
  const uint32_t scA = cv + (w1 ? CV_KO : CV_KE) + 32, scB = scA + 2048;
  const int dl = (t >> 1) ^ 1;
  if (n == 2) mbar_wait(xbar, 0);
  STAMPW(st0 + 3);
#pragma unroll 1
  for (int i = 0; i < n; i++) {
    if (tid == 0) {
      k.r0.x = (k.r0.x & 0xffff0000u) | (pack2(bf_lo(k.r0.x) + bf_lo(k.dd), 0.f) & 0xffffu);
      sts32(cv + CV_KO + 28, k.r0.x << 16);
    }
    sts128(cv + CV_KE + 32 + tid * 16, k.r0.x, k.r0.y, k.r0.z, k.r0.w);
    sts128(cv + CV_KO + 32 + tid * 16, prmt(k.r0.x, k.r0.y, 0x5432), prmt(k.r0.y, k.r0.z, 0x5432), prmt(k.r0.z, k.r0.w, 0x5432), prmt(k.r0.w, k.n0, 0x5432));
    sts128(cv + CV_KE + 2080 + tid * 16, k.r1.x, k.r1.y, k.r1.z, k.r1.w);
    sts128(cv + CV_KO + 2080 + tid * 16, prmt(k.r1.x, k.r1.y, 0x5432), prmt(k.r1.y, k.r1.z, 0x5432), prmt(k.r1.z, k.r1.w, 0x5432), prmt(k.r1.w, k.n1, 0x5432));
    if (i + 1 < n) load_taps(k, p, ch0 + (i + 1) * 128, tid);
    bar_sync(nbar, 128);
    CSTAMP(0);
    const uint64_t db = mkdesc(cv + (i & 0x1000), XB_PL, 128, 0);
    float d[64];
    uint32_t a[8][16];
    conv_load<7>(a[7], ab); conv_load<6>(a[6], ab); conv_load<5>(a[5], ab); conv_load<4>(a[4], ab);
#pragma unroll
    for (int j = 0; j < 64; j++) d[j] = 0.f;
    mbar_wait(xbar, i & 1);
    if (i + 1 == n) mbar_wait(holdbar, 1);
    CSTAMP(1);
    conv_step<7, -1>(d, a, ab, db); conv_step<6, -1>(d, a, ab, db); conv_step<5, -1>(d, a, ab, db); conv_step<4, 3>(d, a, ab, db);
    conv_step<3, 2>(d, a, ab, db);
    conv_step<2, 1>(d, a, ab, db);
    conv_step<1, 0>(d, a, ab, db);
    conv_step<0, -1>(d, a, ab, db);
    acc_fence<64>(d);
    CSTAMP(2);
    bar_sync(nbar + 8, 160);
    float E[16][2];
#pragma unroll
    for (int j = 0; j < 15; j++) { E[j][0] = d[4 * j] + d[4 * j + 6]; E[j][1] = d[4 * j + 1] + d[4 * j + 7]; }
    E[15][0] = d[60]; E[15][1] = d[61];
    if (w0 == 0) {
#pragma unroll
      for (int j = 8; j < 16; j++) sts64f(scA + (j - 8) * 256 + lane * 8, E[j][0], E[j][1]);
    } else {
      const uint32_t a = scB - dl * 256 + (lane ^ 2) * 8;
#pragma unroll
      for (int j = 1; j < 8; j++) sts64f(a + j * 256, E[j][0], E[j][1]);
      sts64f(scB + (dl ? 7 * 256 : 0) + (lane ^ 2) * 8, dl ? E[8][0] : E[0][0], dl ? E[8][1] : E[0][1]);
    }
    bar_sync(nbar, 128);
    CSTAMP(3);
    uint32_t pk[8];
    if (w0 == 0) {
#pragma unroll
      for (int j = 0; j < 8; j++) { const float2 v = lds64f(scB + j * 256 + lane * 8); pk[j] = pack2(E[j][0] + v.x, E[j][1] + v.y); }
    } else {
      const uint32_t a0 = scA - dl * 256 + (lane ^ 2) * 8;
#pragma unroll
      for (int j = 9; j < 16; j++) { const float2 v = lds64f(a0 + (j - 8) * 256); pk[j - 8] = pack2(E[j][0] + v.x, E[j][1] + v.y); }
      const float2 v = lds64f(scA + (dl ? 7 * 256 : 0) + (lane ^ 2) * 8);
      pk[0] = pack2((dl ? 0.f : E[8][0]) + v.x, (dl ? 0.f : E[8][1]) + v.y);
    }
    CSTAMP(4);
    if (i + 1 == n) {
#pragma unroll
      for (int j = 0; j < 8; j++) pk[j] = ~pk[j];
    }
    const int c1 = (w0 ? 35 : 95) - lane, c0 = (w0 && lane < 4) ? c1 - 32 : c1 + 32;
    stsm4t(yb0 + 128 * (c0 & 31) + (((2 * (c0 >> 5) + w1) ^ (c0 & 7)) << 4), pk[0], pk[1], pk[2], pk[3]);
    stsm4t(yb0 + 128 * (c1 & 31) + (((2 * (c1 >> 5) + w1) ^ (c1 & 7)) << 4), pk[4], pk[5], pk[6], pk[7]);
    fence_async_smem();
    bar_sync(nbar + 8, 160);
    CSTAMP(5);
    STAMPW(st0 + i);
    if (n == 2 && i == 0) {
      const int u = (tid >> 3) % 5, kg = rb * 3 + (tid < 120 ? (tid >> 3) / 5 : 0), c = u < 4 ? (u >> 1) * 10 + (u & 1) * 4 : 8, o2 = u < 4 ? 2 : 10;
      const uint4* wp = (const uint4*)p.wout + (uint32_t)((kg * 8 + (tid & 7)) * (kD / 8) + (seg_col(cb, 0) >> 3) + (u < 4 ? (u >> 1) * 8 + (u & 1) * 24 : 16));
      const uint4 w0 = ldg4(wp), w1 = ldg4(wp + 1), w2 = ldg4(wp + 2), w3 = ldg4(wp + 3);
      uint8_t* dst = p.scr->wo + (uint32_t)(cb * (12 * 20480) + kg * 2560 + c * 128 + (tid & 7) * 16);
      const bool f = u < 4, on = tid < 120;
      stg4_if(dst, w0.x, f ? w1.x : w0.z, f ? w2.x : w1.x, f ? w3.x : w1.z, on);
      stg4_if(dst + 128, w0.y, f ? w1.y : w0.w, f ? w2.y : w1.y, f ? w3.y : w1.w, on);
      stg4_if(dst + o2 * 128, f ? w0.z : w2.x, f ? w1.z : w2.z, f ? w2.z : w3.x, w3.z, on);
      stg4_if(dst + o2 * 128 + 128, f ? w0.w : w2.y, f ? w1.w : w2.w, f ? w2.w : w3.y, w3.w, on);
      bar_arrive(NB_WO, 160);
    }
  }
}

struct KvRegs { uint32_t k[11], v[8]; uint4 sh; };
__device__ __forceinline__ void kv_load(KvRegs& q, const __nv_bfloat16* kp, const __nv_bfloat16* vp, const __nv_bfloat16* sp, bool halo) {
#pragma unroll
  for (int i = 0; i < 11; i++) q.k[i] = (i >= 3 || halo) ? ldg1(kp + i * kD) : 0u;
#pragma unroll
  for (int i = 0; i < 8; i++) q.v[i] = ldg1(vp + i * kD);
  q.sh = ldg4(sp);
}
__device__ __forceinline__ void kv_unit(const KvRegs& q, uint32_t oa) {
  const uint32_t w0 = prmt(q.sh.x, q.sh.z, 0x5410), w1 = prmt(q.sh.x, q.sh.z, 0x7632), w2 = prmt(q.sh.y, q.sh.w, 0x5410), w3 = prmt(q.sh.y, q.sh.w, 0x7632);
  uint32_t r[8];
#pragma unroll
  for (int i = 0; i < 8; i++) r[i] = hmul2(hfma2(q.k[i + 3], w0, hfma2(q.k[i + 2], w1, hfma2(q.k[i + 1], w2, hmul2(q.k[i], w3)))), q.v[i]);
  sts128(oa, prmt(r[7], r[6], 0x5410), prmt(r[5], r[4], 0x5410), prmt(r[3], r[2], 0x5410), prmt(r[1], r[0], 0x5410));
  sts128(oa + 2048, prmt(r[7], r[6], 0x7632), prmt(r[5], r[4], 0x7632), prmt(r[3], r[2], 0x7632), prmt(r[1], r[0], 0x7632));
}

__device__ __forceinline__ void helper_cta(const Params& p, uint32_t sb, int cb, int warp, int lane) {
  constexpr int NS = 9, ONES = NS * B_SLOT, BF = ONES + 256, BE = BF + 8 * NS;
  if (warp < NS && elect_one()) {
    mbar_init(sb + BF + 8 * warp, 1); mbar_init(sb + BE + 8 * warp, 1);
    fence_async_smem();
    if (warp == 0) { mbar_expect(sb + BF, B_SLOT); tma3d(sb, &p.tmW, 0, 0, 12 + cb * 3, sb + BF); }
  }
  if (warp == 15) { sts32(sb + ONES + lane * 4, 0x3f803f80u); sts32(sb + ONES + 128 + lane * 4, 0x3f803f80u); fence_async_smem(); }
  __syncthreads();
  if (warp == 4) {
    int s = 1, ph = 1;
    uint32_t tp = clock() + HP0;
#pragma unroll 1
    for (int it = 1; it < 20; it++) {
      if (HPD && it >= 10) pace(tp, HPD);
      mbar_wait(sb + BE + 8 * s, ph);
      if (elect_one()) { mbar_expect(sb + BF + 8 * s, B_SLOT); tma3d(sb + s * B_SLOT, &p.tmW, 0, (it < 10 ? it : it - 10) * 64, (it < 10 ? 12 : 0) + cb * 3, sb + BF + 8 * s); }
      if (++s == NS) { s = 0; ph ^= 1; }
    }
  } else if (warp < 4) {
    const uint32_t tag = load_epoch(p, 128 + cb, lane) + 1;
    const uint64_t db = mkdesc(sb + ONES, 128, 128, 0);
    uint2* dst = p.scr->colsum + cb * 192 + warp * 16 + (lane >> 2);
    if ((lane & 3) == 0) {
#pragma unroll 1
      for (int j = 0; j < 12; j++) st_ll2(dst + (j < 6 ? 768 : 0) + ((j % 6) >> 1) * 64 + (j & 1) * 8, 0, 0);
    }
    int s = 0, ph = 0;
#pragma unroll 1
    for (int part = 0; part < 2; part++) {
      float d[12];
#pragma unroll
      for (int i = 0; i < 12; i++) d[i] = 0.f;
#pragma unroll 1
      for (int it = 0; it < 10; it++) {
        mbar_wait(sb + BF + 8 * s, ph);
        const uint64_t da = mkdesc(sb + s * B_SLOT, 8192, 1024, 1);
        WG_FENCE();
#pragma unroll
        for (int j = 0; j < 12; j++) wgmma_colsum(d + 4 * (j % 3), da + (j % 3) * 512 + (j / 3) * 128, db);
        WG_COMMIT();
        WG_WAIT(1);
        mbar_arrive_if(sb + BE + 8 * (s == 0 ? NS - 1 : s - 1), threadIdx.x == 0 && (it | part) != 0);
        if (++s == NS) { s = 0; ph ^= 1; }
      }
      WG_WAIT(0);
      acc_fence<12>(d);
      if ((lane & 3) == 0) {
#pragma unroll
        for (int j = 0; j < 6; j++) st_ll2(dst + (part ? 0 : 768) + (j >> 1) * 64 + (j & 1) * 8, __float_as_uint(d[2 * j]), tag);
      }
      STAMPW(1 + part);
    }
    if (threadIdx.x == 0) *(volatile uint32_t*)&p.scr->epoch[128 + cb] = tag;
  }
}

__global__ void __launch_bounds__(512, 1) fused_kernel(const __grid_constant__ Params p) {
  extern __shared__ __align__(1024) uint8_t smem[];
  const int warp = __shfl_sync(0xffffffff, (int)(threadIdx.x >> 5), 0);
  const int lane = threadIdx.x & 31, tid = threadIdx.x & 127;
  const uint32_t sb = __shfl_sync(0xffffffff, (uint32_t)__cvta_generic_to_shared(smem), 0);
  const uint32_t tstart = clock();
  if (elect_one()) {
    if (warp < 5) asm volatile("prefetch.tensormap [%0];" ::"l"(&p.tmX + warp) : "memory");
    mbar_init(sb + OFF_BAR + 8 * warp, 1); mbar_init(sb + OFF_BAR + 128 + 8 * warp, 1); mbar_init(sb + OFF_BAR + 256 + 8 * warp, 2);
    asm volatile("fence.mbarrier_init.release.cluster;" ::: "memory");
  }
  int b = blockIdx.x;
  if (p.by_smid) asm volatile("mov.u32 %0, %%smid;" : "=r"(b));
  b = __shfl_sync(0xffffffff, b, 0);
  const int tp = b >> 1, t7 = (tp - 32) / 7;
  const int lin = tp < 32 ? ((tp & 7) ? (tp & 7) * 16 : 8) + (tp >> 3) * 2 + (b & 1)
                          : (tp < 60 ? (tp - 31 - t7 * 7) * 16 + 8 + t7 * 2 + (b & 1) : (tp < 62 ? -1 : b - 124));
  const int hcb = b & 3;
  if (lin < 0) { helper_cta(p, sb, hcb, warp, lane); return; }
  const int cb = ((lin >> 4) & 1) * 2 + ((lin >> 1) & 1), rb = (lin >> 5) * 8 + ((lin >> 2) & 3) * 2 + (lin & 1);
  const int chb = (cb >> 1) * 320 + rb * 2 + (cb & 1);
  if (warp == 0 && elect_one()) {
    mbar_expect(sb + BAR_AF, A_SLOT);
    tma_rows(sb + OFF_A, &p.tmX, 0, rb, sb + BAR_AF);
    mbar_expect(sb + BAR_BF, B_SLOT);
    tma3d(sb + OFF_B, &p.tmW, 0, 0, 12 + cb * 3, sb + BAR_BF);
  }
  if (warp == 1) STAMP(31);
  if (sb & 1023) die();
  __syncthreads();

  if (warp >= 12) {
    asm volatile("setmaxnreg.dec.sync.aligned.u32 32;");
    const uint32_t epoch = load_epoch(p, lin, lane);
    if (warp == 12) {
#pragma unroll 1
      for (int i = 1; i < NA; i++) {
        if (elect_one()) {
          mbar_expect(sb + BAR_AF + 8 * i, A_SLOT);
          tma_rows(sb + OFF_A + i * A_SLOT, &p.tmX, i * 64, rb, sb + BAR_AF + 8 * i);
          if (i < NB) { mbar_expect(sb + BAR_BF + 8 * i, B_SLOT); tma3d(sb + OFF_B + i * B_SLOT, &p.tmW, 0, i * 64, 12 + cb * 3, sb + BAR_BF + 8 * i); }
        }
      }
      STAMP(32);
      uint32_t kvt;
      {
        const int tb = rb * 2 + (cb & 1);
        kvt = __shfl_sync(0xffffffff, (ld_relaxed(p.scr->cnt + CNT_KV + (cb >> 1)) & ~63u) + 64, 0);
        {
          uint32_t tp = tstart;
          pace(tp, KV_T0);
          mbar_arrive_if(sb + BAR_KV + 8, lane == 0);
        }
        if (ST_YIELD) mbar_wait2(sb + BAR_XS, 0, sb + BAR_ST, 0);
#pragma unroll 1
        for (int u = 0; u < 5; u++) {
          mbar_wait(sb + BAR_KU + 8 * u, 0);
          fence_async_smem();
          if (elect_one()) {
            asm volatile("cp.async.bulk.tensor.3d.global.shared::cta.bulk_group [%0, {%2, %3, %4}], [%1];\ncp.async.bulk.commit_group;" ::"l"(&p.tmKV),
                         "r"(sb + OFF_CV + CV_SZ + (u < 3 ? u : u - 3) * 4096), "r"((63 - tb) * 16), "r"((cb >> 1) * 160 + u * 32), "r"(0) : "memory");
            if (u == 1 || u == 4) asm volatile("cp.async.bulk.wait_group 0;" ::: "memory");
            if (u == 1) { mbar_arrive(sb + BAR_KU); red_release(p.scr->cnt + CNT_KV + (cb >> 1)); }
          }
          __syncwarp();
          if (u == 1) {
            STAMP(35);
            if (PFT) { const char* q = (const char*)p.ssmk + chb * 4096 + lane * 128; prefetch_l2(q); prefetch_l2(q + 64 * 4096); }
          }
        }
        zero_pads(sb + OFF_CV + CV_SZ, lane);
        if (elect_one()) { mbar_arrive(sb + BAR_KU + 8); red_release(p.scr->cnt + CNT_KV + 2 + (cb >> 1)); }
        STAMP(30);
        if (lane < 24) {
          const char* r = (const char*)p.wout + (rb * 24 + lane) * (kD * 2) + (cb >> 1) * 640 + (cb & 1) * 384;
          prefetch_l2(r); prefetch_l2(r + 128); prefetch_l2(r + 256 - (cb & 1) * 384);
        }
      }
      poll_counter(p.scr->cnt + CNT_KV + 2 + (cb >> 1), kvt);
      if (elect_one()) mbar_arrive(sb + BAR_KV);
      STAMP(34);
      {
        const char* q = (const char*)p.wsp + (cb * 512 + rb * 16 + (lane >> 1)) * (kS * 2) + (lane & 1) * 128;
        uint32_t tp = clock();
#pragma unroll 1
        for (int i = LEAD / 2; i < WSP_N; i++) {
          prefetch_l2(q + i * 256);
          if (ZQ_N < 4 && i == Z1_AT) {
            poll_counter(p.scr->cnt + CNT_Z1, (epoch + 1) * 128);
            if (elect_one()) mbar_arrive(sb + BAR_ZP);
            STAMP(24);
          }
          pace(tp, WSP_D);
        }
      }
      const uint32_t tag = epoch + 1;
      mbar_wait(sb + BAR_G2, 0);
      if (elect_one()) {
        bulk_s2g(p.scr->h + (size_t)(rb * 12 + cb * 3) * A_SLOT, sb + OFF_A + 5 * A_SLOT, 3 * A_SLOT);
        asm volatile("cp.async.bulk.commit_group;\ncp.async.bulk.wait_group 0;" ::: "memory");
        red_release(&p.scr->hcnt[(rb >> HGRP) * 32]);
      }
      __syncwarp();
      STAMP(20);
      mbar_wait(sb + BAR_AE + 56, 0);
      STAMP(39);
      poll_counter(&p.scr->hcnt[(rb >> HGRP) * 32], tag * (4 << HGRP));
      STAMP(37);
      if (elect_one()) {
        uint32_t tp = clock();
#pragma unroll 1
        for (int it = 3; it < 12; it++) {
          if (HPACE && it > 3) { tp += HPACE; while ((int32_t)((uint32_t)clock() - tp) < 0) {} }
          bulk_g2s(sb + OFF_A + ((it + 5) % 9) * A_SLOT, p.scr->h + (size_t)(rb * 12 + g3_block(cb, it)) * A_SLOT, A_SLOT, sb + BAR_AF + 8 * ((it + 5) % 9));
        }
      }
      STAMP(21);
    } else if (warp == 13) {
      const uint32_t ztarget = __shfl_sync(0xffffffff, ld_relaxed(p.scr->cnt + CNT_Z), 0);
      int s = 0, ph = 0;
#pragma unroll 1
      for (int it = NB; it < 20; it++) {
        mbar_wait(sb + BAR_BE + 8 * s, ph);
        if (elect_one()) { mbar_expect(sb + BAR_BF + 8 * s, B_SLOT); tma3d(sb + OFF_B + s * B_SLOT, &p.tmW, 0, (it < 10 ? it : it - 10) * 64, (it < 10 ? 12 : 0) + cb * 3, sb + BAR_BF + 8 * s); }
        STAMP2(32 + it);
        if (++s == NB) { s = 0; ph ^= 1; }
      }
      mbar_wait(sb + BAR_KU + 16, 0);
#pragma unroll 1
      for (int i = 0; i < LEAD; i++) {
        mbar_wait(sb + BAR_AE + 8 * i, 0);
        if (elect_one()) { mbar_expect(sb + BAR_AF + 8 * i, A_SLOT); tma_rows(sb + OFF_A + i * A_SLOT, &p.tmWsp, i * 64, rb, sb + BAR_AF + 8 * i); }
      }
      mbar_wait(sb + BAR_ZP, 0);
      poll_counter(p.scr->cnt + CNT_Z, (ztarget & ~127u) + 128);
      STAMP(22);
      int sa = LEAD, pa = 0, ia = LEAD;
#pragma unroll 1
      for (int it = 0; it < 32; it++) {
        if (ZQ_N < 4 && it == 8 * ZQ_N) { mbar_wait(sb + BAR_ZP, 1); acquire_fence(); }
        mbar_wait2(sb + BAR_BE + 8 * s, ph, sb + BAR_AE + 8 * sa, pa);
        if (elect_one()) {
          mbar_expect(sb + BAR_BF + 8 * s, B_SLOT);
          bulk_g2s(sb + OFF_B + s * B_SLOT, p.scr->z2 + (size_t)(cb * 32 + it) * B_SLOT, B_SLOT, sb + BAR_BF + 8 * s);
        }
#pragma unroll 1
        for (int j = (it < RAMP ? 0 : (it == 4 ? 1 + RAMP : 1)); j > 0 && ia < 32; j--, ia++) {
          if (it == 4) mbar_wait(sb + BAR_AE + 8 * sa, pa);
          if (elect_one()) { mbar_expect(sb + BAR_AF + 8 * sa, A_SLOT); tma_rows(sb + OFF_A + sa * A_SLOT, &p.tmWsp, ia * 64, rb, sb + BAR_AF + 8 * sa); }
          if (++sa == NA2) { sa = 0; pa ^= 1; }
        }
        STAMP2(52 + it);
        if (++s == NB) { s = 0; ph ^= 1; }
      }
      mbar_wait(sb + BAR_WO, 0);
      acquire_fence();
#pragma unroll 1
      for (int it = 0; it < 12; it++) {
        if (it < 6) mbar_wait(sb + BAR_BE + 8 * ((0x110443 >> (4 * it)) & 7), it < 3 ? 1 : 0);
        else mbar_wait(sb + BAR_BE + 8 * s, ph);
        if (elect_one()) {
          mbar_expect(sb + BAR_BF + 8 * s, 20480);
          bulk_g2s(sb + OFF_B + (s == 5 ? 0 : s + 1) * 20480, p.scr->wo + (size_t)(cb * 12 + g3_block(cb, it)) * 20480, 20480, sb + BAR_BF + 8 * s);
        }
        STAMP2(84 + it);
        if (++s == 6) { s = 0; ph ^= 1; }
      }
    } else if (warp == 14) {
      const uint32_t tag = epoch + 1;
      uint32_t t0 = 0;
      mbar_wait(sb + BAR_AF + 8 * (NA - 1), 0);
#pragma unroll 1
      for (int part = 0; part < 2; part++) {
        uint4 v[3];
#pragma unroll 1
        while (true) {
          bool ok = true;
#pragma unroll
          for (int i = 0; i < 3; i++) {
            v[i] = ld_ll4(&p.scr->colsum[(part ? 0 : 768) + cb * 192 + i * 64 + lane * 2]);
            ok = ok && v[i].y == tag && v[i].w == tag;
          }
          if (__all_sync(0xffffffff, ok)) break;
          spin_guard(t0);
        }
#pragma unroll
        for (int i = 0; i < 3; i++) {
          const uint32_t hi = pack2(__uint_as_float(v[i].x), __uint_as_float(v[i].z)), ca = sb + OFF_CS + (1 - part) * 768 + i * 256 + (lane >> 2) * 32 + (lane & 3) * 4;
          sts32(ca, hi);
          sts32(ca + 16, pack2(__uint_as_float(v[i].x) - bf_lo(hi), __uint_as_float(v[i].z) - bf_hi(hi)));
        }
        if (!CFENCE) fence_async_smem();
        __syncwarp();
        if (lane == 0) mbar_arrive(sb + BAR_ST + 8 * part);
        if (part == 0) STAMP(27);
      }
      STAMP(38);
      bar_sync(NB_Z, 160);
      if (elect_one()) {
        uint8_t* dst = p.scr->z2 + (size_t)(cb * 32 + (rb >> 2)) * B_SLOT + (rb & 3) * 6144;
#pragma unroll 1
        for (int q = 0; q < ZQ_N; q++) bulk_s2g(dst + q * 8 * B_SLOT, sb + OFF_A + LEAD * A_SLOT + q * 6144, 6144);
        asm volatile("cp.async.bulk.commit_group;\ncp.async.bulk.wait_group 0;" ::: "memory");
        red_release(p.scr->cnt + CNT_Z);
#pragma unroll 1
        for (int q = ZQ_N; q < 4; q++) bulk_s2g(dst + q * 8 * B_SLOT, sb + OFF_A + LEAD * A_SLOT + q * 6144, 6144);
        asm volatile("cp.async.bulk.commit_group;\ncp.async.bulk.wait_group 0;" ::: "memory");
        mbar_arrive(sb + BAR_ZP);
        if (ZQ_N < 4) red_release(p.scr->cnt + CNT_Z1);
      }
      STAMP(28);
      mbar_wait(sb + BAR_AE + 72, 0);
      conv_service(p, sb, 0, chb + 64, true);
      bar_sync(NB_WO, 160);
      bar_sync(NB_CD, 64);
      if (elect_one()) { red_release(p.scr->cnt + CNT_WO + cb); red_relaxed(p.scr->cnt + CNT_Y + (cb >> 1)); }
      STAMP(49);
      poll_counter(p.scr->cnt + CNT_WO + cb, tag * 32);
      if (elect_one()) mbar_arrive(sb + BAR_WO);
      STAMP(46);
      held_service(p, sb, 0, chb + 192, rb, cb, tag, lane);
    } else {
      const uint32_t tag = epoch + 1;
      sts32(sb + OFF_BIAS + lane * 4, ldg1(p.bsp + (lane >> 3) * 512 + rb * 16 + (lane & 7) * 2));
      if (lane < 2) sts32(sb + OFF_TAG + lane * 4, lane ? 0 : tag);
      fence_async_smem();
      uint32_t t0 = 0;
      mbar_wait(sb + BAR_AF + 8 * (NA - 1), 0);
#pragma unroll 1
      while (true) {
        const uint4 u = ld_ll4(&p.scr->xstat[rb * 64 + lane]), v = ld_ll4(&p.scr->xstat[rb * 64 + 32 + lane]);
        sts64f(sb + OFF_XS + lane * 8, __uint_as_float(u.x), __uint_as_float(u.z));
        sts64f(sb + OFF_XS + 256 + lane * 8, __uint_as_float(v.x), __uint_as_float(v.z));
        if (__all_sync(0xffffffff, u.y == tag && u.w == tag && v.y == tag && v.w == tag)) break;
        spin_guard(t0);
      }
      STAMP(26);
      __syncwarp();
      if (lane == 0) mbar_arrive(sb + BAR_XS);
      mbar_wait(sb + BAR_KU + 16, 0);
      poll_counter(p.scr->cnt + CNT_KV + (cb >> 1), tag * 64);
      if (elect_one()) load_convx(p, sb + OFF_CV, sb + BAR_XF + 8, chb);
      mbar_wait(sb + BAR_KU + 8, 1);
      if (elect_one()) load_convx(p, sb + OFF_CV + CV_SZ, sb + BAR_XF, chb + 64);
      STAMP(48);
      mbar_wait(sb + BAR_AE + 72, 0);
#pragma unroll 1
      for (int i = 0; i < 2; i++) conv_service(p, sb, 1, chb + i * 128, i == 0);
      bar_arrive(NB_CD, 64);
      mbar_wait(sb + BAR_WO, 0);
      poll_counter(p.scr->cnt + CNT_Y + (cb >> 1), tag * 64);
      STAMP(47);
      if (elect_one()) mbar_arrive(sb + BAR_YT);
      held_service(p, sb, 1, chb + 256, rb, cb, tag, lane);
      if (lane == 0) *(volatile uint32_t*)&p.scr->epoch[lin] = tag;
      STAMP(23);
    }
  } else {
    if (warp == 7) STAMP(36);
    const int wg = warp >> 2, w = warp & 3, g = lane >> 2, t = lane & 3;
    Taps k;
    uint32_t xw[2][10];
    if (wg == 2) {
      asm volatile("setmaxnreg.inc.sync.aligned.u32 160;");
      const int tb = rb * 2 + (cb & 1), c0 = (cb >> 1) * 320;
      const uint32_t cv = sb + OFF_CV + CV_SZ;
      if (w == 0) zero_pads(sb + OFF_CV, lane);
      mbar_wait(sb + BAR_KV + 8, 0);
      const int t0 = tb * 32 + w * 8;
      const __nv_bfloat16* kp = p.k + (size_t)(t0 - 3) * kD + c0 + lane * 2;
      const __nv_bfloat16* vp = p.v + (size_t)t0 * kD + c0 + lane * 2;
      const __nv_bfloat16* sp = p.shift + (c0 + lane * 2) * 4;
      const uint32_t oa = cv + ((3 - w) & 1) * 1024 + lane * 32 + ((((3 - w) >> 1) ^ (lane >> 2)) & 1) * 16;
#pragma unroll 1
      for (int r = 0; r < 2; r++) {
        KvRegs n0, n1, n2;
        kv_load(n0, kp + r * 128, vp + r * 128, sp + r * 512, t0 > 0);
        kv_load(n1, kp + r * 128 + 64, vp + r * 128 + 64, sp + r * 512 + 256, t0 > 0);
        if (r) kv_load(n2, kp + 256, vp + 256, sp + 1024, t0 > 0);
        kv_unit(n0, oa + r * 8192);
        bar_sync(NB_WGC, 128);
        mbar_arrive_if(sb + BAR_KU + 16 * r, tid == 0);
        if (r) mbar_wait(sb + BAR_KU, 1);
        kv_unit(n1, oa + (r ? 0 : 4096));
        bar_sync(NB_WGC, 128);
        mbar_arrive_if(sb + BAR_KU + 16 * r + 8, tid == 0);
        if (r) {
          kv_unit(n2, oa + 4096);
          bar_sync(NB_WGC, 128);
          mbar_arrive_if(sb + BAR_KU + 32, tid == 0);
        } else {
          mbar_wait(sb + BAR_AF + 8 * ((cb >> 1) * 5 + 1), 0);
          mbar_wait2(sb + BAR_AF + 8 * ((cb >> 1) * 5 + 2), 0, sb + BAR_AF + 8 * ((cb >> 1) * 5 + 4), 0);
          final_load_x(xw, sb + OFF_A, cb, 1, w, lane);
        }
      }
      STAMPW(13);
      load_taps(k, p, chb, tid);
    } else {
      float d[96];
      if (wg == 0) st_ll2(&p.scr->zstat[(rb * 256 + cb * 64 + w * 16 + g + (t >> 1) * 8) * 2 + (t & 1)], 0, 0);
      else if ((tid & 7) == 0) st_ll4(&p.scr->xstat[rb * 64 + cb * 16 + (tid >> 3)], 0, 0, 0, 0);
      {
        #pragma unroll
        for (int i = 0; i < 96; i++) d[i] = 0.f;
        {
          if (__builtin_expect(wg == 1, 0)) {
            const int tid = tid_now();
            const uint32_t epoch = load_epoch(p, lin, lane);
            float s = 0.f, q = 0.f;
#pragma unroll 1
            for (int i = 0; i < 10; i++) {
              mbar_wait(sb + BAR_AF + 8 * i, 0);
              const uint4 x4 = lds128(sb + OFF_A + i * A_SLOT + cb * 2048 + tid * 16);
              const uint32_t u[4] = {x4.x, x4.y, x4.z, x4.w};
#pragma unroll
              for (int e = 0; e < 4; e++) { const float a = bf_lo(u[e]), c = bf_hi(u[e]); s += a + c; q = fmaf(a, a, q); q = fmaf(c, c, q); }
            }
#pragma unroll
            for (int o = 1; o <= 4; o <<= 1) { s += __shfl_xor_sync(0xffffffff, s, o); q += __shfl_xor_sync(0xffffffff, q, o); }
            const float m = s * (1.f / kD);
            const float r = rsqrtf(fmaxf(fmaf(-m, m, q * (1.f / kD)), 0.f) + 1e-5f);
            if ((tid & 7) == 0) st_ll4(&p.scr->xstat[rb * 64 + cb * 16 + (tid >> 3)], __float_as_uint(m), epoch + 1, __float_as_uint(r), epoch + 1);
            STAMPW(12);
            bar_sync(NB_G1, 256);
          }
          gemm_loop<192, true, 0, D1>(d, sb, 10, 0, 0, 0, 0, wg, 2, tid_now(), [&]() { if (G1_AT == 0 && wg == 0) bar_arrive(NB_G1, 256); }, [](int) {});
          asm volatile("setmaxnreg.inc.sync.aligned.u32 160;");
          STAMPW(wg ? 14 : 1);
          mbar_wait2(sb + BAR_XS, 0, sb + BAR_ST + 8 * wg, 0);
        }
        const int t1 = tid_now();
        const uint32_t xa1 = sb + OFF_XS + (w * 16 + ((t1 & 31) >> 2)) * 8;
        const float2 s0 = lds64f(xa1), s1 = lds64f(xa1 + 64);
        uint32_t z[48];
        float st[4];
        if (CFENCE) fence_async_smem();
        fold_mean(d, sb + OFF_CS + (1 - wg) * 768, s0.x, s1.x, t1 & 3);
        if (G1_AT == 1 && wg == 0) bar_arrive(NB_G1, 256);
        WG_WAIT(0);
        acc_fence<96>(d);
        gelu_tile(d, z, st, s0.y, s1.y);
        const int tid = tid_now(), lane = tid & 31, g = lane >> 2, t = lane & 3;
        if (wg == 1) {
          uint32_t bra, brb;
          asm volatile("ld.shared.u16 %0, [%1];" : "=r"(bra) : "r"(sb + OFF_BIAS + (w * 16 + g) * 2));
          asm volatile("ld.shared.u16 %0, [%1+16];" : "=r"(brb) : "r"(sb + OFF_BIAS + (w * 16 + g) * 2));
#pragma unroll
          for (int j = 0; j < 96; j++) d[j] = bf_lo((j & 2) ? brb : bra);
          STAMPW(15);
          gemm_loop<192, true, 1, D2>(d, sb, 32, 0, 1, 20, 0, 2, 2, tid, [&]() { if (HOLD_AT < 32) mbar_arrive_if(sb + BAR_GO, tid == 0); }, [](int) {});
          if (HOLD_AT == 32) mbar_arrive_if(sb + BAR_GO, tid == 0);
          STAMPW(16);
          const int t2 = tid_now(), l2 = t2 & 31;
          const uint32_t ha = sb + OFF_A + 5 * A_SLOT + (l2 >> 4) * 1024 + (2 * w + ((l2 >> 3) & 1)) * 128 + (l2 & 7) * 16;
#pragma unroll
          for (int j = 0; j < 24; j += 2) {
#pragma unroll
            for (int e = 0; e < 4; e++) z[2 * j + e] = hmul2(z[2 * j + e], pack2(d[4 * j + 2 * e], d[4 * j + 2 * e + 1]));
            stsm4(ha + j * 1024, z[2 * j], z[2 * j + 1], z[2 * j + 2], z[2 * j + 3]);
          }
          fence_async_smem();
          bar_sync(NB_WGB, 128);
          mbar_arrive_if(sb + BAR_AF + 8 * (t2 == 3 ? (BAR_G2 - BAR_AF) / 8 : (t2 == 4 ? (BAR_GO - BAR_AF) / 8 : 5 + t2)), t2 < (HOLD_AT == 33 ? 5 : 4));
          STAMPW(17);
          {
            float e[80];
#pragma unroll
            for (int j = 0; j < 80; j++) e[j] = 0.f;
            gemm_loop<160, false, 2, DB>(e, sb, 12, 5, 0, 2, 0, 2, 2, tid_now(), []() {}, [](int) {});
            STAMPW(10);
            const int t3 = tid_now();
#pragma unroll
            for (int j = 0; j < 10; j++) {
              sts128(sb + OFF_A + j * 2048 + t3 * 16, pack2(e[8 * j], e[8 * j + 1]), pack2(e[8 * j + 2], e[8 * j + 3]), pack2(e[8 * j + 4], e[8 * j + 5]),
                     pack2(e[8 * j + 6], e[8 * j + 7]));
              if (j == 4) bar_arrive(NB_WO, 256);
            }
            bar_arrive(NB_Z, 256);
            STAMPW(45);
          }
          return;
        }
        const bool hi = t & 2;
        float a0 = (hi ? st[2] : st[0]) + __shfl_xor_sync(0xffffffff, hi ? st[0] : st[2], 2);
        float a1 = (hi ? st[3] : st[1]) + __shfl_xor_sync(0xffffffff, hi ? st[1] : st[3], 2);
        a0 = ((t & 1) ? a1 : a0) + __shfl_xor_sync(0xffffffff, (t & 1) ? a0 : a1, 1);
        const uint32_t tag = lds32<0>(sb + OFF_TAG);
        uint2* zs = p.scr->zstat + (rb * 256 + w * 16 + g + (t >> 1) * 8) * 2 + (t & 1);
        st_ll2(zs + cb * 128, __float_as_uint(a0), tag);
        STAMPW(2);
        uint2 u[4];
        if (ZPOLL == 0) {
#pragma unroll
          for (int i = 0; i < 4; i++) u[i] = ld_ll2(zs + i * 128);
        }
        final_load_x(xw, sb + OFF_A, cb, 0, w, lane);
        fence_async_smem();
        bar_sync(NB_WGA, 128);
        mbar_arrive_if(sb + BAR_AE + 8 * tid, tid < NA);
        if (ZPOLL == 1) {
#pragma unroll
          for (int i = 0; i < 4; i++) u[i] = ld_ll2(zs + i * 128);
        }
        const uint32_t za = sb + OFF_A + LEAD * A_SLOT + (2 * w + ((lane >> 3) & 1)) * 3072 + (lane >> 4) * 128 + (lane & 7) * 16;
        const float ca = 0.5f * (hi ? s1.y : s0.y), inv = 1.f / 768.f;
        mbar_wait2(sb + BAR_AE + 8 * (LEAD + 2), 0, sb + BAR_KU + 16, 0);
        uint32_t t0 = 0;
#pragma unroll 1
        while (!__all_sync(0xffffffff, u[0].y == tag && u[1].y == tag && u[2].y == tag && u[3].y == tag)) {
          spin_guard(t0);
#pragma unroll
          for (int i = 0; i < 4; i++) u[i] = ld_ll2(zs + i * 128);
        }
        STAMPW(3);
        a0 = ((__uint_as_float(u[0].x) + __uint_as_float(u[1].x)) + (__uint_as_float(u[2].x) + __uint_as_float(u[3].x))) * inv;
        a1 = __shfl_xor_sync(0xffffffff, a0, 1);
        const float m = (t & 1) ? a1 : a0, q = (t & 1) ? a0 : a1;
        const float r = bf_lo(pack2(ca * rsqrtf(fmaf(fmaxf(fmaf(-m, m, q), 0.f), ca * ca, 1e-5f)), 0.f));
        const uint32_t rn = pack2(r, -m * r), ro = __shfl_xor_sync(0xffffffff, rn, 2);
        const uint32_t ra2 = prmt(hi ? ro : rn, 0, 0x1010), n2a = prmt(hi ? ro : rn, 0, 0x3232), rb2 = prmt(hi ? rn : ro, 0, 0x1010), n2b = prmt(hi ? rn : ro, 0, 0x3232);
#pragma unroll
        for (int j = 0; j < 24; j += 2)
          stsm4(za + j * 128, hfma2(z[2 * j], ra2, n2a), hfma2(z[2 * j + 1], rb2, n2b), hfma2(z[2 * j + 2], ra2, n2a), hfma2(z[2 * j + 3], rb2, n2b));
        fence_async_smem();
      }
      bar_arrive(NB_Z, 160);
      {
        const uint32_t zero = lds32<0>(sb + OFF_TAG + 4);
#pragma unroll
        for (int i = 0; i < 20; i++) xw[i / 10][i % 10] |= zero;
      }
      load_taps(k, p, chb + 64, tid_now());
      STAMPW(4);
    }
    const int h = wg >> 1;
    {
    const int tid = tid_now(), lane = tid & 31;
    conv_worker(p, k, sb + OFF_CV + (1 - h) * CV_SZ, sb + OFF_A + 9 * A_SLOT + h * 4096, sb + BAR_XF + 8 * h, NB_WGA + h,
                chb + (h ? 0 : 64), 2 + h, sb + BAR_GO, w, lane, tid, h ? 40 : 5, rb, cb);
    {
      const int t3 = tid_now(), l3 = t3 & 31;
      const uint32_t xs_addr = sb + OFF_XS + (w * 16 + (l3 >> 2)) * 8;
      const float2 s0 = lds64f(xs_addr), s1 = lds64f(xs_addr + 64);
      const uint32_t ya = sb + y_tile(h) + ((l3 >> 4) * 8 + (l3 & 7)) * 128 + (((2 * w + ((l3 >> 3) & 1)) ^ (l3 & 7) ^ (rb & 7)) << 4);
      uint32_t sw[2][10];
      mbar_wait(sb + BAR_XF + 8 * h, h);
      final_s_early(sw, xw, ya, s0, s1);
      uint32_t ph = 1, t0 = 0, y[8];
#pragma unroll 1
      while (true) {
        mbar_wait(sb + BAR_YL + 16 * h, ph);
        if (bar_all(NB_WGA + h, 128, final_late(y, ya))) break;
        spin_guard(t0);
        ph ^= 1;
        if (t3 == 0) load_late_y(p, sb, h, rb, cb, lds32<0>(sb + OFF_TAG) & 1);
      }
#pragma unroll
      for (int e = 0; e < 8; e++) sw[e & 1][4 + (e >> 1)] = hmul2(sw[e & 1][4 + (e >> 1)], ~y[e]);
      __nv_bfloat16* o0 = p.out + (size_t)(w * 512 + rb * 16 + (l3 >> 2)) * kD + seg_col(cb, h);
      STAMPW(h ? 44 : 9);
      bar_sync(h ? NB_Z : NB_WO, 256);
      float d[40];
#pragma unroll
      for (int j = 0; j < 5; j++) {
        const uint4 v = lds128(sb + OFF_A + (h * 5 + j) * 2048 + t3 * 16);
        d[8 * j] = bf_lo(v.x); d[8 * j + 1] = bf_hi(v.x); d[8 * j + 2] = bf_lo(v.y); d[8 * j + 3] = bf_hi(v.y);
        d[8 * j + 4] = bf_lo(v.z); d[8 * j + 5] = bf_hi(v.z); d[8 * j + 6] = bf_lo(v.w); d[8 * j + 7] = bf_hi(v.w);
      }
      final_out(d, xw, sw, s0.y, s1.y, o0, h, l3 & 3);
    }
    }
  }
}

typedef CUresult (*EncodeFn)(CUtensorMap*, CUtensorMapDataType, cuuint32_t, void*, const cuuint64_t*, const cuuint64_t*, const cuuint32_t*,
                             const cuuint32_t*, CUtensorMapInterleave, CUtensorMapSwizzle, CUtensorMapL2promotion, CUtensorMapFloatOOBfill);

void encode(EncodeFn fn, CUtensorMap* m, const void* ptr, int rank, const cuuint64_t* dims, const cuuint64_t* strides, const cuuint32_t* box,
            CUtensorMapSwizzle swz = CU_TENSOR_MAP_SWIZZLE_128B) {
  const cuuint32_t es[3] = {1, 1, 1};
  fn(m, CU_TENSOR_MAP_DATA_TYPE_BFLOAT16, rank, const_cast<void*>(ptr), dims, strides, box, es, CU_TENSOR_MAP_INTERLEAVE_NONE,
     swz, CU_TENSOR_MAP_L2_PROMOTION_L2_128B, CU_TENSOR_MAP_FLOAT_OOB_FILL_NONE);
}

}

extern "C" void kernel_launch(void* const* d_in, const int* in_sizes, int n_in, void* d_out, int out_size) {
  (void)in_sizes; (void)n_in; (void)out_size;
  static EncodeFn enc = nullptr;
  static Scratch* scr = nullptr;
  static int sms = 0;
  if (!enc) {
    void* fn = nullptr;
    cudaDriverEntryPointQueryResult qr;
    cudaGetDriverEntryPoint("cuTensorMapEncodeTiled", &fn, cudaEnableDefault, &qr);
    enc = (EncodeFn)fn;
    cudaFuncSetAttribute(fused_kernel, cudaFuncAttributeMaxDynamicSharedMemorySize, SMEM_BYTES);
    cudaGetSymbolAddress((void**)&scr, g_scr);
    int dev = 0;
    cudaGetDevice(&dev);
    cudaDeviceGetAttribute(&sms, cudaDevAttrMultiProcessorCount, dev);
  }
  Params p;
  p.scr = scr;
  p.by_smid = sms == 132;
  p.k = (const __nv_bfloat16*)d_in[1];
  p.v = (const __nv_bfloat16*)d_in[2];
  p.shift = (const __nv_bfloat16*)d_in[3];
  p.ssmk = (const __nv_bfloat16*)d_in[4];
  p.ssmD = (const __nv_bfloat16*)d_in[5];
  p.wsp = (const __nv_bfloat16*)d_in[8];
  p.bsp = (const __nv_bfloat16*)d_in[9];
  p.wout = (const __nv_bfloat16*)d_in[10];
  p.out = (__nv_bfloat16*)d_out;
  for (int i = 0; i < 2; i++) {
    const cuuint64_t n = i ? kS : kD, dims[3] = {n, 512, 4}, st[2] = {n * 2, n * 1024};
    const cuuint32_t box[3] = {64, 16, 4};
    encode(enc, i ? &p.tmWsp : &p.tmX, d_in[i ? 8 : 0], 3, dims, st, box);
  }
  {
    const cuuint64_t dims[3] = {64, kD, kF / 64}, st[2] = {kF * 2, 128};
    const cuuint32_t box[3] = {64, 64, 3};
    encode(enc, &p.tmW, d_in[7], 3, dims, st, box);
  }
  {
    const cuuint64_t dims[2] = {kS, 896}, st[1] = {kS * 2};
    const cuuint32_t box[2] = {64, 16};
    encode(enc, &p.tmY, scr->y, 2, dims, st, box);
  }
  {
    const cuuint64_t dims[3] = {1024, kD / 2, 4}, st[2] = {8192, 2048};
    const cuuint32_t box[3] = {16, 32, 4};
    encode(enc, &p.tmKV, scr->kvx, 3, dims, st, box, CU_TENSOR_MAP_SWIZZLE_32B);
  }
  fused_kernel<<<132, 512, SMEM_BYTES, cudaStreamPerThread>>>(p);
}
```

```cpp
#include <cuda_runtime.h>
#include <cuda.h>
#include <cuda_bf16.h>
#include <stdint.h>

template <int N> struct WG;
template <> struct WG<16> {
  static __device__ __forceinline__ void rs(float* d, const uint32_t* a, uint64_t db) {
    asm volatile("{\n.reg .pred p;\nsetp.ne.b32 p, 1, 0;\nwgmma.mma_async.sync.aligned.m64n16k16.f32.bf16.bf16 {"
      "%0, %1, %2, %3, %4, %5, %6, %7"
      "}, {%8, %9, %10, %11}, %12, p, 1, 1, 0;\n}\n"
      :
      "+f"(d[0]), "+f"(d[1]), "+f"(d[2]), "+f"(d[3]), "+f"(d[4]), "+f"(d[5]), "+f"(d[6]), "+f"(d[7])
      : "r"(a[0]), "r"(a[1]), "r"(a[2]), "r"(a[3]), "l"(db));
  }
};
template <> struct WG<32> {
  static __device__ __forceinline__ void rs(float* d, const uint32_t* a, uint64_t db) {
    asm volatile("{\n.reg .pred p;\nsetp.ne.b32 p, 1, 0;\nwgmma.mma_async.sync.aligned.m64n32k16.f32.bf16.bf16 {"
      "%0, %1, %2, %3, %4, %5, %6, %7, %8, %9, %10, %11, %12, %13, %14, %15"
      "}, {%16, %17, %18, %19}, %20, p, 1, 1, 0;\n}\n"
      :
      "+f"(d[0]), "+f"(d[1]), "+f"(d[2]), "+f"(d[3]), "+f"(d[4]), "+f"(d[5]), "+f"(d[6]), "+f"(d[7]),
      "+f"(d[8]), "+f"(d[9]), "+f"(d[10]), "+f"(d[11]), "+f"(d[12]), "+f"(d[13]), "+f"(d[14]), "+f"(d[15])
      : "r"(a[0]), "r"(a[1]), "r"(a[2]), "r"(a[3]), "l"(db));
  }
};
template <> struct WG<48> {
  static __device__ __forceinline__ void rs(float* d, const uint32_t* a, uint64_t db) {
    asm volatile("{\n.reg .pred p;\nsetp.ne.b32 p, 1, 0;\nwgmma.mma_async.sync.aligned.m64n48k16.f32.bf16.bf16 {"
      "%0, %1, %2, %3, %4, %5, %6, %7, %8, %9, %10, %11, %12, %13, %14, %15, "
      "%16, %17, %18, %19, %20, %21, %22, %23"
      "}, {%24, %25, %26, %27}, %28, p, 1, 1, 0;\n}\n"
      :
      "+f"(d[0]), "+f"(d[1]), "+f"(d[2]), "+f"(d[3]), "+f"(d[4]), "+f"(d[5]), "+f"(d[6]), "+f"(d[7]),
      "+f"(d[8]), "+f"(d[9]), "+f"(d[10]), "+f"(d[11]), "+f"(d[12]), "+f"(d[13]), "+f"(d[14]), "+f"(d[15]),
      "+f"(d[16]), "+f"(d[17]), "+f"(d[18]), "+f"(d[19]), "+f"(d[20]), "+f"(d[21]), "+f"(d[22]), "+f"(d[23])
      : "r"(a[0]), "r"(a[1]), "r"(a[2]), "r"(a[3]), "l"(db));
  }
};
template <> struct WG<64> {
  static __device__ __forceinline__ void rs(float* d, const uint32_t* a, uint64_t db) {
    asm volatile("{\n.reg .pred p;\nsetp.ne.b32 p, 1, 0;\nwgmma.mma_async.sync.aligned.m64n64k16.f32.bf16.bf16 {"
      "%0, %1, %2, %3, %4, %5, %6, %7, %8, %9, %10, %11, %12, %13, %14, %15, "
      "%16, %17, %18, %19, %20, %21, %22, %23, %24, %25, %26, %27, %28, %29, %30, %31"
      "}, {%32, %33, %34, %35}, %36, p, 1, 1, 0;\n}\n"
      :
      "+f"(d[0]), "+f"(d[1]), "+f"(d[2]), "+f"(d[3]), "+f"(d[4]), "+f"(d[5]), "+f"(d[6]), "+f"(d[7]),
      "+f"(d[8]), "+f"(d[9]), "+f"(d[10]), "+f"(d[11]), "+f"(d[12]), "+f"(d[13]), "+f"(d[14]), "+f"(d[15]),
      "+f"(d[16]), "+f"(d[17]), "+f"(d[18]), "+f"(d[19]), "+f"(d[20]), "+f"(d[21]), "+f"(d[22]), "+f"(d[23]),
      "+f"(d[24]), "+f"(d[25]), "+f"(d[26]), "+f"(d[27]), "+f"(d[28]), "+f"(d[29]), "+f"(d[30]), "+f"(d[31])
      : "r"(a[0]), "r"(a[1]), "r"(a[2]), "r"(a[3]), "l"(db));
  }
};
template <> struct WG<80> {
  static __device__ __forceinline__ void rs(float* d, const uint32_t* a, uint64_t db) {
    asm volatile("{\n.reg .pred p;\nsetp.ne.b32 p, 1, 0;\nwgmma.mma_async.sync.aligned.m64n80k16.f32.bf16.bf16 {"
      "%0, %1, %2, %3, %4, %5, %6, %7, %8, %9, %10, %11, %12, %13, %14, %15, "
      "%16, %17, %18, %19, %20, %21, %22, %23, %24, %25, %26, %27, %28, %29, %30, %31, "
      "%32, %33, %34, %35, %36, %37, %38, %39"
      "}, {%40, %41, %42, %43}, %44, p, 1, 1, 0;\n}\n"
      :
      "+f"(d[0]), "+f"(d[1]), "+f"(d[2]), "+f"(d[3]), "+f"(d[4]), "+f"(d[5]), "+f"(d[6]), "+f"(d[7]),
      "+f"(d[8]), "+f"(d[9]), "+f"(d[10]), "+f"(d[11]), "+f"(d[12]), "+f"(d[13]), "+f"(d[14]), "+f"(d[15]),
      "+f"(d[16]), "+f"(d[17]), "+f"(d[18]), "+f"(d[19]), "+f"(d[20]), "+f"(d[21]), "+f"(d[22]), "+f"(d[23]),
      "+f"(d[24]), "+f"(d[25]), "+f"(d[26]), "+f"(d[27]), "+f"(d[28]), "+f"(d[29]), "+f"(d[30]), "+f"(d[31]),
      "+f"(d[32]), "+f"(d[33]), "+f"(d[34]), "+f"(d[35]), "+f"(d[36]), "+f"(d[37]), "+f"(d[38]), "+f"(d[39])
      : "r"(a[0]), "r"(a[1]), "r"(a[2]), "r"(a[3]), "l"(db));
  }
};
template <> struct WG<96> {
  static __device__ __forceinline__ void rs(float* d, const uint32_t* a, uint64_t db) {
    asm volatile("{\n.reg .pred p;\nsetp.ne.b32 p, 1, 0;\nwgmma.mma_async.sync.aligned.m64n96k16.f32.bf16.bf16 {"
      "%0, %1, %2, %3, %4, %5, %6, %7, %8, %9, %10, %11, %12, %13, %14, %15, "
      "%16, %17, %18, %19, %20, %21, %22, %23, %24, %25, %26, %27, %28, %29, %30, %31, "
      "%32, %33, %34, %35, %36, %37, %38, %39, %40, %41, %42, %43, %44, %45, %46, %47"
      "}, {%48, %49, %50, %51}, %52, p, 1, 1, 0;\n}\n"
      :
      "+f"(d[0]), "+f"(d[1]), "+f"(d[2]), "+f"(d[3]), "+f"(d[4]), "+f"(d[5]), "+f"(d[6]), "+f"(d[7]),
      "+f"(d[8]), "+f"(d[9]), "+f"(d[10]), "+f"(d[11]), "+f"(d[12]), "+f"(d[13]), "+f"(d[14]), "+f"(d[15]),
      "+f"(d[16]), "+f"(d[17]), "+f"(d[18]), "+f"(d[19]), "+f"(d[20]), "+f"(d[21]), "+f"(d[22]), "+f"(d[23]),
      "+f"(d[24]), "+f"(d[25]), "+f"(d[26]), "+f"(d[27]), "+f"(d[28]), "+f"(d[29]), "+f"(d[30]), "+f"(d[31]),
      "+f"(d[32]), "+f"(d[33]), "+f"(d[34]), "+f"(d[35]), "+f"(d[36]), "+f"(d[37]), "+f"(d[38]), "+f"(d[39]),
      "+f"(d[40]), "+f"(d[41]), "+f"(d[42]), "+f"(d[43]), "+f"(d[44]), "+f"(d[45]), "+f"(d[46]), "+f"(d[47])
      : "r"(a[0]), "r"(a[1]), "r"(a[2]), "r"(a[3]), "l"(db));
  }
};
template <> struct WG<112> {
  static __device__ __forceinline__ void rs(float* d, const uint32_t* a, uint64_t db) {
    asm volatile("{\n.reg .pred p;\nsetp.ne.b32 p, 1, 0;\nwgmma.mma_async.sync.aligned.m64n112k16.f32.bf16.bf16 {"
      "%0, %1, %2, %3, %4, %5, %6, %7, %8, %9, %10, %11, %12, %13, %14, %15, "
      "%16, %17, %18, %19, %20, %21, %22, %23, %24, %25, %26, %27, %28, %29, %30, %31, "
      "%32, %33, %34, %35, %36, %37, %38, %39, %40, %41, %42, %43, %44, %45, %46, %47, "
      "%48, %49, %50, %51, %52, %53, %54, %55"
      "}, {%56, %57, %58, %59}, %60, p, 1, 1, 0;\n}\n"
      :
      "+f"(d[0]), "+f"(d[1]), "+f"(d[2]), "+f"(d[3]), "+f"(d[4]), "+f"(d[5]), "+f"(d[6]), "+f"(d[7]),
      "+f"(d[8]), "+f"(d[9]), "+f"(d[10]), "+f"(d[11]), "+f"(d[12]), "+f"(d[13]), "+f"(d[14]), "+f"(d[15]),
      "+f"(d[16]), "+f"(d[17]), "+f"(d[18]), "+f"(d[19]), "+f"(d[20]), "+f"(d[21]), "+f"(d[22]), "+f"(d[23]),
      "+f"(d[24]), "+f"(d[25]), "+f"(d[26]), "+f"(d[27]), "+f"(d[28]), "+f"(d[29]), "+f"(d[30]), "+f"(d[31]),
      "+f"(d[32]), "+f"(d[33]), "+f"(d[34]), "+f"(d[35]), "+f"(d[36]), "+f"(d[37]), "+f"(d[38]), "+f"(d[39]),
      "+f"(d[40]), "+f"(d[41]), "+f"(d[42]), "+f"(d[43]), "+f"(d[44]), "+f"(d[45]), "+f"(d[46]), "+f"(d[47]),
      "+f"(d[48]), "+f"(d[49]), "+f"(d[50]), "+f"(d[51]), "+f"(d[52]), "+f"(d[53]), "+f"(d[54]), "+f"(d[55])
      : "r"(a[0]), "r"(a[1]), "r"(a[2]), "r"(a[3]), "l"(db));
  }
};
template <> struct WG<128> {
  static __device__ __forceinline__ void rs(float* d, const uint32_t* a, uint64_t db) {
    asm volatile("{\n.reg .pred p;\nsetp.ne.b32 p, 1, 0;\nwgmma.mma_async.sync.aligned.m64n128k16.f32.bf16.bf16 {"
      "%0, %1, %2, %3, %4, %5, %6, %7, %8, %9, %10, %11, %12, %13, %14, %15, "
      "%16, %17, %18, %19, %20, %21, %22, %23, %24, %25, %26, %27, %28, %29, %30, %31, "
      "%32, %33, %34, %35, %36, %37, %38, %39, %40, %41, %42, %43, %44, %45, %46, %47, "
      "%48, %49, %50, %51, %52, %53, %54, %55, %56, %57, %58, %59, %60, %61, %62, %63"
      "}, {%64, %65, %66, %67}, %68, p, 1, 1, 0;\n}\n"
      :
      "+f"(d[0]), "+f"(d[1]), "+f"(d[2]), "+f"(d[3]), "+f"(d[4]), "+f"(d[5]), "+f"(d[6]), "+f"(d[7]),
      "+f"(d[8]), "+f"(d[9]), "+f"(d[10]), "+f"(d[11]), "+f"(d[12]), "+f"(d[13]), "+f"(d[14]), "+f"(d[15]),
      "+f"(d[16]), "+f"(d[17]), "+f"(d[18]), "+f"(d[19]), "+f"(d[20]), "+f"(d[21]), "+f"(d[22]), "+f"(d[23]),
      "+f"(d[24]), "+f"(d[25]), "+f"(d[26]), "+f"(d[27]), "+f"(d[28]), "+f"(d[29]), "+f"(d[30]), "+f"(d[31]),
      "+f"(d[32]), "+f"(d[33]), "+f"(d[34]), "+f"(d[35]), "+f"(d[36]), "+f"(d[37]), "+f"(d[38]), "+f"(d[39]),
      "+f"(d[40]), "+f"(d[41]), "+f"(d[42]), "+f"(d[43]), "+f"(d[44]), "+f"(d[45]), "+f"(d[46]), "+f"(d[47]),
      "+f"(d[48]), "+f"(d[49]), "+f"(d[50]), "+f"(d[51]), "+f"(d[52]), "+f"(d[53]), "+f"(d[54]), "+f"(d[55]),
      "+f"(d[56]), "+f"(d[57]), "+f"(d[58]), "+f"(d[59]), "+f"(d[60]), "+f"(d[61]), "+f"(d[62]), "+f"(d[63])
      : "r"(a[0]), "r"(a[1]), "r"(a[2]), "r"(a[3]), "l"(db));
  }
};
template <> struct WG<160> {
  static __device__ __forceinline__ void ss(float* d, uint64_t da, uint64_t db, int sd) {
    asm volatile("{\n.reg .pred p;\nsetp.ne.b32 p, %82, 0;\nwgmma.mma_async.sync.aligned.m64n160k16.f32.bf16.bf16 {"
      "%0, %1, %2, %3, %4, %5, %6, %7, %8, %9, %10, %11, %12, %13, %14, %15, "
      "%16, %17, %18, %19, %20, %21, %22, %23, %24, %25, %26, %27, %28, %29, %30, %31, "
      "%32, %33, %34, %35, %36, %37, %38, %39, %40, %41, %42, %43, %44, %45, %46, %47, "
      "%48, %49, %50, %51, %52, %53, %54, %55, %56, %57, %58, %59, %60, %61, %62, %63, "
      "%64, %65, %66, %67, %68, %69, %70, %71, %72, %73, %74, %75, %76, %77, %78, %79"
      "}, %80, %81, p, 1, 1, 0, 1;\n}\n"
      :
      "+f"(d[0]), "+f"(d[1]), "+f"(d[2]), "+f"(d[3]), "+f"(d[4]), "+f"(d[5]), "+f"(d[6]), "+f"(d[7]),
      "+f"(d[8]), "+f"(d[9]), "+f"(d[10]), "+f"(d[11]), "+f"(d[12]), "+f"(d[13]), "+f"(d[14]), "+f"(d[15]),
      "+f"(d[16]), "+f"(d[17]), "+f"(d[18]), "+f"(d[19]), "+f"(d[20]), "+f"(d[21]), "+f"(d[22]), "+f"(d[23]),
      "+f"(d[24]), "+f"(d[25]), "+f"(d[26]), "+f"(d[27]), "+f"(d[28]), "+f"(d[29]), "+f"(d[30]), "+f"(d[31]),
      "+f"(d[32]), "+f"(d[33]), "+f"(d[34]), "+f"(d[35]), "+f"(d[36]), "+f"(d[37]), "+f"(d[38]), "+f"(d[39]),
      "+f"(d[40]), "+f"(d[41]), "+f"(d[42]), "+f"(d[43]), "+f"(d[44]), "+f"(d[45]), "+f"(d[46]), "+f"(d[47]),
      "+f"(d[48]), "+f"(d[49]), "+f"(d[50]), "+f"(d[51]), "+f"(d[52]), "+f"(d[53]), "+f"(d[54]), "+f"(d[55]),
      "+f"(d[56]), "+f"(d[57]), "+f"(d[58]), "+f"(d[59]), "+f"(d[60]), "+f"(d[61]), "+f"(d[62]), "+f"(d[63]),
      "+f"(d[64]), "+f"(d[65]), "+f"(d[66]), "+f"(d[67]), "+f"(d[68]), "+f"(d[69]), "+f"(d[70]), "+f"(d[71]),
      "+f"(d[72]), "+f"(d[73]), "+f"(d[74]), "+f"(d[75]), "+f"(d[76]), "+f"(d[77]), "+f"(d[78]), "+f"(d[79])
      : "l"(da), "l"(db), "r"(sd));
  }
};
template <> struct WG<192> {
  static __device__ __forceinline__ void ss(float* d, uint64_t da, uint64_t db, int sd) {
    asm volatile("{\n.reg .pred p;\nsetp.ne.b32 p, %98, 0;\nwgmma.mma_async.sync.aligned.m64n192k16.f32.bf16.bf16 {"
      "%0, %1, %2, %3, %4, %5, %6, %7, %8, %9, %10, %11, %12, %13, %14, %15, "
      "%16, %17, %18, %19, %20, %21, %22, %23, %24, %25, %26, %27, %28, %29, %30, %31, "
      "%32, %33, %34, %35, %36, %37, %38, %39, %40, %41, %42, %43, %44, %45, %46, %47, "
      "%48, %49, %50, %51, %52, %53, %54, %55, %56, %57, %58, %59, %60, %61, %62, %63, "
      "%64, %65, %66, %67, %68, %69, %70, %71, %72, %73, %74, %75, %76, %77, %78, %79, "
      "%80, %81, %82, %83, %84, %85, %86, %87, %88, %89, %90, %91, %92, %93, %94, %95"
      "}, %96, %97, p, 1, 1, 0, 1;\n}\n"
      :
      "+f"(d[0]), "+f"(d[1]), "+f"(d[2]), "+f"(d[3]), "+f"(d[4]), "+f"(d[5]), "+f"(d[6]), "+f"(d[7]),
      "+f"(d[8]), "+f"(d[9]), "+f"(d[10]), "+f"(d[11]), "+f"(d[12]), "+f"(d[13]), "+f"(d[14]), "+f"(d[15]),
      "+f"(d[16]), "+f"(d[17]), "+f"(d[18]), "+f"(d[19]), "+f"(d[20]), "+f"(d[21]), "+f"(d[22]), "+f"(d[23]),
      "+f"(d[24]), "+f"(d[25]), "+f"(d[26]), "+f"(d[27]), "+f"(d[28]), "+f"(d[29]), "+f"(d[30]), "+f"(d[31]),
      "+f"(d[32]), "+f"(d[33]), "+f"(d[34]), "+f"(d[35]), "+f"(d[36]), "+f"(d[37]), "+f"(d[38]), "+f"(d[39]),
      "+f"(d[40]), "+f"(d[41]), "+f"(d[42]), "+f"(d[43]), "+f"(d[44]), "+f"(d[45]), "+f"(d[46]), "+f"(d[47]),
      "+f"(d[48]), "+f"(d[49]), "+f"(d[50]), "+f"(d[51]), "+f"(d[52]), "+f"(d[53]), "+f"(d[54]), "+f"(d[55]),
      "+f"(d[56]), "+f"(d[57]), "+f"(d[58]), "+f"(d[59]), "+f"(d[60]), "+f"(d[61]), "+f"(d[62]), "+f"(d[63]),
      "+f"(d[64]), "+f"(d[65]), "+f"(d[66]), "+f"(d[67]), "+f"(d[68]), "+f"(d[69]), "+f"(d[70]), "+f"(d[71]),
      "+f"(d[72]), "+f"(d[73]), "+f"(d[74]), "+f"(d[75]), "+f"(d[76]), "+f"(d[77]), "+f"(d[78]), "+f"(d[79]),
      "+f"(d[80]), "+f"(d[81]), "+f"(d[82]), "+f"(d[83]), "+f"(d[84]), "+f"(d[85]), "+f"(d[86]), "+f"(d[87]),
      "+f"(d[88]), "+f"(d[89]), "+f"(d[90]), "+f"(d[91]), "+f"(d[92]), "+f"(d[93]), "+f"(d[94]), "+f"(d[95])
      : "l"(da), "l"(db), "r"(sd));
  }
  static __device__ __forceinline__ void rst(float* d, const uint32_t* a, uint64_t db) {
    asm volatile("{\n.reg .pred p;\nsetp.ne.b32 p, 1, 0;\nwgmma.mma_async.sync.aligned.m64n192k16.f32.bf16.bf16 {"
      "%0, %1, %2, %3, %4, %5, %6, %7, %8, %9, %10, %11, %12, %13, %14, %15, "
      "%16, %17, %18, %19, %20, %21, %22, %23, %24, %25, %26, %27, %28, %29, %30, %31, "
      "%32, %33, %34, %35, %36, %37, %38, %39, %40, %41, %42, %43, %44, %45, %46, %47, "
      "%48, %49, %50, %51, %52, %53, %54, %55, %56, %57, %58, %59, %60, %61, %62, %63, "
      "%64, %65, %66, %67, %68, %69, %70, %71, %72, %73, %74, %75, %76, %77, %78, %79, "
      "%80, %81, %82, %83, %84, %85, %86, %87, %88, %89, %90, %91, %92, %93, %94, %95"
      "}, {%96, %97, %98, %99}, %100, p, 1, 1, 1;\n}\n"
      :
      "+f"(d[0]), "+f"(d[1]), "+f"(d[2]), "+f"(d[3]), "+f"(d[4]), "+f"(d[5]), "+f"(d[6]), "+f"(d[7]),
      "+f"(d[8]), "+f"(d[9]), "+f"(d[10]), "+f"(d[11]), "+f"(d[12]), "+f"(d[13]), "+f"(d[14]), "+f"(d[15]),
      "+f"(d[16]), "+f"(d[17]), "+f"(d[18]), "+f"(d[19]), "+f"(d[20]), "+f"(d[21]), "+f"(d[22]), "+f"(d[23]),
      "+f"(d[24]), "+f"(d[25]), "+f"(d[26]), "+f"(d[27]), "+f"(d[28]), "+f"(d[29]), "+f"(d[30]), "+f"(d[31]),
      "+f"(d[32]), "+f"(d[33]), "+f"(d[34]), "+f"(d[35]), "+f"(d[36]), "+f"(d[37]), "+f"(d[38]), "+f"(d[39]),
      "+f"(d[40]), "+f"(d[41]), "+f"(d[42]), "+f"(d[43]), "+f"(d[44]), "+f"(d[45]), "+f"(d[46]), "+f"(d[47]),
      "+f"(d[48]), "+f"(d[49]), "+f"(d[50]), "+f"(d[51]), "+f"(d[52]), "+f"(d[53]), "+f"(d[54]), "+f"(d[55]),
      "+f"(d[56]), "+f"(d[57]), "+f"(d[58]), "+f"(d[59]), "+f"(d[60]), "+f"(d[61]), "+f"(d[62]), "+f"(d[63]),
      "+f"(d[64]), "+f"(d[65]), "+f"(d[66]), "+f"(d[67]), "+f"(d[68]), "+f"(d[69]), "+f"(d[70]), "+f"(d[71]),
      "+f"(d[72]), "+f"(d[73]), "+f"(d[74]), "+f"(d[75]), "+f"(d[76]), "+f"(d[77]), "+f"(d[78]), "+f"(d[79]),
      "+f"(d[80]), "+f"(d[81]), "+f"(d[82]), "+f"(d[83]), "+f"(d[84]), "+f"(d[85]), "+f"(d[86]), "+f"(d[87]),
      "+f"(d[88]), "+f"(d[89]), "+f"(d[90]), "+f"(d[91]), "+f"(d[92]), "+f"(d[93]), "+f"(d[94]), "+f"(d[95])
      : "r"(a[0]), "r"(a[1]), "r"(a[2]), "r"(a[3]), "l"(db));
  }
};

#define K0_POLL 0
#define ZPOLL 0
#define ZQ_N 2
#define CFENCE 1
#define Z1_AT 4
#define G1_AT 1
#define HGRP 3
#define HPACE 200
#define DB 0
#define HOLD_AT 33
#define LL_AT 4
#define KV_T0 2300
#define ST_YIELD 1
#define HP0 3500
#define HPD 450
#define RAMP 1
#define LEAD 2
#define WSP_N 16
#define EARLY 0
#define CPIN 1
#define CW0 0
#define PFT 1
#define WSP_D 600
#define D1 4
#define D2 4
#define NSLEEP 32

namespace {

constexpr int kS = 2048, kD = 640, kF = 1536;
constexpr int NA = 10, NA2 = 9, NB = 5;
constexpr int A_SLOT = 8192, B_SLOT = 24576;
constexpr int OFF_A = 0;
constexpr int OFF_B = OFF_A + NA * A_SLOT;
constexpr int XB_PL = 2112;
constexpr int CV_KE = 4224, CV_KO = CV_KE + 4160;
constexpr int CV_SZ = CV_KO + 4160;
constexpr int OFF_CV = OFF_B + NB * B_SLOT;
constexpr int OFF_CS = OFF_CV + 2 * CV_SZ;
constexpr int OFF_BIAS = OFF_CS + 1536;
constexpr int OFF_XS = OFF_BIAS + 128;
constexpr int OFF_BAR = OFF_XS + 512;
constexpr int BAR_AF = OFF_BAR, BAR_ST = BAR_AF + 8 * NA, BAR_XF = BAR_ST + 16, BAR_KV = BAR_XF + 16;
constexpr int BAR_BF = OFF_BAR + 128, BAR_G2 = BAR_BF + 8 * (NB + 1), BAR_XS = BAR_G2 + 8, BAR_KU = BAR_XS + 8, BAR_ZP = BAR_KU + 40, BAR_XC = BAR_ZP + 8, BAR_WO = BAR_XC + 8;
constexpr int BAR_AE = OFF_BAR + 256, BAR_BE = BAR_AE + 8 * NA;
constexpr int BAR_YT = BAR_KU + 24;
constexpr int BAR_GO = BAR_XS;
constexpr int BAR_YL = BAR_KU + 16;
constexpr int OFF_TAG = OFF_CS - 32;
constexpr int SMEM_BYTES = OFF_BAR + 384;
static_assert(SMEM_BYTES <= 232448, "smem");
constexpr int NB_WGA = 1, NB_WGC = 2, NB_G1 = 3, NB_WO = 4, NB_CD = 5, NB_Z = 6, NB_WGB = 7;

constexpr int CNT_Z = 0, CNT_Y = 1, CNT_Z1 = 3, CNT_KV = 32, CNT_WO = 36;
struct Scratch {
  uint8_t kvx[kD * 4096];
  uint8_t z2[4 * 32 * 24576];
  uint8_t h[32 * 12 * 8192];
  uint8_t wo[4 * 12 * 20480];
  uint8_t y[896 * 4096];
  uint4 xstat[kS];
  uint2 zstat[kS * 8];
  uint2 colsum[kF];
  uint32_t cnt[2 * 32];
  uint32_t hcnt[32 * 32];
  uint32_t epoch[136];
};
__device__ __align__(1024) Scratch g_scr;
#define STAMP(i)
#define STAMP2(i)
#define STAMPW(i)

struct Params {
  Scratch* scr;
  int by_smid;
  const __nv_bfloat16 *k, *v, *shift, *ssmk, *ssmD, *wsp, *bsp, *wout;
  __nv_bfloat16* out;
  CUtensorMap tmX, tmW, tmWsp, tmY, tmKV;
};

__device__ __forceinline__ uint64_t mkdesc(uint32_t addr, uint32_t lbo, uint32_t sbo, uint32_t swz) {
  return (uint64_t)((addr & 0x3FFFF) >> 4) | ((uint64_t)(lbo >> 4) << 16) | ((uint64_t)(sbo >> 4) << 32) | ((uint64_t)swz << 62);
}
#define WG_FENCE() asm volatile("wgmma.fence.sync.aligned;" ::: "memory")
#define WG_COMMIT() asm volatile("wgmma.commit_group.sync.aligned;" ::: "memory")
#define WG_WAIT(n) asm volatile("wgmma.wait_group.sync.aligned %0;" ::"n"(n) : "memory")
template <int N> __device__ __forceinline__ void acc_fence(float* d) {
#pragma unroll
  for (int i = 0; i < N; i++) asm volatile("" : "+f"(d[i])::"memory");
}
__device__ __forceinline__ void mbar_init(uint32_t bar, int cnt) { asm volatile("mbarrier.init.shared::cta.b64 [%0], %1;" ::"r"(bar), "r"(cnt) : "memory"); }
__device__ __forceinline__ void mbar_expect(uint32_t bar, uint32_t bytes) { asm volatile("mbarrier.arrive.expect_tx.shared::cta.b64 _, [%0], %1;" ::"r"(bar), "r"(bytes) : "memory"); }
__device__ __forceinline__ void mbar_arrive(uint32_t bar) { asm volatile("mbarrier.arrive.shared::cta.b64 _, [%0];" ::"r"(bar) : "memory"); }
__device__ __forceinline__ void mbar_arrive_if(uint32_t bar, bool c) {
  asm volatile("{\n.reg .pred p;\nsetp.ne.u32 p, %1, 0;\n@p mbarrier.arrive.shared::cta.b64 _, [%0];\n}\n" ::"r"(bar), "r"((uint32_t)c) : "memory");
}
__device__ __forceinline__ void mbar_expect_if(uint32_t bar, uint32_t bytes, bool c) {
  asm volatile("{\n.reg .pred p;\nsetp.ne.u32 p, %2, 0;\n@p mbarrier.arrive.expect_tx.shared::cta.b64 _, [%0], %1;\n}\n" ::"r"(bar), "r"(bytes), "r"((uint32_t)c) : "memory");
}
__device__ __forceinline__ bool mbar_try(uint32_t bar, uint32_t parity) {
  uint32_t ok;
  asm volatile("{\n.reg .pred p;\nmbarrier.try_wait.parity.shared::cta.b64 p, [%1], %2;\nselp.u32 %0, 1, 0, p;\n}\n" : "=r"(ok) : "r"(bar), "r"(parity) : "memory");
  return ok;
}
__device__ __forceinline__ bool mbar_test(uint32_t bar, uint32_t parity) {
  uint32_t ok;
  asm volatile("{\n.reg .pred p;\nmbarrier.test_wait.parity.shared::cta.b64 p, [%1], %2;\nselp.u32 %0, 1, 0, p;\n}\n" : "=r"(ok) : "r"(bar), "r"(parity) : "memory");
  return ok;
}
__device__ __forceinline__ void die() { asm volatile("st.volatile.global.u32 [%0], %1;" ::"l"(0ull), "r"(0) : "memory"); }
__device__ __forceinline__ void spin_guard(uint32_t& n) { if (++n == (1u << 22)) die(); }
__device__ __forceinline__ void mbar_wait(uint32_t bar, uint32_t parity) {
  uint32_t t0 = 0;
#pragma unroll 1
  while (!mbar_try(bar, parity)) spin_guard(t0);
}
__device__ __forceinline__ void mbar_wait2(uint32_t b0, uint32_t p0, uint32_t b1, uint32_t p1) {
  uint32_t t0 = 0;
#pragma unroll 1
  while (true) {
    const bool r0 = mbar_try(b0, p0), r1 = mbar_try(b1, p1);
    if (r0 && r1) break;
    spin_guard(t0);
  }
}
__device__ __forceinline__ int tid_now() { int v; asm volatile("mov.u32 %0, %%tid.x;" : "=r"(v)); return v & 127; }
__device__ __forceinline__ bool elect_one() {
  uint32_t p;
  asm volatile("{\n.reg .pred P;\nelect.sync _|P, 0xffffffff;\nselp.u32 %0, 1, 0, P;\n}\n" : "=r"(p));
  return p;
}
__device__ __forceinline__ void bar_sync(int id, int n) { asm volatile("bar.sync %0, %1;" ::"r"(id), "r"(n) : "memory"); }
__device__ __forceinline__ void bar_arrive(int id, int n) { asm volatile("bar.arrive %0, %1;" ::"r"(id), "r"(n) : "memory"); }
__device__ __forceinline__ void fence_async_smem() { asm volatile("fence.proxy.async.shared::cta;" ::: "memory"); }
__device__ __forceinline__ void bulk_g2s(uint32_t dst, const void* src, uint32_t bytes, uint32_t bar) {
  asm volatile("cp.async.bulk.shared::cluster.global.mbarrier::complete_tx::bytes [%0], [%1], %2, [%3];" ::"r"(dst), "l"(src), "r"(bytes), "r"(bar) : "memory");
}
__device__ __forceinline__ void bulk_s2g(void* dst, uint32_t src, uint32_t bytes) {
  asm volatile("cp.async.bulk.global.shared::cta.bulk_group [%0], [%1], %2;" ::"l"(dst), "r"(src), "r"(bytes) : "memory");
}
__device__ __forceinline__ void tma2d(uint32_t dst, const CUtensorMap* m, int c0, int c1, uint32_t bar) {
  asm volatile("cp.async.bulk.tensor.2d.shared::cluster.global.mbarrier::complete_tx::bytes [%0], [%1, {%3, %4}], [%2];" ::"r"(dst), "l"(m), "r"(bar), "r"(c0), "r"(c1) : "memory");
}
__device__ __forceinline__ void tma3d(uint32_t dst, const CUtensorMap* m, int c0, int c1, int c2, uint32_t bar) {
  asm volatile("cp.async.bulk.tensor.3d.shared::cluster.global.mbarrier::complete_tx::bytes [%0], [%1, {%3, %4, %5}], [%2];" ::"r"(dst), "l"(m), "r"(bar), "r"(c0), "r"(c1), "r"(c2) : "memory");
}
__device__ __forceinline__ void tma_rows(uint32_t dst, const CUtensorMap* m, int c0, int rb, uint32_t bar) { tma3d(dst, m, c0, rb * 16, 0, bar); }
__device__ __forceinline__ uint4 ld_ll4(const void* p) {
  uint64_t a, b;
  asm volatile("ld.relaxed.gpu.global.v2.u64 {%0,%1}, [%2];" : "=l"(a), "=l"(b) : "l"(p) : "memory");
  return make_uint4((uint32_t)a, (uint32_t)(a >> 32), (uint32_t)b, (uint32_t)(b >> 32));
}
__device__ __forceinline__ void st_ll4(void* p, uint32_t a, uint32_t b, uint32_t c, uint32_t d) {
  asm volatile("st.relaxed.gpu.global.v2.u64 [%0], {%1,%2};" ::"l"(p), "l"(a | ((uint64_t)b << 32)), "l"(c | ((uint64_t)d << 32)) : "memory");
}
__device__ __forceinline__ void st_ll2(void* p, uint32_t a, uint32_t b) { asm volatile("st.relaxed.gpu.global.u64 [%0], %1;" ::"l"(p), "l"(a | ((uint64_t)b << 32)) : "memory"); }
__device__ __forceinline__ uint2 ld_ll2(const void* p) {
  uint64_t a;
  asm volatile("ld.relaxed.gpu.global.u64 %0, [%1];" : "=l"(a) : "l"(p) : "memory");
  return make_uint2((uint32_t)a, (uint32_t)(a >> 32));
}
__device__ __forceinline__ void wgmma_colsum(float* d, uint64_t da, uint64_t db) {
  asm volatile("{\n.reg .pred p;\nsetp.ne.b32 p, 1, 0;\nwgmma.mma_async.sync.aligned.m64n8k16.f32.bf16.bf16 {%0, %1, %2, %3}, %4, %5, p, 1, 1, 1, 0;\n}\n"
               : "+f"(d[0]), "+f"(d[1]), "+f"(d[2]), "+f"(d[3]) : "l"(da), "l"(db));
}
__device__ __forceinline__ void prefetch_l2(const void* p) { asm volatile("prefetch.global.L2 [%0];" ::"l"(p)); }
__device__ __forceinline__ void pace(uint32_t& t, uint32_t dt) {
  t += dt;
  while ((int32_t)((uint32_t)clock() - t) < 0) { if (NSLEEP) __nanosleep(NSLEEP); }
}
__device__ __forceinline__ void red_relaxed(uint32_t* p) { asm volatile("red.relaxed.gpu.global.add.u32 [%0], 1;" ::"l"(p) : "memory"); }
__device__ __forceinline__ void red_release(uint32_t* p) { asm volatile("red.release.gpu.global.add.u32 [%0], 1;" ::"l"(p) : "memory"); }
__device__ __forceinline__ uint4 ldg4(const void* p) { uint4 v; asm volatile("ld.global.v4.u32 {%0,%1,%2,%3}, [%4];" : "=r"(v.x), "=r"(v.y), "=r"(v.z), "=r"(v.w) : "l"(p) : "memory"); return v; }
__device__ __forceinline__ uint32_t ldg1(const void* p) { uint32_t v; asm volatile("ld.global.u32 %0, [%1];" : "=r"(v) : "l"(p) : "memory"); return v; }
__device__ __forceinline__ void stg4_if(void* p, uint32_t a, uint32_t b, uint32_t c, uint32_t d, bool on) {
  asm volatile("{\n.reg .pred p;\nsetp.ne.u32 p, %5, 0;\n@p st.global.v4.u32 [%0], {%1,%2,%3,%4};\n}\n" ::"l"(p), "r"(a), "r"(b), "r"(c), "r"(d), "r"((uint32_t)on) : "memory");
}
template <int OFF> __device__ __forceinline__ uint32_t lds32(uint32_t a) { uint32_t v; asm volatile("ld.shared.u32 %0, [%1+%2];" : "=r"(v) : "r"(a), "n"(OFF)); return v; }
__device__ __forceinline__ uint4 lds128(uint32_t a) { uint4 v; asm volatile("ld.shared.v4.u32 {%0,%1,%2,%3}, [%4];" : "=r"(v.x), "=r"(v.y), "=r"(v.z), "=r"(v.w) : "r"(a) : "memory"); return v; }
__device__ __forceinline__ float2 lds64f(uint32_t a) { float2 v; asm volatile("ld.shared.v2.f32 {%0,%1}, [%2];" : "=f"(v.x), "=f"(v.y) : "r"(a) : "memory"); return v; }
__device__ __forceinline__ void sts64f(uint32_t a, float x, float y) { asm volatile("st.shared.v2.f32 [%0], {%1,%2};" ::"r"(a), "f"(x), "f"(y) : "memory"); }
__device__ __forceinline__ void sts32(uint32_t a, uint32_t x) { asm volatile("st.shared.u32 [%0], %1;" ::"r"(a), "r"(x) : "memory"); }
__device__ __forceinline__ void sts128(uint32_t a, uint32_t x, uint32_t y, uint32_t z, uint32_t w) { asm volatile("st.shared.v4.u32 [%0], {%1,%2,%3,%4};" ::"r"(a), "r"(x), "r"(y), "r"(z), "r"(w) : "memory"); }
__device__ __forceinline__ void stsm4(uint32_t a, uint32_t r0, uint32_t r1, uint32_t r2, uint32_t r3) {
  asm volatile("stmatrix.sync.aligned.m8n8.x4.shared.b16 [%0], {%1,%2,%3,%4};" ::"r"(a), "r"(r0), "r"(r1), "r"(r2), "r"(r3) : "memory");
}
__device__ __forceinline__ void stsm4t(uint32_t a, uint32_t r0, uint32_t r1, uint32_t r2, uint32_t r3) {
  asm volatile("stmatrix.sync.aligned.m8n8.x4.trans.shared.b16 [%0], {%1,%2,%3,%4};" ::"r"(a), "r"(r0), "r"(r1), "r"(r2), "r"(r3) : "memory");
}
__device__ __forceinline__ void ldsm4t(uint32_t* r, uint32_t a) {
  asm volatile("ldmatrix.sync.aligned.m8n8.x4.trans.shared.b16 {%0,%1,%2,%3}, [%4];" : "=r"(r[0]), "=r"(r[1]), "=r"(r[2]), "=r"(r[3]) : "r"(a) : "memory");
}
__device__ __forceinline__ uint32_t pack2(float lo, float hi) { uint32_t r; asm("cvt.rn.bf16x2.f32 %0, %1, %2;" : "=r"(r) : "f"(hi), "f"(lo)); return r; }
__device__ __forceinline__ float bf_lo(uint32_t u) { return __uint_as_float(u << 16); }
__device__ __forceinline__ float bf_hi(uint32_t u) { return __uint_as_float(u & 0xffff0000u); }
__device__ __forceinline__ float tanh_fast(float x) { float y; asm("tanh.approx.f32 %0, %1;" : "=f"(y) : "f"(x)); return y; }
__device__ __forceinline__ uint32_t hmul2(uint32_t a, uint32_t b) { uint32_t r; asm("mul.rn.bf16x2 %0, %1, %2;" : "=r"(r) : "r"(a), "r"(b)); return r; }
__device__ __forceinline__ uint32_t hfma2(uint32_t a, uint32_t b, uint32_t c) { uint32_t r; asm("fma.rn.bf16x2 %0, %1, %2, %3;" : "=r"(r) : "r"(a), "r"(b), "r"(c)); return r; }
__device__ __forceinline__ uint32_t prmt(uint32_t a, uint32_t b, uint32_t s) { return __byte_perm(a, b, s); }

__device__ __forceinline__ uint32_t ld_relaxed(const uint32_t* p) { uint32_t v; asm volatile("ld.relaxed.gpu.global.u32 %0, [%1];" : "=r"(v) : "l"(p) : "memory"); return v; }
__device__ __forceinline__ void acquire_fence() { asm volatile("fence.acquire.gpu;\nfence.proxy.async.global;" ::: "memory"); }
__device__ __forceinline__ uint32_t load_epoch(const Params& p, int idx, int lane) { return ld_relaxed(&p.scr->epoch[idx + (((lane * lane) & 3) == 2 ? 1 : 0)]); }
__device__ __forceinline__ void poll_counter(const uint32_t* cnt, uint32_t target) {
  uint32_t t0 = 0;
#pragma unroll 1
  while (!__all_sync(0xffffffff, ld_relaxed(cnt) == target)) spin_guard(t0);
  acquire_fence();
}

__device__ __forceinline__ int g3_block(int cb, int it) { return it < 3 ? cb * 3 + it : (it - 3 < cb * 3 ? it - 3 : it); }

template <int N, bool A_SWZ, int B_MODE, int DEPTH, class Hook, class Mid>
__device__ __forceinline__ void gemm_loop(float* d, uint32_t sb, int nkb, int sa, int pa, int b0, uint32_t boff, int relA, int relB, int tid, Hook hook, Mid mid) {
  constexpr uint32_t A_STEP = A_SWZ ? 2 : 128;
  constexpr uint32_t B_STEP = B_MODE == 0 ? 128 : (B_MODE == 1 ? 384 : 320);
  const uint64_t da0 = A_SWZ ? mkdesc(sb + OFF_A, 16, 1024, 1) : mkdesc(sb + OFF_A, 1024, 128, 0);
  const uint64_t db0 = B_MODE == 0 ? mkdesc(sb + OFF_B + boff, 8192, 1024, 1) : mkdesc(sb + OFF_B + boff, B_MODE == 1 ? 3072 : 2560, 128, 0);
  constexpr int MODA = B_MODE == 0 ? NA : NA2;
  constexpr int MODB = B_MODE == 2 ? 6 : NB;
  int sbk = b0 % MODB, pb = (b0 / MODB) & 1;
  auto boffs = [](int s_) { return B_MODE == 2 ? (s_ == 5 ? 0 : s_ + 1) * (20480 >> 4) : s_ * (B_SLOT >> 4); };
  uint32_t rel = 0;
  uint64_t da = da0 + sa * (A_SLOT >> 4), db = db0 + boffs(sbk);
  const bool doR = tid < 2 ? tid < relA : tid - 2 < relB;
  mbar_wait2(sb + BAR_AF + 8 * sa, pa, sb + BAR_BF + 8 * sbk, pb);
  if constexpr (DEPTH == 0) {
    acc_fence<N / 2>(d);
#pragma unroll 1
    for (int it = 0; it < nkb; it++) {
      WG_FENCE();
#pragma unroll
      for (int j = 0; j < 4; j++) WG<N>::ss(d, da + j * A_STEP, db + j * B_STEP, 1);
      WG_COMMIT();
      const uint32_t prel = rel;
      rel = sb + BAR_AE + 8 * (tid < 2 ? sa : sbk + NA);
      if (++sa == MODA) { sa = 0; pa ^= 1; }
      if (++sbk == MODB) { sbk = 0; pb ^= 1; }
      da = da0 + sa * (A_SLOT >> 4); db = db0 + boffs(sbk);
      const bool r0 = mbar_test(sb + BAR_AF + 8 * sa, pa), r1 = mbar_test(sb + BAR_BF + 8 * sbk, pb);
      WG_WAIT(1);
      mbar_arrive_if(prel, doR && prel != 0);
      if (it == 2) {
        WG_WAIT(0);
        mbar_expect_if(sb + BAR_AF + 8 * (tid == 8 ? 8 : tid), A_SLOT, tid < 9);
        mbar_arrive_if(rel, doR);
        rel = 0;
      }
      mid(it);
      if (it + 1 < nkb && !(r0 && r1)) {
        mbar_wait2(sb + BAR_AF + 8 * sa, pa, sb + BAR_BF + 8 * sbk, pb);
      }
    }
  } else
#pragma unroll 1
  for (int it = 0; it < nkb; it++) {
    WG_FENCE();
    WG<N>::ss(d, da, db, 1);
    const uint32_t prel = rel;
    rel = sb + BAR_AE + 8 * (tid < 2 ? sa : sbk + NA);
    if (++sa == MODA) { sa = 0; pa ^= 1; }
    if (++sbk == MODB) { sbk = 0; pb ^= 1; }
    if (DEPTH == 1) { WG_COMMIT(); WG_WAIT(1); }
    WG<N>::ss(d, da + A_STEP, db + B_STEP, 1);
    WG_COMMIT();
    WG_WAIT(1);
    if (EARLY == 1) mbar_arrive_if(prel, doR && it != 0);
    WG<N>::ss(d, da + 2 * A_STEP, db + 2 * B_STEP, 1);
    if (DEPTH == 1) WG_COMMIT();
    if (EARLY != 1) mbar_arrive_if(prel, doR && it != 0);
    const bool r0 = mbar_test(sb + BAR_AF + 8 * sa, pa), r1 = mbar_test(sb + BAR_BF + 8 * sbk, pb);
    const uint64_t da3 = da + 3 * A_STEP, db3 = db + 3 * B_STEP;
    da = da0 + sa * (A_SLOT >> 4); db = db0 + boffs(sbk);
    if (DEPTH == 1) WG_WAIT(1);
    WG<N>::ss(d, da3, db3, 1);
    WG_COMMIT();
    mid(it);
    if (it + 1 < nkb) {
      if (!(r0 && r1)) {
        mbar_wait2(sb + BAR_AF + 8 * sa, pa, sb + BAR_BF + 8 * sbk, pb);
      }
    }
    if (DEPTH == 2) WG_WAIT(1);
  }
  hook();
  WG_WAIT(0);
  acc_fence<N / 2>(d);
  mbar_arrive_if(rel, doR);
}

__device__ __forceinline__ void fold_mean(float* d, uint32_t cs, float ma, float mb, int t) {
  const uint32_t ha = pack2(-ma, -ma), hb = pack2(-mb, -mb);
  const float la = -ma - bf_lo(ha), lb = -mb - bf_lo(hb);
  const uint32_t a[4] = {t ? 0u : ha, t ? 0u : hb, t ? 0u : pack2(la, la), t ? 0u : pack2(lb, lb)};
  WG_FENCE();
  WG<192>::rst(d, a, mkdesc(cs, 0, 32, 0));
  WG_COMMIT();
}
__device__ __forceinline__ void gelu_tile(const float* d, uint32_t* z, float* st, float ra, float rb) {
  const float kA = 0.7978845608028654f, kB = 0.7978845608028654f * 0.044715f;
  const float c1a = kA * ra, c3a = kB * ra * ra * ra, c1b = kA * rb, c3b = kB * rb * rb * rb;
  float acc[8];
#pragma unroll
  for (int i = 0; i < 8; i++) acc[i] = 0.f;
#pragma unroll
  for (int j = 0; j < 24; j++) {
    float r[4];
#pragma unroll
    for (int e = 0; e < 4; e++) {
      const float v = d[4 * j + e];
      const float a = v * fmaf(v * v, e < 2 ? c3a : c3b, e < 2 ? c1a : c1b);
      r[e] = fmaf(v, tanh_fast(a), v);
      acc[e] += r[e];
      acc[4 + e] = fmaf(r[e], r[e], acc[4 + e]);
    }
    z[2 * j] = pack2(r[0], r[1]);
    z[2 * j + 1] = pack2(r[2], r[3]);
  }
  st[0] = acc[0] + acc[1]; st[1] = acc[4] + acc[5]; st[2] = acc[2] + acc[3]; st[3] = acc[6] + acc[7];
}

template <int Q> __device__ __forceinline__ void conv_load(uint32_t* a, uint32_t ab) {
  a[0] = lds32<512 * Q>(ab);       a[1] = lds32<512 * Q + 256>(ab);  a[2] = lds32<512 * Q + 16>(ab);   a[3] = lds32<512 * Q + 272>(ab);
  a[4] = lds32<512 * Q + 32>(ab);  a[5] = lds32<512 * Q + 288>(ab);  a[6] = lds32<512 * Q + 48>(ab);   a[7] = lds32<512 * Q + 304>(ab);
  a[8] = lds32<512 * Q + 64>(ab);  a[9] = lds32<512 * Q + 320>(ab);  a[10] = lds32<512 * Q + 80>(ab);  a[11] = lds32<512 * Q + 336>(ab);
  a[12] = lds32<512 * Q + 96>(ab); a[13] = lds32<512 * Q + 352>(ab); a[14] = lds32<512 * Q + 112>(ab); a[15] = lds32<512 * Q + 368>(ab);
}
template <int Q, int L> __device__ __forceinline__ void conv_step(float* d, uint32_t (*a)[16], uint32_t ab, uint64_t db) {
  WG_FENCE();
#pragma unroll
  for (int s = 0; s < 4; s++) WG<128 - 16 * Q>::rs(d, a[Q] + 4 * s, db + s + 16 * Q);
  WG_COMMIT();
  if (CPIN) WG_WAIT(1);
  if (L >= 0) conv_load<(L >= 0 ? L : 0)>(a[L >= 0 ? L : 0], ab);
  if (CW0 || Q == 0) WG_WAIT(0);
}

__device__ __forceinline__ int seg_col(int cb, int h) { return (cb >> 1) * 320 + (cb & 1) * 32 + h * 64; }
__device__ __forceinline__ void final_load_x(uint32_t (*xw)[10], uint32_t xt, int cb, int h, int w, int lane) {
  const int g = lane >> 2, t = lane & 3, cc = seg_col(cb, h) >> 3;
  const int c0 = cc + t, c1 = c0 + 24, c2 = cc + 16 - 6 * h + (t >> 1);
  const uint32_t r0 = xt + (w * 16 + g) * 128;
#pragma unroll
  for (int r = 0; r < 2; r++) {
    const uint4 u = lds128(r0 + r * 1024 + (c0 >> 3) * A_SLOT + (((c0 ^ g) & 7) << 4)), v = lds128(r0 + r * 1024 + (c1 >> 3) * A_SLOT + (((c1 ^ g) & 7) << 4));
    const float2 z = lds64f(r0 + r * 1024 + (c2 >> 3) * A_SLOT + (((c2 ^ g) & 7) << 4) + (t & 1) * 8);
    xw[r][0] = u.x; xw[r][1] = u.y; xw[r][2] = u.z; xw[r][3] = u.w;
    xw[r][4] = v.x; xw[r][5] = v.y; xw[r][6] = v.z; xw[r][7] = v.w;
    xw[r][8] = __float_as_uint(z.x); xw[r][9] = __float_as_uint(z.y);
  }
}
__device__ __forceinline__ void final_s_early(uint32_t (*sw)[10], const uint32_t (*xw)[10], uint32_t ya, float2 s0, float2 s1) {
  const uint32_t r2[2] = {pack2(s0.y, s0.y), pack2(s1.y, s1.y)};
  const float na = -s0.x * bf_lo(r2[0]), nb = -s1.x * bf_lo(r2[1]);
  const uint32_t n2[2] = {pack2(na, na), pack2(nb, nb)};
#pragma unroll
  for (int j = 0; j < 10; j += 2) {
    uint32_t y[4];
    if (j < 4 || j == 8) ldsm4t(y, ya + (j < 4 ? j : 4) * 1024);
#pragma unroll
    for (int e = 0; e < 4; e++) {
      const uint32_t xn = hfma2(xw[e & 1][j + (e >> 1)], r2[e & 1], n2[e & 1]);
      sw[e & 1][j + (e >> 1)] = (j < 4 || j == 8) ? hmul2(xn, y[e]) : xn;
    }
  }
}
__device__ __forceinline__ bool final_late(uint32_t* y, uint32_t ya) {
  ldsm4t(y, ya + 6144);
  ldsm4t(y + 4, ya + 8192);
  uint32_t zero = 0;
#pragma unroll
  for (int e = 0; e < 8; e++) zero |= (y[e] - 0x00010001u) & ~y[e];
  return (zero & 0x80008000u) == 0;
}
__device__ __forceinline__ bool bar_all(int id, int n, bool c) {
  uint32_t r;
  asm volatile("{\n.reg .pred p, q;\nsetp.ne.u32 p, %3, 0;\nbar.red.and.pred q, %1, %2, p;\nselp.u32 %0, 1, 0, q;\n}\n" : "=r"(r) : "r"(id), "r"(n), "r"((uint32_t)c) : "memory");
  return r;
}
__device__ __forceinline__ void final_out(const float* d, const uint32_t (*xw)[10], const uint32_t (*sw)[10], float ra, float rb, __nv_bfloat16* o0, int h, int t) {
  const float ca = 0.25f * ra, cb = 0.25f * rb;
  uint32_t o[2][10];
#pragma unroll
  for (int j = 0; j < 10; j++) {
#pragma unroll
    for (int r = 0; r < 2; r++) {
      const float h0 = d[4 * j + 2 * r] * (r ? cb : ca), h1 = d[4 * j + 2 * r + 1] * (r ? cb : ca);
      o[r][j] = hfma2(pack2(fmaf(h0, tanh_fast(h0), h0), fmaf(h1, tanh_fast(h1), h1)), sw[r][j], xw[r][j]);
      __nv_bfloat16* q = o0 + r * 8 * kD;
      if (j == 3) stg4_if(q + t * 8, o[r][0], o[r][1], o[r][2], o[r][3], true);
      if (j == 7) stg4_if(q + 192 + t * 8, o[r][4], o[r][5], o[r][6], o[r][7], true);
      if (j == 9) asm volatile("st.global.v2.u32 [%0], {%1,%2};" ::"l"(q + 128 - 48 * h + t * 4), "r"(o[r][8]), "r"(o[r][9]) : "memory");
    }
  }
}

struct Taps { uint4 r0, r1; uint32_t n0, n1, dd; };
__device__ __forceinline__ void load_taps(Taps& k, const Params& p, int ch, int tid) {
  const uint4* kp = (const uint4*)(p.ssmk + (size_t)ch * kS);
  k.r0 = ldg4(kp + tid); k.r1 = ldg4(kp + 128 + tid);
  k.n0 = ldg1(kp + tid + 1); k.n1 = tid < 127 ? ldg1(kp + 129 + tid) : 0u;
  k.dd = __bfloat16_as_ushort(p.ssmD[ch]);
}
__device__ __forceinline__ void load_convx(const Params& p, uint32_t cv, uint32_t bar, int ch) {
  mbar_expect(bar, 4096);
  bulk_g2s(cv, p.scr->kvx + (size_t)ch * 4096, 2048, bar);
  bulk_g2s(cv + XB_PL, p.scr->kvx + (size_t)ch * 4096 + 2048, 2048, bar);
}
#define CW 3
#define CSTAMP(j)
__device__ __forceinline__ void zero_pads(uint32_t cv, int lane) {
  if (lane < 8) sts128(cv + (lane >> 2) * XB_PL + 2048 + (lane & 3) * 16, 0, 0, 0, 0);
  else if (lane < 12) sts128(cv + ((lane & 2) ? CV_KO : CV_KE) + (lane & 1) * 16, 0, 0, 0, 0);
  fence_async_smem();
  __syncwarp();
}
__device__ __forceinline__ int y_row(int c, uint32_t par) {
  const int hf = c >= 320, cc = c - hf * 320, u = cc >> 6, cb = hf * 2 + ((cc >> 5) & 1);
  if (u == 2) return cb * 96 + ((cc >> 4) & 1) * 48 + 32 + (cc & 1) + ((cc >> 1) & 1) * 8 + ((cc >> 2) & 3) * 2;
  return (u < 2 ? cb * 96 + u * 48 : 384 + par * 256 + cb * 64 + (u - 3) * 32) + (cc & 1) + ((cc >> 1) & 3) * 8 + ((cc >> 3) & 3) * 2;
}
__device__ __forceinline__ void y_store(const Params& p, uint32_t sb, int h, int ch, uint32_t par) {
  uint8_t* dst = p.scr->y + (size_t)y_row(ch, par) * 4096;
  if (elect_one()) {
    bulk_s2g(dst, sb + OFF_A + 9 * A_SLOT + h * 4096, 4096);
    asm volatile("cp.async.bulk.commit_group;\ncp.async.bulk.wait_group 0;" ::: "memory");
  }
  __syncwarp();
}
__device__ __forceinline__ void conv_service(const Params& p, uint32_t sb, int h, int ch, bool first) {
  bar_sync(NB_WGA + 8 + h, 160);
  const bool now = !first || __all_sync(0xffffffff, mbar_test(sb + BAR_KV, 0));
  if (now) { acquire_fence(); if (elect_one()) load_convx(p, sb + OFF_CV + (1 - h) * CV_SZ, sb + BAR_XF + 8 * h, ch + 128); }
  bar_sync(NB_WGA + 8 + h, 160);
  y_store(p, sb, h, ch, 0);
  if (!now) {
    mbar_wait(sb + BAR_KV, 0);
    acquire_fence();
    if (elect_one()) load_convx(p, sb + OFF_CV + (1 - h) * CV_SZ, sb + BAR_XF + 8 * h, ch + 128);
  }
}
__device__ __forceinline__ uint32_t y_tile(int h) { return OFF_CV + (1 - h) * 13312; }
__device__ __forceinline__ void load_late_y(const Params& p, uint32_t sb, int h, int rb, int cb, uint32_t par) {
  mbar_expect(sb + BAR_YL + 16 * h, 4096);
  tma2d(sb + y_tile(h) + 6144, &p.tmY, rb * 64, 384 + par * 256 + cb * 64 + h * 32, sb + BAR_YL + 16 * h);
  tma2d(sb + y_tile(h) + 8192, &p.tmY, rb * 64, 400 + par * 256 + cb * 64 + h * 32, sb + BAR_YL + 16 * h);
}
__device__ __forceinline__ void held_service(const Params& p, uint32_t sb, int h, int ch, int rb, int cb, uint32_t tag, int lane) {
#pragma unroll 1
  for (int i = 0; i < 8; i++) sts128(sb + OFF_A + 9 * A_SLOT + h * 4096 + i * 512 + lane * 16, 0, 0, 0, 0);
  fence_async_smem();
  __syncwarp();
  y_store(p, sb, h, ch, ~tag & 1);
  mbar_wait(sb + BAR_YT, 1);
  acquire_fence();
  bar_sync(NB_WGA + 8 + h, 160);
  bar_sync(NB_WGA + 8 + h, 160);
  uint8_t* dst = p.scr->y + (size_t)y_row(ch, tag & 1) * 4096;
  if (elect_one()) {
    bulk_s2g(dst, sb + OFF_A + 9 * A_SLOT + h * 4096, 4096);
    asm volatile("cp.async.bulk.commit_group;" ::: "memory");
    mbar_expect(sb + BAR_XF + 8 * h, 6144);
#pragma unroll 1
    for (int i = 0; i < 3; i++) tma2d(sb + y_tile(h) + i * 2048, &p.tmY, rb * 64, cb * 96 + h * 48 + i * 16, sb + BAR_XF + 8 * h);
  }
  mbar_wait(sb + BAR_AE + 8 * (LL_AT - 1), 1);
  if (elect_one()) { load_late_y(p, sb, h, rb, cb, tag & 1); asm volatile("cp.async.bulk.wait_group 0;" ::: "memory"); }
}
__device__ __forceinline__ void conv_worker(const Params& p, Taps& k, uint32_t cv, uint32_t yb0,
                                            uint32_t xbar, int nbar, int ch0, int n, uint32_t holdbar, int w, int lane,
                                            int tid, int st0, int rb, int cb) {
  const int g = lane >> 2, t = lane & 3, w0 = w & 1, w1 = w >> 1;
  const uint32_t ab = cv + ((g & 1) ? CV_KE : CV_KO) + 32 + 2 * (64 * w0 + 8 * w1 + ((g - 15) & ~1) + 2 * t);
  const uint32_t scA = cv + (w1 ? CV_KO : CV_KE) + 32, scB = scA + 2048;
  const int dl = (t >> 1) ^ 1;
  if (n == 2) mbar_wait(xbar, 0);
  STAMPW(st0 + 3);
#pragma unroll 1
  for (int i = 0; i < n; i++) {
    if (tid == 0) {
      k.r0.x = (k.r0.x & 0xffff0000u) | (pack2(bf_lo(k.r0.x) + bf_lo(k.dd), 0.f) & 0xffffu);
      sts32(cv + CV_KO + 28, k.r0.x << 16);
    }
    sts128(cv + CV_KE + 32 + tid * 16, k.r0.x, k.r0.y, k.r0.z, k.r0.w);
    sts128(cv + CV_KO + 32 + tid * 16, prmt(k.r0.x, k.r0.y, 0x5432), prmt(k.r0.y, k.r0.z, 0x5432), prmt(k.r0.z, k.r0.w, 0x5432), prmt(k.r0.w, k.n0, 0x5432));
    sts128(cv + CV_KE + 2080 + tid * 16, k.r1.x, k.r1.y, k.r1.z, k.r1.w);
    sts128(cv + CV_KO + 2080 + tid * 16, prmt(k.r1.x, k.r1.y, 0x5432), prmt(k.r1.y, k.r1.z, 0x5432), prmt(k.r1.z, k.r1.w, 0x5432), prmt(k.r1.w, k.n1, 0x5432));
    if (i + 1 < n) load_taps(k, p, ch0 + (i + 1) * 128, tid);
    bar_sync(nbar, 128);
    CSTAMP(0);
    const uint64_t db = mkdesc(cv + (i & 0x1000), XB_PL, 128, 0);
    float d[64];
    uint32_t a[8][16];
    conv_load<7>(a[7], ab); conv_load<6>(a[6], ab); conv_load<5>(a[5], ab); conv_load<4>(a[4], ab);
#pragma unroll
    for (int j = 0; j < 64; j++) d[j] = 0.f;
    mbar_wait(xbar, i & 1);
    if (i + 1 == n) mbar_wait(holdbar, 1);
    CSTAMP(1);
    conv_step<7, -1>(d, a, ab, db); conv_step<6, -1>(d, a, ab, db); conv_step<5, -1>(d, a, ab, db); conv_step<4, 3>(d, a, ab, db);
    conv_step<3, 2>(d, a, ab, db);
    conv_step<2, 1>(d, a, ab, db);
    conv_step<1, 0>(d, a, ab, db);
    conv_step<0, -1>(d, a, ab, db);
    acc_fence<64>(d);
    CSTAMP(2);
    bar_sync(nbar + 8, 160);
    float E[16][2];
#pragma unroll
    for (int j = 0; j < 15; j++) { E[j][0] = d[4 * j] + d[4 * j + 6]; E[j][1] = d[4 * j + 1] + d[4 * j + 7]; }
    E[15][0] = d[60]; E[15][1] = d[61];
    if (w0 == 0) {
#pragma unroll
      for (int j = 8; j < 16; j++) sts64f(scA + (j - 8) * 256 + lane * 8, E[j][0], E[j][1]);
    } else {
      const uint32_t a = scB - dl * 256 + (lane ^ 2) * 8;
#pragma unroll
      for (int j = 1; j < 8; j++) sts64f(a + j * 256, E[j][0], E[j][1]);
      sts64f(scB + (dl ? 7 * 256 : 0) + (lane ^ 2) * 8, dl ? E[8][0] : E[0][0], dl ? E[8][1] : E[0][1]);
    }
    bar_sync(nbar, 128);
    CSTAMP(3);
    uint32_t pk[8];
    if (w0 == 0) {
#pragma unroll
      for (int j = 0; j < 8; j++) { const float2 v = lds64f(scB + j * 256 + lane * 8); pk[j] = pack2(E[j][0] + v.x, E[j][1] + v.y); }
    } else {
      const uint32_t a0 = scA - dl * 256 + (lane ^ 2) * 8;
#pragma unroll
      for (int j = 9; j < 16; j++) { const float2 v = lds64f(a0 + (j - 8) * 256); pk[j - 8] = pack2(E[j][0] + v.x, E[j][1] + v.y); }
      const float2 v = lds64f(scA + (dl ? 7 * 256 : 0) + (lane ^ 2) * 8);
      pk[0] = pack2((dl ? 0.f : E[8][0]) + v.x, (dl ? 0.f : E[8][1]) + v.y);
    }
    CSTAMP(4);
    if (i + 1 == n) {
#pragma unroll
      for (int j = 0; j < 8; j++) pk[j] = ~pk[j];
    }
    const int c1 = (w0 ? 35 : 95) - lane, c0 = (w0 && lane < 4) ? c1 - 32 : c1 + 32;
    stsm4t(yb0 + 128 * (c0 & 31) + (((2 * (c0 >> 5) + w1) ^ (c0 & 7)) << 4), pk[0], pk[1], pk[2], pk[3]);
    stsm4t(yb0 + 128 * (c1 & 31) + (((2 * (c1 >> 5) + w1) ^ (c1 & 7)) << 4), pk[4], pk[5], pk[6], pk[7]);
    fence_async_smem();
    bar_sync(nbar + 8, 160);
    CSTAMP(5);
    STAMPW(st0 + i);
    if (n == 2 && i == 0) {
      const int u = (tid >> 3) % 5, kg = rb * 3 + (tid < 120 ? (tid >> 3) / 5 : 0), c = u < 4 ? (u >> 1) * 10 + (u & 1) * 4 : 8, o2 = u < 4 ? 2 : 10;
      const uint4* wp = (const uint4*)p.wout + (uint32_t)((kg * 8 + (tid & 7)) * (kD / 8) + (seg_col(cb, 0) >> 3) + (u < 4 ? (u >> 1) * 8 + (u & 1) * 24 : 16));
      const uint4 w0 = ldg4(wp), w1 = ldg4(wp + 1), w2 = ldg4(wp + 2), w3 = ldg4(wp + 3);
      uint8_t* dst = p.scr->wo + (uint32_t)(cb * (12 * 20480) + kg * 2560 + c * 128 + (tid & 7) * 16);
      const bool f = u < 4, on = tid < 120;
      stg4_if(dst, w0.x, f ? w1.x : w0.z, f ? w2.x : w1.x, f ? w3.x : w1.z, on);
      stg4_if(dst + 128, w0.y, f ? w1.y : w0.w, f ? w2.y : w1.y, f ? w3.y : w1.w, on);
      stg4_if(dst + o2 * 128, f ? w0.z : w2.x, f ? w1.z : w2.z, f ? w2.z : w3.x, w3.z, on);
      stg4_if(dst + o2 * 128 + 128, f ? w0.w : w2.y, f ? w1.w : w2.w, f ? w2.w : w3.y, w3.w, on);
      bar_arrive(NB_WO, 160);
    }
  }
}

struct KvRegs { uint32_t k[11], v[8]; uint4 sh; };
__device__ __forceinline__ void kv_load(KvRegs& q, const __nv_bfloat16* kp, const __nv_bfloat16* vp, const __nv_bfloat16* sp, bool halo) {
#pragma unroll
  for (int i = 0; i < 11; i++) q.k[i] = (i >= 3 || halo) ? ldg1(kp + i * kD) : 0u;
#pragma unroll
  for (int i = 0; i < 8; i++) q.v[i] = ldg1(vp + i * kD);
  q.sh = ldg4(sp);
}
__device__ __forceinline__ void kv_unit(const KvRegs& q, uint32_t oa) {
  const uint32_t w0 = prmt(q.sh.x, q.sh.z, 0x5410), w1 = prmt(q.sh.x, q.sh.z, 0x7632), w2 = prmt(q.sh.y, q.sh.w, 0x5410), w3 = prmt(q.sh.y, q.sh.w, 0x7632);
  uint32_t r[8];
#pragma unroll
  for (int i = 0; i < 8; i++) r[i] = hmul2(hfma2(q.k[i + 3], w0, hfma2(q.k[i + 2], w1, hfma2(q.k[i + 1], w2, hmul2(q.k[i], w3)))), q.v[i]);
  sts128(oa, prmt(r[7], r[6], 0x5410), prmt(r[5], r[4], 0x5410), prmt(r[3], r[2], 0x5410), prmt(r[1], r[0], 0x5410));
  sts128(oa + 2048, prmt(r[7], r[6], 0x7632), prmt(r[5], r[4], 0x7632), prmt(r[3], r[2], 0x7632), prmt(r[1], r[0], 0x7632));
}

__device__ __forceinline__ void helper_cta(const Params& p, uint32_t sb, int cb, int warp, int lane) {
  constexpr int NS = 9, ONES = NS * B_SLOT, BF = ONES + 256, BE = BF + 8 * NS;
  if (warp < NS && elect_one()) {
    mbar_init(sb + BF + 8 * warp, 1); mbar_init(sb + BE + 8 * warp, 1);
    fence_async_smem();
    if (warp == 0) { mbar_expect(sb + BF, B_SLOT); tma3d(sb, &p.tmW, 0, 0, 12 + cb * 3, sb + BF); }
  }
  if (warp == 15) { sts32(sb + ONES + lane * 4, 0x3f803f80u); sts32(sb + ONES + 128 + lane * 4, 0x3f803f80u); fence_async_smem(); }
  __syncthreads();
  if (warp == 4) {
    int s = 1, ph = 1;
    uint32_t tp = clock() + HP0;
#pragma unroll 1
    for (int it = 1; it < 20; it++) {
      if (HPD && it >= 10) pace(tp, HPD);
      mbar_wait(sb + BE + 8 * s, ph);
      if (elect_one()) { mbar_expect(sb + BF + 8 * s, B_SLOT); tma3d(sb + s * B_SLOT, &p.tmW, 0, (it < 10 ? it : it - 10) * 64, (it < 10 ? 12 : 0) + cb * 3, sb + BF + 8 * s); }
      if (++s == NS) { s = 0; ph ^= 1; }
    }
  } else if (warp < 4) {
    const uint32_t tag = load_epoch(p, 128 + cb, lane) + 1;
    const uint64_t db = mkdesc(sb + ONES, 128, 128, 0);
    uint2* dst = p.scr->colsum + cb * 192 + warp * 16 + (lane >> 2);
    if ((lane & 3) == 0) {
#pragma unroll 1
      for (int j = 0; j < 12; j++) st_ll2(dst + (j < 6 ? 768 : 0) + ((j % 6) >> 1) * 64 + (j & 1) * 8, 0, 0);
    }
    int s = 0, ph = 0;
#pragma unroll 1
    for (int part = 0; part < 2; part++) {
      float d[12];
#pragma unroll
      for (int i = 0; i < 12; i++) d[i] = 0.f;
#pragma unroll 1
      for (int it = 0; it < 10; it++) {
        mbar_wait(sb + BF + 8 * s, ph);
        const uint64_t da = mkdesc(sb + s * B_SLOT, 8192, 1024, 1);
        WG_FENCE();
#pragma unroll
        for (int j = 0; j < 12; j++) wgmma_colsum(d + 4 * (j % 3), da + (j % 3) * 512 + (j / 3) * 128, db);
        WG_COMMIT();
        WG_WAIT(1);
        mbar_arrive_if(sb + BE + 8 * (s == 0 ? NS - 1 : s - 1), threadIdx.x == 0 && (it | part) != 0);
        if (++s == NS) { s = 0; ph ^= 1; }
      }
      WG_WAIT(0);
      acc_fence<12>(d);
      if ((lane & 3) == 0) {
#pragma unroll
        for (int j = 0; j < 6; j++) st_ll2(dst + (part ? 0 : 768) + (j >> 1) * 64 + (j & 1) * 8, __float_as_uint(d[2 * j]), tag);
      }
      STAMPW(1 + part);
    }
    if (threadIdx.x == 0) *(volatile uint32_t*)&p.scr->epoch[128 + cb] = tag;
  }
}

__global__ void __launch_bounds__(512, 1) fused_kernel(const __grid_constant__ Params p) {
  extern __shared__ __align__(1024) uint8_t smem[];
  const int warp = __shfl_sync(0xffffffff, (int)(threadIdx.x >> 5), 0);
  const int lane = threadIdx.x & 31, tid = threadIdx.x & 127;
  const uint32_t sb = __shfl_sync(0xffffffff, (uint32_t)__cvta_generic_to_shared(smem), 0);
  const uint32_t tstart = clock();
  if (elect_one()) {
    if (warp < 5) asm volatile("prefetch.tensormap [%0];" ::"l"(&p.tmX + warp) : "memory");
    mbar_init(sb + OFF_BAR + 8 * warp, 1); mbar_init(sb + OFF_BAR + 128 + 8 * warp, 1); mbar_init(sb + OFF_BAR + 256 + 8 * warp, 2);
    asm volatile("fence.mbarrier_init.release.cluster;" ::: "memory");
  }
  int b = blockIdx.x;
  if (p.by_smid) asm volatile("mov.u32 %0, %%smid;" : "=r"(b));
  b = __shfl_sync(0xffffffff, b, 0);
  const int tp = b >> 1, t7 = (tp - 32) / 7;
  const int lin = tp < 32 ? ((tp & 7) ? (tp & 7) * 16 : 8) + (tp >> 3) * 2 + (b & 1)
                          : (tp < 60 ? (tp - 31 - t7 * 7) * 16 + 8 + t7 * 2 + (b & 1) : (tp < 62 ? -1 : b - 124));
  const int hcb = b & 3;
  if (lin < 0) { helper_cta(p, sb, hcb, warp, lane); return; }
  const int cb = ((lin >> 4) & 1) * 2 + ((lin >> 1) & 1), rb = (lin >> 5) * 8 + ((lin >> 2) & 3) * 2 + (lin & 1);
  const int chb = (cb >> 1) * 320 + rb * 2 + (cb & 1);
  if (warp == 0 && elect_one()) {
    mbar_expect(sb + BAR_AF, A_SLOT);
    tma_rows(sb + OFF_A, &p.tmX, 0, rb, sb + BAR_AF);
    mbar_expect(sb + BAR_BF, B_SLOT);
    tma3d(sb + OFF_B, &p.tmW, 0, 0, 12 + cb * 3, sb + BAR_BF);
  }
  if (warp == 1) STAMP(31);
  if (sb & 1023) die();
  __syncthreads();

  if (warp >= 12) {
    asm volatile("setmaxnreg.dec.sync.aligned.u32 32;");
    const uint32_t epoch = load_epoch(p, lin, lane);
    if (warp == 12) {
#pragma unroll 1
      for (int i = 1; i < NA; i++) {
        if (elect_one()) {
          mbar_expect(sb + BAR_AF + 8 * i, A_SLOT);
          tma_rows(sb + OFF_A + i * A_SLOT, &p.tmX, i * 64, rb, sb + BAR_AF + 8 * i);
          if (i < NB) { mbar_expect(sb + BAR_BF + 8 * i, B_SLOT); tma3d(sb + OFF_B + i * B_SLOT, &p.tmW, 0, i * 64, 12 + cb * 3, sb + BAR_BF + 8 * i); }
        }
      }
      STAMP(32);
      uint32_t kvt;
      {
        const int tb = rb * 2 + (cb & 1);
        kvt = __shfl_sync(0xffffffff, (ld_relaxed(p.scr->cnt + CNT_KV + (cb >> 1)) & ~63u) + 64, 0);
        {
          uint32_t tp = tstart;
          pace(tp, KV_T0);
          mbar_arrive_if(sb + BAR_KV + 8, lane == 0);
        }
        if (ST_YIELD) mbar_wait2(sb + BAR_XS, 0, sb + BAR_ST, 0);
#pragma unroll 1
        for (int u = 0; u < 5; u++) {
          mbar_wait(sb + BAR_KU + 8 * u, 0);
          fence_async_smem();
          if (elect_one()) {
            asm volatile("cp.async.bulk.tensor.3d.global.shared::cta.bulk_group [%0, {%2, %3, %4}], [%1];\ncp.async.bulk.commit_group;" ::"l"(&p.tmKV),
                         "r"(sb + OFF_CV + CV_SZ + (u < 3 ? u : u - 3) * 4096), "r"((63 - tb) * 16), "r"((cb >> 1) * 160 + u * 32), "r"(0) : "memory");
            if (u == 1 || u == 4) asm volatile("cp.async.bulk.wait_group 0;" ::: "memory");
            if (u == 1) { mbar_arrive(sb + BAR_KU); red_release(p.scr->cnt + CNT_KV + (cb >> 1)); }
          }
          __syncwarp();
          if (u == 1) {
            STAMP(35);
            if (PFT) { const char* q = (const char*)p.ssmk + chb * 4096 + lane * 128; prefetch_l2(q); prefetch_l2(q + 64 * 4096); }
          }
        }
        zero_pads(sb + OFF_CV + CV_SZ, lane);
        if (elect_one()) { mbar_arrive(sb + BAR_KU + 8); red_release(p.scr->cnt + CNT_KV + 2 + (cb >> 1)); }
        STAMP(30);
        if (lane < 24) {
          const char* r = (const char*)p.wout + (rb * 24 + lane) * (kD * 2) + (cb >> 1) * 640 + (cb & 1) * 384;
          prefetch_l2(r); prefetch_l2(r + 128); prefetch_l2(r + 256 - (cb & 1) * 384);
        }
      }
      poll_counter(p.scr->cnt + CNT_KV + 2 + (cb >> 1), kvt);
      if (elect_one()) mbar_arrive(sb + BAR_KV);
      STAMP(34);
      {
        const char* q = (const char*)p.wsp + (cb * 512 + rb * 16 + (lane >> 1)) * (kS * 2) + (lane & 1) * 128;
        uint32_t tp = clock();
#pragma unroll 1
        for (int i = LEAD / 2; i < WSP_N; i++) {
          prefetch_l2(q + i * 256);
          if (ZQ_N < 4 && i == Z1_AT) {
            poll_counter(p.scr->cnt + CNT_Z1, (epoch + 1) * 128);
            if (elect_one()) mbar_arrive(sb + BAR_ZP);
            STAMP(24);
          }
          pace(tp, WSP_D);
        }
      }
      const uint32_t tag = epoch + 1;
      mbar_wait(sb + BAR_G2, 0);
      if (elect_one()) {
        bulk_s2g(p.scr->h + (size_t)(rb * 12 + cb * 3) * A_SLOT, sb + OFF_A + 5 * A_SLOT, 3 * A_SLOT);
        asm volatile("cp.async.bulk.commit_group;\ncp.async.bulk.wait_group 0;" ::: "memory");
        red_release(&p.scr->hcnt[(rb >> HGRP) * 32]);
      }
      __syncwarp();
      STAMP(20);
      mbar_wait(sb + BAR_AE + 56, 0);
      STAMP(39);
      poll_counter(&p.scr->hcnt[(rb >> HGRP) * 32], tag * (4 << HGRP));
      STAMP(37);
      if (elect_one()) {
        uint32_t tp = clock();
#pragma unroll 1
        for (int it = 3; it < 12; it++) {
          if (HPACE && it > 3) { tp += HPACE; while ((int32_t)((uint32_t)clock() - tp) < 0) {} }
          bulk_g2s(sb + OFF_A + ((it + 5) % 9) * A_SLOT, p.scr->h + (size_t)(rb * 12 + g3_block(cb, it)) * A_SLOT, A_SLOT, sb + BAR_AF + 8 * ((it + 5) % 9));
        }
      }
      STAMP(21);
    } else if (warp == 13) {
      const uint32_t ztarget = __shfl_sync(0xffffffff, ld_relaxed(p.scr->cnt + CNT_Z), 0);
      int s = 0, ph = 0;
#pragma unroll 1
      for (int it = NB; it < 20; it++) {
        mbar_wait(sb + BAR_BE + 8 * s, ph);
        if (elect_one()) { mbar_expect(sb + BAR_BF + 8 * s, B_SLOT); tma3d(sb + OFF_B + s * B_SLOT, &p.tmW, 0, (it < 10 ? it : it - 10) * 64, (it < 10 ? 12 : 0) + cb * 3, sb + BAR_BF + 8 * s); }
        STAMP2(32 + it);
        if (++s == NB) { s = 0; ph ^= 1; }
      }
      mbar_wait(sb + BAR_XC, 0);
#pragma unroll 1
      for (int i = 0; i < LEAD; i++) {
        mbar_wait(sb + BAR_AE + 8 * i, 0);
        if (elect_one()) { mbar_expect(sb + BAR_AF + 8 * i, A_SLOT); tma_rows(sb + OFF_A + i * A_SLOT, &p.tmWsp, i * 64, rb, sb + BAR_AF + 8 * i); }
      }
      mbar_wait(sb + BAR_ZP, 0);
      poll_counter(p.scr->cnt + CNT_Z, (ztarget & ~127u) + 128);
      STAMP(22);
      int sa = LEAD, pa = 0, ia = LEAD;
#pragma unroll 1
      for (int it = 0; it < 32; it++) {
        if (ZQ_N < 4 && it == 8 * ZQ_N) { mbar_wait(sb + BAR_ZP, 1); acquire_fence(); }
        mbar_wait2(sb + BAR_BE + 8 * s, ph, sb + BAR_AE + 8 * sa, pa);
        if (elect_one()) {
          mbar_expect(sb + BAR_BF + 8 * s, B_SLOT);
          bulk_g2s(sb + OFF_B + s * B_SLOT, p.scr->z2 + (size_t)(cb * 32 + it) * B_SLOT, B_SLOT, sb + BAR_BF + 8 * s);
        }
#pragma unroll 1
        for (int j = (it < RAMP ? 0 : (it == 4 ? 1 + RAMP : 1)); j > 0 && ia < 32; j--, ia++) {
          if (it == 4) mbar_wait(sb + BAR_AE + 8 * sa, pa);
          if (elect_one()) { mbar_expect(sb + BAR_AF + 8 * sa, A_SLOT); tma_rows(sb + OFF_A + sa * A_SLOT, &p.tmWsp, ia * 64, rb, sb + BAR_AF + 8 * sa); }
          if (++sa == NA2) { sa = 0; pa ^= 1; }
        }
        STAMP2(52 + it);
        if (++s == NB) { s = 0; ph ^= 1; }
      }
      mbar_wait(sb + BAR_WO, 0);
      acquire_fence();
#pragma unroll 1
      for (int it = 0; it < 12; it++) {
        if (it < 6) mbar_wait(sb + BAR_BE + 8 * ((0x110443 >> (4 * it)) & 7), it < 3 ? 1 : 0);
        else mbar_wait(sb + BAR_BE + 8 * s, ph);
        if (elect_one()) {
          mbar_expect(sb + BAR_BF + 8 * s, 20480);
          bulk_g2s(sb + OFF_B + (s == 5 ? 0 : s + 1) * 20480, p.scr->wo + (size_t)(cb * 12 + g3_block(cb, it)) * 20480, 20480, sb + BAR_BF + 8 * s);
        }
        STAMP2(84 + it);
        if (++s == 6) { s = 0; ph ^= 1; }
      }
    } else if (warp == 14) {
      const uint32_t tag = epoch + 1;
      uint32_t t0 = 0;
      mbar_wait(sb + BAR_AF + 8 * (NA - 1), 0);
#pragma unroll 1
      for (int part = 0; part < 2; part++) {
        uint4 v[3];
#pragma unroll 1
        while (true) {
          bool ok = true;
#pragma unroll
          for (int i = 0; i < 3; i++) {
            v[i] = ld_ll4(&p.scr->colsum[(part ? 0 : 768) + cb * 192 + i * 64 + lane * 2]);
            ok = ok && v[i].y == tag && v[i].w == tag;
          }
          if (__all_sync(0xffffffff, ok)) break;
          spin_guard(t0);
        }
#pragma unroll
        for (int i = 0; i < 3; i++) {
          const uint32_t hi = pack2(__uint_as_float(v[i].x), __uint_as_float(v[i].z)), ca = sb + OFF_CS + (1 - part) * 768 + i * 256 + (lane >> 2) * 32 + (lane & 3) * 4;
          sts32(ca, hi);
          sts32(ca + 16, pack2(__uint_as_float(v[i].x) - bf_lo(hi), __uint_as_float(v[i].z) - bf_hi(hi)));
        }
        if (!CFENCE) fence_async_smem();
        __syncwarp();
        if (lane == 0) mbar_arrive(sb + BAR_ST + 8 * part);
        if (part == 0) STAMP(27);
      }
      STAMP(38);
      bar_sync(NB_Z, 160);
      if (elect_one()) {
        uint8_t* dst = p.scr->z2 + (size_t)(cb * 32 + (rb >> 2)) * B_SLOT + (rb & 3) * 6144;
#pragma unroll 1
        for (int q = 0; q < ZQ_N; q++) bulk_s2g(dst + q * 8 * B_SLOT, sb + OFF_A + LEAD * A_SLOT + q * 6144, 6144);
        asm volatile("cp.async.bulk.commit_group;\ncp.async.bulk.wait_group 0;" ::: "memory");
        red_release(p.scr->cnt + CNT_Z);
#pragma unroll 1
        for (int q = ZQ_N; q < 4; q++) bulk_s2g(dst + q * 8 * B_SLOT, sb + OFF_A + LEAD * A_SLOT + q * 6144, 6144);
        asm volatile("cp.async.bulk.commit_group;\ncp.async.bulk.wait_group 0;" ::: "memory");
        mbar_arrive(sb + BAR_ZP);
        if (ZQ_N < 4) red_release(p.scr->cnt + CNT_Z1);
      }
      STAMP(28);
      mbar_wait(sb + BAR_AE + 72, 0);
      conv_service(p, sb, 0, chb + 64, true);
      bar_sync(NB_WO, 160);
      bar_sync(NB_CD, 64);
      if (elect_one()) { red_release(p.scr->cnt + CNT_WO + cb); red_relaxed(p.scr->cnt + CNT_Y + (cb >> 1)); }
      STAMP(49);
      poll_counter(p.scr->cnt + CNT_WO + cb, tag * 32);
      if (elect_one()) mbar_arrive(sb + BAR_WO);
      STAMP(46);
      held_service(p, sb, 0, chb + 192, rb, cb, tag, lane);
    } else {
      const uint32_t tag = epoch + 1;
      sts32(sb + OFF_BIAS + lane * 4, ldg1(p.bsp + (lane >> 3) * 512 + rb * 16 + (lane & 7) * 2));
      if (lane < 2) sts32(sb + OFF_TAG + lane * 4, lane ? 0 : tag);
      fence_async_smem();
      uint32_t t0 = 0;
      mbar_wait(sb + BAR_AF + 8 * (NA - 1), 0);
#pragma unroll 1
      while (true) {
        const uint4 u = ld_ll4(&p.scr->xstat[rb * 64 + lane]), v = ld_ll4(&p.scr->xstat[rb * 64 + 32 + lane]);
        sts64f(sb + OFF_XS + lane * 8, __uint_as_float(u.x), __uint_as_float(u.z));
        sts64f(sb + OFF_XS + 256 + lane * 8, __uint_as_float(v.x), __uint_as_float(v.z));
        if (__all_sync(0xffffffff, u.y == tag && u.w == tag && v.y == tag && v.w == tag)) break;
        spin_guard(t0);
      }
      STAMP(26);
      __syncwarp();
      if (lane == 0) mbar_arrive(sb + BAR_XS);
      mbar_wait(sb + (K0_POLL ? BAR_KU + 16 : BAR_KU), K0_POLL ? 0 : 1);
      poll_counter(p.scr->cnt + CNT_KV + (cb >> 1), tag * 64);
      if (elect_one()) load_convx(p, sb + OFF_CV, sb + BAR_XF + 8, chb);
      mbar_wait(sb + BAR_KU + 8, 1);
      if (elect_one()) load_convx(p, sb + OFF_CV + CV_SZ, sb + BAR_XF, chb + 64);
      STAMP(48);
      mbar_wait(sb + BAR_AE + 72, 0);
#pragma unroll 1
      for (int i = 0; i < 2; i++) conv_service(p, sb, 1, chb + i * 128, i == 0);
      bar_arrive(NB_CD, 64);
      mbar_wait(sb + BAR_WO, 0);
      poll_counter(p.scr->cnt + CNT_Y + (cb >> 1), tag * 64);
      STAMP(47);
      if (elect_one()) mbar_arrive(sb + BAR_YT);
      held_service(p, sb, 1, chb + 256, rb, cb, tag, lane);
      if (lane == 0) *(volatile uint32_t*)&p.scr->epoch[lin] = tag;
      STAMP(23);
    }
  } else {
    if (warp == 7) STAMP(36);
    const int wg = warp >> 2, w = warp & 3, g = lane >> 2, t = lane & 3;
    Taps k;
    uint32_t xw[2][10];
    if (wg == 2) {
      asm volatile("setmaxnreg.inc.sync.aligned.u32 160;");
      const int tb = rb * 2 + (cb & 1), c0 = (cb >> 1) * 320;
      const uint32_t cv = sb + OFF_CV + CV_SZ;
      if (w == 0) zero_pads(sb + OFF_CV, lane);
      mbar_wait(sb + BAR_KV + 8, 0);
      const int t0 = tb * 32 + w * 8;
      const __nv_bfloat16* kp = p.k + (size_t)(t0 - 3) * kD + c0 + lane * 2;
      const __nv_bfloat16* vp = p.v + (size_t)t0 * kD + c0 + lane * 2;
      const __nv_bfloat16* sp = p.shift + (c0 + lane * 2) * 4;
      const uint32_t oa = cv + ((3 - w) & 1) * 1024 + lane * 32 + ((((3 - w) >> 1) ^ (lane >> 2)) & 1) * 16;
#pragma unroll 1
      for (int r = 0; r < 2; r++) {
        KvRegs n0, n1, n2;
        kv_load(n0, kp + r * 128, vp + r * 128, sp + r * 512, t0 > 0);
        kv_load(n1, kp + r * 128 + 64, vp + r * 128 + 64, sp + r * 512 + 256, t0 > 0);
        if (r) kv_load(n2, kp + 256, vp + 256, sp + 1024, t0 > 0);
        kv_unit(n0, oa + r * 8192);
        bar_sync(NB_WGC, 128);
        mbar_arrive_if(sb + BAR_KU + 16 * r, tid == 0);
        if (r) mbar_wait(sb + BAR_KU, 1);
        kv_unit(n1, oa + (r ? 0 : 4096));
        bar_sync(NB_WGC, 128);
        mbar_arrive_if(sb + BAR_KU + 16 * r + 8, tid == 0);
        if (r) {
          kv_unit(n2, oa + 4096);
          bar_sync(NB_WGC, 128);
          mbar_arrive_if(sb + BAR_KU + 32, tid == 0);
        } else {
          mbar_wait(sb + BAR_AF + 8 * ((cb >> 1) * 5 + 1), 0);
          mbar_wait2(sb + BAR_AF + 8 * ((cb >> 1) * 5 + 2), 0, sb + BAR_AF + 8 * ((cb >> 1) * 5 + 4), 0);
          final_load_x(xw, sb + OFF_A, cb, 1, w, lane);
          fence_async_smem();
          bar_sync(NB_WGC, 128);
          mbar_arrive_if(sb + BAR_XC, tid == 0);
        }
      }
      STAMPW(13);
      load_taps(k, p, chb, tid);
    } else {
      float d[96];
      if (wg == 0) st_ll2(&p.scr->zstat[(rb * 256 + cb * 64 + w * 16 + g + (t >> 1) * 8) * 2 + (t & 1)], 0, 0);
      else if ((tid & 7) == 0) st_ll4(&p.scr->xstat[rb * 64 + cb * 16 + (tid >> 3)], 0, 0, 0, 0);
      {
        #pragma unroll
        for (int i = 0; i < 96; i++) d[i] = 0.f;
        {
          if (__builtin_expect(wg == 1, 0)) {
            const int tid = tid_now();
            const uint32_t epoch = load_epoch(p, lin, lane);
            float s = 0.f, q = 0.f;
#pragma unroll 1
            for (int i = 0; i < 10; i++) {
              mbar_wait(sb + BAR_AF + 8 * i, 0);
              const uint4 x4 = lds128(sb + OFF_A + i * A_SLOT + cb * 2048 + tid * 16);
              const uint32_t u[4] = {x4.x, x4.y, x4.z, x4.w};
#pragma unroll
              for (int e = 0; e < 4; e++) { const float a = bf_lo(u[e]), c = bf_hi(u[e]); s += a + c; q = fmaf(a, a, q); q = fmaf(c, c, q); }
            }
#pragma unroll
            for (int o = 1; o <= 4; o <<= 1) { s += __shfl_xor_sync(0xffffffff, s, o); q += __shfl_xor_sync(0xffffffff, q, o); }
            const float m = s * (1.f / kD);
            const float r = rsqrtf(fmaxf(fmaf(-m, m, q * (1.f / kD)), 0.f) + 1e-5f);
            if ((tid & 7) == 0) st_ll4(&p.scr->xstat[rb * 64 + cb * 16 + (tid >> 3)], __float_as_uint(m), epoch + 1, __float_as_uint(r), epoch + 1);
            STAMPW(12);
            bar_sync(NB_G1, 256);
          }
          gemm_loop<192, true, 0, D1>(d, sb, 10, 0, 0, 0, 0, wg, 2, tid_now(), [&]() { if (G1_AT == 0 && wg == 0) bar_arrive(NB_G1, 256); }, [](int) {});
          asm volatile("setmaxnreg.inc.sync.aligned.u32 160;");
          STAMPW(wg ? 14 : 1);
          mbar_wait2(sb + BAR_XS, 0, sb + BAR_ST + 8 * wg, 0);
        }
        const int t1 = tid_now();
        const uint32_t xa1 = sb + OFF_XS + (w * 16 + ((t1 & 31) >> 2)) * 8;
        const float2 s0 = lds64f(xa1), s1 = lds64f(xa1 + 64);
        uint32_t z[48];
        float st[4];
        if (CFENCE) fence_async_smem();
        fold_mean(d, sb + OFF_CS + (1 - wg) * 768, s0.x, s1.x, t1 & 3);
        if (G1_AT == 1 && wg == 0) bar_arrive(NB_G1, 256);
        WG_WAIT(0);
        acc_fence<96>(d);
        gelu_tile(d, z, st, s0.y, s1.y);
        const int tid = tid_now(), lane = tid & 31, g = lane >> 2, t = lane & 3;
        if (wg == 1) {
          uint32_t bra, brb;
          asm volatile("ld.shared.u16 %0, [%1];" : "=r"(bra) : "r"(sb + OFF_BIAS + (w * 16 + g) * 2));
          asm volatile("ld.shared.u16 %0, [%1+16];" : "=r"(brb) : "r"(sb + OFF_BIAS + (w * 16 + g) * 2));
#pragma unroll
          for (int j = 0; j < 96; j++) d[j] = bf_lo((j & 2) ? brb : bra);
          STAMPW(15);
          gemm_loop<192, true, 1, D2>(d, sb, 32, 0, 1, 20, 0, 2, 2, tid, [&]() { if (HOLD_AT < 32) mbar_arrive_if(sb + BAR_GO, tid == 0); }, [](int) {});
          if (HOLD_AT == 32) mbar_arrive_if(sb + BAR_GO, tid == 0);
          STAMPW(16);
          const int t2 = tid_now(), l2 = t2 & 31;
          const uint32_t ha = sb + OFF_A + 5 * A_SLOT + (l2 >> 4) * 1024 + (2 * w + ((l2 >> 3) & 1)) * 128 + (l2 & 7) * 16;
#pragma unroll
          for (int j = 0; j < 24; j += 2) {
#pragma unroll
            for (int e = 0; e < 4; e++) z[2 * j + e] = hmul2(z[2 * j + e], pack2(d[4 * j + 2 * e], d[4 * j + 2 * e + 1]));
            stsm4(ha + j * 1024, z[2 * j], z[2 * j + 1], z[2 * j + 2], z[2 * j + 3]);
          }
          fence_async_smem();
          bar_sync(NB_WGB, 128);
          mbar_arrive_if(sb + BAR_AF + 8 * (t2 == 3 ? (BAR_G2 - BAR_AF) / 8 : (t2 == 4 ? (BAR_GO - BAR_AF) / 8 : 5 + t2)), t2 < (HOLD_AT == 33 ? 5 : 4));
          STAMPW(17);
          {
            float e[80];
#pragma unroll
            for (int j = 0; j < 80; j++) e[j] = 0.f;
            gemm_loop<160, false, 2, DB>(e, sb, 12, 5, 0, 2, 0, 2, 2, tid_now(), []() {}, [](int) {});
            STAMPW(10);
            const int t3 = tid_now();
#pragma unroll
            for (int j = 0; j < 10; j++) {
              sts128(sb + OFF_A + j * 2048 + t3 * 16, pack2(e[8 * j], e[8 * j + 1]), pack2(e[8 * j + 2], e[8 * j + 3]), pack2(e[8 * j + 4], e[8 * j + 5]),
                     pack2(e[8 * j + 6], e[8 * j + 7]));
              if (j == 4) bar_arrive(NB_WO, 256);
            }
            bar_arrive(NB_Z, 256);
            STAMPW(45);
          }
          return;
        }
        const bool hi = t & 2;
        float a0 = (hi ? st[2] : st[0]) + __shfl_xor_sync(0xffffffff, hi ? st[0] : st[2], 2);
        float a1 = (hi ? st[3] : st[1]) + __shfl_xor_sync(0xffffffff, hi ? st[1] : st[3], 2);
        a0 = ((t & 1) ? a1 : a0) + __shfl_xor_sync(0xffffffff, (t & 1) ? a0 : a1, 1);
        const uint32_t tag = lds32<0>(sb + OFF_TAG);
        uint2* zs = p.scr->zstat + (rb * 256 + w * 16 + g + (t >> 1) * 8) * 2 + (t & 1);
        st_ll2(zs + cb * 128, __float_as_uint(a0), tag);
        STAMPW(2);
        uint2 u[4];
        if (ZPOLL == 0) {
#pragma unroll
          for (int i = 0; i < 4; i++) u[i] = ld_ll2(zs + i * 128);
        }
        final_load_x(xw, sb + OFF_A, cb, 0, w, lane);
        fence_async_smem();
        bar_sync(NB_WGA, 128);
        mbar_arrive_if(sb + BAR_AE + 8 * tid, tid < NA);
        if (ZPOLL == 1) {
#pragma unroll
          for (int i = 0; i < 4; i++) u[i] = ld_ll2(zs + i * 128);
        }
        const uint32_t za = sb + OFF_A + LEAD * A_SLOT + (2 * w + ((lane >> 3) & 1)) * 3072 + (lane >> 4) * 128 + (lane & 7) * 16;
        const float ca = 0.5f * (hi ? s1.y : s0.y), inv = 1.f / 768.f;
        mbar_wait2(sb + BAR_AE + 8 * (LEAD + 2), 0, sb + BAR_XC, 0);
        uint32_t t0 = 0;
#pragma unroll 1
        while (!__all_sync(0xffffffff, u[0].y == tag && u[1].y == tag && u[2].y == tag && u[3].y == tag)) {
          spin_guard(t0);
#pragma unroll
          for (int i = 0; i < 4; i++) u[i] = ld_ll2(zs + i * 128);
        }
        STAMPW(3);
        a0 = ((__uint_as_float(u[0].x) + __uint_as_float(u[1].x)) + (__uint_as_float(u[2].x) + __uint_as_float(u[3].x))) * inv;
        a1 = __shfl_xor_sync(0xffffffff, a0, 1);
        const float m = (t & 1) ? a1 : a0, q = (t & 1) ? a0 : a1;
        const float r = bf_lo(pack2(ca * rsqrtf(fmaf(fmaxf(fmaf(-m, m, q), 0.f), ca * ca, 1e-5f)), 0.f));
        const uint32_t rn = pack2(r, -m * r), ro = __shfl_xor_sync(0xffffffff, rn, 2);
        const uint32_t ra2 = prmt(hi ? ro : rn, 0, 0x1010), n2a = prmt(hi ? ro : rn, 0, 0x3232), rb2 = prmt(hi ? rn : ro, 0, 0x1010), n2b = prmt(hi ? rn : ro, 0, 0x3232);
#pragma unroll
        for (int j = 0; j < 24; j += 2)
          stsm4(za + j * 128, hfma2(z[2 * j], ra2, n2a), hfma2(z[2 * j + 1], rb2, n2b), hfma2(z[2 * j + 2], ra2, n2a), hfma2(z[2 * j + 3], rb2, n2b));
        fence_async_smem();
      }
      bar_arrive(NB_Z, 160);
      {
        const uint32_t zero = lds32<0>(sb + OFF_TAG + 4);
#pragma unroll
        for (int i = 0; i < 20; i++) xw[i / 10][i % 10] |= zero;
      }
      load_taps(k, p, chb + 64, tid_now());
      STAMPW(4);
    }
    const int h = wg >> 1;
    {
    const int tid = tid_now(), lane = tid & 31;
    conv_worker(p, k, sb + OFF_CV + (1 - h) * CV_SZ, sb + OFF_A + 9 * A_SLOT + h * 4096, sb + BAR_XF + 8 * h, NB_WGA + h,
                chb + (h ? 0 : 64), 2 + h, sb + BAR_GO, w, lane, tid, h ? 40 : 5, rb, cb);
    {
      const int t3 = tid_now(), l3 = t3 & 31;
      const uint32_t xs_addr = sb + OFF_XS + (w * 16 + (l3 >> 2)) * 8;
      const float2 s0 = lds64f(xs_addr), s1 = lds64f(xs_addr + 64);
      const uint32_t ya = sb + y_tile(h) + ((l3 >> 4) * 8 + (l3 & 7)) * 128 + (((2 * w + ((l3 >> 3) & 1)) ^ (l3 & 7) ^ (rb & 7)) << 4);
      uint32_t sw[2][10];
      mbar_wait(sb + BAR_XF + 8 * h, h);
      final_s_early(sw, xw, ya, s0, s1);
      uint32_t ph = 1, t0 = 0, y[8];
#pragma unroll 1
      while (true) {
        mbar_wait(sb + BAR_YL + 16 * h, ph);
        if (bar_all(NB_WGA + h, 128, final_late(y, ya))) break;
        spin_guard(t0);
        ph ^= 1;
        if (t3 == 0) load_late_y(p, sb, h, rb, cb, lds32<0>(sb + OFF_TAG) & 1);
      }
#pragma unroll
      for (int e = 0; e < 8; e++) sw[e & 1][4 + (e >> 1)] = hmul2(sw[e & 1][4 + (e >> 1)], ~y[e]);
      __nv_bfloat16* o0 = p.out + (size_t)(w * 512 + rb * 16 + (l3 >> 2)) * kD + seg_col(cb, h);
      STAMPW(h ? 44 : 9);
      bar_sync(h ? NB_Z : NB_WO, 256);
      float d[40];
#pragma unroll
      for (int j = 0; j < 5; j++) {
        const uint4 v = lds128(sb + OFF_A + (h * 5 + j) * 2048 + t3 * 16);
        d[8 * j] = bf_lo(v.x); d[8 * j + 1] = bf_hi(v.x); d[8 * j + 2] = bf_lo(v.y); d[8 * j + 3] = bf_hi(v.y);
        d[8 * j + 4] = bf_lo(v.z); d[8 * j + 5] = bf_hi(v.z); d[8 * j + 6] = bf_lo(v.w); d[8 * j + 7] = bf_hi(v.w);
      }
      final_out(d, xw, sw, s0.y, s1.y, o0, h, l3 & 3);
    }
    }
  }
}

typedef CUresult (*EncodeFn)(CUtensorMap*, CUtensorMapDataType, cuuint32_t, void*, const cuuint64_t*, const cuuint64_t*, const cuuint32_t*,
                             const cuuint32_t*, CUtensorMapInterleave, CUtensorMapSwizzle, CUtensorMapL2promotion, CUtensorMapFloatOOBfill);

void encode(EncodeFn fn, CUtensorMap* m, const void* ptr, int rank, const cuuint64_t* dims, const cuuint64_t* strides, const cuuint32_t* box,
            CUtensorMapSwizzle swz = CU_TENSOR_MAP_SWIZZLE_128B) {
  const cuuint32_t es[3] = {1, 1, 1};
  fn(m, CU_TENSOR_MAP_DATA_TYPE_BFLOAT16, rank, const_cast<void*>(ptr), dims, strides, box, es, CU_TENSOR_MAP_INTERLEAVE_NONE,
     swz, CU_TENSOR_MAP_L2_PROMOTION_L2_128B, CU_TENSOR_MAP_FLOAT_OOB_FILL_NONE);
}

}

extern "C" void kernel_launch(void* const* d_in, const int* in_sizes, int n_in, void* d_out, int out_size) {
  (void)in_sizes; (void)n_in; (void)out_size;
  static EncodeFn enc = nullptr;
  static Scratch* scr = nullptr;
  static int sms = 0;
  if (!enc) {
    void* fn = nullptr;
    cudaDriverEntryPointQueryResult qr;
    cudaGetDriverEntryPoint("cuTensorMapEncodeTiled", &fn, cudaEnableDefault, &qr);
    enc = (EncodeFn)fn;
    cudaFuncSetAttribute(fused_kernel, cudaFuncAttributeMaxDynamicSharedMemorySize, SMEM_BYTES);
    cudaGetSymbolAddress((void**)&scr, g_scr);
    int dev = 0;
    cudaGetDevice(&dev);
    cudaDeviceGetAttribute(&sms, cudaDevAttrMultiProcessorCount, dev);
  }
  Params p;
  p.scr = scr;
  p.by_smid = sms == 132;
  p.k = (const __nv_bfloat16*)d_in[1];
  p.v = (const __nv_bfloat16*)d_in[2];
  p.shift = (const __nv_bfloat16*)d_in[3];
  p.ssmk = (const __nv_bfloat16*)d_in[4];
  p.ssmD = (const __nv_bfloat16*)d_in[5];
  p.wsp = (const __nv_bfloat16*)d_in[8];
  p.bsp = (const __nv_bfloat16*)d_in[9];
  p.wout = (const __nv_bfloat16*)d_in[10];
  p.out = (__nv_bfloat16*)d_out;
  for (int i = 0; i < 2; i++) {
    const cuuint64_t n = i ? kS : kD, dims[3] = {n, 512, 4}, st[2] = {n * 2, n * 1024};
    const cuuint32_t box[3] = {64, 16, 4};
    encode(enc, i ? &p.tmWsp : &p.tmX, d_in[i ? 8 : 0], 3, dims, st, box);
  }
  {
    const cuuint64_t dims[3] = {64, kD, kF / 64}, st[2] = {kF * 2, 128};
    const cuuint32_t box[3] = {64, 64, 3};
    encode(enc, &p.tmW, d_in[7], 3, dims, st, box);
  }
  {
    const cuuint64_t dims[2] = {kS, 896}, st[1] = {kS * 2};
    const cuuint32_t box[2] = {64, 16};
    encode(enc, &p.tmY, scr->y, 2, dims, st, box);
  }
  {
    const cuuint64_t dims[3] = {1024, kD / 2, 4}, st[2] = {8192, 2048};
    const cuuint32_t box[3] = {16, 32, 4};
    encode(enc, &p.tmKV, scr->kvx, 3, dims, st, box, CU_TENSOR_MAP_SWIZZLE_32B);
  }
  fused_kernel<<<132, 512, SMEM_BYTES, cudaStreamPerThread>>>(p);
}
```

```cpp
#include <cuda_runtime.h>
#include <cuda.h>
#include <cuda_bf16.h>
#include <stdint.h>

template <int N> struct WG;
template <> struct WG<16> {
  static __device__ __forceinline__ void rs(float* d, const uint32_t* a, uint64_t db) {
    asm volatile("{\n.reg .pred p;\nsetp.ne.b32 p, 1, 0;\nwgmma.mma_async.sync.aligned.m64n16k16.f32.bf16.bf16 {"
      "%0, %1, %2, %3, %4, %5, %6, %7"
      "}, {%8, %9, %10, %11}, %12, p, 1, 1, 0;\n}\n"
      :
      "+f"(d[0]), "+f"(d[1]), "+f"(d[2]), "+f"(d[3]), "+f"(d[4]), "+f"(d[5]), "+f"(d[6]), "+f"(d[7])
      : "r"(a[0]), "r"(a[1]), "r"(a[2]), "r"(a[3]), "l"(db));
  }
};
template <> struct WG<32> {
  static __device__ __forceinline__ void rs(float* d, const uint32_t* a, uint64_t db) {
    asm volatile("{\n.reg .pred p;\nsetp.ne.b32 p, 1, 0;\nwgmma.mma_async.sync.aligned.m64n32k16.f32.bf16.bf16 {"
      "%0, %1, %2, %3, %4, %5, %6, %7, %8, %9, %10, %11, %12, %13, %14, %15"
      "}, {%16, %17, %18, %19}, %20, p, 1, 1, 0;\n}\n"
      :
      "+f"(d[0]), "+f"(d[1]), "+f"(d[2]), "+f"(d[3]), "+f"(d[4]), "+f"(d[5]), "+f"(d[6]), "+f"(d[7]),
      "+f"(d[8]), "+f"(d[9]), "+f"(d[10]), "+f"(d[11]), "+f"(d[12]), "+f"(d[13]), "+f"(d[14]), "+f"(d[15])
      : "r"(a[0]), "r"(a[1]), "r"(a[2]), "r"(a[3]), "l"(db));
  }
};
template <> struct WG<48> {
  static __device__ __forceinline__ void rs(float* d, const uint32_t* a, uint64_t db) {
    asm volatile("{\n.reg .pred p;\nsetp.ne.b32 p, 1, 0;\nwgmma.mma_async.sync.aligned.m64n48k16.f32.bf16.bf16 {"
      "%0, %1, %2, %3, %4, %5, %6, %7, %8, %9, %10, %11, %12, %13, %14, %15, "
      "%16, %17, %18, %19, %20, %21, %22, %23"
      "}, {%24, %25, %26, %27}, %28, p, 1, 1, 0;\n}\n"
      :
      "+f"(d[0]), "+f"(d[1]), "+f"(d[2]), "+f"(d[3]), "+f"(d[4]), "+f"(d[5]), "+f"(d[6]), "+f"(d[7]),
      "+f"(d[8]), "+f"(d[9]), "+f"(d[10]), "+f"(d[11]), "+f"(d[12]), "+f"(d[13]), "+f"(d[14]), "+f"(d[15]),
      "+f"(d[16]), "+f"(d[17]), "+f"(d[18]), "+f"(d[19]), "+f"(d[20]), "+f"(d[21]), "+f"(d[22]), "+f"(d[23])
      : "r"(a[0]), "r"(a[1]), "r"(a[2]), "r"(a[3]), "l"(db));
  }
};
template <> struct WG<64> {
  static __device__ __forceinline__ void rs(float* d, const uint32_t* a, uint64_t db) {
    asm volatile("{\n.reg .pred p;\nsetp.ne.b32 p, 1, 0;\nwgmma.mma_async.sync.aligned.m64n64k16.f32.bf16.bf16 {"
      "%0, %1, %2, %3, %4, %5, %6, %7, %8, %9, %10, %11, %12, %13, %14, %15, "
      "%16, %17, %18, %19, %20, %21, %22, %23, %24, %25, %26, %27, %28, %29, %30, %31"
      "}, {%32, %33, %34, %35}, %36, p, 1, 1, 0;\n}\n"
      :
      "+f"(d[0]), "+f"(d[1]), "+f"(d[2]), "+f"(d[3]), "+f"(d[4]), "+f"(d[5]), "+f"(d[6]), "+f"(d[7]),
      "+f"(d[8]), "+f"(d[9]), "+f"(d[10]), "+f"(d[11]), "+f"(d[12]), "+f"(d[13]), "+f"(d[14]), "+f"(d[15]),
      "+f"(d[16]), "+f"(d[17]), "+f"(d[18]), "+f"(d[19]), "+f"(d[20]), "+f"(d[21]), "+f"(d[22]), "+f"(d[23]),
      "+f"(d[24]), "+f"(d[25]), "+f"(d[26]), "+f"(d[27]), "+f"(d[28]), "+f"(d[29]), "+f"(d[30]), "+f"(d[31])
      : "r"(a[0]), "r"(a[1]), "r"(a[2]), "r"(a[3]), "l"(db));
  }
};
template <> struct WG<80> {
  static __device__ __forceinline__ void rs(float* d, const uint32_t* a, uint64_t db) {
    asm volatile("{\n.reg .pred p;\nsetp.ne.b32 p, 1, 0;\nwgmma.mma_async.sync.aligned.m64n80k16.f32.bf16.bf16 {"
      "%0, %1, %2, %3, %4, %5, %6, %7, %8, %9, %10, %11, %12, %13, %14, %15, "
      "%16, %17, %18, %19, %20, %21, %22, %23, %24, %25, %26, %27, %28, %29, %30, %31, "
      "%32, %33, %34, %35, %36, %37, %38, %39"
      "}, {%40, %41, %42, %43}, %44, p, 1, 1, 0;\n}\n"
      :
      "+f"(d[0]), "+f"(d[1]), "+f"(d[2]), "+f"(d[3]), "+f"(d[4]), "+f"(d[5]), "+f"(d[6]), "+f"(d[7]),
      "+f"(d[8]), "+f"(d[9]), "+f"(d[10]), "+f"(d[11]), "+f"(d[12]), "+f"(d[13]), "+f"(d[14]), "+f"(d[15]),
      "+f"(d[16]), "+f"(d[17]), "+f"(d[18]), "+f"(d[19]), "+f"(d[20]), "+f"(d[21]), "+f"(d[22]), "+f"(d[23]),
      "+f"(d[24]), "+f"(d[25]), "+f"(d[26]), "+f"(d[27]), "+f"(d[28]), "+f"(d[29]), "+f"(d[30]), "+f"(d[31]),
      "+f"(d[32]), "+f"(d[33]), "+f"(d[34]), "+f"(d[35]), "+f"(d[36]), "+f"(d[37]), "+f"(d[38]), "+f"(d[39])
      : "r"(a[0]), "r"(a[1]), "r"(a[2]), "r"(a[3]), "l"(db));
  }
};
template <> struct WG<96> {
  static __device__ __forceinline__ void rs(float* d, const uint32_t* a, uint64_t db) {
    asm volatile("{\n.reg .pred p;\nsetp.ne.b32 p, 1, 0;\nwgmma.mma_async.sync.aligned.m64n96k16.f32.bf16.bf16 {"
      "%0, %1, %2, %3, %4, %5, %6, %7, %8, %9, %10, %11, %12, %13, %14, %15, "
      "%16, %17, %18, %19, %20, %21, %22, %23, %24, %25, %26, %27, %28, %29, %30, %31, "
      "%32, %33, %34, %35, %36, %37, %38, %39, %40, %41, %42, %43, %44, %45, %46, %47"
      "}, {%48, %49, %50, %51}, %52, p, 1, 1, 0;\n}\n"
      :
      "+f"(d[0]), "+f"(d[1]), "+f"(d[2]), "+f"(d[3]), "+f"(d[4]), "+f"(d[5]), "+f"(d[6]), "+f"(d[7]),
      "+f"(d[8]), "+f"(d[9]), "+f"(d[10]), "+f"(d[11]), "+f"(d[12]), "+f"(d[13]), "+f"(d[14]), "+f"(d[15]),
      "+f"(d[16]), "+f"(d[17]), "+f"(d[18]), "+f"(d[19]), "+f"(d[20]), "+f"(d[21]), "+f"(d[22]), "+f"(d[23]),
      "+f"(d[24]), "+f"(d[25]), "+f"(d[26]), "+f"(d[27]), "+f"(d[28]), "+f"(d[29]), "+f"(d[30]), "+f"(d[31]),
      "+f"(d[32]), "+f"(d[33]), "+f"(d[34]), "+f"(d[35]), "+f"(d[36]), "+f"(d[37]), "+f"(d[38]), "+f"(d[39]),
      "+f"(d[40]), "+f"(d[41]), "+f"(d[42]), "+f"(d[43]), "+f"(d[44]), "+f"(d[45]), "+f"(d[46]), "+f"(d[47])
      : "r"(a[0]), "r"(a[1]), "r"(a[2]), "r"(a[3]), "l"(db));
  }
};
template <> struct WG<112> {
  static __device__ __forceinline__ void rs(float* d, const uint32_t* a, uint64_t db) {
    asm volatile("{\n.reg .pred p;\nsetp.ne.b32 p, 1, 0;\nwgmma.mma_async.sync.aligned.m64n112k16.f32.bf16.bf16 {"
      "%0, %1, %2, %3, %4, %5, %6, %7, %8, %9, %10, %11, %12, %13, %14, %15, "
      "%16, %17, %18, %19, %20, %21, %22, %23, %24, %25, %26, %27, %28, %29, %30, %31, "
      "%32, %33, %34, %35, %36, %37, %38, %39, %40, %41, %42, %43, %44, %45, %46, %47, "
      "%48, %49, %50, %51, %52, %53, %54, %55"
      "}, {%56, %57, %58, %59}, %60, p, 1, 1, 0;\n}\n"
      :
      "+f"(d[0]), "+f"(d[1]), "+f"(d[2]), "+f"(d[3]), "+f"(d[4]), "+f"(d[5]), "+f"(d[6]), "+f"(d[7]),
      "+f"(d[8]), "+f"(d[9]), "+f"(d[10]), "+f"(d[11]), "+f"(d[12]), "+f"(d[13]), "+f"(d[14]), "+f"(d[15]),
      "+f"(d[16]), "+f"(d[17]), "+f"(d[18]), "+f"(d[19]), "+f"(d[20]), "+f"(d[21]), "+f"(d[22]), "+f"(d[23]),
      "+f"(d[24]), "+f"(d[25]), "+f"(d[26]), "+f"(d[27]), "+f"(d[28]), "+f"(d[29]), "+f"(d[30]), "+f"(d[31]),
      "+f"(d[32]), "+f"(d[33]), "+f"(d[34]), "+f"(d[35]), "+f"(d[36]), "+f"(d[37]), "+f"(d[38]), "+f"(d[39]),
      "+f"(d[40]), "+f"(d[41]), "+f"(d[42]), "+f"(d[43]), "+f"(d[44]), "+f"(d[45]), "+f"(d[46]), "+f"(d[47]),
      "+f"(d[48]), "+f"(d[49]), "+f"(d[50]), "+f"(d[51]), "+f"(d[52]), "+f"(d[53]), "+f"(d[54]), "+f"(d[55])
      : "r"(a[0]), "r"(a[1]), "r"(a[2]), "r"(a[3]), "l"(db));
  }
};
template <> struct WG<128> {
  static __device__ __forceinline__ void rs(float* d, const uint32_t* a, uint64_t db) {
    asm volatile("{\n.reg .pred p;\nsetp.ne.b32 p, 1, 0;\nwgmma.mma_async.sync.aligned.m64n128k16.f32.bf16.bf16 {"
      "%0, %1, %2, %3, %4, %5, %6, %7, %8, %9, %10, %11, %12, %13, %14, %15, "
      "%16, %17, %18, %19, %20, %21, %22, %23, %24, %25, %26, %27, %28, %29, %30, %31, "
      "%32, %33, %34, %35, %36, %37, %38, %39, %40, %41, %42, %43, %44, %45, %46, %47, "
      "%48, %49, %50, %51, %52, %53, %54, %55, %56, %57, %58, %59, %60, %61, %62, %63"
      "}, {%64, %65, %66, %67}, %68, p, 1, 1, 0;\n}\n"
      :
      "+f"(d[0]), "+f"(d[1]), "+f"(d[2]), "+f"(d[3]), "+f"(d[4]), "+f"(d[5]), "+f"(d[6]), "+f"(d[7]),
      "+f"(d[8]), "+f"(d[9]), "+f"(d[10]), "+f"(d[11]), "+f"(d[12]), "+f"(d[13]), "+f"(d[14]), "+f"(d[15]),
      "+f"(d[16]), "+f"(d[17]), "+f"(d[18]), "+f"(d[19]), "+f"(d[20]), "+f"(d[21]), "+f"(d[22]), "+f"(d[23]),
      "+f"(d[24]), "+f"(d[25]), "+f"(d[26]), "+f"(d[27]), "+f"(d[28]), "+f"(d[29]), "+f"(d[30]), "+f"(d[31]),
      "+f"(d[32]), "+f"(d[33]), "+f"(d[34]), "+f"(d[35]), "+f"(d[36]), "+f"(d[37]), "+f"(d[38]), "+f"(d[39]),
      "+f"(d[40]), "+f"(d[41]), "+f"(d[42]), "+f"(d[43]), "+f"(d[44]), "+f"(d[45]), "+f"(d[46]), "+f"(d[47]),
      "+f"(d[48]), "+f"(d[49]), "+f"(d[50]), "+f"(d[51]), "+f"(d[52]), "+f"(d[53]), "+f"(d[54]), "+f"(d[55]),
      "+f"(d[56]), "+f"(d[57]), "+f"(d[58]), "+f"(d[59]), "+f"(d[60]), "+f"(d[61]), "+f"(d[62]), "+f"(d[63])
      : "r"(a[0]), "r"(a[1]), "r"(a[2]), "r"(a[3]), "l"(db));
  }
};
template <> struct WG<160> {
  static __device__ __forceinline__ void ss(float* d, uint64_t da, uint64_t db, int sd) {
    asm volatile("{\n.reg .pred p;\nsetp.ne.b32 p, %82, 0;\nwgmma.mma_async.sync.aligned.m64n160k16.f32.bf16.bf16 {"
      "%0, %1, %2, %3, %4, %5, %6, %7, %8, %9, %10, %11, %12, %13, %14, %15, "
      "%16, %17, %18, %19, %20, %21, %22, %23, %24, %25, %26, %27, %28, %29, %30, %31, "
      "%32, %33, %34, %35, %36, %37, %38, %39, %40, %41, %42, %43, %44, %45, %46, %47, "
      "%48, %49, %50, %51, %52, %53, %54, %55, %56, %57, %58, %59, %60, %61, %62, %63, "
      "%64, %65, %66, %67, %68, %69, %70, %71, %72, %73, %74, %75, %76, %77, %78, %79"
      "}, %80, %81, p, 1, 1, 0, 1;\n}\n"
      :
      "+f"(d[0]), "+f"(d[1]), "+f"(d[2]), "+f"(d[3]), "+f"(d[4]), "+f"(d[5]), "+f"(d[6]), "+f"(d[7]),
      "+f"(d[8]), "+f"(d[9]), "+f"(d[10]), "+f"(d[11]), "+f"(d[12]), "+f"(d[13]), "+f"(d[14]), "+f"(d[15]),
      "+f"(d[16]), "+f"(d[17]), "+f"(d[18]), "+f"(d[19]), "+f"(d[20]), "+f"(d[21]), "+f"(d[22]), "+f"(d[23]),
      "+f"(d[24]), "+f"(d[25]), "+f"(d[26]), "+f"(d[27]), "+f"(d[28]), "+f"(d[29]), "+f"(d[30]), "+f"(d[31]),
      "+f"(d[32]), "+f"(d[33]), "+f"(d[34]), "+f"(d[35]), "+f"(d[36]), "+f"(d[37]), "+f"(d[38]), "+f"(d[39]),
      "+f"(d[40]), "+f"(d[41]), "+f"(d[42]), "+f"(d[43]), "+f"(d[44]), "+f"(d[45]), "+f"(d[46]), "+f"(d[47]),
      "+f"(d[48]), "+f"(d[49]), "+f"(d[50]), "+f"(d[51]), "+f"(d[52]), "+f"(d[53]), "+f"(d[54]), "+f"(d[55]),
      "+f"(d[56]), "+f"(d[57]), "+f"(d[58]), "+f"(d[59]), "+f"(d[60]), "+f"(d[61]), "+f"(d[62]), "+f"(d[63]),
      "+f"(d[64]), "+f"(d[65]), "+f"(d[66]), "+f"(d[67]), "+f"(d[68]), "+f"(d[69]), "+f"(d[70]), "+f"(d[71]),
      "+f"(d[72]), "+f"(d[73]), "+f"(d[74]), "+f"(d[75]), "+f"(d[76]), "+f"(d[77]), "+f"(d[78]), "+f"(d[79])
      : "l"(da), "l"(db), "r"(sd));
  }
};
template <> struct WG<192> {
  static __device__ __forceinline__ void ss(float* d, uint64_t da, uint64_t db, int sd) {
    asm volatile("{\n.reg .pred p;\nsetp.ne.b32 p, %98, 0;\nwgmma.mma_async.sync.aligned.m64n192k16.f32.bf16.bf16 {"
      "%0, %1, %2, %3, %4, %5, %6, %7, %8, %9, %10, %11, %12, %13, %14, %15, "
      "%16, %17, %18, %19, %20, %21, %22, %23, %24, %25, %26, %27, %28, %29, %30, %31, "
      "%32, %33, %34, %35, %36, %37, %38, %39, %40, %41, %42, %43, %44, %45, %46, %47, "
      "%48, %49, %50, %51, %52, %53, %54, %55, %56, %57, %58, %59, %60, %61, %62, %63, "
      "%64, %65, %66, %67, %68, %69, %70, %71, %72, %73, %74, %75, %76, %77, %78, %79, "
      "%80, %81, %82, %83, %84, %85, %86, %87, %88, %89, %90, %91, %92, %93, %94, %95"
      "}, %96, %97, p, 1, 1, 0, 1;\n}\n"
      :
      "+f"(d[0]), "+f"(d[1]), "+f"(d[2]), "+f"(d[3]), "+f"(d[4]), "+f"(d[5]), "+f"(d[6]), "+f"(d[7]),
      "+f"(d[8]), "+f"(d[9]), "+f"(d[10]), "+f"(d[11]), "+f"(d[12]), "+f"(d[13]), "+f"(d[14]), "+f"(d[15]),
      "+f"(d[16]), "+f"(d[17]), "+f"(d[18]), "+f"(d[19]), "+f"(d[20]), "+f"(d[21]), "+f"(d[22]), "+f"(d[23]),
      "+f"(d[24]), "+f"(d[25]), "+f"(d[26]), "+f"(d[27]), "+f"(d[28]), "+f"(d[29]), "+f"(d[30]), "+f"(d[31]),
      "+f"(d[32]), "+f"(d[33]), "+f"(d[34]), "+f"(d[35]), "+f"(d[36]), "+f"(d[37]), "+f"(d[38]), "+f"(d[39]),
      "+f"(d[40]), "+f"(d[41]), "+f"(d[42]), "+f"(d[43]), "+f"(d[44]), "+f"(d[45]), "+f"(d[46]), "+f"(d[47]),
      "+f"(d[48]), "+f"(d[49]), "+f"(d[50]), "+f"(d[51]), "+f"(d[52]), "+f"(d[53]), "+f"(d[54]), "+f"(d[55]),
      "+f"(d[56]), "+f"(d[57]), "+f"(d[58]), "+f"(d[59]), "+f"(d[60]), "+f"(d[61]), "+f"(d[62]), "+f"(d[63]),
      "+f"(d[64]), "+f"(d[65]), "+f"(d[66]), "+f"(d[67]), "+f"(d[68]), "+f"(d[69]), "+f"(d[70]), "+f"(d[71]),
      "+f"(d[72]), "+f"(d[73]), "+f"(d[74]), "+f"(d[75]), "+f"(d[76]), "+f"(d[77]), "+f"(d[78]), "+f"(d[79]),
      "+f"(d[80]), "+f"(d[81]), "+f"(d[82]), "+f"(d[83]), "+f"(d[84]), "+f"(d[85]), "+f"(d[86]), "+f"(d[87]),
      "+f"(d[88]), "+f"(d[89]), "+f"(d[90]), "+f"(d[91]), "+f"(d[92]), "+f"(d[93]), "+f"(d[94]), "+f"(d[95])
      : "l"(da), "l"(db), "r"(sd));
  }
  static __device__ __forceinline__ void rst(float* d, const uint32_t* a, uint64_t db) {
    asm volatile("{\n.reg .pred p;\nsetp.ne.b32 p, 1, 0;\nwgmma.mma_async.sync.aligned.m64n192k16.f32.bf16.bf16 {"
      "%0, %1, %2, %3, %4, %5, %6, %7, %8, %9, %10, %11, %12, %13, %14, %15, "
      "%16, %17, %18, %19, %20, %21, %22, %23, %24, %25, %26, %27, %28, %29, %30, %31, "
      "%32, %33, %34, %35, %36, %37, %38, %39, %40, %41, %42, %43, %44, %45, %46, %47, "
      "%48, %49, %50, %51, %52, %53, %54, %55, %56, %57, %58, %59, %60, %61, %62, %63, "
      "%64, %65, %66, %67, %68, %69, %70, %71, %72, %73, %74, %75, %76, %77, %78, %79, "
      "%80, %81, %82, %83, %84, %85, %86, %87, %88, %89, %90, %91, %92, %93, %94, %95"
      "}, {%96, %97, %98, %99}, %100, p, 1, 1, 1;\n}\n"
      :
      "+f"(d[0]), "+f"(d[1]), "+f"(d[2]), "+f"(d[3]), "+f"(d[4]), "+f"(d[5]), "+f"(d[6]), "+f"(d[7]),
      "+f"(d[8]), "+f"(d[9]), "+f"(d[10]), "+f"(d[11]), "+f"(d[12]), "+f"(d[13]), "+f"(d[14]), "+f"(d[15]),
      "+f"(d[16]), "+f"(d[17]), "+f"(d[18]), "+f"(d[19]), "+f"(d[20]), "+f"(d[21]), "+f"(d[22]), "+f"(d[23]),
      "+f"(d[24]), "+f"(d[25]), "+f"(d[26]), "+f"(d[27]), "+f"(d[28]), "+f"(d[29]), "+f"(d[30]), "+f"(d[31]),
      "+f"(d[32]), "+f"(d[33]), "+f"(d[34]), "+f"(d[35]), "+f"(d[36]), "+f"(d[37]), "+f"(d[38]), "+f"(d[39]),
      "+f"(d[40]), "+f"(d[41]), "+f"(d[42]), "+f"(d[43]), "+f"(d[44]), "+f"(d[45]), "+f"(d[46]), "+f"(d[47]),
      "+f"(d[48]), "+f"(d[49]), "+f"(d[50]), "+f"(d[51]), "+f"(d[52]), "+f"(d[53]), "+f"(d[54]), "+f"(d[55]),
      "+f"(d[56]), "+f"(d[57]), "+f"(d[58]), "+f"(d[59]), "+f"(d[60]), "+f"(d[61]), "+f"(d[62]), "+f"(d[63]),
      "+f"(d[64]), "+f"(d[65]), "+f"(d[66]), "+f"(d[67]), "+f"(d[68]), "+f"(d[69]), "+f"(d[70]), "+f"(d[71]),
      "+f"(d[72]), "+f"(d[73]), "+f"(d[74]), "+f"(d[75]), "+f"(d[76]), "+f"(d[77]), "+f"(d[78]), "+f"(d[79]),
      "+f"(d[80]), "+f"(d[81]), "+f"(d[82]), "+f"(d[83]), "+f"(d[84]), "+f"(d[85]), "+f"(d[86]), "+f"(d[87]),
      "+f"(d[88]), "+f"(d[89]), "+f"(d[90]), "+f"(d[91]), "+f"(d[92]), "+f"(d[93]), "+f"(d[94]), "+f"(d[95])
      : "r"(a[0]), "r"(a[1]), "r"(a[2]), "r"(a[3]), "l"(db));
  }
};

#define ZORD 1
#define K0_POLL 0
#define CFENCE 1
#define Z1_AT 4
#define G1_AT 1
#define HGRP 3
#define HPACE 200
#define DB 0
#define HOLD_AT 33
#define LL_AT 4
#define KV_T0 2300
#define ST_YIELD 1
#define HP0 3500
#define HPD 450
#define RAMP 1
#define LEAD 2
#define WSP_N 16
#define EARLY 0
#define CPIN 1
#define CW0 0
#define PFT 1
#define WSP_D 600
#define D1 4
#define D2 4
#define NSLEEP 32

namespace {

constexpr int kS = 2048, kD = 640, kF = 1536;
constexpr int NA = 10, NA2 = 9, NB = 5;
constexpr int A_SLOT = 8192, B_SLOT = 24576;
constexpr int OFF_A = 0;
constexpr int OFF_B = OFF_A + NA * A_SLOT;
constexpr int XB_PL = 2112;
constexpr int CV_KE = 4224, CV_KO = CV_KE + 4160;
constexpr int CV_SZ = CV_KO + 4160;
constexpr int OFF_CV = OFF_B + NB * B_SLOT;
constexpr int OFF_CS = OFF_CV + 2 * CV_SZ;
constexpr int OFF_BIAS = OFF_CS + 1536;
constexpr int OFF_XS = OFF_BIAS + 128;
constexpr int OFF_BAR = OFF_XS + 512;
constexpr int BAR_AF = OFF_BAR, BAR_ST = BAR_AF + 8 * NA, BAR_XF = BAR_ST + 16, BAR_KV = BAR_XF + 16;
constexpr int BAR_BF = OFF_BAR + 128, BAR_G2 = BAR_BF + 8 * (NB + 1), BAR_XS = BAR_G2 + 8, BAR_KU = BAR_XS + 8, BAR_ZP = BAR_KU + 40, BAR_XC = BAR_ZP + 8, BAR_WO = BAR_XC + 8;
constexpr int BAR_AE = OFF_BAR + 256, BAR_BE = BAR_AE + 8 * NA;
constexpr int BAR_YT = BAR_KU + 24;
constexpr int BAR_GO = BAR_XS;
constexpr int BAR_YL = BAR_KU + 16;
constexpr int OFF_TAG = OFF_CS - 32;
constexpr int SMEM_BYTES = OFF_BAR + 384;
static_assert(SMEM_BYTES <= 232448, "smem");
constexpr int NB_WGA = 1, NB_WGC = 2, NB_G1 = 3, NB_WO = 4, NB_CD = 5, NB_Z = 6, NB_WGB = 7, NB_Z2 = 8;

constexpr int CNT_Z = 0, CNT_Y = 1, CNT_Z1 = 3, CNT_KV = 32, CNT_WO = 36;
struct Scratch {
  uint8_t kvx[kD * 4096];
  uint8_t z2[4 * 32 * 24576];
  uint8_t h[32 * 12 * 8192];
  uint8_t wo[4 * 12 * 20480];
  uint8_t y[896 * 4096];
  uint4 xstat[kS];
  uint2 zstat[kS * 8];
  uint2 colsum[kF];
  uint32_t cnt[2 * 32];
  uint32_t hcnt[32 * 32];
  uint32_t epoch[136];
};
__device__ __align__(1024) Scratch g_scr;
#define ZS(i)
#define STAMP(i)
#define STAMP2(i)
#define STAMPW(i)

struct Params {
  Scratch* scr;
  int by_smid;
  const __nv_bfloat16 *k, *v, *shift, *ssmk, *ssmD, *wsp, *bsp, *wout;
  __nv_bfloat16* out;
  CUtensorMap tmX, tmW, tmWsp, tmY, tmKV;
};

__device__ __forceinline__ uint64_t mkdesc(uint32_t addr, uint32_t lbo, uint32_t sbo, uint32_t swz) {
  return (uint64_t)((addr & 0x3FFFF) >> 4) | ((uint64_t)(lbo >> 4) << 16) | ((uint64_t)(sbo >> 4) << 32) | ((uint64_t)swz << 62);
}
#define WG_FENCE() asm volatile("wgmma.fence.sync.aligned;" ::: "memory")
#define WG_COMMIT() asm volatile("wgmma.commit_group.sync.aligned;" ::: "memory")
#define WG_WAIT(n) asm volatile("wgmma.wait_group.sync.aligned %0;" ::"n"(n) : "memory")
template <int N> __device__ __forceinline__ void acc_fence(float* d) {
#pragma unroll
  for (int i = 0; i < N; i++) asm volatile("" : "+f"(d[i])::"memory");
}
__device__ __forceinline__ void mbar_init(uint32_t bar, int cnt) { asm volatile("mbarrier.init.shared::cta.b64 [%0], %1;" ::"r"(bar), "r"(cnt) : "memory"); }
__device__ __forceinline__ void mbar_expect(uint32_t bar, uint32_t bytes) { asm volatile("mbarrier.arrive.expect_tx.shared::cta.b64 _, [%0], %1;" ::"r"(bar), "r"(bytes) : "memory"); }
__device__ __forceinline__ void mbar_arrive(uint32_t bar) { asm volatile("mbarrier.arrive.shared::cta.b64 _, [%0];" ::"r"(bar) : "memory"); }
__device__ __forceinline__ void mbar_arrive_if(uint32_t bar, bool c) {
  asm volatile("{\n.reg .pred p;\nsetp.ne.u32 p, %1, 0;\n@p mbarrier.arrive.shared::cta.b64 _, [%0];\n}\n" ::"r"(bar), "r"((uint32_t)c) : "memory");
}
__device__ __forceinline__ void mbar_expect_if(uint32_t bar, uint32_t bytes, bool c) {
  asm volatile("{\n.reg .pred p;\nsetp.ne.u32 p, %2, 0;\n@p mbarrier.arrive.expect_tx.shared::cta.b64 _, [%0], %1;\n}\n" ::"r"(bar), "r"(bytes), "r"((uint32_t)c) : "memory");
}
__device__ __forceinline__ bool mbar_try(uint32_t bar, uint32_t parity) {
  uint32_t ok;
  asm volatile("{\n.reg .pred p;\nmbarrier.try_wait.parity.shared::cta.b64 p, [%1], %2;\nselp.u32 %0, 1, 0, p;\n}\n" : "=r"(ok) : "r"(bar), "r"(parity) : "memory");
  return ok;
}
__device__ __forceinline__ bool mbar_test(uint32_t bar, uint32_t parity) {
  uint32_t ok;
  asm volatile("{\n.reg .pred p;\nmbarrier.test_wait.parity.shared::cta.b64 p, [%1], %2;\nselp.u32 %0, 1, 0, p;\n}\n" : "=r"(ok) : "r"(bar), "r"(parity) : "memory");
  return ok;
}
__device__ __forceinline__ void die() { asm volatile("st.volatile.global.u32 [%0], %1;" ::"l"(0ull), "r"(0) : "memory"); }
__device__ __forceinline__ void spin_guard(uint32_t& n) { if (++n == (1u << 22)) die(); }
__device__ __forceinline__ void mbar_wait(uint32_t bar, uint32_t parity) {
  uint32_t t0 = 0;
#pragma unroll 1
  while (!mbar_try(bar, parity)) spin_guard(t0);
}
__device__ __forceinline__ void mbar_wait2(uint32_t b0, uint32_t p0, uint32_t b1, uint32_t p1) {
  uint32_t t0 = 0;
#pragma unroll 1
  while (true) {
    const bool r0 = mbar_try(b0, p0), r1 = mbar_try(b1, p1);
    if (r0 && r1) break;
    spin_guard(t0);
  }
}
__device__ __forceinline__ int tid_now() { int v; asm volatile("mov.u32 %0, %%tid.x;" : "=r"(v)); return v & 127; }
__device__ __forceinline__ bool elect_one() {
  uint32_t p;
  asm volatile("{\n.reg .pred P;\nelect.sync _|P, 0xffffffff;\nselp.u32 %0, 1, 0, P;\n}\n" : "=r"(p));
  return p;
}
__device__ __forceinline__ void bar_sync(int id, int n) { asm volatile("bar.sync %0, %1;" ::"r"(id), "r"(n) : "memory"); }
__device__ __forceinline__ void bar_arrive(int id, int n) { asm volatile("bar.arrive %0, %1;" ::"r"(id), "r"(n) : "memory"); }
__device__ __forceinline__ void fence_async_smem() { asm volatile("fence.proxy.async.shared::cta;" ::: "memory"); }
__device__ __forceinline__ void bulk_g2s(uint32_t dst, const void* src, uint32_t bytes, uint32_t bar) {
  asm volatile("cp.async.bulk.shared::cluster.global.mbarrier::complete_tx::bytes [%0], [%1], %2, [%3];" ::"r"(dst), "l"(src), "r"(bytes), "r"(bar) : "memory");
}
__device__ __forceinline__ void bulk_s2g(void* dst, uint32_t src, uint32_t bytes) {
  asm volatile("cp.async.bulk.global.shared::cta.bulk_group [%0], [%1], %2;" ::"l"(dst), "r"(src), "r"(bytes) : "memory");
}
__device__ __forceinline__ void tma2d(uint32_t dst, const CUtensorMap* m, int c0, int c1, uint32_t bar) {
  asm volatile("cp.async.bulk.tensor.2d.shared::cluster.global.mbarrier::complete_tx::bytes [%0], [%1, {%3, %4}], [%2];" ::"r"(dst), "l"(m), "r"(bar), "r"(c0), "r"(c1) : "memory");
}
__device__ __forceinline__ void tma3d(uint32_t dst, const CUtensorMap* m, int c0, int c1, int c2, uint32_t bar) {
  asm volatile("cp.async.bulk.tensor.3d.shared::cluster.global.mbarrier::complete_tx::bytes [%0], [%1, {%3, %4, %5}], [%2];" ::"r"(dst), "l"(m), "r"(bar), "r"(c0), "r"(c1), "r"(c2) : "memory");
}
__device__ __forceinline__ void tma_rows(uint32_t dst, const CUtensorMap* m, int c0, int rb, uint32_t bar) { tma3d(dst, m, c0, rb * 16, 0, bar); }
__device__ __forceinline__ uint4 ld_ll4(const void* p) {
  uint64_t a, b;
  asm volatile("ld.relaxed.gpu.global.v2.u64 {%0,%1}, [%2];" : "=l"(a), "=l"(b) : "l"(p) : "memory");
  return make_uint4((uint32_t)a, (uint32_t)(a >> 32), (uint32_t)b, (uint32_t)(b >> 32));
}
__device__ __forceinline__ void st_ll4(void* p, uint32_t a, uint32_t b, uint32_t c, uint32_t d) {
  asm volatile("st.relaxed.gpu.global.v2.u64 [%0], {%1,%2};" ::"l"(p), "l"(a | ((uint64_t)b << 32)), "l"(c | ((uint64_t)d << 32)) : "memory");
}
__device__ __forceinline__ void st_ll2(void* p, uint32_t a, uint32_t b) { asm volatile("st.relaxed.gpu.global.u64 [%0], %1;" ::"l"(p), "l"(a | ((uint64_t)b << 32)) : "memory"); }
__device__ __forceinline__ uint2 ld_ll2(const void* p) {
  uint64_t a;
  asm volatile("ld.relaxed.gpu.global.u64 %0, [%1];" : "=l"(a) : "l"(p) : "memory");
  return make_uint2((uint32_t)a, (uint32_t)(a >> 32));
}
__device__ __forceinline__ void wgmma_colsum(float* d, uint64_t da, uint64_t db) {
  asm volatile("{\n.reg .pred p;\nsetp.ne.b32 p, 1, 0;\nwgmma.mma_async.sync.aligned.m64n8k16.f32.bf16.bf16 {%0, %1, %2, %3}, %4, %5, p, 1, 1, 1, 0;\n}\n"
               : "+f"(d[0]), "+f"(d[1]), "+f"(d[2]), "+f"(d[3]) : "l"(da), "l"(db));
}
__device__ __forceinline__ void prefetch_l2(const void* p) { asm volatile("prefetch.global.L2 [%0];" ::"l"(p)); }
__device__ __forceinline__ void pace(uint32_t& t, uint32_t dt) {
  t += dt;
  while ((int32_t)((uint32_t)clock() - t) < 0) { if (NSLEEP) __nanosleep(NSLEEP); }
}
__device__ __forceinline__ void red_relaxed(uint32_t* p) { asm volatile("red.relaxed.gpu.global.add.u32 [%0], 1;" ::"l"(p) : "memory"); }
__device__ __forceinline__ void red_release(uint32_t* p) { asm volatile("red.release.gpu.global.add.u32 [%0], 1;" ::"l"(p) : "memory"); }
__device__ __forceinline__ uint4 ldg4(const void* p) { uint4 v; asm volatile("ld.global.v4.u32 {%0,%1,%2,%3}, [%4];" : "=r"(v.x), "=r"(v.y), "=r"(v.z), "=r"(v.w) : "l"(p) : "memory"); return v; }
__device__ __forceinline__ uint32_t ldg1(const void* p) { uint32_t v; asm volatile("ld.global.u32 %0, [%1];" : "=r"(v) : "l"(p) : "memory"); return v; }
__device__ __forceinline__ void stg4_if(void* p, uint32_t a, uint32_t b, uint32_t c, uint32_t d, bool on) {
  asm volatile("{\n.reg .pred p;\nsetp.ne.u32 p, %5, 0;\n@p st.global.v4.u32 [%0], {%1,%2,%3,%4};\n}\n" ::"l"(p), "r"(a), "r"(b), "r"(c), "r"(d), "r"((uint32_t)on) : "memory");
}
template <int OFF> __device__ __forceinline__ uint32_t lds32(uint32_t a) { uint32_t v; asm volatile("ld.shared.u32 %0, [%1+%2];" : "=r"(v) : "r"(a), "n"(OFF)); return v; }
__device__ __forceinline__ uint4 lds128(uint32_t a) { uint4 v; asm volatile("ld.shared.v4.u32 {%0,%1,%2,%3}, [%4];" : "=r"(v.x), "=r"(v.y), "=r"(v.z), "=r"(v.w) : "r"(a) : "memory"); return v; }
__device__ __forceinline__ float2 lds64f(uint32_t a) { float2 v; asm volatile("ld.shared.v2.f32 {%0,%1}, [%2];" : "=f"(v.x), "=f"(v.y) : "r"(a) : "memory"); return v; }
__device__ __forceinline__ void sts64f(uint32_t a, float x, float y) { asm volatile("st.shared.v2.f32 [%0], {%1,%2};" ::"r"(a), "f"(x), "f"(y) : "memory"); }
__device__ __forceinline__ void sts32(uint32_t a, uint32_t x) { asm volatile("st.shared.u32 [%0], %1;" ::"r"(a), "r"(x) : "memory"); }
__device__ __forceinline__ void sts128(uint32_t a, uint32_t x, uint32_t y, uint32_t z, uint32_t w) { asm volatile("st.shared.v4.u32 [%0], {%1,%2,%3,%4};" ::"r"(a), "r"(x), "r"(y), "r"(z), "r"(w) : "memory"); }
__device__ __forceinline__ void stsm4(uint32_t a, uint32_t r0, uint32_t r1, uint32_t r2, uint32_t r3) {
  asm volatile("stmatrix.sync.aligned.m8n8.x4.shared.b16 [%0], {%1,%2,%3,%4};" ::"r"(a), "r"(r0), "r"(r1), "r"(r2), "r"(r3) : "memory");
}
__device__ __forceinline__ void stsm4t(uint32_t a, uint32_t r0, uint32_t r1, uint32_t r2, uint32_t r3) {
  asm volatile("stmatrix.sync.aligned.m8n8.x4.trans.shared.b16 [%0], {%1,%2,%3,%4};" ::"r"(a), "r"(r0), "r"(r1), "r"(r2), "r"(r3) : "memory");
}
__device__ __forceinline__ void ldsm4t(uint32_t* r, uint32_t a) {
  asm volatile("ldmatrix.sync.aligned.m8n8.x4.trans.shared.b16 {%0,%1,%2,%3}, [%4];" : "=r"(r[0]), "=r"(r[1]), "=r"(r[2]), "=r"(r[3]) : "r"(a) : "memory");
}
__device__ __forceinline__ uint32_t pack2(float lo, float hi) { uint32_t r; asm("cvt.rn.bf16x2.f32 %0, %1, %2;" : "=r"(r) : "f"(hi), "f"(lo)); return r; }
__device__ __forceinline__ float bf_lo(uint32_t u) { return __uint_as_float(u << 16); }
__device__ __forceinline__ float bf_hi(uint32_t u) { return __uint_as_float(u & 0xffff0000u); }
__device__ __forceinline__ float tanh_fast(float x) { float y; asm("tanh.approx.f32 %0, %1;" : "=f"(y) : "f"(x)); return y; }
__device__ __forceinline__ uint32_t hmul2(uint32_t a, uint32_t b) { uint32_t r; asm("mul.rn.bf16x2 %0, %1, %2;" : "=r"(r) : "r"(a), "r"(b)); return r; }
__device__ __forceinline__ uint32_t hfma2(uint32_t a, uint32_t b, uint32_t c) { uint32_t r; asm("fma.rn.bf16x2 %0, %1, %2, %3;" : "=r"(r) : "r"(a), "r"(b), "r"(c)); return r; }
__device__ __forceinline__ uint32_t prmt(uint32_t a, uint32_t b, uint32_t s) { return __byte_perm(a, b, s); }

__device__ __forceinline__ uint32_t ld_relaxed(const uint32_t* p) { uint32_t v; asm volatile("ld.relaxed.gpu.global.u32 %0, [%1];" : "=r"(v) : "l"(p) : "memory"); return v; }
__device__ __forceinline__ void acquire_fence() { asm volatile("fence.acquire.gpu;\nfence.proxy.async.global;" ::: "memory"); }
__device__ __forceinline__ uint32_t load_epoch(const Params& p, int idx, int lane) { return ld_relaxed(&p.scr->epoch[idx + (((lane * lane) & 3) == 2 ? 1 : 0)]); }
__device__ __forceinline__ void poll_counter(const uint32_t* cnt, uint32_t target) {
  uint32_t t0 = 0;
#pragma unroll 1
  while (!__all_sync(0xffffffff, ld_relaxed(cnt) == target)) spin_guard(t0);
  acquire_fence();
}

__device__ __forceinline__ int g3_block(int cb, int it) { return it < 3 ? cb * 3 + it : (it - 3 < cb * 3 ? it - 3 : it); }

template <int N, bool A_SWZ, int B_MODE, int DEPTH, class Hook, class Mid>
__device__ __forceinline__ void gemm_loop(float* d, uint32_t sb, int nkb, int sa, int pa, int b0, uint32_t boff, int relA, int relB, int tid, Hook hook, Mid mid) {
  constexpr uint32_t A_STEP = A_SWZ ? 2 : 128;
  constexpr uint32_t B_STEP = B_MODE == 0 ? 128 : (B_MODE == 1 ? 384 : 320);
  const uint64_t da0 = A_SWZ ? mkdesc(sb + OFF_A, 16, 1024, 1) : mkdesc(sb + OFF_A, 1024, 128, 0);
  const uint64_t db0 = B_MODE == 0 ? mkdesc(sb + OFF_B + boff, 8192, 1024, 1) : mkdesc(sb + OFF_B + boff, B_MODE == 1 ? 3072 : 2560, 128, 0);
  constexpr int MODA = B_MODE == 0 ? NA : NA2;
  constexpr int MODB = B_MODE == 2 ? 6 : NB;
  int sbk = b0 % MODB, pb = (b0 / MODB) & 1;
  auto boffs = [](int s_) { return B_MODE == 2 ? (s_ == 5 ? 0 : s_ + 1) * (20480 >> 4) : s_ * (B_SLOT >> 4); };
  uint32_t rel = 0;
  uint64_t da = da0 + sa * (A_SLOT >> 4), db = db0 + boffs(sbk);
  const bool doR = tid < 2 ? tid < relA : tid - 2 < relB;
  mbar_wait2(sb + BAR_AF + 8 * sa, pa, sb + BAR_BF + 8 * sbk, pb);
  if constexpr (DEPTH == 0) {
    acc_fence<N / 2>(d);
#pragma unroll 1
    for (int it = 0; it < nkb; it++) {
      WG_FENCE();
#pragma unroll
      for (int j = 0; j < 4; j++) WG<N>::ss(d, da + j * A_STEP, db + j * B_STEP, 1);
      WG_COMMIT();
      const uint32_t prel = rel;
      rel = sb + BAR_AE + 8 * (tid < 2 ? sa : sbk + NA);
      if (++sa == MODA) { sa = 0; pa ^= 1; }
      if (++sbk == MODB) { sbk = 0; pb ^= 1; }
      da = da0 + sa * (A_SLOT >> 4); db = db0 + boffs(sbk);
      const bool r0 = mbar_test(sb + BAR_AF + 8 * sa, pa), r1 = mbar_test(sb + BAR_BF + 8 * sbk, pb);
      WG_WAIT(1);
      mbar_arrive_if(prel, doR && prel != 0);
      if (it == 2) {
        WG_WAIT(0);
        mbar_expect_if(sb + BAR_AF + 8 * (tid == 8 ? 8 : tid), A_SLOT, tid < 9);
        mbar_arrive_if(rel, doR);
        rel = 0;
      }
      mid(it);
      if (it + 1 < nkb && !(r0 && r1)) {
        mbar_wait2(sb + BAR_AF + 8 * sa, pa, sb + BAR_BF + 8 * sbk, pb);
      }
    }
  } else
#pragma unroll 1
  for (int it = 0; it < nkb; it++) {
    WG_FENCE();
    WG<N>::ss(d, da, db, 1);
    const uint32_t prel = rel;
    rel = sb + BAR_AE + 8 * (tid < 2 ? sa : sbk + NA);
    if (++sa == MODA) { sa = 0; if (B_MODE) pa ^= 1; }
    if (++sbk == MODB) { sbk = 0; pb ^= 1; }
    if (DEPTH == 1) { WG_COMMIT(); WG_WAIT(1); }
    WG<N>::ss(d, da + A_STEP, db + B_STEP, 1);
    WG_COMMIT();
    WG_WAIT(1);
    if (EARLY == 1) mbar_arrive_if(prel, doR && it != 0);
    WG<N>::ss(d, da + 2 * A_STEP, db + 2 * B_STEP, 1);
    if (DEPTH == 1) WG_COMMIT();
    if (EARLY != 1) mbar_arrive_if(prel, doR && it != 0);
    const bool r0 = mbar_test(sb + BAR_AF + 8 * sa, pa), r1 = mbar_test(sb + BAR_BF + 8 * sbk, pb);
    const uint64_t da3 = da + 3 * A_STEP, db3 = db + 3 * B_STEP;
    da = da0 + sa * (A_SLOT >> 4); db = db0 + boffs(sbk);
    if (DEPTH == 1) WG_WAIT(1);
    WG<N>::ss(d, da3, db3, 1);
    WG_COMMIT();
    mid(it);
    if (it + 1 < nkb) {
      if (!(r0 && r1)) {
        mbar_wait2(sb + BAR_AF + 8 * sa, pa, sb + BAR_BF + 8 * sbk, pb);
      }
    }
    if (DEPTH == 2) WG_WAIT(1);
  }
  hook();
  WG_WAIT(0);
  acc_fence<N / 2>(d);
  mbar_arrive_if(rel, doR);
}

__device__ __forceinline__ void fold_mean(float* d, uint32_t cs, float ma, float mb, int t) {
  const uint32_t ha = pack2(-ma, -ma), hb = pack2(-mb, -mb);
  const float la = -ma - bf_lo(ha), lb = -mb - bf_lo(hb);
  const uint32_t a[4] = {t ? 0u : ha, t ? 0u : hb, t ? 0u : pack2(la, la), t ? 0u : pack2(lb, lb)};
  WG_FENCE();
  WG<192>::rst(d, a, mkdesc(cs, 0, 32, 0));
  WG_COMMIT();
}
__device__ __forceinline__ void gelu_tile(const float* d, uint32_t* z, float* st, float ra, float rb) {
  const float kA = 0.7978845608028654f, kB = 0.7978845608028654f * 0.044715f;
  const float c1a = kA * ra, c3a = kB * ra * ra * ra, c1b = kA * rb, c3b = kB * rb * rb * rb;
  float acc[8];
#pragma unroll
  for (int i = 0; i < 8; i++) acc[i] = 0.f;
#pragma unroll
  for (int j = 0; j < 24; j++) {
    float r[4];
#pragma unroll
    for (int e = 0; e < 4; e++) {
      const float v = d[4 * j + e];
      const float a = v * fmaf(v * v, e < 2 ? c3a : c3b, e < 2 ? c1a : c1b);
      r[e] = fmaf(v, tanh_fast(a), v);
      acc[e] += r[e];
      acc[4 + e] = fmaf(r[e], r[e], acc[4 + e]);
    }
    z[2 * j] = pack2(r[0], r[1]);
    z[2 * j + 1] = pack2(r[2], r[3]);
  }
  st[0] = acc[0] + acc[1]; st[1] = acc[4] + acc[5]; st[2] = acc[2] + acc[3]; st[3] = acc[6] + acc[7];
}

template <int Q> __device__ __forceinline__ void conv_load(uint32_t* a, uint32_t ab) {
  a[0] = lds32<512 * Q>(ab);       a[1] = lds32<512 * Q + 256>(ab);  a[2] = lds32<512 * Q + 16>(ab);   a[3] = lds32<512 * Q + 272>(ab);
  a[4] = lds32<512 * Q + 32>(ab);  a[5] = lds32<512 * Q + 288>(ab);  a[6] = lds32<512 * Q + 48>(ab);   a[7] = lds32<512 * Q + 304>(ab);
  a[8] = lds32<512 * Q + 64>(ab);  a[9] = lds32<512 * Q + 320>(ab);  a[10] = lds32<512 * Q + 80>(ab);  a[11] = lds32<512 * Q + 336>(ab);
  a[12] = lds32<512 * Q + 96>(ab); a[13] = lds32<512 * Q + 352>(ab); a[14] = lds32<512 * Q + 112>(ab); a[15] = lds32<512 * Q + 368>(ab);
}
template <int Q, int L> __device__ __forceinline__ void conv_step(float* d, uint32_t (*a)[16], uint32_t ab, uint64_t db) {
  WG_FENCE();
#pragma unroll
  for (int s = 0; s < 4; s++) WG<128 - 16 * Q>::rs(d, a[Q] + 4 * s, db + s + 16 * Q);
  WG_COMMIT();
  if (CPIN) WG_WAIT(1);
  if (L >= 0) conv_load<(L >= 0 ? L : 0)>(a[L >= 0 ? L : 0], ab);
  if (CW0 || Q == 0) WG_WAIT(0);
}

__device__ __forceinline__ int seg_col(int cb, int h) { return (cb >> 1) * 320 + (cb & 1) * 32 + h * 64; }
__device__ __forceinline__ void final_load_x(uint32_t (*xw)[10], uint32_t xt, int cb, int h, int w, int lane) {
  const int g = lane >> 2, t = lane & 3, cc = seg_col(cb, h) >> 3;
  const int c0 = cc + t, c1 = c0 + 24, c2 = cc + 16 - 6 * h + (t >> 1);
  const uint32_t r0 = xt + (w * 16 + g) * 128;
#pragma unroll
  for (int r = 0; r < 2; r++) {
    const uint4 u = lds128(r0 + r * 1024 + (c0 >> 3) * A_SLOT + (((c0 ^ g) & 7) << 4)), v = lds128(r0 + r * 1024 + (c1 >> 3) * A_SLOT + (((c1 ^ g) & 7) << 4));
    const float2 z = lds64f(r0 + r * 1024 + (c2 >> 3) * A_SLOT + (((c2 ^ g) & 7) << 4) + (t & 1) * 8);
    xw[r][0] = u.x; xw[r][1] = u.y; xw[r][2] = u.z; xw[r][3] = u.w;
    xw[r][4] = v.x; xw[r][5] = v.y; xw[r][6] = v.z; xw[r][7] = v.w;
    xw[r][8] = __float_as_uint(z.x); xw[r][9] = __float_as_uint(z.y);
  }
}
__device__ __forceinline__ void final_s_early(uint32_t (*sw)[10], const uint32_t (*xw)[10], uint32_t ya, float2 s0, float2 s1) {
  const uint32_t r2[2] = {pack2(s0.y, s0.y), pack2(s1.y, s1.y)};
  const float na = -s0.x * bf_lo(r2[0]), nb = -s1.x * bf_lo(r2[1]);
  const uint32_t n2[2] = {pack2(na, na), pack2(nb, nb)};
#pragma unroll
  for (int j = 0; j < 10; j += 2) {
    uint32_t y[4];
    if (j < 4 || j == 8) ldsm4t(y, ya + (j < 4 ? j : 4) * 1024);
#pragma unroll
    for (int e = 0; e < 4; e++) {
      const uint32_t xn = hfma2(xw[e & 1][j + (e >> 1)], r2[e & 1], n2[e & 1]);
      sw[e & 1][j + (e >> 1)] = (j < 4 || j == 8) ? hmul2(xn, y[e]) : xn;
    }
  }
}
__device__ __forceinline__ bool final_late(uint32_t* y, uint32_t ya) {
  ldsm4t(y, ya + 6144);
  ldsm4t(y + 4, ya + 8192);
  uint32_t zero = 0;
#pragma unroll
  for (int e = 0; e < 8; e++) zero |= (y[e] - 0x00010001u) & ~y[e];
  return (zero & 0x80008000u) == 0;
}
__device__ __forceinline__ bool bar_all(int id, int n, bool c) {
  uint32_t r;
  asm volatile("{\n.reg .pred p, q;\nsetp.ne.u32 p, %3, 0;\nbar.red.and.pred q, %1, %2, p;\nselp.u32 %0, 1, 0, q;\n}\n" : "=r"(r) : "r"(id), "r"(n), "r"((uint32_t)c) : "memory");
  return r;
}
__device__ __forceinline__ void final_out(const float* d, const uint32_t (*xw)[10], const uint32_t (*sw)[10], float ra, float rb, __nv_bfloat16* o0, int h, int t) {
  const float ca = 0.25f * ra, cb = 0.25f * rb;
  uint32_t o[2][10];
#pragma unroll
  for (int j = 0; j < 10; j++) {
#pragma unroll
    for (int r = 0; r < 2; r++) {
      const float h0 = d[4 * j + 2 * r] * (r ? cb : ca), h1 = d[4 * j + 2 * r + 1] * (r ? cb : ca);
      o[r][j] = hfma2(pack2(fmaf(h0, tanh_fast(h0), h0), fmaf(h1, tanh_fast(h1), h1)), sw[r][j], xw[r][j]);
      __nv_bfloat16* q = o0 + r * 8 * kD;
      if (j == 3) stg4_if(q + t * 8, o[r][0], o[r][1], o[r][2], o[r][3], true);
      if (j == 7) stg4_if(q + 192 + t * 8, o[r][4], o[r][5], o[r][6], o[r][7], true);
      if (j == 9) asm volatile("st.global.v2.u32 [%0], {%1,%2};" ::"l"(q + 128 - 48 * h + t * 4), "r"(o[r][8]), "r"(o[r][9]) : "memory");
    }
  }
}

struct Taps { uint4 r0, r1; uint32_t n0, n1, dd; };
__device__ __forceinline__ void load_taps(Taps& k, const Params& p, int ch, int tid) {
  const uint4* kp = (const uint4*)(p.ssmk + (size_t)ch * kS);
  k.r0 = ldg4(kp + tid); k.r1 = ldg4(kp + 128 + tid);
  k.n0 = ldg1(kp + tid + 1); k.n1 = tid < 127 ? ldg1(kp + 129 + tid) : 0u;
  k.dd = __bfloat16_as_ushort(p.ssmD[ch]);
}
__device__ __forceinline__ void load_convx(const Params& p, uint32_t cv, uint32_t bar, int ch) {
  mbar_expect(bar, 4096);
  bulk_g2s(cv, p.scr->kvx + (size_t)ch * 4096, 2048, bar);
  bulk_g2s(cv + XB_PL, p.scr->kvx + (size_t)ch * 4096 + 2048, 2048, bar);
}
#define CW 3
#define CSTAMP(j)
__device__ __forceinline__ void zero_pads(uint32_t cv, int lane) {
  if (lane < 8) sts128(cv + (lane >> 2) * XB_PL + 2048 + (lane & 3) * 16, 0, 0, 0, 0);
  else if (lane < 12) sts128(cv + ((lane & 2) ? CV_KO : CV_KE) + (lane & 1) * 16, 0, 0, 0, 0);
  fence_async_smem();
  __syncwarp();
}
__device__ __forceinline__ int y_row(int c, uint32_t par) {
  const int hf = c >= 320, cc = c - hf * 320, u = cc >> 6, cb = hf * 2 + ((cc >> 5) & 1);
  if (u == 2) return cb * 96 + ((cc >> 4) & 1) * 48 + 32 + (cc & 1) + ((cc >> 1) & 1) * 8 + ((cc >> 2) & 3) * 2;
  return (u < 2 ? cb * 96 + u * 48 : 384 + par * 256 + cb * 64 + (u - 3) * 32) + (cc & 1) + ((cc >> 1) & 3) * 8 + ((cc >> 3) & 3) * 2;
}
__device__ __forceinline__ void y_store(const Params& p, uint32_t sb, int h, int ch, uint32_t par) {
  uint8_t* dst = p.scr->y + (size_t)y_row(ch, par) * 4096;
  if (elect_one()) {
    bulk_s2g(dst, sb + OFF_A + 9 * A_SLOT + h * 4096, 4096);
    asm volatile("cp.async.bulk.commit_group;\ncp.async.bulk.wait_group 0;" ::: "memory");
  }
  __syncwarp();
}
__device__ __forceinline__ void conv_service(const Params& p, uint32_t sb, int h, int ch, bool first) {
  bar_sync(NB_WGA + 8 + h, 160);
  const bool now = !first || __all_sync(0xffffffff, mbar_test(sb + BAR_KV, 0));
  if (now) { acquire_fence(); if (elect_one()) load_convx(p, sb + OFF_CV + (1 - h) * CV_SZ, sb + BAR_XF + 8 * h, ch + 128); }
  bar_sync(NB_WGA + 8 + h, 160);
  y_store(p, sb, h, ch, 0);
  if (!now) {
    mbar_wait(sb + BAR_KV, 0);
    acquire_fence();
    if (elect_one()) load_convx(p, sb + OFF_CV + (1 - h) * CV_SZ, sb + BAR_XF + 8 * h, ch + 128);
  }
}
__device__ __forceinline__ uint32_t y_tile(int h) { return OFF_CV + (1 - h) * 13312; }
__device__ __forceinline__ void load_late_y(const Params& p, uint32_t sb, int h, int rb, int cb, uint32_t par) {
  mbar_expect(sb + BAR_YL + 16 * h, 4096);
  tma2d(sb + y_tile(h) + 6144, &p.tmY, rb * 64, 384 + par * 256 + cb * 64 + h * 32, sb + BAR_YL + 16 * h);
  tma2d(sb + y_tile(h) + 8192, &p.tmY, rb * 64, 400 + par * 256 + cb * 64 + h * 32, sb + BAR_YL + 16 * h);
}
__device__ __forceinline__ void held_service(const Params& p, uint32_t sb, int h, int ch, int rb, int cb, uint32_t tag, int lane) {
#pragma unroll 1
  for (int i = 0; i < 8; i++) sts128(sb + OFF_A + 9 * A_SLOT + h * 4096 + i * 512 + lane * 16, 0, 0, 0, 0);
  fence_async_smem();
  __syncwarp();
  y_store(p, sb, h, ch, ~tag & 1);
  mbar_wait(sb + BAR_YT, 1);
  acquire_fence();
  bar_sync(NB_WGA + 8 + h, 160);
  bar_sync(NB_WGA + 8 + h, 160);
  uint8_t* dst = p.scr->y + (size_t)y_row(ch, tag & 1) * 4096;
  if (elect_one()) {
    bulk_s2g(dst, sb + OFF_A + 9 * A_SLOT + h * 4096, 4096);
    asm volatile("cp.async.bulk.commit_group;" ::: "memory");
    mbar_expect(sb + BAR_XF + 8 * h, 6144);
#pragma unroll 1
    for (int i = 0; i < 3; i++) tma2d(sb + y_tile(h) + i * 2048, &p.tmY, rb * 64, cb * 96 + h * 48 + i * 16, sb + BAR_XF + 8 * h);
  }
  mbar_wait(sb + BAR_AE + 8 * (LL_AT - 1), 1);
  if (elect_one()) { load_late_y(p, sb, h, rb, cb, tag & 1); asm volatile("cp.async.bulk.wait_group 0;" ::: "memory"); }
}
__device__ __forceinline__ void conv_worker(const Params& p, Taps& k, uint32_t cv, uint32_t yb0,
                                            uint32_t xbar, int nbar, int ch0, int n, uint32_t holdbar, int w, int lane,
                                            int tid, int st0, int rb, int cb) {
  const int g = lane >> 2, t = lane & 3, w0 = w & 1, w1 = w >> 1;
  const uint32_t ab = cv + ((g & 1) ? CV_KE : CV_KO) + 32 + 2 * (64 * w0 + 8 * w1 + ((g - 15) & ~1) + 2 * t);
  const uint32_t scA = cv + (w1 ? CV_KO : CV_KE) + 32, scB = scA + 2048;
  const int dl = (t >> 1) ^ 1;
  if (n == 2) mbar_wait(xbar, 0);
  STAMPW(st0 + 3);
#pragma unroll 1
  for (int i = 0; i < n; i++) {
    if (tid == 0) {
      k.r0.x = (k.r0.x & 0xffff0000u) | (pack2(bf_lo(k.r0.x) + bf_lo(k.dd), 0.f) & 0xffffu);
      sts32(cv + CV_KO + 28, k.r0.x << 16);
    }
    sts128(cv + CV_KE + 32 + tid * 16, k.r0.x, k.r0.y, k.r0.z, k.r0.w);
    sts128(cv + CV_KO + 32 + tid * 16, prmt(k.r0.x, k.r0.y, 0x5432), prmt(k.r0.y, k.r0.z, 0x5432), prmt(k.r0.z, k.r0.w, 0x5432), prmt(k.r0.w, k.n0, 0x5432));
    sts128(cv + CV_KE + 2080 + tid * 16, k.r1.x, k.r1.y, k.r1.z, k.r1.w);
    sts128(cv + CV_KO + 2080 + tid * 16, prmt(k.r1.x, k.r1.y, 0x5432), prmt(k.r1.y, k.r1.z, 0x5432), prmt(k.r1.z, k.r1.w, 0x5432), prmt(k.r1.w, k.n1, 0x5432));
    if (i + 1 < n) load_taps(k, p, ch0 + (i + 1) * 128, tid);
    bar_sync(nbar, 128);
    CSTAMP(0);
    const uint64_t db = mkdesc(cv + (i & 0x1000), XB_PL, 128, 0);
    float d[64];
    uint32_t a[8][16];
    conv_load<7>(a[7], ab); conv_load<6>(a[6], ab); conv_load<5>(a[5], ab); conv_load<4>(a[4], ab);
#pragma unroll
    for (int j = 0; j < 64; j++) d[j] = 0.f;
    mbar_wait(xbar, i & 1);
    if (i + 1 == n) mbar_wait(holdbar, 1);
    CSTAMP(1);
    conv_step<7, -1>(d, a, ab, db); conv_step<6, -1>(d, a, ab, db); conv_step<5, -1>(d, a, ab, db); conv_step<4, 3>(d, a, ab, db);
    conv_step<3, 2>(d, a, ab, db);
    conv_step<2, 1>(d, a, ab, db);
    conv_step<1, 0>(d, a, ab, db);
    conv_step<0, -1>(d, a, ab, db);
    acc_fence<64>(d);
    CSTAMP(2);
    bar_sync(nbar + 8, 160);
    float E[16][2];
#pragma unroll
    for (int j = 0; j < 15; j++) { E[j][0] = d[4 * j] + d[4 * j + 6]; E[j][1] = d[4 * j + 1] + d[4 * j + 7]; }
    E[15][0] = d[60]; E[15][1] = d[61];
    if (w0 == 0) {
#pragma unroll
      for (int j = 8; j < 16; j++) sts64f(scA + (j - 8) * 256 + lane * 8, E[j][0], E[j][1]);
    } else {
      const uint32_t a = scB - dl * 256 + (lane ^ 2) * 8;
#pragma unroll
      for (int j = 1; j < 8; j++) sts64f(a + j * 256, E[j][0], E[j][1]);
      sts64f(scB + (dl ? 7 * 256 : 0) + (lane ^ 2) * 8, dl ? E[8][0] : E[0][0], dl ? E[8][1] : E[0][1]);
    }
    bar_sync(nbar, 128);
    CSTAMP(3);
    uint32_t pk[8];
    if (w0 == 0) {
#pragma unroll
      for (int j = 0; j < 8; j++) { const float2 v = lds64f(scB + j * 256 + lane * 8); pk[j] = pack2(E[j][0] + v.x, E[j][1] + v.y); }
    } else {
      const uint32_t a0 = scA - dl * 256 + (lane ^ 2) * 8;
#pragma unroll
      for (int j = 9; j < 16; j++) { const float2 v = lds64f(a0 + (j - 8) * 256); pk[j - 8] = pack2(E[j][0] + v.x, E[j][1] + v.y); }
      const float2 v = lds64f(scA + (dl ? 7 * 256 : 0) + (lane ^ 2) * 8);
      pk[0] = pack2((dl ? 0.f : E[8][0]) + v.x, (dl ? 0.f : E[8][1]) + v.y);
    }
    CSTAMP(4);
    if (i + 1 == n) {
#pragma unroll
      for (int j = 0; j < 8; j++) pk[j] = ~pk[j];
    }
    const int c1 = (w0 ? 35 : 95) - lane, c0 = (w0 && lane < 4) ? c1 - 32 : c1 + 32;
    stsm4t(yb0 + 128 * (c0 & 31) + (((2 * (c0 >> 5) + w1) ^ (c0 & 7)) << 4), pk[0], pk[1], pk[2], pk[3]);
    stsm4t(yb0 + 128 * (c1 & 31) + (((2 * (c1 >> 5) + w1) ^ (c1 & 7)) << 4), pk[4], pk[5], pk[6], pk[7]);
    fence_async_smem();
    bar_sync(nbar + 8, 160);
    CSTAMP(5);
    STAMPW(st0 + i);
    if (n == 2 && i == 0) {
      const int u = (tid >> 3) % 5, kg = rb * 3 + (tid < 120 ? (tid >> 3) / 5 : 0), c = u < 4 ? (u >> 1) * 10 + (u & 1) * 4 : 8, o2 = u < 4 ? 2 : 10;
      const uint4* wp = (const uint4*)p.wout + (uint32_t)((kg * 8 + (tid & 7)) * (kD / 8) + (seg_col(cb, 0) >> 3) + (u < 4 ? (u >> 1) * 8 + (u & 1) * 24 : 16));
      const uint4 w0 = ldg4(wp), w1 = ldg4(wp + 1), w2 = ldg4(wp + 2), w3 = ldg4(wp + 3);
      uint8_t* dst = p.scr->wo + (uint32_t)(cb * (12 * 20480) + kg * 2560 + c * 128 + (tid & 7) * 16);
      const bool f = u < 4, on = tid < 120;
      stg4_if(dst, w0.x, f ? w1.x : w0.z, f ? w2.x : w1.x, f ? w3.x : w1.z, on);
      stg4_if(dst + 128, w0.y, f ? w1.y : w0.w, f ? w2.y : w1.y, f ? w3.y : w1.w, on);
      stg4_if(dst + o2 * 128, f ? w0.z : w2.x, f ? w1.z : w2.z, f ? w2.z : w3.x, w3.z, on);
      stg4_if(dst + o2 * 128 + 128, f ? w0.w : w2.y, f ? w1.w : w2.w, f ? w2.w : w3.y, w3.w, on);
      bar_arrive(NB_WO, 160);
    }
  }
}

struct KvRegs { uint32_t k[11], v[8]; uint4 sh; };
__device__ __forceinline__ void kv_load(KvRegs& q, const __nv_bfloat16* kp, const __nv_bfloat16* vp, const __nv_bfloat16* sp, bool halo) {
#pragma unroll
  for (int i = 0; i < 11; i++) q.k[i] = (i >= 3 || halo) ? ldg1(kp + i * kD) : 0u;
#pragma unroll
  for (int i = 0; i < 8; i++) q.v[i] = ldg1(vp + i * kD);
  q.sh = ldg4(sp);
}
__device__ __forceinline__ void kv_unit(const KvRegs& q, uint32_t oa) {
  const uint32_t w0 = prmt(q.sh.x, q.sh.z, 0x5410), w1 = prmt(q.sh.x, q.sh.z, 0x7632), w2 = prmt(q.sh.y, q.sh.w, 0x5410), w3 = prmt(q.sh.y, q.sh.w, 0x7632);
  uint32_t r[8];
#pragma unroll
  for (int i = 0; i < 8; i++) r[i] = hmul2(hfma2(q.k[i + 3], w0, hfma2(q.k[i + 2], w1, hfma2(q.k[i + 1], w2, hmul2(q.k[i], w3)))), q.v[i]);
  sts128(oa, prmt(r[7], r[6], 0x5410), prmt(r[5], r[4], 0x5410), prmt(r[3], r[2], 0x5410), prmt(r[1], r[0], 0x5410));
  sts128(oa + 2048, prmt(r[7], r[6], 0x7632), prmt(r[5], r[4], 0x7632), prmt(r[3], r[2], 0x7632), prmt(r[1], r[0], 0x7632));
}

__device__ __forceinline__ void helper_cta(const Params& p, uint32_t sb, int cb, int warp, int lane) {
  constexpr int NS = 9, ONES = NS * B_SLOT, BF = ONES + 256, BE = BF + 8 * NS;
  if (warp < NS && elect_one()) {
    mbar_init(sb + BF + 8 * warp, 1); mbar_init(sb + BE + 8 * warp, 1);
    fence_async_smem();
    if (warp == 0) { mbar_expect(sb + BF, B_SLOT); tma3d(sb, &p.tmW, 0, 0, 12 + cb * 3, sb + BF); }
  }
  if (warp == 15) { sts32(sb + ONES + lane * 4, 0x3f803f80u); sts32(sb + ONES + 128 + lane * 4, 0x3f803f80u); fence_async_smem(); }
  __syncthreads();
  if (warp == 4) {
    int s = 1, ph = 1;
    uint32_t tp = clock() + HP0;
#pragma unroll 1
    for (int it = 1; it < 20; it++) {
      if (HPD && it >= 10) pace(tp, HPD);
      mbar_wait(sb + BE + 8 * s, ph);
      if (elect_one()) { mbar_expect(sb + BF + 8 * s, B_SLOT); tma3d(sb + s * B_SLOT, &p.tmW, 0, (it < 10 ? it : it - 10) * 64, (it < 10 ? 12 : 0) + cb * 3, sb + BF + 8 * s); }
      if (++s == NS) { s = 0; ph ^= 1; }
    }
  } else if (warp < 4) {
    const uint32_t tag = load_epoch(p, 128 + cb, lane) + 1;
    const uint64_t db = mkdesc(sb + ONES, 128, 128, 0);
    uint2* dst = p.scr->colsum + cb * 192 + warp * 16 + (lane >> 2);
    if ((lane & 3) == 0) {
#pragma unroll 1
      for (int j = 0; j < 12; j++) st_ll2(dst + (j < 6 ? 768 : 0) + ((j % 6) >> 1) * 64 + (j & 1) * 8, 0, 0);
    }
    int s = 0, ph = 0;
#pragma unroll 1
    for (int part = 0; part < 2; part++) {
      float d[12];
#pragma unroll
      for (int i = 0; i < 12; i++) d[i] = 0.f;
#pragma unroll 1
      for (int it = 0; it < 10; it++) {
        mbar_wait(sb + BF + 8 * s, ph);
        const uint64_t da = mkdesc(sb + s * B_SLOT, 8192, 1024, 1);
        WG_FENCE();
#pragma unroll
        for (int j = 0; j < 12; j++) wgmma_colsum(d + 4 * (j % 3), da + (j % 3) * 512 + (j / 3) * 128, db);
        WG_COMMIT();
        WG_WAIT(1);
        mbar_arrive_if(sb + BE + 8 * (s == 0 ? NS - 1 : s - 1), threadIdx.x == 0 && (it | part) != 0);
        if (++s == NS) { s = 0; ph ^= 1; }
      }
      WG_WAIT(0);
      acc_fence<12>(d);
      if ((lane & 3) == 0) {
#pragma unroll
        for (int j = 0; j < 6; j++) st_ll2(dst + (part ? 0 : 768) + (j >> 1) * 64 + (j & 1) * 8, __float_as_uint(d[2 * j]), tag);
      }
      STAMPW(1 + part);
    }
    if (threadIdx.x == 0) *(volatile uint32_t*)&p.scr->epoch[128 + cb] = tag;
  }
}

__global__ void __launch_bounds__(512, 1) fused_kernel(const __grid_constant__ Params p) {
  extern __shared__ __align__(1024) uint8_t smem[];
  const int warp = __shfl_sync(0xffffffff, (int)(threadIdx.x >> 5), 0);
  const int lane = threadIdx.x & 31, tid = threadIdx.x & 127;
  const uint32_t sb = __shfl_sync(0xffffffff, (uint32_t)__cvta_generic_to_shared(smem), 0);
  const uint32_t tstart = clock();
  if (elect_one()) {
    if (warp < 5) asm volatile("prefetch.tensormap [%0];" ::"l"(&p.tmX + warp) : "memory");
    mbar_init(sb + OFF_BAR + 8 * warp, 1); mbar_init(sb + OFF_BAR + 128 + 8 * warp, 1); mbar_init(sb + OFF_BAR + 256 + 8 * warp, 2);
    asm volatile("fence.mbarrier_init.release.cluster;" ::: "memory");
  }
  int b = blockIdx.x;
  if (p.by_smid) asm volatile("mov.u32 %0, %%smid;" : "=r"(b));
  b = __shfl_sync(0xffffffff, b, 0);
  const int tp = b >> 1, t7 = (tp - 32) / 7;
  const int lin = tp < 32 ? ((tp & 7) ? (tp & 7) * 16 : 8) + (tp >> 3) * 2 + (b & 1)
                          : (tp < 60 ? (tp - 31 - t7 * 7) * 16 + 8 + t7 * 2 + (b & 1) : (tp < 62 ? -1 : b - 124));
  const int hcb = b & 3;
  if (lin < 0) { helper_cta(p, sb, hcb, warp, lane); return; }
  const int cb = ((lin >> 4) & 1) * 2 + ((lin >> 1) & 1), rb = (lin >> 5) * 8 + ((lin >> 2) & 3) * 2 + (lin & 1);
  const int zs0 = 4 - (cb & 2);
  const int chb = (cb >> 1) * 320 + rb * 2 + (cb & 1);
  if (warp == 0 && elect_one()) {
    mbar_expect(sb + BAR_AF, A_SLOT);
    tma_rows(sb + OFF_A, &p.tmX, 0, rb, sb + BAR_AF);
    mbar_expect(sb + BAR_BF, B_SLOT);
    tma3d(sb + OFF_B, &p.tmW, 0, 0, 12 + cb * 3, sb + BAR_BF);
  }
  if (warp == 1) STAMP(31);
  if (sb & 1023) die();
  __syncthreads();

  if (warp >= 12) {
    asm volatile("setmaxnreg.dec.sync.aligned.u32 32;");
    const uint32_t epoch = load_epoch(p, lin, lane);
    if (warp == 12) {
#pragma unroll 1
      for (int i = 1; i < NA; i++) {
        if (elect_one()) {
          mbar_expect(sb + BAR_AF + 8 * i, A_SLOT);
          tma_rows(sb + OFF_A + i * A_SLOT, &p.tmX, i * 64, rb, sb + BAR_AF + 8 * i);
          if (i < NB) { mbar_expect(sb + BAR_BF + 8 * i, B_SLOT); tma3d(sb + OFF_B + i * B_SLOT, &p.tmW, 0, i * 64, 12 + cb * 3, sb + BAR_BF + 8 * i); }
        }
      }
      STAMP(32);
      uint32_t kvt;
      {
        const int tb = rb * 2 + (cb & 1);
        kvt = __shfl_sync(0xffffffff, (ld_relaxed(p.scr->cnt + CNT_KV + (cb >> 1)) & ~63u) + 64, 0);
        {
          uint32_t tp = tstart;
          pace(tp, KV_T0);
          mbar_arrive_if(sb + BAR_KV + 8, lane == 0);
        }
        if (ST_YIELD) mbar_wait2(sb + BAR_XS, 0, sb + BAR_ST, 0);
#pragma unroll 1
        for (int u = 0; u < 5; u++) {
          mbar_wait(sb + BAR_KU + 8 * u, 0);
          fence_async_smem();
          if (elect_one()) {
            asm volatile("cp.async.bulk.tensor.3d.global.shared::cta.bulk_group [%0, {%2, %3, %4}], [%1];\ncp.async.bulk.commit_group;" ::"l"(&p.tmKV),
                         "r"(sb + OFF_CV + CV_SZ + (u < 3 ? u : u - 3) * 4096), "r"((63 - tb) * 16), "r"((cb >> 1) * 160 + u * 32), "r"(0) : "memory");
            if (u == 1 || u == 4) asm volatile("cp.async.bulk.wait_group 0;" ::: "memory");
            if (u == 1) { mbar_arrive(sb + BAR_KU); red_release(p.scr->cnt + CNT_KV + (cb >> 1)); }
          }
          __syncwarp();
          if (u == 1) {
            STAMP(35);
            if (PFT) { const char* q = (const char*)p.ssmk + chb * 4096 + lane * 128; prefetch_l2(q); prefetch_l2(q + 64 * 4096); }
          }
        }
        zero_pads(sb + OFF_CV + CV_SZ, lane);
        if (elect_one()) { mbar_arrive(sb + BAR_KU + 8); red_release(p.scr->cnt + CNT_KV + 2 + (cb >> 1)); }
        STAMP(30);
        if (lane < 24) {
          const char* r = (const char*)p.wout + (rb * 24 + lane) * (kD * 2) + (cb >> 1) * 640 + (cb & 1) * 384;
          prefetch_l2(r); prefetch_l2(r + 128); prefetch_l2(r + 256 - (cb & 1) * 384);
        }
      }
      poll_counter(p.scr->cnt + CNT_KV + 2 + (cb >> 1), kvt);
      if (elect_one()) mbar_arrive(sb + BAR_KV);
      STAMP(34);
      {
        const char* q = (const char*)p.wsp + (cb * 512 + rb * 16 + (lane >> 1)) * (kS * 2) + (lane & 1) * 128;
        uint32_t tp = clock();
#pragma unroll 1
        for (int i = LEAD / 2; i < WSP_N; i++) {
          prefetch_l2(q + i * 256);
          if (i == Z1_AT) {
            poll_counter(p.scr->cnt + CNT_Z1, (epoch + 1) * 128);
            if (elect_one()) mbar_arrive(sb + BAR_ZP);
            STAMP(24);
          }
          pace(tp, WSP_D);
        }
      }
      const uint32_t tag = epoch + 1;
      mbar_wait(sb + BAR_G2, 0);
      if (elect_one()) {
        bulk_s2g(p.scr->h + (size_t)(rb * 12 + cb * 3) * A_SLOT, sb + OFF_A + 5 * A_SLOT, 3 * A_SLOT);
        asm volatile("cp.async.bulk.commit_group;\ncp.async.bulk.wait_group 0;" ::: "memory");
        red_release(&p.scr->hcnt[(rb >> HGRP) * 32]);
      }
      __syncwarp();
      STAMP(20);
      mbar_wait(sb + BAR_AE + 56, 0);
      STAMP(39);
      poll_counter(&p.scr->hcnt[(rb >> HGRP) * 32], tag * (4 << HGRP));
      STAMP(37);
      if (elect_one()) {
        uint32_t tp = clock();
#pragma unroll 1
        for (int it = 3; it < 12; it++) {
          if (HPACE && it > 3) { tp += HPACE; while ((int32_t)((uint32_t)clock() - tp) < 0) {} }
          bulk_g2s(sb + OFF_A + ((it + 5) % 9) * A_SLOT, p.scr->h + (size_t)(rb * 12 + g3_block(cb, it)) * A_SLOT, A_SLOT, sb + BAR_AF + 8 * ((it + 5) % 9));
        }
      }
      STAMP(21);
    } else if (warp == 13) {
      const uint32_t ztarget = __shfl_sync(0xffffffff, ld_relaxed(p.scr->cnt + CNT_Z), 0);
      int s = 0, ph = 0;
#pragma unroll 1
      for (int it = NB; it < 20; it++) {
        mbar_wait(sb + BAR_BE + 8 * s, ph);
        if (elect_one()) { mbar_expect(sb + BAR_BF + 8 * s, B_SLOT); tma3d(sb + OFF_B + s * B_SLOT, &p.tmW, 0, (it < 10 ? it : (it + zs0) % 10) * 64, (it < 10 ? 12 : 0) + cb * 3, sb + BAR_BF + 8 * s); }
        STAMP2(32 + it);
        if (++s == NB) { s = 0; ph ^= 1; }
      }
      mbar_wait(sb + BAR_XC, 0);
#pragma unroll 1
      for (int i = 0; i < LEAD; i++) {
        mbar_wait(sb + BAR_AE + 8 * i, 0);
        if (elect_one()) { mbar_expect(sb + BAR_AF + 8 * i, A_SLOT); tma_rows(sb + OFF_A + i * A_SLOT, &p.tmWsp, i * 64, rb, sb + BAR_AF + 8 * i); }
      }
      mbar_wait(sb + BAR_ZP, 0);
      poll_counter(p.scr->cnt + CNT_Z, (ztarget & ~127u) + 128);
      STAMP(22);
      int sa = LEAD, pa = 0, ia = LEAD;
#pragma unroll 1
      for (int it = 0; it < 32; it++) {
        if (it == 16) { mbar_wait(sb + BAR_ZP, 1); acquire_fence(); }
        mbar_wait2(sb + BAR_BE + 8 * s, ph, sb + BAR_AE + 8 * sa, pa);
        if (elect_one()) {
          mbar_expect(sb + BAR_BF + 8 * s, B_SLOT);
          bulk_g2s(sb + OFF_B + s * B_SLOT, p.scr->z2 + (size_t)(cb * 32 + it) * B_SLOT, B_SLOT, sb + BAR_BF + 8 * s);
        }
#pragma unroll 1
        for (int j = (it < RAMP ? 0 : (it == 4 ? 1 + RAMP : 1)); j > 0 && ia < 32; j--, ia++) {
          if (it == 4) mbar_wait(sb + BAR_AE + 8 * sa, pa);
          if (elect_one()) { mbar_expect(sb + BAR_AF + 8 * sa, A_SLOT); tma_rows(sb + OFF_A + sa * A_SLOT, &p.tmWsp, ia * 64, rb, sb + BAR_AF + 8 * sa); }
          if (++sa == NA2) { sa = 0; pa ^= 1; }
        }
        STAMP2(52 + it);
        if (++s == NB) { s = 0; ph ^= 1; }
      }
      mbar_wait(sb + BAR_WO, 0);
      acquire_fence();
#pragma unroll 1
      for (int it = 0; it < 12; it++) {
        if (it < 6) mbar_wait(sb + BAR_BE + 8 * ((0x110443 >> (4 * it)) & 7), it < 3 ? 1 : 0);
        else mbar_wait(sb + BAR_BE + 8 * s, ph);
        if (elect_one()) {
          mbar_expect(sb + BAR_BF + 8 * s, 20480);
          bulk_g2s(sb + OFF_B + (s == 5 ? 0 : s + 1) * 20480, p.scr->wo + (size_t)(cb * 12 + g3_block(cb, it)) * 20480, 20480, sb + BAR_BF + 8 * s);
        }
        STAMP2(84 + it);
        if (++s == 6) { s = 0; ph ^= 1; }
      }
    } else if (warp == 14) {
      const uint32_t tag = epoch + 1;
      uint32_t t0 = 0;
      mbar_wait(sb + BAR_AF + 8 * (NA - 1), 0);
#pragma unroll 1
      for (int part = 0; part < 2; part++) {
        uint4 v[3];
#pragma unroll 1
        while (true) {
          bool ok = true;
#pragma unroll
          for (int i = 0; i < 3; i++) {
            v[i] = ld_ll4(&p.scr->colsum[(part ? 0 : 768) + cb * 192 + i * 64 + lane * 2]);
            ok = ok && v[i].y == tag && v[i].w == tag;
          }
          if (__all_sync(0xffffffff, ok)) break;
          spin_guard(t0);
        }
#pragma unroll
        for (int i = 0; i < 3; i++) {
          const uint32_t hi = pack2(__uint_as_float(v[i].x), __uint_as_float(v[i].z)), ca = sb + OFF_CS + (1 - part) * 768 + i * 256 + (lane >> 2) * 32 + (lane & 3) * 4;
          sts32(ca, hi);
          sts32(ca + 16, pack2(__uint_as_float(v[i].x) - bf_lo(hi), __uint_as_float(v[i].z) - bf_hi(hi)));
        }
        if (!CFENCE) fence_async_smem();
        __syncwarp();
        if (lane == 0) mbar_arrive(sb + BAR_ST + 8 * part);
        if (part == 0) STAMP(27);
      }
      STAMP(38);
      uint8_t* dst = p.scr->z2 + (size_t)(cb * 32 + (rb >> 2)) * B_SLOT + (rb & 3) * 6144;
#pragma unroll 1
      for (int q = 0; q < 4; q += 2) {
        if (q) bar_sync(NB_Z2, 96);
        else bar_sync(NB_Z, ZORD ? 160 : 96);
        if (elect_one()) {
          bulk_s2g(dst + q * 8 * B_SLOT, sb + OFF_A + zs0 * A_SLOT + q * 6144, 6144);
          bulk_s2g(dst + (q + 1) * 8 * B_SLOT, sb + OFF_A + zs0 * A_SLOT + (q + 1) * 6144, 6144);
          asm volatile("cp.async.bulk.commit_group;\ncp.async.bulk.wait_group 0;" ::: "memory");
          if (q) mbar_arrive(sb + BAR_ZP);
          red_release(p.scr->cnt + (q ? CNT_Z1 : CNT_Z));
        }
      }
      STAMP(28);
      mbar_wait(sb + BAR_AE + 72, 0);
      conv_service(p, sb, 0, chb + 64, true);
      bar_sync(NB_WO, 160);
      bar_sync(NB_CD, 64);
      if (elect_one()) { red_release(p.scr->cnt + CNT_WO + cb); red_relaxed(p.scr->cnt + CNT_Y + (cb >> 1)); }
      STAMP(49);
      poll_counter(p.scr->cnt + CNT_WO + cb, tag * 32);
      if (elect_one()) mbar_arrive(sb + BAR_WO);
      STAMP(46);
      held_service(p, sb, 0, chb + 192, rb, cb, tag, lane);
    } else {
      const uint32_t tag = epoch + 1;
      sts32(sb + OFF_BIAS + lane * 4, ldg1(p.bsp + (lane >> 3) * 512 + rb * 16 + (lane & 7) * 2));
      if (lane < 2) sts32(sb + OFF_TAG + lane * 4, lane ? 0 : tag);
      fence_async_smem();
      uint32_t t0 = 0;
      mbar_wait(sb + BAR_AF + 8 * (NA - 1), 0);
#pragma unroll 1
      while (true) {
        const uint4 u = ld_ll4(&p.scr->xstat[rb * 64 + lane]), v = ld_ll4(&p.scr->xstat[rb * 64 + 32 + lane]);
        sts64f(sb + OFF_XS + lane * 8, __uint_as_float(u.x), __uint_as_float(u.z));
        sts64f(sb + OFF_XS + 256 + lane * 8, __uint_as_float(v.x), __uint_as_float(v.z));
        if (__all_sync(0xffffffff, u.y == tag && u.w == tag && v.y == tag && v.w == tag)) break;
        spin_guard(t0);
      }
      STAMP(26);
      __syncwarp();
      if (lane == 0) mbar_arrive(sb + BAR_XS);
      mbar_wait(sb + (K0_POLL ? BAR_KU + 16 : BAR_KU), K0_POLL ? 0 : 1);
      poll_counter(p.scr->cnt + CNT_KV + (cb >> 1), tag * 64);
      if (elect_one()) load_convx(p, sb + OFF_CV, sb + BAR_XF + 8, chb);
      mbar_wait(sb + BAR_KU + 8, 1);
      if (elect_one()) load_convx(p, sb + OFF_CV + CV_SZ, sb + BAR_XF, chb + 64);
      STAMP(48);
      mbar_wait(sb + BAR_AE + 72, 0);
#pragma unroll 1
      for (int i = 0; i < 2; i++) conv_service(p, sb, 1, chb + i * 128, i == 0);
      bar_arrive(NB_CD, 64);
      mbar_wait(sb + BAR_WO, 0);
      poll_counter(p.scr->cnt + CNT_Y + (cb >> 1), tag * 64);
      STAMP(47);
      if (elect_one()) mbar_arrive(sb + BAR_YT);
      held_service(p, sb, 1, chb + 256, rb, cb, tag, lane);
      if (lane == 0) *(volatile uint32_t*)&p.scr->epoch[lin] = tag;
      STAMP(23);
    }
  } else {
    if (warp == 7) STAMP(36);
    const int wg = warp >> 2, w = warp & 3, g = lane >> 2, t = lane & 3;
    Taps k;
    uint32_t xw[2][10];
    if (wg == 2) {
      asm volatile("setmaxnreg.inc.sync.aligned.u32 160;");
      const int tb = rb * 2 + (cb & 1), c0 = (cb >> 1) * 320;
      const uint32_t cv = sb + OFF_CV + CV_SZ;
      if (w == 0) zero_pads(sb + OFF_CV, lane);
      mbar_wait(sb + BAR_KV + 8, 0);
      const int t0 = tb * 32 + w * 8;
      const __nv_bfloat16* kp = p.k + (size_t)(t0 - 3) * kD + c0 + lane * 2;
      const __nv_bfloat16* vp = p.v + (size_t)t0 * kD + c0 + lane * 2;
      const __nv_bfloat16* sp = p.shift + (c0 + lane * 2) * 4;
      const uint32_t oa = cv + ((3 - w) & 1) * 1024 + lane * 32 + ((((3 - w) >> 1) ^ (lane >> 2)) & 1) * 16;
#pragma unroll 1
      for (int r = 0; r < 2; r++) {
        KvRegs n0, n1, n2;
        kv_load(n0, kp + r * 128, vp + r * 128, sp + r * 512, t0 > 0);
        kv_load(n1, kp + r * 128 + 64, vp + r * 128 + 64, sp + r * 512 + 256, t0 > 0);
        if (r) kv_load(n2, kp + 256, vp + 256, sp + 1024, t0 > 0);
        kv_unit(n0, oa + r * 8192);
        bar_sync(NB_WGC, 128);
        mbar_arrive_if(sb + BAR_KU + 16 * r, tid == 0);
        if (r) mbar_wait(sb + BAR_KU, 1);
        kv_unit(n1, oa + (r ? 0 : 4096));
        bar_sync(NB_WGC, 128);
        mbar_arrive_if(sb + BAR_KU + 16 * r + 8, tid == 0);
        if (r) {
          kv_unit(n2, oa + 4096);
          bar_sync(NB_WGC, 128);
          mbar_arrive_if(sb + BAR_KU + 32, tid == 0);
        } else {
          mbar_wait(sb + BAR_AF + 8 * ((cb >> 1) * 5 + 1), 0);
          mbar_wait2(sb + BAR_AF + 8 * ((cb >> 1) * 5 + 2), 0, sb + BAR_AF + 8 * ((cb >> 1) * 5 + 4), 0);
          final_load_x(xw, sb + OFF_A, cb, 1, w, lane);
          fence_async_smem();
          bar_sync(NB_WGC, 128);
          mbar_arrive_if(sb + BAR_XC, tid == 0);
        }
      }
      STAMPW(13);
      load_taps(k, p, chb, tid);
    } else {
      float d[96];
      if (wg == 0) st_ll2(&p.scr->zstat[(rb * 256 + cb * 64 + w * 16 + g + (t >> 1) * 8) * 2 + (t & 1)], 0, 0);
      else if ((tid & 7) == 0) st_ll4(&p.scr->xstat[rb * 64 + cb * 16 + (tid >> 3)], 0, 0, 0, 0);
      {
        #pragma unroll
        for (int i = 0; i < 96; i++) d[i] = 0.f;
        {
          if (__builtin_expect(wg == 1, 0)) {
            const int tid = tid_now();
            const uint32_t epoch = load_epoch(p, lin, lane);
            float s = 0.f, q = 0.f;
#pragma unroll 1
            for (int i = 0; i < 10; i++) {
              mbar_wait(sb + BAR_AF + 8 * i, 0);
              const uint4 x4 = lds128(sb + OFF_A + i * A_SLOT + cb * 2048 + tid * 16);
              const uint32_t u[4] = {x4.x, x4.y, x4.z, x4.w};
#pragma unroll
              for (int e = 0; e < 4; e++) { const float a = bf_lo(u[e]), c = bf_hi(u[e]); s += a + c; q = fmaf(a, a, q); q = fmaf(c, c, q); }
            }
#pragma unroll
            for (int o = 1; o <= 4; o <<= 1) { s += __shfl_xor_sync(0xffffffff, s, o); q += __shfl_xor_sync(0xffffffff, q, o); }
            const float m = s * (1.f / kD);
            const float r = rsqrtf(fmaxf(fmaf(-m, m, q * (1.f / kD)), 0.f) + 1e-5f);
            if ((tid & 7) == 0) st_ll4(&p.scr->xstat[rb * 64 + cb * 16 + (tid >> 3)], __float_as_uint(m), epoch + 1, __float_as_uint(r), epoch + 1);
            STAMPW(12);
            bar_sync(NB_G1, 256);
          }
          gemm_loop<192, true, 0, D1>(d, sb, 10, wg ? zs0 : 0, 0, 0, 0, wg, 2, tid_now(), [&]() { if (G1_AT == 0 && wg == 0) bar_arrive(NB_G1, 256); }, [](int) {});
          asm volatile("setmaxnreg.inc.sync.aligned.u32 160;");
          STAMPW(wg ? 14 : 1);
          if (wg == 0) ZS(0);
          mbar_wait2(sb + BAR_XS, 0, sb + BAR_ST + 8 * wg, 0);
          if (wg == 0) ZS(1);
        }
        const int t1 = tid_now();
        const uint32_t xa1 = sb + OFF_XS + (w * 16 + ((t1 & 31) >> 2)) * 8;
        const float2 s0 = lds64f(xa1), s1 = lds64f(xa1 + 64);
        uint32_t z[48];
        float st[4];
        if (CFENCE) fence_async_smem();
        fold_mean(d, sb + OFF_CS + (1 - wg) * 768, s0.x, s1.x, t1 & 3);
        if (G1_AT == 1 && wg == 0) bar_arrive(NB_G1, 256);
        WG_WAIT(0);
        acc_fence<96>(d);
        if (wg == 0) ZS(2);
        gelu_tile(d, z, st, s0.y, s1.y);
        const int tid = tid_now(), lane = tid & 31, g = lane >> 2, t = lane & 3;
        if (wg == 1) {
          uint32_t bra, brb;
          asm volatile("ld.shared.u16 %0, [%1];" : "=r"(bra) : "r"(sb + OFF_BIAS + (w * 16 + g) * 2));
          asm volatile("ld.shared.u16 %0, [%1+16];" : "=r"(brb) : "r"(sb + OFF_BIAS + (w * 16 + g) * 2));
#pragma unroll
          for (int j = 0; j < 96; j++) d[j] = bf_lo((j & 2) ? brb : bra);
          STAMPW(15);
          gemm_loop<192, true, 1, D2>(d, sb, 32, 0, 1, 20, 0, 2, 2, tid, [&]() { if (HOLD_AT < 32) mbar_arrive_if(sb + BAR_GO, tid == 0); }, [](int) {});
          if (HOLD_AT == 32) mbar_arrive_if(sb + BAR_GO, tid == 0);
          STAMPW(16);
          const int t2 = tid_now(), l2 = t2 & 31;
          const uint32_t ha = sb + OFF_A + 5 * A_SLOT + (l2 >> 4) * 1024 + (2 * w + ((l2 >> 3) & 1)) * 128 + (l2 & 7) * 16;
#pragma unroll
          for (int j = 0; j < 24; j += 2) {
#pragma unroll
            for (int e = 0; e < 4; e++) z[2 * j + e] = hmul2(z[2 * j + e], pack2(d[4 * j + 2 * e], d[4 * j + 2 * e + 1]));
            stsm4(ha + j * 1024, z[2 * j], z[2 * j + 1], z[2 * j + 2], z[2 * j + 3]);
          }
          fence_async_smem();
          bar_sync(NB_WGB, 128);
          mbar_arrive_if(sb + BAR_AF + 8 * (t2 == 3 ? (BAR_G2 - BAR_AF) / 8 : (t2 == 4 ? (BAR_GO - BAR_AF) / 8 : 5 + t2)), t2 < (HOLD_AT == 33 ? 5 : 4));
          STAMPW(17);
          {
            float e[80];
#pragma unroll
            for (int j = 0; j < 80; j++) e[j] = 0.f;
            gemm_loop<160, false, 2, DB>(e, sb, 12, 5, 0, 2, 0, 2, 2, tid_now(), []() {}, [](int) {});
            STAMPW(10);
            const int t3 = tid_now();
#pragma unroll
            for (int j = 0; j < 10; j++) {
              sts128(sb + OFF_A + j * 2048 + t3 * 16, pack2(e[8 * j], e[8 * j + 1]), pack2(e[8 * j + 2], e[8 * j + 3]), pack2(e[8 * j + 4], e[8 * j + 5]),
                     pack2(e[8 * j + 6], e[8 * j + 7]));
              if (j == 4) bar_arrive(NB_WO, 256);
            }
            bar_arrive(NB_Z, 256);
            STAMPW(45);
          }
          return;
        }
        ZS(3);
        const bool hi = t & 2;
        float a0 = (hi ? st[2] : st[0]) + __shfl_xor_sync(0xffffffff, hi ? st[0] : st[2], 2);
        float a1 = (hi ? st[3] : st[1]) + __shfl_xor_sync(0xffffffff, hi ? st[1] : st[3], 2);
        a0 = ((t & 1) ? a1 : a0) + __shfl_xor_sync(0xffffffff, (t & 1) ? a0 : a1, 1);
        const uint32_t tag = lds32<0>(sb + OFF_TAG);
        uint2* zs = p.scr->zstat + (rb * 256 + w * 16 + g + (t >> 1) * 8) * 2 + (t & 1);
        st_ll2(zs + cb * 128, __float_as_uint(a0), tag);
        STAMPW(2); ZS(4);
        uint2 u[4];
#pragma unroll
        for (int i = 0; i < 4; i++) u[i] = ld_ll2(zs + i * 128);
        const uint32_t keep = (cb & 2) ? 13 << 5 : 13;
        mbar_arrive_if(sb + BAR_AE + 8 * tid, tid < NA && !((keep >> tid) & 1));
        const uint32_t za = sb + OFF_A + zs0 * A_SLOT + (2 * w + ((lane >> 3) & 1)) * 3072 + (lane >> 4) * 128 + (lane & 7) * 16;
        const float ca = 0.5f * (hi ? s1.y : s0.y), inv = 1.f / 768.f;
        mbar_wait2(sb + BAR_AE + 8 * (zs0 + 2), 0, sb + BAR_XC, 0);
        ZS(6);
        uint32_t t0 = 0;
#pragma unroll 1
        while (!__all_sync(0xffffffff, u[0].y == tag && u[1].y == tag && u[2].y == tag && u[3].y == tag)) {
          spin_guard(t0);
#pragma unroll
          for (int i = 0; i < 4; i++) u[i] = ld_ll2(zs + i * 128);
        }
        STAMPW(3); ZS(7);
        a0 = ((__uint_as_float(u[0].x) + __uint_as_float(u[1].x)) + (__uint_as_float(u[2].x) + __uint_as_float(u[3].x))) * inv;
        a1 = __shfl_xor_sync(0xffffffff, a0, 1);
        const float m = (t & 1) ? a1 : a0, q = (t & 1) ? a0 : a1;
        const float r = bf_lo(pack2(ca * rsqrtf(fmaf(fmaxf(fmaf(-m, m, q), 0.f), ca * ca, 1e-5f)), 0.f));
        const uint32_t rn = pack2(r, -m * r), ro = __shfl_xor_sync(0xffffffff, rn, 2);
        const uint32_t ra2 = prmt(hi ? ro : rn, 0, 0x1010), n2a = prmt(hi ? ro : rn, 0, 0x3232), rb2 = prmt(hi ? rn : ro, 0, 0x1010), n2b = prmt(hi ? rn : ro, 0, 0x3232);
        if (ZORD && w >= 2) bar_sync(NB_Z, 160);
#pragma unroll
        for (int j = 0; j < 24; j += 2)
          stsm4(za + j * 128, hfma2(z[2 * j], ra2, n2a), hfma2(z[2 * j + 1], rb2, n2b), hfma2(z[2 * j + 2], ra2, n2a), hfma2(z[2 * j + 3], rb2, n2b));
        ZS(8);
        fence_async_smem();
        ZS(9);
        if (w < 2) bar_arrive(NB_Z, ZORD ? 160 : 96);
        else bar_arrive(NB_Z2, 96);
        final_load_x(xw, sb + OFF_A, cb, 0, w, lane);
        fence_async_smem();
        bar_sync(NB_WGA, 128);
        mbar_arrive_if(sb + BAR_AE + 8 * tid, tid < NA && ((keep >> tid) & 1));
      }
      {
        const uint32_t zero = lds32<0>(sb + OFF_TAG + 4);
#pragma unroll
        for (int i = 0; i < 20; i++) xw[i / 10][i % 10] |= zero;
      }
      load_taps(k, p, chb + 64, tid_now());
      STAMPW(4);
    }
    const int h = wg >> 1;
    {
    const int tid = tid_now(), lane = tid & 31;
    conv_worker(p, k, sb + OFF_CV + (1 - h) * CV_SZ, sb + OFF_A + 9 * A_SLOT + h * 4096, sb + BAR_XF + 8 * h, NB_WGA + h,
                chb + (h ? 0 : 64), 2 + h, sb + BAR_GO, w, lane, tid, h ? 40 : 5, rb, cb);
    {
      const int t3 = tid_now(), l3 = t3 & 31;
      const uint32_t xs_addr = sb + OFF_XS + (w * 16 + (l3 >> 2)) * 8;
      const float2 s0 = lds64f(xs_addr), s1 = lds64f(xs_addr + 64);
      const uint32_t ya = sb + y_tile(h) + ((l3 >> 4) * 8 + (l3 & 7)) * 128 + (((2 * w + ((l3 >> 3) & 1)) ^ (l3 & 7) ^ (rb & 7)) << 4);
      uint32_t sw[2][10];
      mbar_wait(sb + BAR_XF + 8 * h, h);
      final_s_early(sw, xw, ya, s0, s1);
      uint32_t ph = 1, t0 = 0, y[8];
#pragma unroll 1
      while (true) {
        mbar_wait(sb + BAR_YL + 16 * h, ph);
        if (bar_all(NB_WGA + h, 128, final_late(y, ya))) break;
        spin_guard(t0);
        ph ^= 1;
        if (t3 == 0) load_late_y(p, sb, h, rb, cb, lds32<0>(sb + OFF_TAG) & 1);
      }
#pragma unroll
      for (int e = 0; e < 8; e++) sw[e & 1][4 + (e >> 1)] = hmul2(sw[e & 1][4 + (e >> 1)], ~y[e]);
      __nv_bfloat16* o0 = p.out + (size_t)(w * 512 + rb * 16 + (l3 >> 2)) * kD + seg_col(cb, h);
      STAMPW(h ? 44 : 9);
      bar_sync(h ? NB_Z : NB_WO, 256);
      float d[40];
#pragma unroll
      for (int j = 0; j < 5; j++) {
        const uint4 v = lds128(sb + OFF_A + (h * 5 + j) * 2048 + t3 * 16);
        d[8 * j] = bf_lo(v.x); d[8 * j + 1] = bf_hi(v.x); d[8 * j + 2] = bf_lo(v.y); d[8 * j + 3] = bf_hi(v.y);
        d[8 * j + 4] = bf_lo(v.z); d[8 * j + 5] = bf_hi(v.z); d[8 * j + 6] = bf_lo(v.w); d[8 * j + 7] = bf_hi(v.w);
      }
      final_out(d, xw, sw, s0.y, s1.y, o0, h, l3 & 3);
    }
    }
  }
}

typedef CUresult (*EncodeFn)(CUtensorMap*, CUtensorMapDataType, cuuint32_t, void*, const cuuint64_t*, const cuuint64_t*, const cuuint32_t*,
                             const cuuint32_t*, CUtensorMapInterleave, CUtensorMapSwizzle, CUtensorMapL2promotion, CUtensorMapFloatOOBfill);

void encode(EncodeFn fn, CUtensorMap* m, const void* ptr, int rank, const cuuint64_t* dims, const cuuint64_t* strides, const cuuint32_t* box,
            CUtensorMapSwizzle swz = CU_TENSOR_MAP_SWIZZLE_128B) {
  const cuuint32_t es[3] = {1, 1, 1};
  fn(m, CU_TENSOR_MAP_DATA_TYPE_BFLOAT16, rank, const_cast<void*>(ptr), dims, strides, box, es, CU_TENSOR_MAP_INTERLEAVE_NONE,
     swz, CU_TENSOR_MAP_L2_PROMOTION_L2_128B, CU_TENSOR_MAP_FLOAT_OOB_FILL_NONE);
}

}

extern "C" void kernel_launch(void* const* d_in, const int* in_sizes, int n_in, void* d_out, int out_size) {
  (void)in_sizes; (void)n_in; (void)out_size;
  static EncodeFn enc = nullptr;
  static Scratch* scr = nullptr;
  static int sms = 0;
  if (!enc) {
    void* fn = nullptr;
    cudaDriverEntryPointQueryResult qr;
    cudaGetDriverEntryPoint("cuTensorMapEncodeTiled", &fn, cudaEnableDefault, &qr);
    enc = (EncodeFn)fn;
    cudaFuncSetAttribute(fused_kernel, cudaFuncAttributeMaxDynamicSharedMemorySize, SMEM_BYTES);
    cudaGetSymbolAddress((void**)&scr, g_scr);
    int dev = 0;
    cudaGetDevice(&dev);
    cudaDeviceGetAttribute(&sms, cudaDevAttrMultiProcessorCount, dev);
  }
  Params p;
  p.scr = scr;
  p.by_smid = sms == 132;
  p.k = (const __nv_bfloat16*)d_in[1];
  p.v = (const __nv_bfloat16*)d_in[2];
  p.shift = (const __nv_bfloat16*)d_in[3];
  p.ssmk = (const __nv_bfloat16*)d_in[4];
  p.ssmD = (const __nv_bfloat16*)d_in[5];
  p.wsp = (const __nv_bfloat16*)d_in[8];
  p.bsp = (const __nv_bfloat16*)d_in[9];
  p.wout = (const __nv_bfloat16*)d_in[10];
  p.out = (__nv_bfloat16*)d_out;
  for (int i = 0; i < 2; i++) {
    const cuuint64_t n = i ? kS : kD, dims[3] = {n, 512, 4}, st[2] = {n * 2, n * 1024};
    const cuuint32_t box[3] = {64, 16, 4};
    encode(enc, i ? &p.tmWsp : &p.tmX, d_in[i ? 8 : 0], 3, dims, st, box);
  }
  {
    const cuuint64_t dims[3] = {64, kD, kF / 64}, st[2] = {kF * 2, 128};
    const cuuint32_t box[3] = {64, 64, 3};
    encode(enc, &p.tmW, d_in[7], 3, dims, st, box);
  }
  {
    const cuuint64_t dims[2] = {kS, 896}, st[1] = {kS * 2};
    const cuuint32_t box[2] = {64, 16};
    encode(enc, &p.tmY, scr->y, 2, dims, st, box);
  }
  {
    const cuuint64_t dims[3] = {1024, kD / 2, 4}, st[2] = {8192, 2048};
    const cuuint32_t box[3] = {16, 32, 4};
    encode(enc, &p.tmKV, scr->kvx, 3, dims, st, box, CU_TENSOR_MAP_SWIZZLE_32B);
  }
  fused_kernel<<<132, 512, SMEM_BYTES, cudaStreamPerThread>>>(p);
}
```

```cpp
#include <cuda_runtime.h>
#include <cuda.h>
#include <cuda_bf16.h>
#include <stdint.h>

template <int N> struct WG;
template <> struct WG<16> {
  static __device__ __forceinline__ void rs(float* d, const uint32_t* a, uint64_t db) {
    asm volatile("{\n.reg .pred p;\nsetp.ne.b32 p, 1, 0;\nwgmma.mma_async.sync.aligned.m64n16k16.f32.bf16.bf16 {"
      "%0, %1, %2, %3, %4, %5, %6, %7"
      "}, {%8, %9, %10, %11}, %12, p, 1, 1, 0;\n}\n"
      :
      "+f"(d[0]), "+f"(d[1]), "+f"(d[2]), "+f"(d[3]), "+f"(d[4]), "+f"(d[5]), "+f"(d[6]), "+f"(d[7])
      : "r"(a[0]), "r"(a[1]), "r"(a[2]), "r"(a[3]), "l"(db));
  }
};
template <> struct WG<32> {
  static __device__ __forceinline__ void rs(float* d, const uint32_t* a, uint64_t db) {
    asm volatile("{\n.reg .pred p;\nsetp.ne.b32 p, 1, 0;\nwgmma.mma_async.sync.aligned.m64n32k16.f32.bf16.bf16 {"
      "%0, %1, %2, %3, %4, %5, %6, %7, %8, %9, %10, %11, %12, %13, %14, %15"
      "}, {%16, %17, %18, %19}, %20, p, 1, 1, 0;\n}\n"
      :
      "+f"(d[0]), "+f"(d[1]), "+f"(d[2]), "+f"(d[3]), "+f"(d[4]), "+f"(d[5]), "+f"(d[6]), "+f"(d[7]),
      "+f"(d[8]), "+f"(d[9]), "+f"(d[10]), "+f"(d[11]), "+f"(d[12]), "+f"(d[13]), "+f"(d[14]), "+f"(d[15])
      : "r"(a[0]), "r"(a[1]), "r"(a[2]), "r"(a[3]), "l"(db));
  }
};
template <> struct WG<48> {
  static __device__ __forceinline__ void rs(float* d, const uint32_t* a, uint64_t db) {
    asm volatile("{\n.reg .pred p;\nsetp.ne.b32 p, 1, 0;\nwgmma.mma_async.sync.aligned.m64n48k16.f32.bf16.bf16 {"
      "%0, %1, %2, %3, %4, %5, %6, %7, %8, %9, %10, %11, %12, %13, %14, %15, "
      "%16, %17, %18, %19, %20, %21, %22, %23"
      "}, {%24, %25, %26, %27}, %28, p, 1, 1, 0;\n}\n"
      :
      "+f"(d[0]), "+f"(d[1]), "+f"(d[2]), "+f"(d[3]), "+f"(d[4]), "+f"(d[5]), "+f"(d[6]), "+f"(d[7]),
      "+f"(d[8]), "+f"(d[9]), "+f"(d[10]), "+f"(d[11]), "+f"(d[12]), "+f"(d[13]), "+f"(d[14]), "+f"(d[15]),
      "+f"(d[16]), "+f"(d[17]), "+f"(d[18]), "+f"(d[19]), "+f"(d[20]), "+f"(d[21]), "+f"(d[22]), "+f"(d[23])
      : "r"(a[0]), "r"(a[1]), "r"(a[2]), "r"(a[3]), "l"(db));
  }
};
template <> struct WG<64> {
  static __device__ __forceinline__ void rs(float* d, const uint32_t* a, uint64_t db) {
    asm volatile("{\n.reg .pred p;\nsetp.ne.b32 p, 1, 0;\nwgmma.mma_async.sync.aligned.m64n64k16.f32.bf16.bf16 {"
      "%0, %1, %2, %3, %4, %5, %6, %7, %8, %9, %10, %11, %12, %13, %14, %15, "
      "%16, %17, %18, %19, %20, %21, %22, %23, %24, %25, %26, %27, %28, %29, %30, %31"
      "}, {%32, %33, %34, %35}, %36, p, 1, 1, 0;\n}\n"
      :
      "+f"(d[0]), "+f"(d[1]), "+f"(d[2]), "+f"(d[3]), "+f"(d[4]), "+f"(d[5]), "+f"(d[6]), "+f"(d[7]),
      "+f"(d[8]), "+f"(d[9]), "+f"(d[10]), "+f"(d[11]), "+f"(d[12]), "+f"(d[13]), "+f"(d[14]), "+f"(d[15]),
      "+f"(d[16]), "+f"(d[17]), "+f"(d[18]), "+f"(d[19]), "+f"(d[20]), "+f"(d[21]), "+f"(d[22]), "+f"(d[23]),
      "+f"(d[24]), "+f"(d[25]), "+f"(d[26]), "+f"(d[27]), "+f"(d[28]), "+f"(d[29]), "+f"(d[30]), "+f"(d[31])
      : "r"(a[0]), "r"(a[1]), "r"(a[2]), "r"(a[3]), "l"(db));
  }
};
template <> struct WG<80> {
  static __device__ __forceinline__ void rs(float* d, const uint32_t* a, uint64_t db) {
    asm volatile("{\n.reg .pred p;\nsetp.ne.b32 p, 1, 0;\nwgmma.mma_async.sync.aligned.m64n80k16.f32.bf16.bf16 {"
      "%0, %1, %2, %3, %4, %5, %6, %7, %8, %9, %10, %11, %12, %13, %14, %15, "
      "%16, %17, %18, %19, %20, %21, %22, %23, %24, %25, %26, %27, %28, %29, %30, %31, "
      "%32, %33, %34, %35, %36, %37, %38, %39"
      "}, {%40, %41, %42, %43}, %44, p, 1, 1, 0;\n}\n"
      :
      "+f"(d[0]), "+f"(d[1]), "+f"(d[2]), "+f"(d[3]), "+f"(d[4]), "+f"(d[5]), "+f"(d[6]), "+f"(d[7]),
      "+f"(d[8]), "+f"(d[9]), "+f"(d[10]), "+f"(d[11]), "+f"(d[12]), "+f"(d[13]), "+f"(d[14]), "+f"(d[15]),
      "+f"(d[16]), "+f"(d[17]), "+f"(d[18]), "+f"(d[19]), "+f"(d[20]), "+f"(d[21]), "+f"(d[22]), "+f"(d[23]),
      "+f"(d[24]), "+f"(d[25]), "+f"(d[26]), "+f"(d[27]), "+f"(d[28]), "+f"(d[29]), "+f"(d[30]), "+f"(d[31]),
      "+f"(d[32]), "+f"(d[33]), "+f"(d[34]), "+f"(d[35]), "+f"(d[36]), "+f"(d[37]), "+f"(d[38]), "+f"(d[39])
      : "r"(a[0]), "r"(a[1]), "r"(a[2]), "r"(a[3]), "l"(db));
  }
};
template <> struct WG<96> {
  static __device__ __forceinline__ void rs(float* d, const uint32_t* a, uint64_t db) {
    asm volatile("{\n.reg .pred p;\nsetp.ne.b32 p, 1, 0;\nwgmma.mma_async.sync.aligned.m64n96k16.f32.bf16.bf16 {"
      "%0, %1, %2, %3, %4, %5, %6, %7, %8, %9, %10, %11, %12, %13, %14, %15, "
      "%16, %17, %18, %19, %20, %21, %22, %23, %24, %25, %26, %27, %28, %29, %30, %31, "
      "%32, %33, %34, %35, %36, %37, %38, %39, %40, %41, %42, %43, %44, %45, %46, %47"
      "}, {%48, %49, %50, %51}, %52, p, 1, 1, 0;\n}\n"
      :
      "+f"(d[0]), "+f"(d[1]), "+f"(d[2]), "+f"(d[3]), "+f"(d[4]), "+f"(d[5]), "+f"(d[6]), "+f"(d[7]),
      "+f"(d[8]), "+f"(d[9]), "+f"(d[10]), "+f"(d[11]), "+f"(d[12]), "+f"(d[13]), "+f"(d[14]), "+f"(d[15]),
      "+f"(d[16]), "+f"(d[17]), "+f"(d[18]), "+f"(d[19]), "+f"(d[20]), "+f"(d[21]), "+f"(d[22]), "+f"(d[23]),
      "+f"(d[24]), "+f"(d[25]), "+f"(d[26]), "+f"(d[27]), "+f"(d[28]), "+f"(d[29]), "+f"(d[30]), "+f"(d[31]),
      "+f"(d[32]), "+f"(d[33]), "+f"(d[34]), "+f"(d[35]), "+f"(d[36]), "+f"(d[37]), "+f"(d[38]), "+f"(d[39]),
      "+f"(d[40]), "+f"(d[41]), "+f"(d[42]), "+f"(d[43]), "+f"(d[44]), "+f"(d[45]), "+f"(d[46]), "+f"(d[47])
      : "r"(a[0]), "r"(a[1]), "r"(a[2]), "r"(a[3]), "l"(db));
  }
};
template <> struct WG<112> {
  static __device__ __forceinline__ void rs(float* d, const uint32_t* a, uint64_t db) {
    asm volatile("{\n.reg .pred p;\nsetp.ne.b32 p, 1, 0;\nwgmma.mma_async.sync.aligned.m64n112k16.f32.bf16.bf16 {"
      "%0, %1, %2, %3, %4, %5, %6, %7, %8, %9, %10, %11, %12, %13, %14, %15, "
      "%16, %17, %18, %19, %20, %21, %22, %23, %24, %25, %26, %27, %28, %29, %30, %31, "
      "%32, %33, %34, %35, %36, %37, %38, %39, %40, %41, %42, %43, %44, %45, %46, %47, "
      "%48, %49, %50, %51, %52, %53, %54, %55"
      "}, {%56, %57, %58, %59}, %60, p, 1, 1, 0;\n}\n"
      :
      "+f"(d[0]), "+f"(d[1]), "+f"(d[2]), "+f"(d[3]), "+f"(d[4]), "+f"(d[5]), "+f"(d[6]), "+f"(d[7]),
      "+f"(d[8]), "+f"(d[9]), "+f"(d[10]), "+f"(d[11]), "+f"(d[12]), "+f"(d[13]), "+f"(d[14]), "+f"(d[15]),
      "+f"(d[16]), "+f"(d[17]), "+f"(d[18]), "+f"(d[19]), "+f"(d[20]), "+f"(d[21]), "+f"(d[22]), "+f"(d[23]),
      "+f"(d[24]), "+f"(d[25]), "+f"(d[26]), "+f"(d[27]), "+f"(d[28]), "+f"(d[29]), "+f"(d[30]), "+f"(d[31]),
      "+f"(d[32]), "+f"(d[33]), "+f"(d[34]), "+f"(d[35]), "+f"(d[36]), "+f"(d[37]), "+f"(d[38]), "+f"(d[39]),
      "+f"(d[40]), "+f"(d[41]), "+f"(d[42]), "+f"(d[43]), "+f"(d[44]), "+f"(d[45]), "+f"(d[46]), "+f"(d[47]),
      "+f"(d[48]), "+f"(d[49]), "+f"(d[50]), "+f"(d[51]), "+f"(d[52]), "+f"(d[53]), "+f"(d[54]), "+f"(d[55])
      : "r"(a[0]), "r"(a[1]), "r"(a[2]), "r"(a[3]), "l"(db));
  }
};
template <> struct WG<128> {
  static __device__ __forceinline__ void rs(float* d, const uint32_t* a, uint64_t db) {
    asm volatile("{\n.reg .pred p;\nsetp.ne.b32 p, 1, 0;\nwgmma.mma_async.sync.aligned.m64n128k16.f32.bf16.bf16 {"
      "%0, %1, %2, %3, %4, %5, %6, %7, %8, %9, %10, %11, %12, %13, %14, %15, "
      "%16, %17, %18, %19, %20, %21, %22, %23, %24, %25, %26, %27, %28, %29, %30, %31, "
      "%32, %33, %34, %35, %36, %37, %38, %39, %40, %41, %42, %43, %44, %45, %46, %47, "
      "%48, %49, %50, %51, %52, %53, %54, %55, %56, %57, %58, %59, %60, %61, %62, %63"
      "}, {%64, %65, %66, %67}, %68, p, 1, 1, 0;\n}\n"
      :
      "+f"(d[0]), "+f"(d[1]), "+f"(d[2]), "+f"(d[3]), "+f"(d[4]), "+f"(d[5]), "+f"(d[6]), "+f"(d[7]),
      "+f"(d[8]), "+f"(d[9]), "+f"(d[10]), "+f"(d[11]), "+f"(d[12]), "+f"(d[13]), "+f"(d[14]), "+f"(d[15]),
      "+f"(d[16]), "+f"(d[17]), "+f"(d[18]), "+f"(d[19]), "+f"(d[20]), "+f"(d[21]), "+f"(d[22]), "+f"(d[23]),
      "+f"(d[24]), "+f"(d[25]), "+f"(d[26]), "+f"(d[27]), "+f"(d[28]), "+f"(d[29]), "+f"(d[30]), "+f"(d[31]),
      "+f"(d[32]), "+f"(d[33]), "+f"(d[34]), "+f"(d[35]), "+f"(d[36]), "+f"(d[37]), "+f"(d[38]), "+f"(d[39]),
      "+f"(d[40]), "+f"(d[41]), "+f"(d[42]), "+f"(d[43]), "+f"(d[44]), "+f"(d[45]), "+f"(d[46]), "+f"(d[47]),
      "+f"(d[48]), "+f"(d[49]), "+f"(d[50]), "+f"(d[51]), "+f"(d[52]), "+f"(d[53]), "+f"(d[54]), "+f"(d[55]),
      "+f"(d[56]), "+f"(d[57]), "+f"(d[58]), "+f"(d[59]), "+f"(d[60]), "+f"(d[61]), "+f"(d[62]), "+f"(d[63])
      : "r"(a[0]), "r"(a[1]), "r"(a[2]), "r"(a[3]), "l"(db));
  }
};
template <> struct WG<160> {
  static __device__ __forceinline__ void ss(float* d, uint64_t da, uint64_t db, int sd) {
    asm volatile("{\n.reg .pred p;\nsetp.ne.b32 p, %82, 0;\nwgmma.mma_async.sync.aligned.m64n160k16.f32.bf16.bf16 {"
      "%0, %1, %2, %3, %4, %5, %6, %7, %8, %9, %10, %11, %12, %13, %14, %15, "
      "%16, %17, %18, %19, %20, %21, %22, %23, %24, %25, %26, %27, %28, %29, %30, %31, "
      "%32, %33, %34, %35, %36, %37, %38, %39, %40, %41, %42, %43, %44, %45, %46, %47, "
      "%48, %49, %50, %51, %52, %53, %54, %55, %56, %57, %58, %59, %60, %61, %62, %63, "
      "%64, %65, %66, %67, %68, %69, %70, %71, %72, %73, %74, %75, %76, %77, %78, %79"
      "}, %80, %81, p, 1, 1, 0, 1;\n}\n"
      :
      "+f"(d[0]), "+f"(d[1]), "+f"(d[2]), "+f"(d[3]), "+f"(d[4]), "+f"(d[5]), "+f"(d[6]), "+f"(d[7]),
      "+f"(d[8]), "+f"(d[9]), "+f"(d[10]), "+f"(d[11]), "+f"(d[12]), "+f"(d[13]), "+f"(d[14]), "+f"(d[15]),
      "+f"(d[16]), "+f"(d[17]), "+f"(d[18]), "+f"(d[19]), "+f"(d[20]), "+f"(d[21]), "+f"(d[22]), "+f"(d[23]),
      "+f"(d[24]), "+f"(d[25]), "+f"(d[26]), "+f"(d[27]), "+f"(d[28]), "+f"(d[29]), "+f"(d[30]), "+f"(d[31]),
      "+f"(d[32]), "+f"(d[33]), "+f"(d[34]), "+f"(d[35]), "+f"(d[36]), "+f"(d[37]), "+f"(d[38]), "+f"(d[39]),
      "+f"(d[40]), "+f"(d[41]), "+f"(d[42]), "+f"(d[43]), "+f"(d[44]), "+f"(d[45]), "+f"(d[46]), "+f"(d[47]),
      "+f"(d[48]), "+f"(d[49]), "+f"(d[50]), "+f"(d[51]), "+f"(d[52]), "+f"(d[53]), "+f"(d[54]), "+f"(d[55]),
      "+f"(d[56]), "+f"(d[57]), "+f"(d[58]), "+f"(d[59]), "+f"(d[60]), "+f"(d[61]), "+f"(d[62]), "+f"(d[63]),
      "+f"(d[64]), "+f"(d[65]), "+f"(d[66]), "+f"(d[67]), "+f"(d[68]), "+f"(d[69]), "+f"(d[70]), "+f"(d[71]),
      "+f"(d[72]), "+f"(d[73]), "+f"(d[74]), "+f"(d[75]), "+f"(d[76]), "+f"(d[77]), "+f"(d[78]), "+f"(d[79])
      : "l"(da), "l"(db), "r"(sd));
  }
};
template <> struct WG<192> {
  static __device__ __forceinline__ void ss(float* d, uint64_t da, uint64_t db, int sd) {
    asm volatile("{\n.reg .pred p;\nsetp.ne.b32 p, %98, 0;\nwgmma.mma_async.sync.aligned.m64n192k16.f32.bf16.bf16 {"
      "%0, %1, %2, %3, %4, %5, %6, %7, %8, %9, %10, %11, %12, %13, %14, %15, "
      "%16, %17, %18, %19, %20, %21, %22, %23, %24, %25, %26, %27, %28, %29, %30, %31, "
      "%32, %33, %34, %35, %36, %37, %38, %39, %40, %41, %42, %43, %44, %45, %46, %47, "
      "%48, %49, %50, %51, %52, %53, %54, %55, %56, %57, %58, %59, %60, %61, %62, %63, "
      "%64, %65, %66, %67, %68, %69, %70, %71, %72, %73, %74, %75, %76, %77, %78, %79, "
      "%80, %81, %82, %83, %84, %85, %86, %87, %88, %89, %90, %91, %92, %93, %94, %95"
      "}, %96, %97, p, 1, 1, 0, 1;\n}\n"
      :
      "+f"(d[0]), "+f"(d[1]), "+f"(d[2]), "+f"(d[3]), "+f"(d[4]), "+f"(d[5]), "+f"(d[6]), "+f"(d[7]),
      "+f"(d[8]), "+f"(d[9]), "+f"(d[10]), "+f"(d[11]), "+f"(d[12]), "+f"(d[13]), "+f"(d[14]), "+f"(d[15]),
      "+f"(d[16]), "+f"(d[17]), "+f"(d[18]), "+f"(d[19]), "+f"(d[20]), "+f"(d[21]), "+f"(d[22]), "+f"(d[23]),
      "+f"(d[24]), "+f"(d[25]), "+f"(d[26]), "+f"(d[27]), "+f"(d[28]), "+f"(d[29]), "+f"(d[30]), "+f"(d[31]),
      "+f"(d[32]), "+f"(d[33]), "+f"(d[34]), "+f"(d[35]), "+f"(d[36]), "+f"(d[37]), "+f"(d[38]), "+f"(d[39]),
      "+f"(d[40]), "+f"(d[41]), "+f"(d[42]), "+f"(d[43]), "+f"(d[44]), "+f"(d[45]), "+f"(d[46]), "+f"(d[47]),
      "+f"(d[48]), "+f"(d[49]), "+f"(d[50]), "+f"(d[51]), "+f"(d[52]), "+f"(d[53]), "+f"(d[54]), "+f"(d[55]),
      "+f"(d[56]), "+f"(d[57]), "+f"(d[58]), "+f"(d[59]), "+f"(d[60]), "+f"(d[61]), "+f"(d[62]), "+f"(d[63]),
      "+f"(d[64]), "+f"(d[65]), "+f"(d[66]), "+f"(d[67]), "+f"(d[68]), "+f"(d[69]), "+f"(d[70]), "+f"(d[71]),
      "+f"(d[72]), "+f"(d[73]), "+f"(d[74]), "+f"(d[75]), "+f"(d[76]), "+f"(d[77]), "+f"(d[78]), "+f"(d[79]),
      "+f"(d[80]), "+f"(d[81]), "+f"(d[82]), "+f"(d[83]), "+f"(d[84]), "+f"(d[85]), "+f"(d[86]), "+f"(d[87]),
      "+f"(d[88]), "+f"(d[89]), "+f"(d[90]), "+f"(d[91]), "+f"(d[92]), "+f"(d[93]), "+f"(d[94]), "+f"(d[95])
      : "l"(da), "l"(db), "r"(sd));
  }
  static __device__ __forceinline__ void rst(float* d, const uint32_t* a, uint64_t db) {
    asm volatile("{\n.reg .pred p;\nsetp.ne.b32 p, 1, 0;\nwgmma.mma_async.sync.aligned.m64n192k16.f32.bf16.bf16 {"
      "%0, %1, %2, %3, %4, %5, %6, %7, %8, %9, %10, %11, %12, %13, %14, %15, "
      "%16, %17, %18, %19, %20, %21, %22, %23, %24, %25, %26, %27, %28, %29, %30, %31, "
      "%32, %33, %34, %35, %36, %37, %38, %39, %40, %41, %42, %43, %44, %45, %46, %47, "
      "%48, %49, %50, %51, %52, %53, %54, %55, %56, %57, %58, %59, %60, %61, %62, %63, "
      "%64, %65, %66, %67, %68, %69, %70, %71, %72, %73, %74, %75, %76, %77, %78, %79, "
      "%80, %81, %82, %83, %84, %85, %86, %87, %88, %89, %90, %91, %92, %93, %94, %95"
      "}, {%96, %97, %98, %99}, %100, p, 1, 1, 1;\n}\n"
      :
      "+f"(d[0]), "+f"(d[1]), "+f"(d[2]), "+f"(d[3]), "+f"(d[4]), "+f"(d[5]), "+f"(d[6]), "+f"(d[7]),
      "+f"(d[8]), "+f"(d[9]), "+f"(d[10]), "+f"(d[11]), "+f"(d[12]), "+f"(d[13]), "+f"(d[14]), "+f"(d[15]),
      "+f"(d[16]), "+f"(d[17]), "+f"(d[18]), "+f"(d[19]), "+f"(d[20]), "+f"(d[21]), "+f"(d[22]), "+f"(d[23]),
      "+f"(d[24]), "+f"(d[25]), "+f"(d[26]), "+f"(d[27]), "+f"(d[28]), "+f"(d[29]), "+f"(d[30]), "+f"(d[31]),
      "+f"(d[32]), "+f"(d[33]), "+f"(d[34]), "+f"(d[35]), "+f"(d[36]), "+f"(d[37]), "+f"(d[38]), "+f"(d[39]),
      "+f"(d[40]), "+f"(d[41]), "+f"(d[42]), "+f"(d[43]), "+f"(d[44]), "+f"(d[45]), "+f"(d[46]), "+f"(d[47]),
      "+f"(d[48]), "+f"(d[49]), "+f"(d[50]), "+f"(d[51]), "+f"(d[52]), "+f"(d[53]), "+f"(d[54]), "+f"(d[55]),
      "+f"(d[56]), "+f"(d[57]), "+f"(d[58]), "+f"(d[59]), "+f"(d[60]), "+f"(d[61]), "+f"(d[62]), "+f"(d[63]),
      "+f"(d[64]), "+f"(d[65]), "+f"(d[66]), "+f"(d[67]), "+f"(d[68]), "+f"(d[69]), "+f"(d[70]), "+f"(d[71]),
      "+f"(d[72]), "+f"(d[73]), "+f"(d[74]), "+f"(d[75]), "+f"(d[76]), "+f"(d[77]), "+f"(d[78]), "+f"(d[79]),
      "+f"(d[80]), "+f"(d[81]), "+f"(d[82]), "+f"(d[83]), "+f"(d[84]), "+f"(d[85]), "+f"(d[86]), "+f"(d[87]),
      "+f"(d[88]), "+f"(d[89]), "+f"(d[90]), "+f"(d[91]), "+f"(d[92]), "+f"(d[93]), "+f"(d[94]), "+f"(d[95])
      : "r"(a[0]), "r"(a[1]), "r"(a[2]), "r"(a[3]), "l"(db));
  }
};

#define ZP_AT 1
#define CPRE0 1
#define ZORD 1
#define K0_POLL 0
#define CFENCE 1
#define Z1_AT 4
#define G1_AT 0
#define HGRP 3
#define HPACE 200
#define DB 0
#define HOLD_AT 33
#define LL_AT 4
#define KV_T0 2300
#define ST_YIELD 1
#define HP0 3500
#define HPD 450
#define RAMP 1
#define LEAD 2
#define WSP_N 16
#define EARLY 0
#define CPIN 1
#define CW0 0
#define PFT 1
#define WSP_D 600
#define D1 4
#define D2 4
#define NSLEEP 32

static_assert(ZP_AT <= RAMP && LEAD <= 2, "staging slots");

namespace {

constexpr int kS = 2048, kD = 640, kF = 1536;
constexpr int NA = 10, NA2 = 9, NB = 5;
constexpr int A_SLOT = 8192, B_SLOT = 24576;
constexpr int OFF_A = 0;
constexpr int OFF_B = OFF_A + NA * A_SLOT;
constexpr int XB_PL = 2112;
constexpr int CV_KE = 4224, CV_KO = CV_KE + 4160;
constexpr int CV_SZ = CV_KO + 4160;
constexpr int OFF_CV = OFF_B + NB * B_SLOT;
constexpr int OFF_CS = OFF_CV + 2 * CV_SZ;
constexpr int OFF_BIAS = OFF_CS + 1536;
constexpr int OFF_XS = OFF_BIAS + 128;
constexpr int OFF_BAR = OFF_XS + 512;
constexpr int BAR_AF = OFF_BAR, BAR_ST = BAR_AF + 8 * NA, BAR_XF = BAR_ST + 16, BAR_KV = BAR_XF + 16;
constexpr int BAR_BF = OFF_BAR + 128, BAR_G2 = BAR_BF + 8 * (NB + 1), BAR_XS = BAR_G2 + 8, BAR_KU = BAR_XS + 8, BAR_ZP = BAR_KU + 40, BAR_XC = BAR_ZP + 8, BAR_WO = BAR_XC + 8;
constexpr int BAR_AE = OFF_BAR + 256, BAR_BE = BAR_AE + 8 * NA;
constexpr int BAR_YT = BAR_KU + 24;
constexpr int BAR_Z1 = BAR_ST;
constexpr int BAR_GO = BAR_XS;
constexpr int BAR_YL = BAR_KU + 16;
constexpr int OFF_TAG = OFF_CS - 32;
constexpr int SMEM_BYTES = OFF_BAR + 384;
static_assert(SMEM_BYTES <= 232448, "smem");
constexpr int NB_WGA = 1, NB_WGC = 2, NB_G1 = 3, NB_WO = 4, NB_CD = 5, NB_Z = 6, NB_WGB = 7, NB_Z2 = 8;

constexpr int CNT_Z = 0, CNT_Y = 1, CNT_Z1 = 3, CNT_KV = 32, CNT_WO = 36;
struct Scratch {
  uint8_t kvx[kD * 4096];
  uint8_t z2[4 * 32 * 24576];
  uint8_t h[32 * 12 * 8192];
  uint8_t wo[4 * 12 * 20480];
  uint8_t y[896 * 4096];
  uint4 xstat[kS];
  uint2 zstat[kS * 8];
  uint2 colsum[kF];
  uint32_t cnt[2 * 32];
  uint32_t hcnt[32 * 32];
  uint32_t epoch[136];
};
__device__ __align__(1024) Scratch g_scr;
#define ZS(i)
#define STAMP(i)
#define STAMP2(i)
#define STAMPW(i)

struct Params {
  Scratch* scr;
  int by_smid;
  const __nv_bfloat16 *k, *v, *shift, *ssmk, *ssmD, *wsp, *bsp, *wout;
  __nv_bfloat16* out;
  CUtensorMap tmX, tmW, tmWsp, tmY, tmKV;
};

__device__ __forceinline__ uint64_t mkdesc(uint32_t addr, uint32_t lbo, uint32_t sbo, uint32_t swz) {
  return (uint64_t)((addr & 0x3FFFF) >> 4) | ((uint64_t)(lbo >> 4) << 16) | ((uint64_t)(sbo >> 4) << 32) | ((uint64_t)swz << 62);
}
#define WG_FENCE() asm volatile("wgmma.fence.sync.aligned;" ::: "memory")
#define WG_COMMIT() asm volatile("wgmma.commit_group.sync.aligned;" ::: "memory")
#define WG_WAIT(n) asm volatile("wgmma.wait_group.sync.aligned %0;" ::"n"(n) : "memory")
template <int N> __device__ __forceinline__ void acc_fence(float* d) {
#pragma unroll
  for (int i = 0; i < N; i++) asm volatile("" : "+f"(d[i])::"memory");
}
__device__ __forceinline__ void mbar_init(uint32_t bar, int cnt) { asm volatile("mbarrier.init.shared::cta.b64 [%0], %1;" ::"r"(bar), "r"(cnt) : "memory"); }
__device__ __forceinline__ void mbar_expect(uint32_t bar, uint32_t bytes) { asm volatile("mbarrier.arrive.expect_tx.shared::cta.b64 _, [%0], %1;" ::"r"(bar), "r"(bytes) : "memory"); }
__device__ __forceinline__ void mbar_arrive(uint32_t bar) { asm volatile("mbarrier.arrive.shared::cta.b64 _, [%0];" ::"r"(bar) : "memory"); }
__device__ __forceinline__ void mbar_arrive_if(uint32_t bar, bool c) {
  asm volatile("{\n.reg .pred p;\nsetp.ne.u32 p, %1, 0;\n@p mbarrier.arrive.shared::cta.b64 _, [%0];\n}\n" ::"r"(bar), "r"((uint32_t)c) : "memory");
}
__device__ __forceinline__ void mbar_expect_if(uint32_t bar, uint32_t bytes, bool c) {
  asm volatile("{\n.reg .pred p;\nsetp.ne.u32 p, %2, 0;\n@p mbarrier.arrive.expect_tx.shared::cta.b64 _, [%0], %1;\n}\n" ::"r"(bar), "r"(bytes), "r"((uint32_t)c) : "memory");
}
__device__ __forceinline__ bool mbar_try(uint32_t bar, uint32_t parity) {
  uint32_t ok;
  asm volatile("{\n.reg .pred p;\nmbarrier.try_wait.parity.shared::cta.b64 p, [%1], %2;\nselp.u32 %0, 1, 0, p;\n}\n" : "=r"(ok) : "r"(bar), "r"(parity) : "memory");
  return ok;
}
__device__ __forceinline__ bool mbar_test(uint32_t bar, uint32_t parity) {
  uint32_t ok;
  asm volatile("{\n.reg .pred p;\nmbarrier.test_wait.parity.shared::cta.b64 p, [%1], %2;\nselp.u32 %0, 1, 0, p;\n}\n" : "=r"(ok) : "r"(bar), "r"(parity) : "memory");
  return ok;
}
__device__ __forceinline__ void die() { asm volatile("st.volatile.global.u32 [%0], %1;" ::"l"(0ull), "r"(0) : "memory"); }
__device__ __forceinline__ void spin_guard(uint32_t& n) { if (++n == (1u << 22)) die(); }
__device__ __forceinline__ void mbar_wait(uint32_t bar, uint32_t parity) {
  uint32_t t0 = 0;
#pragma unroll 1
  while (!mbar_try(bar, parity)) spin_guard(t0);
}
__device__ __forceinline__ void mbar_wait2(uint32_t b0, uint32_t p0, uint32_t b1, uint32_t p1) {
  uint32_t t0 = 0;
#pragma unroll 1
  while (true) {
    const bool r0 = mbar_try(b0, p0), r1 = mbar_try(b1, p1);
    if (r0 && r1) break;
    spin_guard(t0);
  }
}
__device__ __forceinline__ int tid_now() { int v; asm volatile("mov.u32 %0, %%tid.x;" : "=r"(v)); return v & 127; }
__device__ __forceinline__ bool elect_one() {
  uint32_t p;
  asm volatile("{\n.reg .pred P;\nelect.sync _|P, 0xffffffff;\nselp.u32 %0, 1, 0, P;\n}\n" : "=r"(p));
  return p;
}
__device__ __forceinline__ void bar_sync(int id, int n) { asm volatile("bar.sync %0, %1;" ::"r"(id), "r"(n) : "memory"); }
__device__ __forceinline__ void bar_arrive(int id, int n) { asm volatile("bar.arrive %0, %1;" ::"r"(id), "r"(n) : "memory"); }
__device__ __forceinline__ void fence_async_smem() { asm volatile("fence.proxy.async.shared::cta;" ::: "memory"); }
__device__ __forceinline__ void bulk_g2s(uint32_t dst, const void* src, uint32_t bytes, uint32_t bar) {
  asm volatile("cp.async.bulk.shared::cluster.global.mbarrier::complete_tx::bytes [%0], [%1], %2, [%3];" ::"r"(dst), "l"(src), "r"(bytes), "r"(bar) : "memory");
}
__device__ __forceinline__ void bulk_s2g(void* dst, uint32_t src, uint32_t bytes) {
  asm volatile("cp.async.bulk.global.shared::cta.bulk_group [%0], [%1], %2;" ::"l"(dst), "r"(src), "r"(bytes) : "memory");
}
__device__ __forceinline__ void tma2d(uint32_t dst, const CUtensorMap* m, int c0, int c1, uint32_t bar) {
  asm volatile("cp.async.bulk.tensor.2d.shared::cluster.global.mbarrier::complete_tx::bytes [%0], [%1, {%3, %4}], [%2];" ::"r"(dst), "l"(m), "r"(bar), "r"(c0), "r"(c1) : "memory");
}
__device__ __forceinline__ void tma3d(uint32_t dst, const CUtensorMap* m, int c0, int c1, int c2, uint32_t bar) {
  asm volatile("cp.async.bulk.tensor.3d.shared::cluster.global.mbarrier::complete_tx::bytes [%0], [%1, {%3, %4, %5}], [%2];" ::"r"(dst), "l"(m), "r"(bar), "r"(c0), "r"(c1), "r"(c2) : "memory");
}
__device__ __forceinline__ void tma_rows(uint32_t dst, const CUtensorMap* m, int c0, int rb, uint32_t bar) { tma3d(dst, m, c0, rb * 16, 0, bar); }
__device__ __forceinline__ uint4 ld_ll4(const void* p) {
  uint64_t a, b;
  asm volatile("ld.relaxed.gpu.global.v2.u64 {%0,%1}, [%2];" : "=l"(a), "=l"(b) : "l"(p) : "memory");
  return make_uint4((uint32_t)a, (uint32_t)(a >> 32), (uint32_t)b, (uint32_t)(b >> 32));
}
__device__ __forceinline__ void st_ll4(void* p, uint32_t a, uint32_t b, uint32_t c, uint32_t d) {
  asm volatile("st.relaxed.gpu.global.v2.u64 [%0], {%1,%2};" ::"l"(p), "l"(a | ((uint64_t)b << 32)), "l"(c | ((uint64_t)d << 32)) : "memory");
}
__device__ __forceinline__ void st_ll2(void* p, uint32_t a, uint32_t b) { asm volatile("st.relaxed.gpu.global.u64 [%0], %1;" ::"l"(p), "l"(a | ((uint64_t)b << 32)) : "memory"); }
__device__ __forceinline__ uint2 ld_ll2(const void* p) {
  uint64_t a;
  asm volatile("ld.relaxed.gpu.global.u64 %0, [%1];" : "=l"(a) : "l"(p) : "memory");
  return make_uint2((uint32_t)a, (uint32_t)(a >> 32));
}
__device__ __forceinline__ void wgmma_colsum(float* d, uint64_t da, uint64_t db) {
  asm volatile("{\n.reg .pred p;\nsetp.ne.b32 p, 1, 0;\nwgmma.mma_async.sync.aligned.m64n8k16.f32.bf16.bf16 {%0, %1, %2, %3}, %4, %5, p, 1, 1, 1, 0;\n}\n"
               : "+f"(d[0]), "+f"(d[1]), "+f"(d[2]), "+f"(d[3]) : "l"(da), "l"(db));
}
__device__ __forceinline__ void prefetch_l2(const void* p) { asm volatile("prefetch.global.L2 [%0];" ::"l"(p)); }
__device__ __forceinline__ void pace(uint32_t& t, uint32_t dt) {
  t += dt;
  while ((int32_t)((uint32_t)clock() - t) < 0) { if (NSLEEP) __nanosleep(NSLEEP); }
}
__device__ __forceinline__ void red_relaxed(uint32_t* p) { asm volatile("red.relaxed.gpu.global.add.u32 [%0], 1;" ::"l"(p) : "memory"); }
__device__ __forceinline__ void red_release(uint32_t* p) { asm volatile("red.release.gpu.global.add.u32 [%0], 1;" ::"l"(p) : "memory"); }
__device__ __forceinline__ uint4 ldg4(const void* p) { uint4 v; asm volatile("ld.global.v4.u32 {%0,%1,%2,%3}, [%4];" : "=r"(v.x), "=r"(v.y), "=r"(v.z), "=r"(v.w) : "l"(p) : "memory"); return v; }
__device__ __forceinline__ uint32_t ldg1(const void* p) { uint32_t v; asm volatile("ld.global.u32 %0, [%1];" : "=r"(v) : "l"(p) : "memory"); return v; }
__device__ __forceinline__ void stg4_if(void* p, uint32_t a, uint32_t b, uint32_t c, uint32_t d, bool on) {
  asm volatile("{\n.reg .pred p;\nsetp.ne.u32 p, %5, 0;\n@p st.global.v4.u32 [%0], {%1,%2,%3,%4};\n}\n" ::"l"(p), "r"(a), "r"(b), "r"(c), "r"(d), "r"((uint32_t)on) : "memory");
}
template <int OFF> __device__ __forceinline__ uint32_t lds32(uint32_t a) { uint32_t v; asm volatile("ld.shared.u32 %0, [%1+%2];" : "=r"(v) : "r"(a), "n"(OFF)); return v; }
__device__ __forceinline__ uint4 lds128(uint32_t a) { uint4 v; asm volatile("ld.shared.v4.u32 {%0,%1,%2,%3}, [%4];" : "=r"(v.x), "=r"(v.y), "=r"(v.z), "=r"(v.w) : "r"(a) : "memory"); return v; }
__device__ __forceinline__ float2 lds64f(uint32_t a) { float2 v; asm volatile("ld.shared.v2.f32 {%0,%1}, [%2];" : "=f"(v.x), "=f"(v.y) : "r"(a) : "memory"); return v; }
__device__ __forceinline__ void sts64f(uint32_t a, float x, float y) { asm volatile("st.shared.v2.f32 [%0], {%1,%2};" ::"r"(a), "f"(x), "f"(y) : "memory"); }
__device__ __forceinline__ void sts32(uint32_t a, uint32_t x) { asm volatile("st.shared.u32 [%0], %1;" ::"r"(a), "r"(x) : "memory"); }
__device__ __forceinline__ void sts128(uint32_t a, uint32_t x, uint32_t y, uint32_t z, uint32_t w) { asm volatile("st.shared.v4.u32 [%0], {%1,%2,%3,%4};" ::"r"(a), "r"(x), "r"(y), "r"(z), "r"(w) : "memory"); }
__device__ __forceinline__ void stsm4(uint32_t a, uint32_t r0, uint32_t r1, uint32_t r2, uint32_t r3) {
  asm volatile("stmatrix.sync.aligned.m8n8.x4.shared.b16 [%0], {%1,%2,%3,%4};" ::"r"(a), "r"(r0), "r"(r1), "r"(r2), "r"(r3) : "memory");
}
__device__ __forceinline__ void stsm4t(uint32_t a, uint32_t r0, uint32_t r1, uint32_t r2, uint32_t r3) {
  asm volatile("stmatrix.sync.aligned.m8n8.x4.trans.shared.b16 [%0], {%1,%2,%3,%4};" ::"r"(a), "r"(r0), "r"(r1), "r"(r2), "r"(r3) : "memory");
}
__device__ __forceinline__ void ldsm4t(uint32_t* r, uint32_t a) {
  asm volatile("ldmatrix.sync.aligned.m8n8.x4.trans.shared.b16 {%0,%1,%2,%3}, [%4];" : "=r"(r[0]), "=r"(r[1]), "=r"(r[2]), "=r"(r[3]) : "r"(a) : "memory");
}
__device__ __forceinline__ uint32_t pack2(float lo, float hi) { uint32_t r; asm("cvt.rn.bf16x2.f32 %0, %1, %2;" : "=r"(r) : "f"(hi), "f"(lo)); return r; }
__device__ __forceinline__ float bf_lo(uint32_t u) { return __uint_as_float(u << 16); }
__device__ __forceinline__ float bf_hi(uint32_t u) { return __uint_as_float(u & 0xffff0000u); }
__device__ __forceinline__ float tanh_fast(float x) { float y; asm("tanh.approx.f32 %0, %1;" : "=f"(y) : "f"(x)); return y; }
__device__ __forceinline__ uint32_t hmul2(uint32_t a, uint32_t b) { uint32_t r; asm("mul.rn.bf16x2 %0, %1, %2;" : "=r"(r) : "r"(a), "r"(b)); return r; }
__device__ __forceinline__ uint32_t hfma2(uint32_t a, uint32_t b, uint32_t c) { uint32_t r; asm("fma.rn.bf16x2 %0, %1, %2, %3;" : "=r"(r) : "r"(a), "r"(b), "r"(c)); return r; }
__device__ __forceinline__ uint32_t prmt(uint32_t a, uint32_t b, uint32_t s) { return __byte_perm(a, b, s); }

__device__ __forceinline__ uint32_t ld_relaxed(const uint32_t* p) { uint32_t v; asm volatile("ld.relaxed.gpu.global.u32 %0, [%1];" : "=r"(v) : "l"(p) : "memory"); return v; }
__device__ __forceinline__ void acquire_fence() { asm volatile("fence.acquire.gpu;\nfence.proxy.async.global;" ::: "memory"); }
__device__ __forceinline__ uint32_t load_epoch(const Params& p, int idx, int lane) { return ld_relaxed(&p.scr->epoch[idx + (((lane * lane) & 3) == 2 ? 1 : 0)]); }
__device__ __forceinline__ void poll_counter(const uint32_t* cnt, uint32_t target) {
  uint32_t t0 = 0;
#pragma unroll 1
  while (!__all_sync(0xffffffff, ld_relaxed(cnt) == target)) spin_guard(t0);
  acquire_fence();
}

__device__ __forceinline__ int g3_block(int cb, int it) { return it < 3 ? cb * 3 + it : (it - 3 < cb * 3 ? it - 3 : it); }

template <int N, bool A_SWZ, int B_MODE, int DEPTH, class Hook, class Mid>
__device__ __forceinline__ void gemm_loop(float* d, uint32_t sb, int nkb, int sa, int pa, int b0, uint32_t boff, int relA, int relB, int tid, Hook hook, Mid mid) {
  constexpr uint32_t A_STEP = A_SWZ ? 2 : 128;
  constexpr uint32_t B_STEP = B_MODE == 0 ? 128 : (B_MODE == 1 ? 384 : 320);
  const uint64_t da0 = A_SWZ ? mkdesc(sb + OFF_A, 16, 1024, 1) : mkdesc(sb + OFF_A, 1024, 128, 0);
  const uint64_t db0 = B_MODE == 0 ? mkdesc(sb + OFF_B + boff, 8192, 1024, 1) : mkdesc(sb + OFF_B + boff, B_MODE == 1 ? 3072 : 2560, 128, 0);
  constexpr int MODA = B_MODE == 0 ? NA : NA2;
  constexpr int MODB = B_MODE == 2 ? 6 : NB;
  int sbk = b0 % MODB, pb = (b0 / MODB) & 1;
  auto boffs = [](int s_) { return B_MODE == 2 ? (s_ == 5 ? 0 : s_ + 1) * (20480 >> 4) : s_ * (B_SLOT >> 4); };
  uint32_t rel = 0;
  uint64_t da = da0 + sa * (A_SLOT >> 4), db = db0 + boffs(sbk);
  const bool doR = tid < 2 ? tid < relA : tid - 2 < relB;
  mbar_wait2(sb + BAR_AF + 8 * sa, pa, sb + BAR_BF + 8 * sbk, pb);
  if constexpr (DEPTH == 0) {
    acc_fence<N / 2>(d);
#pragma unroll 1
    for (int it = 0; it < nkb; it++) {
      WG_FENCE();
#pragma unroll
      for (int j = 0; j < 4; j++) WG<N>::ss(d, da + j * A_STEP, db + j * B_STEP, 1);
      WG_COMMIT();
      const uint32_t prel = rel;
      rel = sb + BAR_AE + 8 * (tid < 2 ? sa : sbk + NA);
      if (++sa == MODA) { sa = 0; pa ^= 1; }
      if (++sbk == MODB) { sbk = 0; pb ^= 1; }
      da = da0 + sa * (A_SLOT >> 4); db = db0 + boffs(sbk);
      const bool r0 = mbar_test(sb + BAR_AF + 8 * sa, pa), r1 = mbar_test(sb + BAR_BF + 8 * sbk, pb);
      WG_WAIT(1);
      mbar_arrive_if(prel, doR && prel != 0);
      if (it == 2) {
        WG_WAIT(0);
        mbar_expect_if(sb + BAR_AF + 8 * (tid == 8 ? 8 : tid), A_SLOT, tid < 9);
        mbar_arrive_if(rel, doR);
        rel = 0;
      }
      mid(it);
      if (it + 1 < nkb && !(r0 && r1)) {
        mbar_wait2(sb + BAR_AF + 8 * sa, pa, sb + BAR_BF + 8 * sbk, pb);
      }
    }
  } else
#pragma unroll 1
  for (int it = 0; it < nkb; it++) {
    WG_FENCE();
    WG<N>::ss(d, da, db, 1);
    const uint32_t prel = rel;
    rel = sb + BAR_AE + 8 * (tid < 2 ? sa : sbk + NA);
    if (++sa == MODA) { sa = 0; if (B_MODE) pa ^= 1; }
    if (++sbk == MODB) { sbk = 0; pb ^= 1; }
    if (DEPTH == 1) { WG_COMMIT(); WG_WAIT(1); }
    WG<N>::ss(d, da + A_STEP, db + B_STEP, 1);
    WG_COMMIT();
    WG_WAIT(1);
    if (EARLY == 1) mbar_arrive_if(prel, doR && it != 0);
    WG<N>::ss(d, da + 2 * A_STEP, db + 2 * B_STEP, 1);
    if (DEPTH == 1) WG_COMMIT();
    if (EARLY != 1) mbar_arrive_if(prel, doR && it != 0);
    const bool r0 = mbar_test(sb + BAR_AF + 8 * sa, pa), r1 = mbar_test(sb + BAR_BF + 8 * sbk, pb);
    const uint64_t da3 = da + 3 * A_STEP, db3 = db + 3 * B_STEP;
    da = da0 + sa * (A_SLOT >> 4); db = db0 + boffs(sbk);
    if (DEPTH == 1) WG_WAIT(1);
    WG<N>::ss(d, da3, db3, 1);
    WG_COMMIT();
    mid(it);
    if (it + 1 < nkb) {
      if (!(r0 && r1)) {
        mbar_wait2(sb + BAR_AF + 8 * sa, pa, sb + BAR_BF + 8 * sbk, pb);
      }
    }
    if (DEPTH == 2) WG_WAIT(1);
  }
  hook();
  WG_WAIT(0);
  acc_fence<N / 2>(d);
  mbar_arrive_if(rel, doR);
}

__device__ __forceinline__ void fold_mean(float* d, uint32_t cs, float ma, float mb, int t) {
  const uint32_t ha = pack2(-ma, -ma), hb = pack2(-mb, -mb);
  const float la = -ma - bf_lo(ha), lb = -mb - bf_lo(hb);
  const uint32_t a[4] = {t ? 0u : ha, t ? 0u : hb, t ? 0u : pack2(la, la), t ? 0u : pack2(lb, lb)};
  WG_FENCE();
  WG<192>::rst(d, a, mkdesc(cs, 0, 32, 0));
  WG_COMMIT();
}
__device__ __forceinline__ void gelu_tile(const float* d, uint32_t* z, float* st, float ra, float rb) {
  const float kA = 0.7978845608028654f, kB = 0.7978845608028654f * 0.044715f;
  const float c1a = kA * ra, c3a = kB * ra * ra * ra, c1b = kA * rb, c3b = kB * rb * rb * rb;
  float acc[8];
#pragma unroll
  for (int i = 0; i < 8; i++) acc[i] = 0.f;
#pragma unroll
  for (int j = 0; j < 24; j++) {
    float r[4];
#pragma unroll
    for (int e = 0; e < 4; e++) {
      const float v = d[4 * j + e];
      const float a = v * fmaf(v * v, e < 2 ? c3a : c3b, e < 2 ? c1a : c1b);
      r[e] = fmaf(v, tanh_fast(a), v);
      acc[e] += r[e];
      acc[4 + e] = fmaf(r[e], r[e], acc[4 + e]);
    }
    z[2 * j] = pack2(r[0], r[1]);
    z[2 * j + 1] = pack2(r[2], r[3]);
  }
  st[0] = acc[0] + acc[1]; st[1] = acc[4] + acc[5]; st[2] = acc[2] + acc[3]; st[3] = acc[6] + acc[7];
}

template <int Q> __device__ __forceinline__ void conv_load(uint32_t* a, uint32_t ab) {
  a[0] = lds32<512 * Q>(ab);       a[1] = lds32<512 * Q + 256>(ab);  a[2] = lds32<512 * Q + 16>(ab);   a[3] = lds32<512 * Q + 272>(ab);
  a[4] = lds32<512 * Q + 32>(ab);  a[5] = lds32<512 * Q + 288>(ab);  a[6] = lds32<512 * Q + 48>(ab);   a[7] = lds32<512 * Q + 304>(ab);
  a[8] = lds32<512 * Q + 64>(ab);  a[9] = lds32<512 * Q + 320>(ab);  a[10] = lds32<512 * Q + 80>(ab);  a[11] = lds32<512 * Q + 336>(ab);
  a[12] = lds32<512 * Q + 96>(ab); a[13] = lds32<512 * Q + 352>(ab); a[14] = lds32<512 * Q + 112>(ab); a[15] = lds32<512 * Q + 368>(ab);
}
template <int Q, int L> __device__ __forceinline__ void conv_step(float* d, uint32_t (*a)[16], uint32_t ab, uint64_t db) {
  WG_FENCE();
#pragma unroll
  for (int s = 0; s < 4; s++) WG<128 - 16 * Q>::rs(d, a[Q] + 4 * s, db + s + 16 * Q);
  WG_COMMIT();
  if (CPIN) WG_WAIT(1);
  if (L >= 0) conv_load<(L >= 0 ? L : 0)>(a[L >= 0 ? L : 0], ab);
  if (CW0 || Q == 0) WG_WAIT(0);
}

__device__ __forceinline__ int seg_col(int cb, int h) { return (cb >> 1) * 320 + (cb & 1) * 32 + h * 64; }
__device__ __forceinline__ void final_load_x(uint32_t (*xw)[10], uint32_t xt, int cb, int h, int w, int lane) {
  const int g = lane >> 2, t = lane & 3, cc = seg_col(cb, h) >> 3;
  const int c0 = cc + t, c1 = c0 + 24, c2 = cc + 16 - 6 * h + (t >> 1);
  const uint32_t r0 = xt + (w * 16 + g) * 128;
#pragma unroll
  for (int r = 0; r < 2; r++) {
    const uint4 u = lds128(r0 + r * 1024 + (c0 >> 3) * A_SLOT + (((c0 ^ g) & 7) << 4)), v = lds128(r0 + r * 1024 + (c1 >> 3) * A_SLOT + (((c1 ^ g) & 7) << 4));
    const float2 z = lds64f(r0 + r * 1024 + (c2 >> 3) * A_SLOT + (((c2 ^ g) & 7) << 4) + (t & 1) * 8);
    xw[r][0] = u.x; xw[r][1] = u.y; xw[r][2] = u.z; xw[r][3] = u.w;
    xw[r][4] = v.x; xw[r][5] = v.y; xw[r][6] = v.z; xw[r][7] = v.w;
    xw[r][8] = __float_as_uint(z.x); xw[r][9] = __float_as_uint(z.y);
  }
}
__device__ __forceinline__ void final_s_early(uint32_t (*sw)[10], const uint32_t (*xw)[10], uint32_t ya, float2 s0, float2 s1) {
  const uint32_t r2[2] = {pack2(s0.y, s0.y), pack2(s1.y, s1.y)};
  const float na = -s0.x * bf_lo(r2[0]), nb = -s1.x * bf_lo(r2[1]);
  const uint32_t n2[2] = {pack2(na, na), pack2(nb, nb)};
#pragma unroll
  for (int j = 0; j < 10; j += 2) {
    uint32_t y[4];
    if (j < 4 || j == 8) ldsm4t(y, ya + (j < 4 ? j : 4) * 1024);
#pragma unroll
    for (int e = 0; e < 4; e++) {
      const uint32_t xn = hfma2(xw[e & 1][j + (e >> 1)], r2[e & 1], n2[e & 1]);
      sw[e & 1][j + (e >> 1)] = (j < 4 || j == 8) ? hmul2(xn, y[e]) : xn;
    }
  }
}
__device__ __forceinline__ bool final_late(uint32_t* y, uint32_t ya) {
  ldsm4t(y, ya + 6144);
  ldsm4t(y + 4, ya + 8192);
  uint32_t zero = 0;
#pragma unroll
  for (int e = 0; e < 8; e++) zero |= (y[e] - 0x00010001u) & ~y[e];
  return (zero & 0x80008000u) == 0;
}
__device__ __forceinline__ bool bar_all(int id, int n, bool c) {
  uint32_t r;
  asm volatile("{\n.reg .pred p, q;\nsetp.ne.u32 p, %3, 0;\nbar.red.and.pred q, %1, %2, p;\nselp.u32 %0, 1, 0, q;\n}\n" : "=r"(r) : "r"(id), "r"(n), "r"((uint32_t)c) : "memory");
  return r;
}
__device__ __forceinline__ void final_out(const float* d, const uint32_t (*xw)[10], const uint32_t (*sw)[10], float ra, float rb, __nv_bfloat16* o0, int h, int t) {
  const float ca = 0.25f * ra, cb = 0.25f * rb;
  uint32_t o[2][10];
#pragma unroll
  for (int j = 0; j < 10; j++) {
#pragma unroll
    for (int r = 0; r < 2; r++) {
      const float h0 = d[4 * j + 2 * r] * (r ? cb : ca), h1 = d[4 * j + 2 * r + 1] * (r ? cb : ca);
      o[r][j] = hfma2(pack2(fmaf(h0, tanh_fast(h0), h0), fmaf(h1, tanh_fast(h1), h1)), sw[r][j], xw[r][j]);
      __nv_bfloat16* q = o0 + r * 8 * kD;
      if (j == 3) stg4_if(q + t * 8, o[r][0], o[r][1], o[r][2], o[r][3], true);
      if (j == 7) stg4_if(q + 192 + t * 8, o[r][4], o[r][5], o[r][6], o[r][7], true);
      if (j == 9) asm volatile("st.global.v2.u32 [%0], {%1,%2};" ::"l"(q + 128 - 48 * h + t * 4), "r"(o[r][8]), "r"(o[r][9]) : "memory");
    }
  }
}

struct Taps { uint4 r0, r1; uint32_t n0, n1, dd; };
__device__ __forceinline__ void load_taps(Taps& k, const Params& p, int ch, int tid) {
  const uint4* kp = (const uint4*)(p.ssmk + (size_t)ch * kS);
  k.r0 = ldg4(kp + tid); k.r1 = ldg4(kp + 128 + tid);
  k.n0 = ldg1(kp + tid + 1); k.n1 = tid < 127 ? ldg1(kp + 129 + tid) : 0u;
  k.dd = __bfloat16_as_ushort(p.ssmD[ch]);
}
__device__ __forceinline__ void load_convx(const Params& p, uint32_t cv, uint32_t bar, int ch) {
  mbar_expect(bar, 4096);
  bulk_g2s(cv, p.scr->kvx + (size_t)ch * 4096, 2048, bar);
  bulk_g2s(cv + XB_PL, p.scr->kvx + (size_t)ch * 4096 + 2048, 2048, bar);
}
#define CW 3
#define CSTAMP(j)
__device__ __forceinline__ void zero_pads(uint32_t cv, int lane) {
  if (lane < 8) sts128(cv + (lane >> 2) * XB_PL + 2048 + (lane & 3) * 16, 0, 0, 0, 0);
  else if (lane < 12) sts128(cv + ((lane & 2) ? CV_KO : CV_KE) + (lane & 1) * 16, 0, 0, 0, 0);
  fence_async_smem();
  __syncwarp();
}
__device__ __forceinline__ int y_row(int c, uint32_t par) {
  const int hf = c >= 320, cc = c - hf * 320, u = cc >> 6, cb = hf * 2 + ((cc >> 5) & 1);
  if (u == 2) return cb * 96 + ((cc >> 4) & 1) * 48 + 32 + (cc & 1) + ((cc >> 1) & 1) * 8 + ((cc >> 2) & 3) * 2;
  return (u < 2 ? cb * 96 + u * 48 : 384 + par * 256 + cb * 64 + (u - 3) * 32) + (cc & 1) + ((cc >> 1) & 3) * 8 + ((cc >> 3) & 3) * 2;
}
__device__ __forceinline__ void z_store(const Params& p, uint32_t src, int rb, int cb, int q) {
  uint8_t* dst = p.scr->z2 + (size_t)(cb * 32 + q * 16 + (rb >> 2)) * B_SLOT + (rb & 3) * 6144;
  bulk_s2g(dst, src + q * 12288, 6144);
  bulk_s2g(dst + 8 * B_SLOT, src + q * 12288 + 6144, 6144);
  asm volatile("cp.async.bulk.commit_group;\ncp.async.bulk.wait_group 0;" ::: "memory");
}
__device__ __forceinline__ void y_store(const Params& p, uint32_t sb, int h, int ch, uint32_t par) {
  uint8_t* dst = p.scr->y + (size_t)y_row(ch, par) * 4096;
  if (elect_one()) {
    bulk_s2g(dst, sb + OFF_A + 9 * A_SLOT + h * 4096, 4096);
    asm volatile("cp.async.bulk.commit_group;\ncp.async.bulk.wait_group 0;" ::: "memory");
  }
  __syncwarp();
}
__device__ __forceinline__ void conv_service(const Params& p, uint32_t sb, int h, int ch, bool first) {
  bar_sync(NB_WGA + 8 + h, 160);
  const bool now = !first || __all_sync(0xffffffff, mbar_test(sb + BAR_KV, 0));
  if (now) { acquire_fence(); if (elect_one()) load_convx(p, sb + OFF_CV + (1 - h) * CV_SZ, sb + BAR_XF + 8 * h, ch + 128); }
  bar_sync(NB_WGA + 8 + h, 160);
  y_store(p, sb, h, ch, 0);
  if (!now) {
    mbar_wait(sb + BAR_KV, 0);
    acquire_fence();
    if (elect_one()) load_convx(p, sb + OFF_CV + (1 - h) * CV_SZ, sb + BAR_XF + 8 * h, ch + 128);
  }
}
__device__ __forceinline__ uint32_t y_tile(int h) { return OFF_CV + (1 - h) * 13312; }
__device__ __forceinline__ void load_late_y(const Params& p, uint32_t sb, int h, int rb, int cb, uint32_t par) {
  mbar_expect(sb + BAR_YL + 16 * h, 4096);
  tma2d(sb + y_tile(h) + 6144, &p.tmY, rb * 64, 384 + par * 256 + cb * 64 + h * 32, sb + BAR_YL + 16 * h);
  tma2d(sb + y_tile(h) + 8192, &p.tmY, rb * 64, 400 + par * 256 + cb * 64 + h * 32, sb + BAR_YL + 16 * h);
}
__device__ __forceinline__ void held_service(const Params& p, uint32_t sb, int h, int ch, int rb, int cb, uint32_t tag, int lane) {
#pragma unroll 1
  for (int i = 0; i < 8; i++) sts128(sb + OFF_A + 9 * A_SLOT + h * 4096 + i * 512 + lane * 16, 0, 0, 0, 0);
  fence_async_smem();
  __syncwarp();
  y_store(p, sb, h, ch, ~tag & 1);
  mbar_wait(sb + BAR_YT, 1);
  acquire_fence();
  bar_sync(NB_WGA + 8 + h, 160);
  bar_sync(NB_WGA + 8 + h, 160);
  uint8_t* dst = p.scr->y + (size_t)y_row(ch, tag & 1) * 4096;
  if (elect_one()) {
    bulk_s2g(dst, sb + OFF_A + 9 * A_SLOT + h * 4096, 4096);
    asm volatile("cp.async.bulk.commit_group;" ::: "memory");
    mbar_expect(sb + BAR_XF + 8 * h, 6144);
#pragma unroll 1
    for (int i = 0; i < 3; i++) tma2d(sb + y_tile(h) + i * 2048, &p.tmY, rb * 64, cb * 96 + h * 48 + i * 16, sb + BAR_XF + 8 * h);
  }
  mbar_wait(sb + BAR_AE + 8 * (LL_AT - 1), 1);
  if (elect_one()) { load_late_y(p, sb, h, rb, cb, tag & 1); asm volatile("cp.async.bulk.wait_group 0;" ::: "memory"); }
}
__device__ __forceinline__ void conv_worker(const Params& p, Taps& k, uint32_t cv, uint32_t yb0,
                                            uint32_t xbar, int nbar, int ch0, int n, uint32_t holdbar, int w, int lane,
                                            int tid, int st0, int rb, int cb) {
  const int g = lane >> 2, t = lane & 3, w0 = w & 1, w1 = w >> 1;
  const uint32_t ab = cv + ((g & 1) ? CV_KE : CV_KO) + 32 + 2 * (64 * w0 + 8 * w1 + ((g - 15) & ~1) + 2 * t);
  const uint32_t scA = cv + (w1 ? CV_KO : CV_KE) + 32, scB = scA + 2048;
  const int dl = (t >> 1) ^ 1;
  if (n == 2 || CPRE0 == 2) mbar_wait(xbar, 0);
  STAMPW(st0 + 3);
#pragma unroll 1
  for (int i = 0; i < n; i++) {
    if (tid == 0) {
      k.r0.x = (k.r0.x & 0xffff0000u) | (pack2(bf_lo(k.r0.x) + bf_lo(k.dd), 0.f) & 0xffffu);
      sts32(cv + CV_KO + 28, k.r0.x << 16);
    }
    sts128(cv + CV_KE + 32 + tid * 16, k.r0.x, k.r0.y, k.r0.z, k.r0.w);
    sts128(cv + CV_KO + 32 + tid * 16, prmt(k.r0.x, k.r0.y, 0x5432), prmt(k.r0.y, k.r0.z, 0x5432), prmt(k.r0.z, k.r0.w, 0x5432), prmt(k.r0.w, k.n0, 0x5432));
    sts128(cv + CV_KE + 2080 + tid * 16, k.r1.x, k.r1.y, k.r1.z, k.r1.w);
    sts128(cv + CV_KO + 2080 + tid * 16, prmt(k.r1.x, k.r1.y, 0x5432), prmt(k.r1.y, k.r1.z, 0x5432), prmt(k.r1.z, k.r1.w, 0x5432), prmt(k.r1.w, k.n1, 0x5432));
    if (i + 1 < n) load_taps(k, p, ch0 + (i + 1) * 128, tid);
    bar_sync(nbar, 128);
    CSTAMP(0);
    const uint64_t db = mkdesc(cv + (i & 0x1000), XB_PL, 128, 0);
    float d[64];
    uint32_t a[8][16];
    if (CPRE0 == 1 && i == 0) mbar_wait(xbar, 0);
    conv_load<7>(a[7], ab); conv_load<6>(a[6], ab); conv_load<5>(a[5], ab); conv_load<4>(a[4], ab);
#pragma unroll
    for (int j = 0; j < 64; j++) d[j] = 0.f;
    mbar_wait(xbar, i & 1);
    if (i + 1 == n) mbar_wait(holdbar, 1);
    CSTAMP(1);
    conv_step<7, -1>(d, a, ab, db); conv_step<6, -1>(d, a, ab, db); conv_step<5, -1>(d, a, ab, db); conv_step<4, 3>(d, a, ab, db);
    conv_step<3, 2>(d, a, ab, db);
    conv_step<2, 1>(d, a, ab, db);
    conv_step<1, 0>(d, a, ab, db);
    conv_step<0, -1>(d, a, ab, db);
    acc_fence<64>(d);
    CSTAMP(2);
    bar_sync(nbar + 8, 160);
    float E[16][2];
#pragma unroll
    for (int j = 0; j < 15; j++) { E[j][0] = d[4 * j] + d[4 * j + 6]; E[j][1] = d[4 * j + 1] + d[4 * j + 7]; }
    E[15][0] = d[60]; E[15][1] = d[61];
    if (w0 == 0) {
#pragma unroll
      for (int j = 8; j < 16; j++) sts64f(scA + (j - 8) * 256 + lane * 8, E[j][0], E[j][1]);
    } else {
      const uint32_t a = scB - dl * 256 + (lane ^ 2) * 8;
#pragma unroll
      for (int j = 1; j < 8; j++) sts64f(a + j * 256, E[j][0], E[j][1]);
      sts64f(scB + (dl ? 7 * 256 : 0) + (lane ^ 2) * 8, dl ? E[8][0] : E[0][0], dl ? E[8][1] : E[0][1]);
    }
    bar_sync(nbar, 128);
    CSTAMP(3);
    uint32_t pk[8];
    if (w0 == 0) {
#pragma unroll
      for (int j = 0; j < 8; j++) { const float2 v = lds64f(scB + j * 256 + lane * 8); pk[j] = pack2(E[j][0] + v.x, E[j][1] + v.y); }
    } else {
      const uint32_t a0 = scA - dl * 256 + (lane ^ 2) * 8;
#pragma unroll
      for (int j = 9; j < 16; j++) { const float2 v = lds64f(a0 + (j - 8) * 256); pk[j - 8] = pack2(E[j][0] + v.x, E[j][1] + v.y); }
      const float2 v = lds64f(scA + (dl ? 7 * 256 : 0) + (lane ^ 2) * 8);
      pk[0] = pack2((dl ? 0.f : E[8][0]) + v.x, (dl ? 0.f : E[8][1]) + v.y);
    }
    CSTAMP(4);
    if (i + 1 == n) {
#pragma unroll
      for (int j = 0; j < 8; j++) pk[j] = ~pk[j];
    }
    const int c1 = (w0 ? 35 : 95) - lane, c0 = (w0 && lane < 4) ? c1 - 32 : c1 + 32;
    stsm4t(yb0 + 128 * (c0 & 31) + (((2 * (c0 >> 5) + w1) ^ (c0 & 7)) << 4), pk[0], pk[1], pk[2], pk[3]);
    stsm4t(yb0 + 128 * (c1 & 31) + (((2 * (c1 >> 5) + w1) ^ (c1 & 7)) << 4), pk[4], pk[5], pk[6], pk[7]);
    fence_async_smem();
    bar_sync(nbar + 8, 160);
    CSTAMP(5);
    STAMPW(st0 + i);
    if (n == 2 && i == 0) {
      const int u = (tid >> 3) % 5, kg = rb * 3 + (tid < 120 ? (tid >> 3) / 5 : 0), c = u < 4 ? (u >> 1) * 10 + (u & 1) * 4 : 8, o2 = u < 4 ? 2 : 10;
      const uint4* wp = (const uint4*)p.wout + (uint32_t)((kg * 8 + (tid & 7)) * (kD / 8) + (seg_col(cb, 0) >> 3) + (u < 4 ? (u >> 1) * 8 + (u & 1) * 24 : 16));
      const uint4 w0 = ldg4(wp), w1 = ldg4(wp + 1), w2 = ldg4(wp + 2), w3 = ldg4(wp + 3);
      uint8_t* dst = p.scr->wo + (uint32_t)(cb * (12 * 20480) + kg * 2560 + c * 128 + (tid & 7) * 16);
      const bool f = u < 4, on = tid < 120;
      stg4_if(dst, w0.x, f ? w1.x : w0.z, f ? w2.x : w1.x, f ? w3.x : w1.z, on);
      stg4_if(dst + 128, w0.y, f ? w1.y : w0.w, f ? w2.y : w1.y, f ? w3.y : w1.w, on);
      stg4_if(dst + o2 * 128, f ? w0.z : w2.x, f ? w1.z : w2.z, f ? w2.z : w3.x, w3.z, on);
      stg4_if(dst + o2 * 128 + 128, f ? w0.w : w2.y, f ? w1.w : w2.w, f ? w2.w : w3.y, w3.w, on);
      bar_arrive(NB_WO, 160);
    }
  }
}

struct KvRegs { uint32_t k[11], v[8]; uint4 sh; };
__device__ __forceinline__ void kv_load(KvRegs& q, const __nv_bfloat16* kp, const __nv_bfloat16* vp, const __nv_bfloat16* sp, bool halo) {
#pragma unroll
  for (int i = 0; i < 11; i++) q.k[i] = (i >= 3 || halo) ? ldg1(kp + i * kD) : 0u;
#pragma unroll
  for (int i = 0; i < 8; i++) q.v[i] = ldg1(vp + i * kD);
  q.sh = ldg4(sp);
}
__device__ __forceinline__ void kv_unit(const KvRegs& q, uint32_t oa) {
  const uint32_t w0 = prmt(q.sh.x, q.sh.z, 0x5410), w1 = prmt(q.sh.x, q.sh.z, 0x7632), w2 = prmt(q.sh.y, q.sh.w, 0x5410), w3 = prmt(q.sh.y, q.sh.w, 0x7632);
  uint32_t r[8];
#pragma unroll
  for (int i = 0; i < 8; i++) r[i] = hmul2(hfma2(q.k[i + 3], w0, hfma2(q.k[i + 2], w1, hfma2(q.k[i + 1], w2, hmul2(q.k[i], w3)))), q.v[i]);
  sts128(oa, prmt(r[7], r[6], 0x5410), prmt(r[5], r[4], 0x5410), prmt(r[3], r[2], 0x5410), prmt(r[1], r[0], 0x5410));
  sts128(oa + 2048, prmt(r[7], r[6], 0x7632), prmt(r[5], r[4], 0x7632), prmt(r[3], r[2], 0x7632), prmt(r[1], r[0], 0x7632));
}

__device__ __forceinline__ void helper_cta(const Params& p, uint32_t sb, int cb, int warp, int lane) {
  constexpr int NS = 9, ONES = NS * B_SLOT, BF = ONES + 256, BE = BF + 8 * NS;
  if (warp < NS && elect_one()) {
    mbar_init(sb + BF + 8 * warp, 1); mbar_init(sb + BE + 8 * warp, 1);
    fence_async_smem();
    if (warp == 0) { mbar_expect(sb + BF, B_SLOT); tma3d(sb, &p.tmW, 0, 0, 12 + cb * 3, sb + BF); }
  }
  if (warp == 15) { sts32(sb + ONES + lane * 4, 0x3f803f80u); sts32(sb + ONES + 128 + lane * 4, 0x3f803f80u); fence_async_smem(); }
  __syncthreads();
  if (warp == 4) {
    int s = 1, ph = 1;
    uint32_t tp = clock() + HP0;
#pragma unroll 1
    for (int it = 1; it < 20; it++) {
      if (HPD && it >= 10) pace(tp, HPD);
      mbar_wait(sb + BE + 8 * s, ph);
      if (elect_one()) { mbar_expect(sb + BF + 8 * s, B_SLOT); tma3d(sb + s * B_SLOT, &p.tmW, 0, (it < 10 ? it : it - 10) * 64, (it < 10 ? 12 : 0) + cb * 3, sb + BF + 8 * s); }
      if (++s == NS) { s = 0; ph ^= 1; }
    }
  } else if (warp < 4) {
    const uint32_t tag = load_epoch(p, 128 + cb, lane) + 1;
    const uint64_t db = mkdesc(sb + ONES, 128, 128, 0);
    uint2* dst = p.scr->colsum + cb * 192 + warp * 16 + (lane >> 2);
    if ((lane & 3) == 0) {
#pragma unroll 1
      for (int j = 0; j < 12; j++) st_ll2(dst + (j < 6 ? 768 : 0) + ((j % 6) >> 1) * 64 + (j & 1) * 8, 0, 0);
    }
    int s = 0, ph = 0;
#pragma unroll 1
    for (int part = 0; part < 2; part++) {
      float d[12];
#pragma unroll
      for (int i = 0; i < 12; i++) d[i] = 0.f;
#pragma unroll 1
      for (int it = 0; it < 10; it++) {
        mbar_wait(sb + BF + 8 * s, ph);
        const uint64_t da = mkdesc(sb + s * B_SLOT, 8192, 1024, 1);
        WG_FENCE();
#pragma unroll
        for (int j = 0; j < 12; j++) wgmma_colsum(d + 4 * (j % 3), da + (j % 3) * 512 + (j / 3) * 128, db);
        WG_COMMIT();
        WG_WAIT(1);
        mbar_arrive_if(sb + BE + 8 * (s == 0 ? NS - 1 : s - 1), threadIdx.x == 0 && (it | part) != 0);
        if (++s == NS) { s = 0; ph ^= 1; }
      }
      WG_WAIT(0);
      acc_fence<12>(d);
      if ((lane & 3) == 0) {
#pragma unroll
        for (int j = 0; j < 6; j++) st_ll2(dst + (part ? 0 : 768) + (j >> 1) * 64 + (j & 1) * 8, __float_as_uint(d[2 * j]), tag);
      }
      STAMPW(1 + part);
    }
    if (threadIdx.x == 0) *(volatile uint32_t*)&p.scr->epoch[128 + cb] = tag;
  }
}

__global__ void __launch_bounds__(512, 1) fused_kernel(const __grid_constant__ Params p) {
  extern __shared__ __align__(1024) uint8_t smem[];
  const int warp = __shfl_sync(0xffffffff, (int)(threadIdx.x >> 5), 0);
  const int lane = threadIdx.x & 31, tid = threadIdx.x & 127;
  const uint32_t sb = __shfl_sync(0xffffffff, (uint32_t)__cvta_generic_to_shared(smem), 0);
  const uint32_t tstart = clock();
  if (elect_one()) {
    if (warp < 5) asm volatile("prefetch.tensormap [%0];" ::"l"(&p.tmX + warp) : "memory");
    mbar_init(sb + OFF_BAR + 8 * warp, 1); mbar_init(sb + OFF_BAR + 128 + 8 * warp, 1); mbar_init(sb + OFF_BAR + 256 + 8 * warp, 2);
    asm volatile("fence.mbarrier_init.release.cluster;" ::: "memory");
  }
  int b = blockIdx.x;
  if (p.by_smid) asm volatile("mov.u32 %0, %%smid;" : "=r"(b));
  b = __shfl_sync(0xffffffff, b, 0);
  const int tp = b >> 1, t7 = (tp - 32) / 7;
  const int lin = tp < 32 ? ((tp & 7) ? (tp & 7) * 16 : 8) + (tp >> 3) * 2 + (b & 1)
                          : (tp < 60 ? (tp - 31 - t7 * 7) * 16 + 8 + t7 * 2 + (b & 1) : (tp < 62 ? -1 : b - 124));
  const int hcb = b & 3;
  if (lin < 0) { helper_cta(p, sb, hcb, warp, lane); return; }
  const int cb = ((lin >> 4) & 1) * 2 + ((lin >> 1) & 1), rb = (lin >> 5) * 8 + ((lin >> 2) & 3) * 2 + (lin & 1);
  const int zs0 = 4 - (cb & 2);
  const int chb = (cb >> 1) * 320 + rb * 2 + (cb & 1);
  if (warp == 0 && elect_one()) {
    mbar_expect(sb + BAR_AF, A_SLOT);
    tma_rows(sb + OFF_A, &p.tmX, 0, rb, sb + BAR_AF);
    mbar_expect(sb + BAR_BF, B_SLOT);
    tma3d(sb + OFF_B, &p.tmW, 0, 0, 12 + cb * 3, sb + BAR_BF);
  }
  if (warp == 1) STAMP(31);
  if (sb & 1023) die();
  __syncthreads();

  if (warp >= 12) {
    asm volatile("setmaxnreg.dec.sync.aligned.u32 32;");
    const uint32_t epoch = load_epoch(p, lin, lane);
    if (warp == 12) {
#pragma unroll 1
      for (int i = 1; i < NA; i++) {
        if (elect_one()) {
          mbar_expect(sb + BAR_AF + 8 * i, A_SLOT);
          tma_rows(sb + OFF_A + i * A_SLOT, &p.tmX, i * 64, rb, sb + BAR_AF + 8 * i);
          if (i < NB) { mbar_expect(sb + BAR_BF + 8 * i, B_SLOT); tma3d(sb + OFF_B + i * B_SLOT, &p.tmW, 0, i * 64, 12 + cb * 3, sb + BAR_BF + 8 * i); }
        }
      }
      STAMP(32);
      uint32_t kvt;
      {
        const int tb = rb * 2 + (cb & 1);
        kvt = __shfl_sync(0xffffffff, (ld_relaxed(p.scr->cnt + CNT_KV + (cb >> 1)) & ~63u) + 64, 0);
        {
          uint32_t tp = tstart;
          pace(tp, KV_T0);
          mbar_arrive_if(sb + BAR_KV + 8, lane == 0);
        }
        if (ST_YIELD) mbar_wait2(sb + BAR_XS, 0, sb + BAR_ST, 0);
#pragma unroll 1
        for (int u = 0; u < 5; u++) {
          mbar_wait(sb + BAR_KU + 8 * u, 0);
          fence_async_smem();
          if (elect_one()) {
            asm volatile("cp.async.bulk.tensor.3d.global.shared::cta.bulk_group [%0, {%2, %3, %4}], [%1];\ncp.async.bulk.commit_group;" ::"l"(&p.tmKV),
                         "r"(sb + OFF_CV + CV_SZ + (u < 3 ? u : u - 3) * 4096), "r"((63 - tb) * 16), "r"((cb >> 1) * 160 + u * 32), "r"(0) : "memory");
            if (u == 1 || u == 4) asm volatile("cp.async.bulk.wait_group 0;" ::: "memory");
            if (u == 1) { mbar_arrive(sb + BAR_KU); red_release(p.scr->cnt + CNT_KV + (cb >> 1)); }
          }
          __syncwarp();
          if (u == 1) {
            STAMP(35);
            if (PFT) { const char* q = (const char*)p.ssmk + chb * 4096 + lane * 128; prefetch_l2(q); prefetch_l2(q + 64 * 4096); }
          }
        }
        zero_pads(sb + OFF_CV + CV_SZ, lane);
        if (elect_one()) { mbar_arrive(sb + BAR_KU + 8); red_release(p.scr->cnt + CNT_KV + 2 + (cb >> 1)); }
        STAMP(30);
        if (lane < 24) {
          const char* r = (const char*)p.wout + (rb * 24 + lane) * (kD * 2) + (cb >> 1) * 640 + (cb & 1) * 384;
          prefetch_l2(r); prefetch_l2(r + 128); prefetch_l2(r + 256 - (cb & 1) * 384);
        }
      }
      poll_counter(p.scr->cnt + CNT_KV + 2 + (cb >> 1), kvt);
      if (elect_one()) mbar_arrive(sb + BAR_KV);
      STAMP(34);
      {
        const char* q = (const char*)p.wsp + (cb * 512 + rb * 16 + (lane >> 1)) * (kS * 2) + (lane & 1) * 128;
        uint32_t tp = clock();
#pragma unroll 1
        for (int i = LEAD / 2; i < WSP_N; i++) {
          prefetch_l2(q + i * 256);
          if (i == Z1_AT) {
            poll_counter(p.scr->cnt + CNT_Z1, (epoch + 1) * 128);
            if (elect_one()) mbar_arrive(sb + BAR_Z1);
            STAMP(24);
          }
          pace(tp, WSP_D);
        }
      }
      const uint32_t tag = epoch + 1;
      mbar_wait(sb + BAR_G2, 0);
      if (elect_one()) {
        bulk_s2g(p.scr->h + (size_t)(rb * 12 + cb * 3) * A_SLOT, sb + OFF_A + 5 * A_SLOT, 3 * A_SLOT);
        asm volatile("cp.async.bulk.commit_group;\ncp.async.bulk.wait_group 0;" ::: "memory");
        red_release(&p.scr->hcnt[(rb >> HGRP) * 32]);
      }
      __syncwarp();
      STAMP(20);
      mbar_wait(sb + BAR_AE + 56, 0);
      STAMP(39);
      poll_counter(&p.scr->hcnt[(rb >> HGRP) * 32], tag * (4 << HGRP));
      STAMP(37);
      if (elect_one()) {
        uint32_t tp = clock();
#pragma unroll 1
        for (int it = 3; it < 12; it++) {
          if (HPACE && it > 3) { tp += HPACE; while ((int32_t)((uint32_t)clock() - tp) < 0) {} }
          bulk_g2s(sb + OFF_A + ((it + 5) % 9) * A_SLOT, p.scr->h + (size_t)(rb * 12 + g3_block(cb, it)) * A_SLOT, A_SLOT, sb + BAR_AF + 8 * ((it + 5) % 9));
        }
      }
      STAMP(21);
    } else if (warp == 13) {
      const uint32_t ztarget = __shfl_sync(0xffffffff, ld_relaxed(p.scr->cnt + CNT_Z), 0);
      int s = 0, ph = 0;
#pragma unroll 1
      for (int it = NB; it < 20; it++) {
        mbar_wait(sb + BAR_BE + 8 * s, ph);
        if (elect_one()) { mbar_expect(sb + BAR_BF + 8 * s, B_SLOT); tma3d(sb + OFF_B + s * B_SLOT, &p.tmW, 0, (it < 10 ? it : (it + zs0) % 10) * 64, (it < 10 ? 12 : 0) + cb * 3, sb + BAR_BF + 8 * s); }
        STAMP2(32 + it);
        if (++s == NB) { s = 0; ph ^= 1; }
      }
      mbar_wait(sb + BAR_XC, 0);
#pragma unroll 1
      for (int i = 0; i < LEAD; i++) {
        mbar_wait(sb + BAR_AE + 8 * i, 0);
        if (elect_one()) { mbar_expect(sb + BAR_AF + 8 * i, A_SLOT); tma_rows(sb + OFF_A + i * A_SLOT, &p.tmWsp, i * 64, rb, sb + BAR_AF + 8 * i); }
      }
      if (ZP_AT < 0) mbar_wait(sb + BAR_ZP, 0);
      poll_counter(p.scr->cnt + CNT_Z, (ztarget & ~127u) + 128);
      STAMP(22);
      int sa = LEAD, pa = 0, ia = LEAD;
#pragma unroll 1
      for (int it = 0; it < 32; it++) {
        if (it == ZP_AT) mbar_wait(sb + BAR_ZP, 0);
        if (it == 16) { mbar_wait(sb + BAR_Z1, 1); acquire_fence(); }
        mbar_wait2(sb + BAR_BE + 8 * s, ph, sb + BAR_AE + 8 * sa, pa);
        if (elect_one()) {
          mbar_expect(sb + BAR_BF + 8 * s, B_SLOT);
          bulk_g2s(sb + OFF_B + s * B_SLOT, p.scr->z2 + (size_t)(cb * 32 + it) * B_SLOT, B_SLOT, sb + BAR_BF + 8 * s);
        }
#pragma unroll 1
        for (int j = (it < RAMP ? 0 : (it == 4 ? 1 + RAMP : 1)); j > 0 && ia < 32; j--, ia++) {
          if (it == 4) mbar_wait(sb + BAR_AE + 8 * sa, pa);
          if (elect_one()) { mbar_expect(sb + BAR_AF + 8 * sa, A_SLOT); tma_rows(sb + OFF_A + sa * A_SLOT, &p.tmWsp, ia * 64, rb, sb + BAR_AF + 8 * sa); }
          if (++sa == NA2) { sa = 0; pa ^= 1; }
        }
        STAMP2(52 + it);
        if (++s == NB) { s = 0; ph ^= 1; }
      }
      mbar_wait(sb + BAR_WO, 0);
      acquire_fence();
#pragma unroll 1
      for (int it = 0; it < 12; it++) {
        if (it < 6) mbar_wait(sb + BAR_BE + 8 * ((0x110443 >> (4 * it)) & 7), it < 3 ? 1 : 0);
        else mbar_wait(sb + BAR_BE + 8 * s, ph);
        if (elect_one()) {
          mbar_expect(sb + BAR_BF + 8 * s, 20480);
          bulk_g2s(sb + OFF_B + (s == 5 ? 0 : s + 1) * 20480, p.scr->wo + (size_t)(cb * 12 + g3_block(cb, it)) * 20480, 20480, sb + BAR_BF + 8 * s);
        }
        STAMP2(84 + it);
        if (++s == 6) { s = 0; ph ^= 1; }
      }
    } else if (warp == 14) {
      const uint32_t tag = epoch + 1;
      uint32_t t0 = 0;
      mbar_wait(sb + BAR_AF + 8 * (NA - 1), 0);
#pragma unroll 1
      for (int part = 0; part < 2; part++) {
        uint4 v[3];
#pragma unroll 1
        while (true) {
          bool ok = true;
#pragma unroll
          for (int i = 0; i < 3; i++) {
            v[i] = ld_ll4(&p.scr->colsum[(part ? 0 : 768) + cb * 192 + i * 64 + lane * 2]);
            ok = ok && v[i].y == tag && v[i].w == tag;
          }
          if (__all_sync(0xffffffff, ok)) break;
          spin_guard(t0);
        }
#pragma unroll
        for (int i = 0; i < 3; i++) {
          const uint32_t hi = pack2(__uint_as_float(v[i].x), __uint_as_float(v[i].z)), ca = sb + OFF_CS + (1 - part) * 768 + i * 256 + (lane >> 2) * 32 + (lane & 3) * 4;
          sts32(ca, hi);
          sts32(ca + 16, pack2(__uint_as_float(v[i].x) - bf_lo(hi), __uint_as_float(v[i].z) - bf_hi(hi)));
        }
        if (!CFENCE) fence_async_smem();
        __syncwarp();
        if (lane == 0) mbar_arrive(sb + BAR_ST + 8 * part);
        if (part == 0) STAMP(27);
      }
      STAMP(38);
      bar_sync(NB_Z, ZORD ? 160 : 96);
      if (elect_one()) {
        z_store(p, sb + OFF_A + zs0 * A_SLOT, rb, cb, 0);
        red_release(p.scr->cnt + CNT_Z);
      }
      STAMP(25);
      bar_sync(NB_Z2, 96);
      if (elect_one()) {
        z_store(p, sb + OFF_A + zs0 * A_SLOT, rb, cb, 1);
        mbar_arrive(sb + BAR_ZP);
        red_release(p.scr->cnt + CNT_Z1);
      }
      STAMP(28);
      mbar_wait(sb + BAR_AE + 72, 0);
      conv_service(p, sb, 0, chb + 64, true);
      bar_sync(NB_WO, 160);
      bar_sync(NB_CD, 64);
      if (elect_one()) { red_release(p.scr->cnt + CNT_WO + cb); red_relaxed(p.scr->cnt + CNT_Y + (cb >> 1)); }
      STAMP(49);
      poll_counter(p.scr->cnt + CNT_WO + cb, tag * 32);
      if (elect_one()) mbar_arrive(sb + BAR_WO);
      STAMP(46);
      held_service(p, sb, 0, chb + 192, rb, cb, tag, lane);
    } else {
      const uint32_t tag = epoch + 1;
      sts32(sb + OFF_BIAS + lane * 4, ldg1(p.bsp + (lane >> 3) * 512 + rb * 16 + (lane & 7) * 2));
      if (lane < 2) sts32(sb + OFF_TAG + lane * 4, lane ? 0 : tag);
      fence_async_smem();
      uint32_t t0 = 0;
      mbar_wait(sb + BAR_AF + 8 * (NA - 1), 0);
#pragma unroll 1
      while (true) {
        const uint4 u = ld_ll4(&p.scr->xstat[rb * 64 + lane]), v = ld_ll4(&p.scr->xstat[rb * 64 + 32 + lane]);
        sts64f(sb + OFF_XS + lane * 8, __uint_as_float(u.x), __uint_as_float(u.z));
        sts64f(sb + OFF_XS + 256 + lane * 8, __uint_as_float(v.x), __uint_as_float(v.z));
        if (__all_sync(0xffffffff, u.y == tag && u.w == tag && v.y == tag && v.w == tag)) break;
        spin_guard(t0);
      }
      STAMP(26);
      __syncwarp();
      if (lane == 0) mbar_arrive(sb + BAR_XS);
      mbar_wait(sb + (K0_POLL ? BAR_KU + 16 : BAR_KU), K0_POLL ? 0 : 1);
      poll_counter(p.scr->cnt + CNT_KV + (cb >> 1), tag * 64);
      if (elect_one()) load_convx(p, sb + OFF_CV, sb + BAR_XF + 8, chb);
      mbar_wait(sb + BAR_KU + 8, 1);
      if (elect_one()) load_convx(p, sb + OFF_CV + CV_SZ, sb + BAR_XF, chb + 64);
      STAMP(48);
      mbar_wait(sb + BAR_AE + 72, 0);
#pragma unroll 1
      for (int i = 0; i < 2; i++) conv_service(p, sb, 1, chb + i * 128, i == 0);
      bar_arrive(NB_CD, 64);
      mbar_wait(sb + BAR_WO, 0);
      poll_counter(p.scr->cnt + CNT_Y + (cb >> 1), tag * 64);
      STAMP(47);
      if (elect_one()) mbar_arrive(sb + BAR_YT);
      held_service(p, sb, 1, chb + 256, rb, cb, tag, lane);
      if (lane == 0) *(volatile uint32_t*)&p.scr->epoch[lin] = tag;
      STAMP(23);
    }
  } else {
    if (warp == 7) STAMP(36);
    const int wg = warp >> 2, w = warp & 3, g = lane >> 2, t = lane & 3;
    Taps k;
    uint32_t xw[2][10];
    if (wg == 2) {
      asm volatile("setmaxnreg.inc.sync.aligned.u32 160;");
      const int tb = rb * 2 + (cb & 1), c0 = (cb >> 1) * 320;
      const uint32_t cv = sb + OFF_CV + CV_SZ;
      if (w == 0) zero_pads(sb + OFF_CV, lane);
      mbar_wait(sb + BAR_KV + 8, 0);
      const int t0 = tb * 32 + w * 8;
      const __nv_bfloat16* kp = p.k + (size_t)(t0 - 3) * kD + c0 + lane * 2;
      const __nv_bfloat16* vp = p.v + (size_t)t0 * kD + c0 + lane * 2;
      const __nv_bfloat16* sp = p.shift + (c0 + lane * 2) * 4;
      const uint32_t oa = cv + ((3 - w) & 1) * 1024 + lane * 32 + ((((3 - w) >> 1) ^ (lane >> 2)) & 1) * 16;
#pragma unroll 1
      for (int r = 0; r < 2; r++) {
        KvRegs n0, n1, n2;
        kv_load(n0, kp + r * 128, vp + r * 128, sp + r * 512, t0 > 0);
        kv_load(n1, kp + r * 128 + 64, vp + r * 128 + 64, sp + r * 512 + 256, t0 > 0);
        if (r) kv_load(n2, kp + 256, vp + 256, sp + 1024, t0 > 0);
        kv_unit(n0, oa + r * 8192);
        bar_sync(NB_WGC, 128);
        mbar_arrive_if(sb + BAR_KU + 16 * r, tid == 0);
        if (r) mbar_wait(sb + BAR_KU, 1);
        kv_unit(n1, oa + (r ? 0 : 4096));
        bar_sync(NB_WGC, 128);
        mbar_arrive_if(sb + BAR_KU + 16 * r + 8, tid == 0);
        if (r) {
          kv_unit(n2, oa + 4096);
          bar_sync(NB_WGC, 128);
          mbar_arrive_if(sb + BAR_KU + 32, tid == 0);
        } else {
          mbar_wait(sb + BAR_AF + 8 * ((cb >> 1) * 5 + 1), 0);
          mbar_wait2(sb + BAR_AF + 8 * ((cb >> 1) * 5 + 2), 0, sb + BAR_AF + 8 * ((cb >> 1) * 5 + 4), 0);
          final_load_x(xw, sb + OFF_A, cb, 1, w, lane);
          fence_async_smem();
          bar_sync(NB_WGC, 128);
          mbar_arrive_if(sb + BAR_XC, tid == 0);
        }
      }
      STAMPW(13);
      load_taps(k, p, chb, tid);
    } else {
      float d[96];
      if (wg == 0) st_ll2(&p.scr->zstat[(rb * 256 + cb * 64 + w * 16 + g + (t >> 1) * 8) * 2 + (t & 1)], 0, 0);
      else if ((tid & 7) == 0) st_ll4(&p.scr->xstat[rb * 64 + cb * 16 + (tid >> 3)], 0, 0, 0, 0);
      {
        #pragma unroll
        for (int i = 0; i < 96; i++) d[i] = 0.f;
        {
          if (__builtin_expect(wg == 1, 0)) {
            const int tid = tid_now();
            const uint32_t epoch = load_epoch(p, lin, lane);
            float s = 0.f, q = 0.f;
#pragma unroll 1
            for (int i = 0; i < 10; i++) {
              mbar_wait(sb + BAR_AF + 8 * i, 0);
              const uint4 x4 = lds128(sb + OFF_A + i * A_SLOT + cb * 2048 + tid * 16);
              const uint32_t u[4] = {x4.x, x4.y, x4.z, x4.w};
#pragma unroll
              for (int e = 0; e < 4; e++) { const float a = bf_lo(u[e]), c = bf_hi(u[e]); s += a + c; q = fmaf(a, a, q); q = fmaf(c, c, q); }
            }
#pragma unroll
            for (int o = 1; o <= 4; o <<= 1) { s += __shfl_xor_sync(0xffffffff, s, o); q += __shfl_xor_sync(0xffffffff, q, o); }
            const float m = s * (1.f / kD);
            const float r = rsqrtf(fmaxf(fmaf(-m, m, q * (1.f / kD)), 0.f) + 1e-5f);
            if ((tid & 7) == 0) st_ll4(&p.scr->xstat[rb * 64 + cb * 16 + (tid >> 3)], __float_as_uint(m), epoch + 1, __float_as_uint(r), epoch + 1);
            STAMPW(12);
            bar_sync(NB_G1, 256);
          }
          gemm_loop<192, true, 0, D1>(d, sb, 10, wg ? zs0 : 0, 0, 0, 0, wg, 2, tid_now(), [&]() { if (G1_AT == 0 && wg == 0) bar_arrive(NB_G1, 256); }, [](int) {});
          asm volatile("setmaxnreg.inc.sync.aligned.u32 160;");
          STAMPW(wg ? 14 : 1);
          if (wg == 0) ZS(0);
          mbar_wait2(sb + BAR_XS, 0, sb + BAR_ST + 8 * wg, 0);
          if (wg == 0) ZS(1);
        }
        const int t1 = tid_now();
        const uint32_t xa1 = sb + OFF_XS + (w * 16 + ((t1 & 31) >> 2)) * 8;
        const float2 s0 = lds64f(xa1), s1 = lds64f(xa1 + 64);
        uint32_t z[48];
        float st[4];
        if (CFENCE) fence_async_smem();
        fold_mean(d, sb + OFF_CS + (1 - wg) * 768, s0.x, s1.x, t1 & 3);
        if (G1_AT == 1 && wg == 0) bar_arrive(NB_G1, 256);
        WG_WAIT(0);
        acc_fence<96>(d);
        if (wg == 0) ZS(2);
        gelu_tile(d, z, st, s0.y, s1.y);
        const int tid = tid_now(), lane = tid & 31, g = lane >> 2, t = lane & 3;
        if (wg == 1) {
          uint32_t bra, brb;
          asm volatile("ld.shared.u16 %0, [%1];" : "=r"(bra) : "r"(sb + OFF_BIAS + (w * 16 + g) * 2));
          asm volatile("ld.shared.u16 %0, [%1+16];" : "=r"(brb) : "r"(sb + OFF_BIAS + (w * 16 + g) * 2));
#pragma unroll
          for (int j = 0; j < 96; j++) d[j] = bf_lo((j & 2) ? brb : bra);
          STAMPW(15);
          gemm_loop<192, true, 1, D2>(d, sb, 32, 0, 1, 20, 0, 2, 2, tid, [&]() { if (HOLD_AT < 32) mbar_arrive_if(sb + BAR_GO, tid == 0); }, [](int) {});
          if (HOLD_AT == 32) mbar_arrive_if(sb + BAR_GO, tid == 0);
          STAMPW(16);
          const int t2 = tid_now(), l2 = t2 & 31;
          const uint32_t ha = sb + OFF_A + 5 * A_SLOT + (l2 >> 4) * 1024 + (2 * w + ((l2 >> 3) & 1)) * 128 + (l2 & 7) * 16;
#pragma unroll
          for (int j = 0; j < 24; j += 2) {
#pragma unroll
            for (int e = 0; e < 4; e++) z[2 * j + e] = hmul2(z[2 * j + e], pack2(d[4 * j + 2 * e], d[4 * j + 2 * e + 1]));
            stsm4(ha + j * 1024, z[2 * j], z[2 * j + 1], z[2 * j + 2], z[2 * j + 3]);
          }
          fence_async_smem();
          bar_sync(NB_WGB, 128);
          mbar_arrive_if(sb + BAR_AF + 8 * (t2 == 3 ? (BAR_G2 - BAR_AF) / 8 : (t2 == 4 ? (BAR_GO - BAR_AF) / 8 : 5 + t2)), t2 < (HOLD_AT == 33 ? 5 : 4));
          STAMPW(17);
          {
            float e[80];
#pragma unroll
            for (int j = 0; j < 80; j++) e[j] = 0.f;
            gemm_loop<160, false, 2, DB>(e, sb, 12, 5, 0, 2, 0, 2, 2, tid_now(), []() {}, [](int) {});
            STAMPW(10);
            const int t3 = tid_now();
#pragma unroll
            for (int j = 0; j < 10; j++) {
              sts128(sb + OFF_A + j * 2048 + t3 * 16, pack2(e[8 * j], e[8 * j + 1]), pack2(e[8 * j + 2], e[8 * j + 3]), pack2(e[8 * j + 4], e[8 * j + 5]),
                     pack2(e[8 * j + 6], e[8 * j + 7]));
              if (j == 4) bar_arrive(NB_WO, 256);
            }
            bar_arrive(NB_Z, 256);
            STAMPW(45);
          }
          return;
        }
        ZS(3);
        const bool hi = t & 2;
        float a0 = (hi ? st[2] : st[0]) + __shfl_xor_sync(0xffffffff, hi ? st[0] : st[2], 2);
        float a1 = (hi ? st[3] : st[1]) + __shfl_xor_sync(0xffffffff, hi ? st[1] : st[3], 2);
        a0 = ((t & 1) ? a1 : a0) + __shfl_xor_sync(0xffffffff, (t & 1) ? a0 : a1, 1);
        const uint32_t tag = lds32<0>(sb + OFF_TAG);
        uint2* zs = p.scr->zstat + (rb * 256 + w * 16 + g + (t >> 1) * 8) * 2 + (t & 1);
        st_ll2(zs + cb * 128, __float_as_uint(a0), tag);
        STAMPW(2); ZS(4);
        uint2 u[4];
#pragma unroll
        for (int i = 0; i < 4; i++) u[i] = ld_ll2(zs + i * 128);
        const uint32_t keep = (cb & 2) ? 13 << 5 : 13;
        mbar_arrive_if(sb + BAR_AE + 8 * tid, tid < NA && !((keep >> tid) & 1));
        const uint32_t za = sb + OFF_A + zs0 * A_SLOT + (2 * w + ((lane >> 3) & 1)) * 3072 + (lane >> 4) * 128 + (lane & 7) * 16;
        const float ca = 0.5f * (hi ? s1.y : s0.y), inv = 1.f / 768.f;
        mbar_wait2(sb + BAR_AE + 8 * (zs0 + 2), 0, sb + BAR_XC, 0);
        ZS(6);
        uint32_t t0 = 0;
#pragma unroll 1
        while (!__all_sync(0xffffffff, u[0].y == tag && u[1].y == tag && u[2].y == tag && u[3].y == tag)) {
          spin_guard(t0);
#pragma unroll
          for (int i = 0; i < 4; i++) u[i] = ld_ll2(zs + i * 128);
        }
        STAMPW(3); ZS(7);
        a0 = ((__uint_as_float(u[0].x) + __uint_as_float(u[1].x)) + (__uint_as_float(u[2].x) + __uint_as_float(u[3].x))) * inv;
        a1 = __shfl_xor_sync(0xffffffff, a0, 1);
        const float m = (t & 1) ? a1 : a0, q = (t & 1) ? a0 : a1;
        const float r = bf_lo(pack2(ca * rsqrtf(fmaf(fmaxf(fmaf(-m, m, q), 0.f), ca * ca, 1e-5f)), 0.f));
        const uint32_t rn = pack2(r, -m * r), ro = __shfl_xor_sync(0xffffffff, rn, 2);
        const uint32_t ra2 = prmt(hi ? ro : rn, 0, 0x1010), n2a = prmt(hi ? ro : rn, 0, 0x3232), rb2 = prmt(hi ? rn : ro, 0, 0x1010), n2b = prmt(hi ? rn : ro, 0, 0x3232);
        if (ZORD && w >= 2) bar_sync(NB_Z, 160);
#pragma unroll
        for (int j = 0; j < 24; j += 2)
          stsm4(za + j * 128, hfma2(z[2 * j], ra2, n2a), hfma2(z[2 * j + 1], rb2, n2b), hfma2(z[2 * j + 2], ra2, n2a), hfma2(z[2 * j + 3], rb2, n2b));
        ZS(8);
        fence_async_smem();
        ZS(9);
        if (w < 2) bar_arrive(NB_Z, ZORD ? 160 : 96);
        else bar_arrive(NB_Z2, 96);
        final_load_x(xw, sb + OFF_A, cb, 0, w, lane);
        fence_async_smem();
        bar_sync(NB_WGA, 128);
        mbar_arrive_if(sb + BAR_AE + 8 * tid, tid < NA && ((keep >> tid) & 1));
      }
      {
        const uint32_t zero = lds32<0>(sb + OFF_TAG + 4);
#pragma unroll
        for (int i = 0; i < 20; i++) xw[i / 10][i % 10] |= zero;
      }
      load_taps(k, p, chb + 64, tid_now());
      STAMPW(4);
    }
    const int h = wg >> 1;
    {
    const int tid = tid_now(), lane = tid & 31;
    conv_worker(p, k, sb + OFF_CV + (1 - h) * CV_SZ, sb + OFF_A + 9 * A_SLOT + h * 4096, sb + BAR_XF + 8 * h, NB_WGA + h,
                chb + (h ? 0 : 64), 2 + h, sb + BAR_GO, w, lane, tid, h ? 40 : 5, rb, cb);
    {
      const int t3 = tid_now(), l3 = t3 & 31;
      const uint32_t xs_addr = sb + OFF_XS + (w * 16 + (l3 >> 2)) * 8;
      const float2 s0 = lds64f(xs_addr), s1 = lds64f(xs_addr + 64);
      const uint32_t ya = sb + y_tile(h) + ((l3 >> 4) * 8 + (l3 & 7)) * 128 + (((2 * w + ((l3 >> 3) & 1)) ^ (l3 & 7) ^ (rb & 7)) << 4);
      uint32_t sw[2][10];
      mbar_wait(sb + BAR_XF + 8 * h, h);
      final_s_early(sw, xw, ya, s0, s1);
      uint32_t ph = 1, t0 = 0, y[8];
#pragma unroll 1
      while (true) {
        mbar_wait(sb + BAR_YL + 16 * h, ph);
        if (bar_all(NB_WGA + h, 128, final_late(y, ya))) break;
        spin_guard(t0);
        ph ^= 1;
        if (t3 == 0) load_late_y(p, sb, h, rb, cb, lds32<0>(sb + OFF_TAG) & 1);
      }
#pragma unroll
      for (int e = 0; e < 8; e++) sw[e & 1][4 + (e >> 1)] = hmul2(sw[e & 1][4 + (e >> 1)], ~y[e]);
      __nv_bfloat16* o0 = p.out + (size_t)(w * 512 + rb * 16 + (l3 >> 2)) * kD + seg_col(cb, h);
      STAMPW(h ? 44 : 9);
      bar_sync(h ? NB_Z : NB_WO, 256);
      float d[40];
#pragma unroll
      for (int j = 0; j < 5; j++) {
        const uint4 v = lds128(sb + OFF_A + (h * 5 + j) * 2048 + t3 * 16);
        d[8 * j] = bf_lo(v.x); d[8 * j + 1] = bf_hi(v.x); d[8 * j + 2] = bf_lo(v.y); d[8 * j + 3] = bf_hi(v.y);
        d[8 * j + 4] = bf_lo(v.z); d[8 * j + 5] = bf_hi(v.z); d[8 * j + 6] = bf_lo(v.w); d[8 * j + 7] = bf_hi(v.w);
      }
      final_out(d, xw, sw, s0.y, s1.y, o0, h, l3 & 3);
    }
    }
  }
}

typedef CUresult (*EncodeFn)(CUtensorMap*, CUtensorMapDataType, cuuint32_t, void*, const cuuint64_t*, const cuuint64_t*, const cuuint32_t*,
                             const cuuint32_t*, CUtensorMapInterleave, CUtensorMapSwizzle, CUtensorMapL2promotion, CUtensorMapFloatOOBfill);

void encode(EncodeFn fn, CUtensorMap* m, const void* ptr, int rank, const cuuint64_t* dims, const cuuint64_t* strides, const cuuint32_t* box,
            CUtensorMapSwizzle swz = CU_TENSOR_MAP_SWIZZLE_128B) {
  const cuuint32_t es[3] = {1, 1, 1};
  fn(m, CU_TENSOR_MAP_DATA_TYPE_BFLOAT16, rank, const_cast<void*>(ptr), dims, strides, box, es, CU_TENSOR_MAP_INTERLEAVE_NONE,
     swz, CU_TENSOR_MAP_L2_PROMOTION_L2_128B, CU_TENSOR_MAP_FLOAT_OOB_FILL_NONE);
}

}

extern "C" void kernel_launch(void* const* d_in, const int* in_sizes, int n_in, void* d_out, int out_size) {
  (void)in_sizes; (void)n_in; (void)out_size;
  static EncodeFn enc = nullptr;
  static Scratch* scr = nullptr;
  static int sms = 0;
  if (!enc) {
    void* fn = nullptr;
    cudaDriverEntryPointQueryResult qr;
    cudaGetDriverEntryPoint("cuTensorMapEncodeTiled", &fn, cudaEnableDefault, &qr);
    enc = (EncodeFn)fn;
    cudaFuncSetAttribute(fused_kernel, cudaFuncAttributeMaxDynamicSharedMemorySize, SMEM_BYTES);
    cudaGetSymbolAddress((void**)&scr, g_scr);
    int dev = 0;
    cudaGetDevice(&dev);
    cudaDeviceGetAttribute(&sms, cudaDevAttrMultiProcessorCount, dev);
  }
  Params p;
  p.scr = scr;
  p.by_smid = sms == 132;
  p.k = (const __nv_bfloat16*)d_in[1];
  p.v = (const __nv_bfloat16*)d_in[2];
  p.shift = (const __nv_bfloat16*)d_in[3];
  p.ssmk = (const __nv_bfloat16*)d_in[4];
  p.ssmD = (const __nv_bfloat16*)d_in[5];
  p.wsp = (const __nv_bfloat16*)d_in[8];
  p.bsp = (const __nv_bfloat16*)d_in[9];
  p.wout = (const __nv_bfloat16*)d_in[10];
  p.out = (__nv_bfloat16*)d_out;
  for (int i = 0; i < 2; i++) {
    const cuuint64_t n = i ? kS : kD, dims[3] = {n, 512, 4}, st[2] = {n * 2, n * 1024};
    const cuuint32_t box[3] = {64, 16, 4};
    encode(enc, i ? &p.tmWsp : &p.tmX, d_in[i ? 8 : 0], 3, dims, st, box);
  }
  {
    const cuuint64_t dims[3] = {64, kD, kF / 64}, st[2] = {kF * 2, 128};
    const cuuint32_t box[3] = {64, 64, 3};
    encode(enc, &p.tmW, d_in[7], 3, dims, st, box);
  }
  {
    const cuuint64_t dims[2] = {kS, 896}, st[1] = {kS * 2};
    const cuuint32_t box[2] = {64, 16};
    encode(enc, &p.tmY, scr->y, 2, dims, st, box);
  }
  {
    const cuuint64_t dims[3] = {1024, kD / 2, 4}, st[2] = {8192, 2048};
    const cuuint32_t box[3] = {16, 32, 4};
    encode(enc, &p.tmKV, scr->kvx, 3, dims, st, box, CU_TENSOR_MAP_SWIZZLE_32B);
  }
  fused_kernel<<<132, 512, SMEM_BYTES, cudaStreamPerThread>>>(p);
}
```

```cpp
#include <cuda_runtime.h>
#include <cuda.h>
#include <cuda_bf16.h>
#include <stdint.h>

template <int N> struct WG;
template <> struct WG<16> {
  static __device__ __forceinline__ void rs(float* d, const uint32_t* a, uint64_t db) {
    asm volatile("{\n.reg .pred p;\nsetp.ne.b32 p, 1, 0;\nwgmma.mma_async.sync.aligned.m64n16k16.f32.bf16.bf16 {"
      "%0, %1, %2, %3, %4, %5, %6, %7"
      "}, {%8, %9, %10, %11}, %12, p, 1, 1, 0;\n}\n"
      :
      "+f"(d[0]), "+f"(d[1]), "+f"(d[2]), "+f"(d[3]), "+f"(d[4]), "+f"(d[5]), "+f"(d[6]), "+f"(d[7])
      : "r"(a[0]), "r"(a[1]), "r"(a[2]), "r"(a[3]), "l"(db));
  }
};
template <> struct WG<32> {
  static __device__ __forceinline__ void rs(float* d, const uint32_t* a, uint64_t db) {
    asm volatile("{\n.reg .pred p;\nsetp.ne.b32 p, 1, 0;\nwgmma.mma_async.sync.aligned.m64n32k16.f32.bf16.bf16 {"
      "%0, %1, %2, %3, %4, %5, %6, %7, %8, %9, %10, %11, %12, %13, %14, %15"
      "}, {%16, %17, %18, %19}, %20, p, 1, 1, 0;\n}\n"
      :
      "+f"(d[0]), "+f"(d[1]), "+f"(d[2]), "+f"(d[3]), "+f"(d[4]), "+f"(d[5]), "+f"(d[6]), "+f"(d[7]),
      "+f"(d[8]), "+f"(d[9]), "+f"(d[10]), "+f"(d[11]), "+f"(d[12]), "+f"(d[13]), "+f"(d[14]), "+f"(d[15])
      : "r"(a[0]), "r"(a[1]), "r"(a[2]), "r"(a[3]), "l"(db));
  }
};
template <> struct WG<48> {
  static __device__ __forceinline__ void rs(float* d, const uint32_t* a, uint64_t db) {
    asm volatile("{\n.reg .pred p;\nsetp.ne.b32 p, 1, 0;\nwgmma.mma_async.sync.aligned.m64n48k16.f32.bf16.bf16 {"
      "%0, %1, %2, %3, %4, %5, %6, %7, %8, %9, %10, %11, %12, %13, %14, %15, "
      "%16, %17, %18, %19, %20, %21, %22, %23"
      "}, {%24, %25, %26, %27}, %28, p, 1, 1, 0;\n}\n"
      :
      "+f"(d[0]), "+f"(d[1]), "+f"(d[2]), "+f"(d[3]), "+f"(d[4]), "+f"(d[5]), "+f"(d[6]), "+f"(d[7]),
      "+f"(d[8]), "+f"(d[9]), "+f"(d[10]), "+f"(d[11]), "+f"(d[12]), "+f"(d[13]), "+f"(d[14]), "+f"(d[15]),
      "+f"(d[16]), "+f"(d[17]), "+f"(d[18]), "+f"(d[19]), "+f"(d[20]), "+f"(d[21]), "+f"(d[22]), "+f"(d[23])
      : "r"(a[0]), "r"(a[1]), "r"(a[2]), "r"(a[3]), "l"(db));
  }
};
template <> struct WG<64> {
  static __device__ __forceinline__ void rs(float* d, const uint32_t* a, uint64_t db) {
    asm volatile("{\n.reg .pred p;\nsetp.ne.b32 p, 1, 0;\nwgmma.mma_async.sync.aligned.m64n64k16.f32.bf16.bf16 {"
      "%0, %1, %2, %3, %4, %5, %6, %7, %8, %9, %10, %11, %12, %13, %14, %15, "
      "%16, %17, %18, %19, %20, %21, %22, %23, %24, %25, %26, %27, %28, %29, %30, %31"
      "}, {%32, %33, %34, %35}, %36, p, 1, 1, 0;\n}\n"
      :
      "+f"(d[0]), "+f"(d[1]), "+f"(d[2]), "+f"(d[3]), "+f"(d[4]), "+f"(d[5]), "+f"(d[6]), "+f"(d[7]),
      "+f"(d[8]), "+f"(d[9]), "+f"(d[10]), "+f"(d[11]), "+f"(d[12]), "+f"(d[13]), "+f"(d[14]), "+f"(d[15]),
      "+f"(d[16]), "+f"(d[17]), "+f"(d[18]), "+f"(d[19]), "+f"(d[20]), "+f"(d[21]), "+f"(d[22]), "+f"(d[23]),
      "+f"(d[24]), "+f"(d[25]), "+f"(d[26]), "+f"(d[27]), "+f"(d[28]), "+f"(d[29]), "+f"(d[30]), "+f"(d[31])
      : "r"(a[0]), "r"(a[1]), "r"(a[2]), "r"(a[3]), "l"(db));
  }
};
template <> struct WG<80> {
  static __device__ __forceinline__ void rs(float* d, const uint32_t* a, uint64_t db) {
    asm volatile("{\n.reg .pred p;\nsetp.ne.b32 p, 1, 0;\nwgmma.mma_async.sync.aligned.m64n80k16.f32.bf16.bf16 {"
      "%0, %1, %2, %3, %4, %5, %6, %7, %8, %9, %10, %11, %12, %13, %14, %15, "
      "%16, %17, %18, %19, %20, %21, %22, %23, %24, %25, %26, %27, %28, %29, %30, %31, "
      "%32, %33, %34, %35, %36, %37, %38, %39"
      "}, {%40, %41, %42, %43}, %44, p, 1, 1, 0;\n}\n"
      :
      "+f"(d[0]), "+f"(d[1]), "+f"(d[2]), "+f"(d[3]), "+f"(d[4]), "+f"(d[5]), "+f"(d[6]), "+f"(d[7]),
      "+f"(d[8]), "+f"(d[9]), "+f"(d[10]), "+f"(d[11]), "+f"(d[12]), "+f"(d[13]), "+f"(d[14]), "+f"(d[15]),
      "+f"(d[16]), "+f"(d[17]), "+f"(d[18]), "+f"(d[19]), "+f"(d[20]), "+f"(d[21]), "+f"(d[22]), "+f"(d[23]),
      "+f"(d[24]), "+f"(d[25]), "+f"(d[26]), "+f"(d[27]), "+f"(d[28]), "+f"(d[29]), "+f"(d[30]), "+f"(d[31]),
      "+f"(d[32]), "+f"(d[33]), "+f"(d[34]), "+f"(d[35]), "+f"(d[36]), "+f"(d[37]), "+f"(d[38]), "+f"(d[39])
      : "r"(a[0]), "r"(a[1]), "r"(a[2]), "r"(a[3]), "l"(db));
  }
};
template <> struct WG<96> {
  static __device__ __forceinline__ void rs(float* d, const uint32_t* a, uint64_t db) {
    asm volatile("{\n.reg .pred p;\nsetp.ne.b32 p, 1, 0;\nwgmma.mma_async.sync.aligned.m64n96k16.f32.bf16.bf16 {"
      "%0, %1, %2, %3, %4, %5, %6, %7, %8, %9, %10, %11, %12, %13, %14, %15, "
      "%16, %17, %18, %19, %20, %21, %22, %23, %24, %25, %26, %27, %28, %29, %30, %31, "
      "%32, %33, %34, %35, %36, %37, %38, %39, %40, %41, %42, %43, %44, %45, %46, %47"
      "}, {%48, %49, %50, %51}, %52, p, 1, 1, 0;\n}\n"
      :
      "+f"(d[0]), "+f"(d[1]), "+f"(d[2]), "+f"(d[3]), "+f"(d[4]), "+f"(d[5]), "+f"(d[6]), "+f"(d[7]),
      "+f"(d[8]), "+f"(d[9]), "+f"(d[10]), "+f"(d[11]), "+f"(d[12]), "+f"(d[13]), "+f"(d[14]), "+f"(d[15]),
      "+f"(d[16]), "+f"(d[17]), "+f"(d[18]), "+f"(d[19]), "+f"(d[20]), "+f"(d[21]), "+f"(d[22]), "+f"(d[23]),
      "+f"(d[24]), "+f"(d[25]), "+f"(d[26]), "+f"(d[27]), "+f"(d[28]), "+f"(d[29]), "+f"(d[30]), "+f"(d[31]),
      "+f"(d[32]), "+f"(d[33]), "+f"(d[34]), "+f"(d[35]), "+f"(d[36]), "+f"(d[37]), "+f"(d[38]), "+f"(d[39]),
      "+f"(d[40]), "+f"(d[41]), "+f"(d[42]), "+f"(d[43]), "+f"(d[44]), "+f"(d[45]), "+f"(d[46]), "+f"(d[47])
      : "r"(a[0]), "r"(a[1]), "r"(a[2]), "r"(a[3]), "l"(db));
  }
};
template <> struct WG<112> {
  static __device__ __forceinline__ void rs(float* d, const uint32_t* a, uint64_t db) {
    asm volatile("{\n.reg .pred p;\nsetp.ne.b32 p, 1, 0;\nwgmma.mma_async.sync.aligned.m64n112k16.f32.bf16.bf16 {"
      "%0, %1, %2, %3, %4, %5, %6, %7, %8, %9, %10, %11, %12, %13, %14, %15, "
      "%16, %17, %18, %19, %20, %21, %22, %23, %24, %25, %26, %27, %28, %29, %30, %31, "
      "%32, %33, %34, %35, %36, %37, %38, %39, %40, %41, %42, %43, %44, %45, %46, %47, "
      "%48, %49, %50, %51, %52, %53, %54, %55"
      "}, {%56, %57, %58, %59}, %60, p, 1, 1, 0;\n}\n"
      :
      "+f"(d[0]), "+f"(d[1]), "+f"(d[2]), "+f"(d[3]), "+f"(d[4]), "+f"(d[5]), "+f"(d[6]), "+f"(d[7]),
      "+f"(d[8]), "+f"(d[9]), "+f"(d[10]), "+f"(d[11]), "+f"(d[12]), "+f"(d[13]), "+f"(d[14]), "+f"(d[15]),
      "+f"(d[16]), "+f"(d[17]), "+f"(d[18]), "+f"(d[19]), "+f"(d[20]), "+f"(d[21]), "+f"(d[22]), "+f"(d[23]),
      "+f"(d[24]), "+f"(d[25]), "+f"(d[26]), "+f"(d[27]), "+f"(d[28]), "+f"(d[29]), "+f"(d[30]), "+f"(d[31]),
      "+f"(d[32]), "+f"(d[33]), "+f"(d[34]), "+f"(d[35]), "+f"(d[36]), "+f"(d[37]), "+f"(d[38]), "+f"(d[39]),
      "+f"(d[40]), "+f"(d[41]), "+f"(d[42]), "+f"(d[43]), "+f"(d[44]), "+f"(d[45]), "+f"(d[46]), "+f"(d[47]),
      "+f"(d[48]), "+f"(d[49]), "+f"(d[50]), "+f"(d[51]), "+f"(d[52]), "+f"(d[53]), "+f"(d[54]), "+f"(d[55])
      : "r"(a[0]), "r"(a[1]), "r"(a[2]), "r"(a[3]), "l"(db));
  }
};
template <> struct WG<128> {
  static __device__ __forceinline__ void rs(float* d, const uint32_t* a, uint64_t db) {
    asm volatile("{\n.reg .pred p;\nsetp.ne.b32 p, 1, 0;\nwgmma.mma_async.sync.aligned.m64n128k16.f32.bf16.bf16 {"
      "%0, %1, %2, %3, %4, %5, %6, %7, %8, %9, %10, %11, %12, %13, %14, %15, "
      "%16, %17, %18, %19, %20, %21, %22, %23, %24, %25, %26, %27, %28, %29, %30, %31, "
      "%32, %33, %34, %35, %36, %37, %38, %39, %40, %41, %42, %43, %44, %45, %46, %47, "
      "%48, %49, %50, %51, %52, %53, %54, %55, %56, %57, %58, %59, %60, %61, %62, %63"
      "}, {%64, %65, %66, %67}, %68, p, 1, 1, 0;\n}\n"
      :
      "+f"(d[0]), "+f"(d[1]), "+f"(d[2]), "+f"(d[3]), "+f"(d[4]), "+f"(d[5]), "+f"(d[6]), "+f"(d[7]),
      "+f"(d[8]), "+f"(d[9]), "+f"(d[10]), "+f"(d[11]), "+f"(d[12]), "+f"(d[13]), "+f"(d[14]), "+f"(d[15]),
      "+f"(d[16]), "+f"(d[17]), "+f"(d[18]), "+f"(d[19]), "+f"(d[20]), "+f"(d[21]), "+f"(d[22]), "+f"(d[23]),
      "+f"(d[24]), "+f"(d[25]), "+f"(d[26]), "+f"(d[27]), "+f"(d[28]), "+f"(d[29]), "+f"(d[30]), "+f"(d[31]),
      "+f"(d[32]), "+f"(d[33]), "+f"(d[34]), "+f"(d[35]), "+f"(d[36]), "+f"(d[37]), "+f"(d[38]), "+f"(d[39]),
      "+f"(d[40]), "+f"(d[41]), "+f"(d[42]), "+f"(d[43]), "+f"(d[44]), "+f"(d[45]), "+f"(d[46]), "+f"(d[47]),
      "+f"(d[48]), "+f"(d[49]), "+f"(d[50]), "+f"(d[51]), "+f"(d[52]), "+f"(d[53]), "+f"(d[54]), "+f"(d[55]),
      "+f"(d[56]), "+f"(d[57]), "+f"(d[58]), "+f"(d[59]), "+f"(d[60]), "+f"(d[61]), "+f"(d[62]), "+f"(d[63])
      : "r"(a[0]), "r"(a[1]), "r"(a[2]), "r"(a[3]), "l"(db));
  }
};
template <> struct WG<160> {
  static __device__ __forceinline__ void ss(float* d, uint64_t da, uint64_t db, int sd) {
    asm volatile("{\n.reg .pred p;\nsetp.ne.b32 p, %82, 0;\nwgmma.mma_async.sync.aligned.m64n160k16.f32.bf16.bf16 {"
      "%0, %1, %2, %3, %4, %5, %6, %7, %8, %9, %10, %11, %12, %13, %14, %15, "
      "%16, %17, %18, %19, %20, %21, %22, %23, %24, %25, %26, %27, %28, %29, %30, %31, "
      "%32, %33, %34, %35, %36, %37, %38, %39, %40, %41, %42, %43, %44, %45, %46, %47, "
      "%48, %49, %50, %51, %52, %53, %54, %55, %56, %57, %58, %59, %60, %61, %62, %63, "
      "%64, %65, %66, %67, %68, %69, %70, %71, %72, %73, %74, %75, %76, %77, %78, %79"
      "}, %80, %81, p, 1, 1, 0, 1;\n}\n"
      :
      "+f"(d[0]), "+f"(d[1]), "+f"(d[2]), "+f"(d[3]), "+f"(d[4]), "+f"(d[5]), "+f"(d[6]), "+f"(d[7]),
      "+f"(d[8]), "+f"(d[9]), "+f"(d[10]), "+f"(d[11]), "+f"(d[12]), "+f"(d[13]), "+f"(d[14]), "+f"(d[15]),
      "+f"(d[16]), "+f"(d[17]), "+f"(d[18]), "+f"(d[19]), "+f"(d[20]), "+f"(d[21]), "+f"(d[22]), "+f"(d[23]),
      "+f"(d[24]), "+f"(d[25]), "+f"(d[26]), "+f"(d[27]), "+f"(d[28]), "+f"(d[29]), "+f"(d[30]), "+f"(d[31]),
      "+f"(d[32]), "+f"(d[33]), "+f"(d[34]), "+f"(d[35]), "+f"(d[36]), "+f"(d[37]), "+f"(d[38]), "+f"(d[39]),
      "+f"(d[40]), "+f"(d[41]), "+f"(d[42]), "+f"(d[43]), "+f"(d[44]), "+f"(d[45]), "+f"(d[46]), "+f"(d[47]),
      "+f"(d[48]), "+f"(d[49]), "+f"(d[50]), "+f"(d[51]), "+f"(d[52]), "+f"(d[53]), "+f"(d[54]), "+f"(d[55]),
      "+f"(d[56]), "+f"(d[57]), "+f"(d[58]), "+f"(d[59]), "+f"(d[60]), "+f"(d[61]), "+f"(d[62]), "+f"(d[63]),
      "+f"(d[64]), "+f"(d[65]), "+f"(d[66]), "+f"(d[67]), "+f"(d[68]), "+f"(d[69]), "+f"(d[70]), "+f"(d[71]),
      "+f"(d[72]), "+f"(d[73]), "+f"(d[74]), "+f"(d[75]), "+f"(d[76]), "+f"(d[77]), "+f"(d[78]), "+f"(d[79])
      : "l"(da), "l"(db), "r"(sd));
  }
};
template <> struct WG<192> {
  static __device__ __forceinline__ void ss(float* d, uint64_t da, uint64_t db, int sd) {
    asm volatile("{\n.reg .pred p;\nsetp.ne.b32 p, %98, 0;\nwgmma.mma_async.sync.aligned.m64n192k16.f32.bf16.bf16 {"
      "%0, %1, %2, %3, %4, %5, %6, %7, %8, %9, %10, %11, %12, %13, %14, %15, "
      "%16, %17, %18, %19, %20, %21, %22, %23, %24, %25, %26, %27, %28, %29, %30, %31, "
      "%32, %33, %34, %35, %36, %37, %38, %39, %40, %41, %42, %43, %44, %45, %46, %47, "
      "%48, %49, %50, %51, %52, %53, %54, %55, %56, %57, %58, %59, %60, %61, %62, %63, "
      "%64, %65, %66, %67, %68, %69, %70, %71, %72, %73, %74, %75, %76, %77, %78, %79, "
      "%80, %81, %82, %83, %84, %85, %86, %87, %88, %89, %90, %91, %92, %93, %94, %95"
      "}, %96, %97, p, 1, 1, 0, 1;\n}\n"
      :
      "+f"(d[0]), "+f"(d[1]), "+f"(d[2]), "+f"(d[3]), "+f"(d[4]), "+f"(d[5]), "+f"(d[6]), "+f"(d[7]),
      "+f"(d[8]), "+f"(d[9]), "+f"(d[10]), "+f"(d[11]), "+f"(d[12]), "+f"(d[13]), "+f"(d[14]), "+f"(d[15]),
      "+f"(d[16]), "+f"(d[17]), "+f"(d[18]), "+f"(d[19]), "+f"(d[20]), "+f"(d[21]), "+f"(d[22]), "+f"(d[23]),
      "+f"(d[24]), "+f"(d[25]), "+f"(d[26]), "+f"(d[27]), "+f"(d[28]), "+f"(d[29]), "+f"(d[30]), "+f"(d[31]),
      "+f"(d[32]), "+f"(d[33]), "+f"(d[34]), "+f"(d[35]), "+f"(d[36]), "+f"(d[37]), "+f"(d[38]), "+f"(d[39]),
      "+f"(d[40]), "+f"(d[41]), "+f"(d[42]), "+f"(d[43]), "+f"(d[44]), "+f"(d[45]), "+f"(d[46]), "+f"(d[47]),
      "+f"(d[48]), "+f"(d[49]), "+f"(d[50]), "+f"(d[51]), "+f"(d[52]), "+f"(d[53]), "+f"(d[54]), "+f"(d[55]),
      "+f"(d[56]), "+f"(d[57]), "+f"(d[58]), "+f"(d[59]), "+f"(d[60]), "+f"(d[61]), "+f"(d[62]), "+f"(d[63]),
      "+f"(d[64]), "+f"(d[65]), "+f"(d[66]), "+f"(d[67]), "+f"(d[68]), "+f"(d[69]), "+f"(d[70]), "+f"(d[71]),
      "+f"(d[72]), "+f"(d[73]), "+f"(d[74]), "+f"(d[75]), "+f"(d[76]), "+f"(d[77]), "+f"(d[78]), "+f"(d[79]),
      "+f"(d[80]), "+f"(d[81]), "+f"(d[82]), "+f"(d[83]), "+f"(d[84]), "+f"(d[85]), "+f"(d[86]), "+f"(d[87]),
      "+f"(d[88]), "+f"(d[89]), "+f"(d[90]), "+f"(d[91]), "+f"(d[92]), "+f"(d[93]), "+f"(d[94]), "+f"(d[95])
      : "l"(da), "l"(db), "r"(sd));
  }
  static __device__ __forceinline__ void rst(float* d, const uint32_t* a, uint64_t db) {
    asm volatile("{\n.reg .pred p;\nsetp.ne.b32 p, 1, 0;\nwgmma.mma_async.sync.aligned.m64n192k16.f32.bf16.bf16 {"
      "%0, %1, %2, %3, %4, %5, %6, %7, %8, %9, %10, %11, %12, %13, %14, %15, "
      "%16, %17, %18, %19, %20, %21, %22, %23, %24, %25, %26, %27, %28, %29, %30, %31, "
      "%32, %33, %34, %35, %36, %37, %38, %39, %40, %41, %42, %43, %44, %45, %46, %47, "
      "%48, %49, %50, %51, %52, %53, %54, %55, %56, %57, %58, %59, %60, %61, %62, %63, "
      "%64, %65, %66, %67, %68, %69, %70, %71, %72, %73, %74, %75, %76, %77, %78, %79, "
      "%80, %81, %82, %83, %84, %85, %86, %87, %88, %89, %90, %91, %92, %93, %94, %95"
      "}, {%96, %97, %98, %99}, %100, p, 1, 1, 1;\n}\n"
      :
      "+f"(d[0]), "+f"(d[1]), "+f"(d[2]), "+f"(d[3]), "+f"(d[4]), "+f"(d[5]), "+f"(d[6]), "+f"(d[7]),
      "+f"(d[8]), "+f"(d[9]), "+f"(d[10]), "+f"(d[11]), "+f"(d[12]), "+f"(d[13]), "+f"(d[14]), "+f"(d[15]),
      "+f"(d[16]), "+f"(d[17]), "+f"(d[18]), "+f"(d[19]), "+f"(d[20]), "+f"(d[21]), "+f"(d[22]), "+f"(d[23]),
      "+f"(d[24]), "+f"(d[25]), "+f"(d[26]), "+f"(d[27]), "+f"(d[28]), "+f"(d[29]), "+f"(d[30]), "+f"(d[31]),
      "+f"(d[32]), "+f"(d[33]), "+f"(d[34]), "+f"(d[35]), "+f"(d[36]), "+f"(d[37]), "+f"(d[38]), "+f"(d[39]),
      "+f"(d[40]), "+f"(d[41]), "+f"(d[42]), "+f"(d[43]), "+f"(d[44]), "+f"(d[45]), "+f"(d[46]), "+f"(d[47]),
      "+f"(d[48]), "+f"(d[49]), "+f"(d[50]), "+f"(d[51]), "+f"(d[52]), "+f"(d[53]), "+f"(d[54]), "+f"(d[55]),
      "+f"(d[56]), "+f"(d[57]), "+f"(d[58]), "+f"(d[59]), "+f"(d[60]), "+f"(d[61]), "+f"(d[62]), "+f"(d[63]),
      "+f"(d[64]), "+f"(d[65]), "+f"(d[66]), "+f"(d[67]), "+f"(d[68]), "+f"(d[69]), "+f"(d[70]), "+f"(d[71]),
      "+f"(d[72]), "+f"(d[73]), "+f"(d[74]), "+f"(d[75]), "+f"(d[76]), "+f"(d[77]), "+f"(d[78]), "+f"(d[79]),
      "+f"(d[80]), "+f"(d[81]), "+f"(d[82]), "+f"(d[83]), "+f"(d[84]), "+f"(d[85]), "+f"(d[86]), "+f"(d[87]),
      "+f"(d[88]), "+f"(d[89]), "+f"(d[90]), "+f"(d[91]), "+f"(d[92]), "+f"(d[93]), "+f"(d[94]), "+f"(d[95])
      : "r"(a[0]), "r"(a[1]), "r"(a[2]), "r"(a[3]), "l"(db));
  }
};

#define ZP_AT 1
#define CPRE0 1
#define ZORD 1
#define CS1BY 1
#define CS1_T 9500
#define Z1_AT 4
#define G1_AT 0
#define HGRP 3
#define HPACE 200
#define DB 0
#define HOLD_AT 33
#define LL_AT 4
#define KV_T0 2300
#define ST_YIELD 1
#define HP0 0
#define HPD 0
#define RAMP 1
#define LEAD 2
#define WSP_N 16
#define EARLY 0
#define CPIN 1
#define CW0 0
#define PFT 1
#define WSP_D 600
#define D1 4
#define D2 4
#define NSLEEP 32

static_assert(ZP_AT <= RAMP && LEAD <= 2, "staging slots");

namespace {

constexpr int kS = 2048, kD = 640, kF = 1536;
constexpr int NA = 10, NA2 = 9, NB = 5;
constexpr int A_SLOT = 8192, B_SLOT = 24576;
constexpr int OFF_A = 0;
constexpr int OFF_B = OFF_A + NA * A_SLOT;
constexpr int XB_PL = 2112;
constexpr int CV_KE = 4224, CV_KO = CV_KE + 4160;
constexpr int CV_SZ = CV_KO + 4160;
constexpr int OFF_CV = OFF_B + NB * B_SLOT;
constexpr int OFF_CS = OFF_CV + 2 * CV_SZ;
constexpr int OFF_BIAS = OFF_CS + 1536;
constexpr int OFF_XS = OFF_BIAS + 128;
constexpr int OFF_BAR = OFF_XS + 512;
constexpr int BAR_AF = OFF_BAR, BAR_ST = BAR_AF + 8 * NA, BAR_XF = BAR_ST + 16, BAR_KV = BAR_XF + 16;
constexpr int BAR_BF = OFF_BAR + 128, BAR_G2 = BAR_BF + 8 * (NB + 1), BAR_XS = BAR_G2 + 8, BAR_KU = BAR_XS + 8, BAR_ZP = BAR_KU + 40, BAR_XC = BAR_ZP + 8, BAR_WO = BAR_XC + 8;
constexpr int BAR_AE = OFF_BAR + 256, BAR_BE = BAR_AE + 8 * NA;
constexpr int BAR_YT = BAR_KU + 24;
constexpr int BAR_Z1 = BAR_ST;
constexpr int BAR_GO = BAR_XS;
constexpr int BAR_YL = BAR_KU + 16;
constexpr int OFF_TAG = OFF_CS - 32;
constexpr int SMEM_BYTES = OFF_BAR + 384;
static_assert(SMEM_BYTES <= 232448, "smem");
constexpr int NB_WGA = 1, NB_WGC = 2, NB_G1 = 3, NB_WO = 4, NB_CD = 5, NB_Z = 6, NB_WGB = 7, NB_Z2 = 8;

constexpr int CNT_Z = 0, CNT_Y = 1, CNT_Z1 = 3, CNT_KV = 32, CNT_WO = 36;
struct Scratch {
  uint8_t kvx[kD * 4096];
  uint8_t z2[4 * 32 * 24576];
  uint8_t h[32 * 12 * 8192];
  uint8_t wo[4 * 12 * 20480];
  uint8_t y[896 * 4096];
  uint4 xstat[kS];
  uint2 zstat[kS * 8];
  uint2 colsum[kF];
  uint32_t cnt[2 * 32];
  uint32_t hcnt[32 * 32];
  uint32_t epoch[136];
};
__device__ __align__(1024) Scratch g_scr;
#define ZS(i)
#define STAMP(i)
#define STAMP2(i)
#define STAMPW(i)

struct Params {
  Scratch* scr;
  int by_smid;
  const __nv_bfloat16 *k, *v, *shift, *ssmk, *ssmD, *wsp, *bsp, *wout;
  __nv_bfloat16* out;
  CUtensorMap tmX, tmW, tmWsp, tmY, tmKV;
};

__device__ __forceinline__ uint64_t mkdesc(uint32_t addr, uint32_t lbo, uint32_t sbo, uint32_t swz) {
  return (uint64_t)((addr & 0x3FFFF) >> 4) | ((uint64_t)(lbo >> 4) << 16) | ((uint64_t)(sbo >> 4) << 32) | ((uint64_t)swz << 62);
}
#define WG_FENCE() asm volatile("wgmma.fence.sync.aligned;" ::: "memory")
#define WG_COMMIT() asm volatile("wgmma.commit_group.sync.aligned;" ::: "memory")
#define WG_WAIT(n) asm volatile("wgmma.wait_group.sync.aligned %0;" ::"n"(n) : "memory")
template <int N> __device__ __forceinline__ void acc_fence(float* d) {
#pragma unroll
  for (int i = 0; i < N; i++) asm volatile("" : "+f"(d[i])::"memory");
}
__device__ __forceinline__ void mbar_init(uint32_t bar, int cnt) { asm volatile("mbarrier.init.shared::cta.b64 [%0], %1;" ::"r"(bar), "r"(cnt) : "memory"); }
__device__ __forceinline__ void mbar_expect(uint32_t bar, uint32_t bytes) { asm volatile("mbarrier.arrive.expect_tx.shared::cta.b64 _, [%0], %1;" ::"r"(bar), "r"(bytes) : "memory"); }
__device__ __forceinline__ void mbar_arrive(uint32_t bar) { asm volatile("mbarrier.arrive.shared::cta.b64 _, [%0];" ::"r"(bar) : "memory"); }
__device__ __forceinline__ void mbar_arrive_if(uint32_t bar, bool c) {
  asm volatile("{\n.reg .pred p;\nsetp.ne.u32 p, %1, 0;\n@p mbarrier.arrive.shared::cta.b64 _, [%0];\n}\n" ::"r"(bar), "r"((uint32_t)c) : "memory");
}
__device__ __forceinline__ void mbar_expect_if(uint32_t bar, uint32_t bytes, bool c) {
  asm volatile("{\n.reg .pred p;\nsetp.ne.u32 p, %2, 0;\n@p mbarrier.arrive.expect_tx.shared::cta.b64 _, [%0], %1;\n}\n" ::"r"(bar), "r"(bytes), "r"((uint32_t)c) : "memory");
}
__device__ __forceinline__ bool mbar_try(uint32_t bar, uint32_t parity) {
  uint32_t ok;
  asm volatile("{\n.reg .pred p;\nmbarrier.try_wait.parity.shared::cta.b64 p, [%1], %2;\nselp.u32 %0, 1, 0, p;\n}\n" : "=r"(ok) : "r"(bar), "r"(parity) : "memory");
  return ok;
}
__device__ __forceinline__ bool mbar_test(uint32_t bar, uint32_t parity) {
  uint32_t ok;
  asm volatile("{\n.reg .pred p;\nmbarrier.test_wait.parity.shared::cta.b64 p, [%1], %2;\nselp.u32 %0, 1, 0, p;\n}\n" : "=r"(ok) : "r"(bar), "r"(parity) : "memory");
  return ok;
}
__device__ __forceinline__ void die() { asm volatile("st.volatile.global.u32 [%0], %1;" ::"l"(0ull), "r"(0) : "memory"); }
__device__ __forceinline__ void spin_guard(uint32_t& n) { if (++n == (1u << 22)) die(); }
__device__ __forceinline__ void mbar_wait(uint32_t bar, uint32_t parity) {
  uint32_t t0 = 0;
#pragma unroll 1
  while (!mbar_try(bar, parity)) spin_guard(t0);
}
__device__ __forceinline__ void mbar_wait2(uint32_t b0, uint32_t p0, uint32_t b1, uint32_t p1) {
  uint32_t t0 = 0;
#pragma unroll 1
  while (true) {
    const bool r0 = mbar_try(b0, p0), r1 = mbar_try(b1, p1);
    if (r0 && r1) break;
    spin_guard(t0);
  }
}
__device__ __forceinline__ int tid_now() { int v; asm volatile("mov.u32 %0, %%tid.x;" : "=r"(v)); return v & 127; }
__device__ __forceinline__ bool elect_one() {
  uint32_t p;
  asm volatile("{\n.reg .pred P;\nelect.sync _|P, 0xffffffff;\nselp.u32 %0, 1, 0, P;\n}\n" : "=r"(p));
  return p;
}
__device__ __forceinline__ void bar_sync(int id, int n) { asm volatile("bar.sync %0, %1;" ::"r"(id), "r"(n) : "memory"); }
__device__ __forceinline__ void bar_arrive(int id, int n) { asm volatile("bar.arrive %0, %1;" ::"r"(id), "r"(n) : "memory"); }
__device__ __forceinline__ void fence_async_smem() { asm volatile("fence.proxy.async.shared::cta;" ::: "memory"); }
__device__ __forceinline__ void bulk_g2s(uint32_t dst, const void* src, uint32_t bytes, uint32_t bar) {
  asm volatile("cp.async.bulk.shared::cluster.global.mbarrier::complete_tx::bytes [%0], [%1], %2, [%3];" ::"r"(dst), "l"(src), "r"(bytes), "r"(bar) : "memory");
}
__device__ __forceinline__ void bulk_s2g(void* dst, uint32_t src, uint32_t bytes) {
  asm volatile("cp.async.bulk.global.shared::cta.bulk_group [%0], [%1], %2;" ::"l"(dst), "r"(src), "r"(bytes) : "memory");
}
__device__ __forceinline__ void tma2d(uint32_t dst, const CUtensorMap* m, int c0, int c1, uint32_t bar) {
  asm volatile("cp.async.bulk.tensor.2d.shared::cluster.global.mbarrier::complete_tx::bytes [%0], [%1, {%3, %4}], [%2];" ::"r"(dst), "l"(m), "r"(bar), "r"(c0), "r"(c1) : "memory");
}
__device__ __forceinline__ void tma3d(uint32_t dst, const CUtensorMap* m, int c0, int c1, int c2, uint32_t bar) {
  asm volatile("cp.async.bulk.tensor.3d.shared::cluster.global.mbarrier::complete_tx::bytes [%0], [%1, {%3, %4, %5}], [%2];" ::"r"(dst), "l"(m), "r"(bar), "r"(c0), "r"(c1), "r"(c2) : "memory");
}
__device__ __forceinline__ void tma_rows(uint32_t dst, const CUtensorMap* m, int c0, int rb, uint32_t bar) { tma3d(dst, m, c0, rb * 16, 0, bar); }
__device__ __forceinline__ uint4 ld_ll4(const void* p) {
  uint64_t a, b;
  asm volatile("ld.relaxed.gpu.global.v2.u64 {%0,%1}, [%2];" : "=l"(a), "=l"(b) : "l"(p) : "memory");
  return make_uint4((uint32_t)a, (uint32_t)(a >> 32), (uint32_t)b, (uint32_t)(b >> 32));
}
__device__ __forceinline__ void st_ll4(void* p, uint32_t a, uint32_t b, uint32_t c, uint32_t d) {
  asm volatile("st.relaxed.gpu.global.v2.u64 [%0], {%1,%2};" ::"l"(p), "l"(a | ((uint64_t)b << 32)), "l"(c | ((uint64_t)d << 32)) : "memory");
}
__device__ __forceinline__ void st_ll2(void* p, uint32_t a, uint32_t b) { asm volatile("st.relaxed.gpu.global.u64 [%0], %1;" ::"l"(p), "l"(a | ((uint64_t)b << 32)) : "memory"); }
__device__ __forceinline__ uint2 ld_ll2(const void* p) {
  uint64_t a;
  asm volatile("ld.relaxed.gpu.global.u64 %0, [%1];" : "=l"(a) : "l"(p) : "memory");
  return make_uint2((uint32_t)a, (uint32_t)(a >> 32));
}
__device__ __forceinline__ void wgmma_colsum(float* d, uint64_t da, uint64_t db) {
  asm volatile("{\n.reg .pred p;\nsetp.ne.b32 p, 1, 0;\nwgmma.mma_async.sync.aligned.m64n8k16.f32.bf16.bf16 {%0, %1, %2, %3}, %4, %5, p, 1, 1, 1, 0;\n}\n"
               : "+f"(d[0]), "+f"(d[1]), "+f"(d[2]), "+f"(d[3]) : "l"(da), "l"(db));
}
__device__ __forceinline__ void prefetch_l2(const void* p) { asm volatile("prefetch.global.L2 [%0];" ::"l"(p)); }
__device__ __forceinline__ void pace(uint32_t& t, uint32_t dt) {
  t += dt;
  while ((int32_t)((uint32_t)clock() - t) < 0) { if (NSLEEP) __nanosleep(NSLEEP); }
}
__device__ __forceinline__ void red_relaxed(uint32_t* p) { asm volatile("red.relaxed.gpu.global.add.u32 [%0], 1;" ::"l"(p) : "memory"); }
__device__ __forceinline__ void red_release(uint32_t* p) { asm volatile("red.release.gpu.global.add.u32 [%0], 1;" ::"l"(p) : "memory"); }
__device__ __forceinline__ uint4 ldg4(const void* p) { uint4 v; asm volatile("ld.global.v4.u32 {%0,%1,%2,%3}, [%4];" : "=r"(v.x), "=r"(v.y), "=r"(v.z), "=r"(v.w) : "l"(p) : "memory"); return v; }
__device__ __forceinline__ uint32_t ldg1(const void* p) { uint32_t v; asm volatile("ld.global.u32 %0, [%1];" : "=r"(v) : "l"(p) : "memory"); return v; }
__device__ __forceinline__ void stg4_if(void* p, uint32_t a, uint32_t b, uint32_t c, uint32_t d, bool on) {
  asm volatile("{\n.reg .pred p;\nsetp.ne.u32 p, %5, 0;\n@p st.global.v4.u32 [%0], {%1,%2,%3,%4};\n}\n" ::"l"(p), "r"(a), "r"(b), "r"(c), "r"(d), "r"((uint32_t)on) : "memory");
}
template <int OFF> __device__ __forceinline__ uint32_t lds32(uint32_t a) { uint32_t v; asm volatile("ld.shared.u32 %0, [%1+%2];" : "=r"(v) : "r"(a), "n"(OFF)); return v; }
__device__ __forceinline__ uint4 lds128(uint32_t a) { uint4 v; asm volatile("ld.shared.v4.u32 {%0,%1,%2,%3}, [%4];" : "=r"(v.x), "=r"(v.y), "=r"(v.z), "=r"(v.w) : "r"(a) : "memory"); return v; }
__device__ __forceinline__ float2 lds64f(uint32_t a) { float2 v; asm volatile("ld.shared.v2.f32 {%0,%1}, [%2];" : "=f"(v.x), "=f"(v.y) : "r"(a) : "memory"); return v; }
__device__ __forceinline__ void sts64f(uint32_t a, float x, float y) { asm volatile("st.shared.v2.f32 [%0], {%1,%2};" ::"r"(a), "f"(x), "f"(y) : "memory"); }
__device__ __forceinline__ void sts32(uint32_t a, uint32_t x) { asm volatile("st.shared.u32 [%0], %1;" ::"r"(a), "r"(x) : "memory"); }
__device__ __forceinline__ void sts128(uint32_t a, uint32_t x, uint32_t y, uint32_t z, uint32_t w) { asm volatile("st.shared.v4.u32 [%0], {%1,%2,%3,%4};" ::"r"(a), "r"(x), "r"(y), "r"(z), "r"(w) : "memory"); }
__device__ __forceinline__ void stsm4(uint32_t a, uint32_t r0, uint32_t r1, uint32_t r2, uint32_t r3) {
  asm volatile("stmatrix.sync.aligned.m8n8.x4.shared.b16 [%0], {%1,%2,%3,%4};" ::"r"(a), "r"(r0), "r"(r1), "r"(r2), "r"(r3) : "memory");
}
__device__ __forceinline__ void stsm4t(uint32_t a, uint32_t r0, uint32_t r1, uint32_t r2, uint32_t r3) {
  asm volatile("stmatrix.sync.aligned.m8n8.x4.trans.shared.b16 [%0], {%1,%2,%3,%4};" ::"r"(a), "r"(r0), "r"(r1), "r"(r2), "r"(r3) : "memory");
}
__device__ __forceinline__ void ldsm4t(uint32_t* r, uint32_t a) {
  asm volatile("ldmatrix.sync.aligned.m8n8.x4.trans.shared.b16 {%0,%1,%2,%3}, [%4];" : "=r"(r[0]), "=r"(r[1]), "=r"(r[2]), "=r"(r[3]) : "r"(a) : "memory");
}
__device__ __forceinline__ uint32_t pack2(float lo, float hi) { uint32_t r; asm("cvt.rn.bf16x2.f32 %0, %1, %2;" : "=r"(r) : "f"(hi), "f"(lo)); return r; }
__device__ __forceinline__ float bf_lo(uint32_t u) { return __uint_as_float(u << 16); }
__device__ __forceinline__ float bf_hi(uint32_t u) { return __uint_as_float(u & 0xffff0000u); }
__device__ __forceinline__ float tanh_fast(float x) { float y; asm("tanh.approx.f32 %0, %1;" : "=f"(y) : "f"(x)); return y; }
__device__ __forceinline__ uint32_t hmul2(uint32_t a, uint32_t b) { uint32_t r; asm("mul.rn.bf16x2 %0, %1, %2;" : "=r"(r) : "r"(a), "r"(b)); return r; }
__device__ __forceinline__ uint32_t hfma2(uint32_t a, uint32_t b, uint32_t c) { uint32_t r; asm("fma.rn.bf16x2 %0, %1, %2, %3;" : "=r"(r) : "r"(a), "r"(b), "r"(c)); return r; }
__device__ __forceinline__ uint32_t prmt(uint32_t a, uint32_t b, uint32_t s) { return __byte_perm(a, b, s); }

__device__ __forceinline__ uint32_t ld_relaxed(const uint32_t* p) { uint32_t v; asm volatile("ld.relaxed.gpu.global.u32 %0, [%1];" : "=r"(v) : "l"(p) : "memory"); return v; }
__device__ __forceinline__ void acquire_fence() { asm volatile("fence.acquire.gpu;\nfence.proxy.async.global;" ::: "memory"); }
__device__ __forceinline__ uint32_t load_epoch(const Params& p, int idx, int lane) { return ld_relaxed(&p.scr->epoch[idx + (((lane * lane) & 3) == 2 ? 1 : 0)]); }
__device__ __forceinline__ void poll_counter(const uint32_t* cnt, uint32_t target) {
  uint32_t t0 = 0;
#pragma unroll 1
  while (!__all_sync(0xffffffff, ld_relaxed(cnt) == target)) spin_guard(t0);
  acquire_fence();
}

__device__ __forceinline__ int g3_block(int cb, int it) { return it < 3 ? cb * 3 + it : (it - 3 < cb * 3 ? it - 3 : it); }

template <int N, bool A_SWZ, int B_MODE, int DEPTH, class Hook, class Mid>
__device__ __forceinline__ void gemm_loop(float* d, uint32_t sb, int nkb, int sa, int pa, int b0, uint32_t boff, int relA, int relB, int tid, Hook hook, Mid mid) {
  constexpr uint32_t A_STEP = A_SWZ ? 2 : 128;
  constexpr uint32_t B_STEP = B_MODE == 0 ? 128 : (B_MODE == 1 ? 384 : 320);
  const uint64_t da0 = A_SWZ ? mkdesc(sb + OFF_A, 16, 1024, 1) : mkdesc(sb + OFF_A, 1024, 128, 0);
  const uint64_t db0 = B_MODE == 0 ? mkdesc(sb + OFF_B + boff, 8192, 1024, 1) : mkdesc(sb + OFF_B + boff, B_MODE == 1 ? 3072 : 2560, 128, 0);
  constexpr int MODA = B_MODE == 0 ? NA : NA2;
  constexpr int MODB = B_MODE == 2 ? 6 : NB;
  int sbk = b0 % MODB, pb = (b0 / MODB) & 1;
  auto boffs = [](int s_) { return B_MODE == 2 ? (s_ == 5 ? 0 : s_ + 1) * (20480 >> 4) : s_ * (B_SLOT >> 4); };
  uint32_t rel = 0;
  uint64_t da = da0 + sa * (A_SLOT >> 4), db = db0 + boffs(sbk);
  const bool doR = tid < 2 ? tid < relA : tid - 2 < relB;
  mbar_wait2(sb + BAR_AF + 8 * sa, pa, sb + BAR_BF + 8 * sbk, pb);
  if constexpr (DEPTH == 0) {
    acc_fence<N / 2>(d);
#pragma unroll 1
    for (int it = 0; it < nkb; it++) {
      WG_FENCE();
#pragma unroll
      for (int j = 0; j < 4; j++) WG<N>::ss(d, da + j * A_STEP, db + j * B_STEP, 1);
      WG_COMMIT();
      const uint32_t prel = rel;
      rel = sb + BAR_AE + 8 * (tid < 2 ? sa : sbk + NA);
      if (++sa == MODA) { sa = 0; pa ^= 1; }
      if (++sbk == MODB) { sbk = 0; pb ^= 1; }
      da = da0 + sa * (A_SLOT >> 4); db = db0 + boffs(sbk);
      const bool r0 = mbar_test(sb + BAR_AF + 8 * sa, pa), r1 = mbar_test(sb + BAR_BF + 8 * sbk, pb);
      WG_WAIT(1);
      mbar_arrive_if(prel, doR && prel != 0);
      if (it == 2) {
        WG_WAIT(0);
        mbar_expect_if(sb + BAR_AF + 8 * (tid == 8 ? 8 : tid), A_SLOT, tid < 9);
        mbar_arrive_if(rel, doR);
        rel = 0;
      }
      mid(it);
      if (it + 1 < nkb && !(r0 && r1)) {
        mbar_wait2(sb + BAR_AF + 8 * sa, pa, sb + BAR_BF + 8 * sbk, pb);
      }
    }
  } else
#pragma unroll 1
  for (int it = 0; it < nkb; it++) {
    WG_FENCE();
    WG<N>::ss(d, da, db, 1);
    const uint32_t prel = rel;
    rel = sb + BAR_AE + 8 * (tid < 2 ? sa : sbk + NA);
    if (++sa == MODA) { sa = 0; if (B_MODE) pa ^= 1; }
    if (++sbk == MODB) { sbk = 0; pb ^= 1; }
    if (DEPTH == 1) { WG_COMMIT(); WG_WAIT(1); }
    WG<N>::ss(d, da + A_STEP, db + B_STEP, 1);
    WG_COMMIT();
    WG_WAIT(1);
    if (EARLY == 1) mbar_arrive_if(prel, doR && it != 0);
    WG<N>::ss(d, da + 2 * A_STEP, db + 2 * B_STEP, 1);
    if (DEPTH == 1) WG_COMMIT();
    if (EARLY != 1) mbar_arrive_if(prel, doR && it != 0);
    const bool r0 = mbar_test(sb + BAR_AF + 8 * sa, pa), r1 = mbar_test(sb + BAR_BF + 8 * sbk, pb);
    const uint64_t da3 = da + 3 * A_STEP, db3 = db + 3 * B_STEP;
    da = da0 + sa * (A_SLOT >> 4); db = db0 + boffs(sbk);
    if (DEPTH == 1) WG_WAIT(1);
    WG<N>::ss(d, da3, db3, 1);
    WG_COMMIT();
    mid(it);
    if (it + 1 < nkb) {
      if (!(r0 && r1)) {
        mbar_wait2(sb + BAR_AF + 8 * sa, pa, sb + BAR_BF + 8 * sbk, pb);
      }
    }
    if (DEPTH == 2) WG_WAIT(1);
  }
  hook();
  WG_WAIT(0);
  acc_fence<N / 2>(d);
  mbar_arrive_if(rel, doR);
}

__device__ __forceinline__ void fold_mean(float* d, uint32_t cs, float ma, float mb, int t) {
  const uint32_t ha = pack2(-ma, -ma), hb = pack2(-mb, -mb);
  const float la = -ma - bf_lo(ha), lb = -mb - bf_lo(hb);
  const uint32_t a[4] = {t ? 0u : ha, t ? 0u : hb, t ? 0u : pack2(la, la), t ? 0u : pack2(lb, lb)};
  WG_FENCE();
  WG<192>::rst(d, a, mkdesc(cs, 0, 32, 0));
  WG_COMMIT();
}
__device__ __forceinline__ void gelu_tile(const float* d, uint32_t* z, float* st, float ra, float rb) {
  const float kA = 0.7978845608028654f, kB = 0.7978845608028654f * 0.044715f;
  const float c1a = kA * ra, c3a = kB * ra * ra * ra, c1b = kA * rb, c3b = kB * rb * rb * rb;
  float acc[8];
#pragma unroll
  for (int i = 0; i < 8; i++) acc[i] = 0.f;
#pragma unroll
  for (int j = 0; j < 24; j++) {
    float r[4];
#pragma unroll
    for (int e = 0; e < 4; e++) {
      const float v = d[4 * j + e];
      const float a = v * fmaf(v * v, e < 2 ? c3a : c3b, e < 2 ? c1a : c1b);
      r[e] = fmaf(v, tanh_fast(a), v);
      acc[e] += r[e];
      acc[4 + e] = fmaf(r[e], r[e], acc[4 + e]);
    }
    z[2 * j] = pack2(r[0], r[1]);
    z[2 * j + 1] = pack2(r[2], r[3]);
  }
  st[0] = acc[0] + acc[1]; st[1] = acc[4] + acc[5]; st[2] = acc[2] + acc[3]; st[3] = acc[6] + acc[7];
}

template <int Q> __device__ __forceinline__ void conv_load(uint32_t* a, uint32_t ab) {
  a[0] = lds32<512 * Q>(ab);       a[1] = lds32<512 * Q + 256>(ab);  a[2] = lds32<512 * Q + 16>(ab);   a[3] = lds32<512 * Q + 272>(ab);
  a[4] = lds32<512 * Q + 32>(ab);  a[5] = lds32<512 * Q + 288>(ab);  a[6] = lds32<512 * Q + 48>(ab);   a[7] = lds32<512 * Q + 304>(ab);
  a[8] = lds32<512 * Q + 64>(ab);  a[9] = lds32<512 * Q + 320>(ab);  a[10] = lds32<512 * Q + 80>(ab);  a[11] = lds32<512 * Q + 336>(ab);
  a[12] = lds32<512 * Q + 96>(ab); a[13] = lds32<512 * Q + 352>(ab); a[14] = lds32<512 * Q + 112>(ab); a[15] = lds32<512 * Q + 368>(ab);
}
template <int Q, int L> __device__ __forceinline__ void conv_step(float* d, uint32_t (*a)[16], uint32_t ab, uint64_t db) {
  WG_FENCE();
#pragma unroll
  for (int s = 0; s < 4; s++) WG<128 - 16 * Q>::rs(d, a[Q] + 4 * s, db + s + 16 * Q);
  WG_COMMIT();
  if (CPIN) WG_WAIT(1);
  if (L >= 0) conv_load<(L >= 0 ? L : 0)>(a[L >= 0 ? L : 0], ab);
  if (CW0 || Q == 0) WG_WAIT(0);
}

__device__ __forceinline__ int seg_col(int cb, int h) { return (cb >> 1) * 320 + (cb & 1) * 32 + h * 64; }
__device__ __forceinline__ void final_load_x(uint32_t (*xw)[10], uint32_t xt, int cb, int h, int w, int lane) {
  const int g = lane >> 2, t = lane & 3, cc = seg_col(cb, h) >> 3;
  const int c0 = cc + t, c1 = c0 + 24, c2 = cc + 16 - 6 * h + (t >> 1);
  const uint32_t r0 = xt + (w * 16 + g) * 128;
#pragma unroll
  for (int r = 0; r < 2; r++) {
    const uint4 u = lds128(r0 + r * 1024 + (c0 >> 3) * A_SLOT + (((c0 ^ g) & 7) << 4)), v = lds128(r0 + r * 1024 + (c1 >> 3) * A_SLOT + (((c1 ^ g) & 7) << 4));
    const float2 z = lds64f(r0 + r * 1024 + (c2 >> 3) * A_SLOT + (((c2 ^ g) & 7) << 4) + (t & 1) * 8);
    xw[r][0] = u.x; xw[r][1] = u.y; xw[r][2] = u.z; xw[r][3] = u.w;
    xw[r][4] = v.x; xw[r][5] = v.y; xw[r][6] = v.z; xw[r][7] = v.w;
    xw[r][8] = __float_as_uint(z.x); xw[r][9] = __float_as_uint(z.y);
  }
}
__device__ __forceinline__ void final_s_early(uint32_t (*sw)[10], const uint32_t (*xw)[10], uint32_t ya, float2 s0, float2 s1) {
  const uint32_t r2[2] = {pack2(s0.y, s0.y), pack2(s1.y, s1.y)};
  const float na = -s0.x * bf_lo(r2[0]), nb = -s1.x * bf_lo(r2[1]);
  const uint32_t n2[2] = {pack2(na, na), pack2(nb, nb)};
#pragma unroll
  for (int j = 0; j < 10; j += 2) {
    uint32_t y[4];
    if (j < 4 || j == 8) ldsm4t(y, ya + (j < 4 ? j : 4) * 1024);
#pragma unroll
    for (int e = 0; e < 4; e++) {
      const uint32_t xn = hfma2(xw[e & 1][j + (e >> 1)], r2[e & 1], n2[e & 1]);
      sw[e & 1][j + (e >> 1)] = (j < 4 || j == 8) ? hmul2(xn, y[e]) : xn;
    }
  }
}
__device__ __forceinline__ bool final_late(uint32_t* y, uint32_t ya) {
  ldsm4t(y, ya + 6144);
  ldsm4t(y + 4, ya + 8192);
  uint32_t zero = 0;
#pragma unroll
  for (int e = 0; e < 8; e++) zero |= (y[e] - 0x00010001u) & ~y[e];
  return (zero & 0x80008000u) == 0;
}
__device__ __forceinline__ bool bar_all(int id, int n, bool c) {
  uint32_t r;
  asm volatile("{\n.reg .pred p, q;\nsetp.ne.u32 p, %3, 0;\nbar.red.and.pred q, %1, %2, p;\nselp.u32 %0, 1, 0, q;\n}\n" : "=r"(r) : "r"(id), "r"(n), "r"((uint32_t)c) : "memory");
  return r;
}
__device__ __forceinline__ void final_out(const float* d, const uint32_t (*xw)[10], const uint32_t (*sw)[10], float ra, float rb, __nv_bfloat16* o0, int h, int t) {
  const float ca = 0.25f * ra, cb = 0.25f * rb;
  uint32_t o[2][10];
#pragma unroll
  for (int j = 0; j < 10; j++) {
#pragma unroll
    for (int r = 0; r < 2; r++) {
      const float h0 = d[4 * j + 2 * r] * (r ? cb : ca), h1 = d[4 * j + 2 * r + 1] * (r ? cb : ca);
      o[r][j] = hfma2(pack2(fmaf(h0, tanh_fast(h0), h0), fmaf(h1, tanh_fast(h1), h1)), sw[r][j], xw[r][j]);
      __nv_bfloat16* q = o0 + r * 8 * kD;
      if (j == 3) stg4_if(q + t * 8, o[r][0], o[r][1], o[r][2], o[r][3], true);
      if (j == 7) stg4_if(q + 192 + t * 8, o[r][4], o[r][5], o[r][6], o[r][7], true);
      if (j == 9) asm volatile("st.global.v2.u32 [%0], {%1,%2};" ::"l"(q + 128 - 48 * h + t * 4), "r"(o[r][8]), "r"(o[r][9]) : "memory");
    }
  }
}

struct Taps { uint4 r0, r1; uint32_t n0, n1, dd; };
__device__ __forceinline__ void load_taps(Taps& k, const Params& p, int ch, int tid) {
  const uint4* kp = (const uint4*)(p.ssmk + (size_t)ch * kS);
  k.r0 = ldg4(kp + tid); k.r1 = ldg4(kp + 128 + tid);
  k.n0 = ldg1(kp + tid + 1); k.n1 = tid < 127 ? ldg1(kp + 129 + tid) : 0u;
  k.dd = __bfloat16_as_ushort(p.ssmD[ch]);
}
__device__ __forceinline__ void load_convx(const Params& p, uint32_t cv, uint32_t bar, int ch) {
  mbar_expect(bar, 4096);
  bulk_g2s(cv, p.scr->kvx + (size_t)ch * 4096, 2048, bar);
  bulk_g2s(cv + XB_PL, p.scr->kvx + (size_t)ch * 4096 + 2048, 2048, bar);
}
#define CW 3
#define CSTAMP(j)
__device__ __forceinline__ void zero_pads(uint32_t cv, int lane) {
  if (lane < 8) sts128(cv + (lane >> 2) * XB_PL + 2048 + (lane & 3) * 16, 0, 0, 0, 0);
  else if (lane < 12) sts128(cv + ((lane & 2) ? CV_KO : CV_KE) + (lane & 1) * 16, 0, 0, 0, 0);
  fence_async_smem();
  __syncwarp();
}
__device__ __forceinline__ int y_row(int c, uint32_t par) {
  const int hf = c >= 320, cc = c - hf * 320, u = cc >> 6, cb = hf * 2 + ((cc >> 5) & 1);
  if (u == 2) return cb * 96 + ((cc >> 4) & 1) * 48 + 32 + (cc & 1) + ((cc >> 1) & 1) * 8 + ((cc >> 2) & 3) * 2;
  return (u < 2 ? cb * 96 + u * 48 : 384 + par * 256 + cb * 64 + (u - 3) * 32) + (cc & 1) + ((cc >> 1) & 3) * 8 + ((cc >> 3) & 3) * 2;
}
__device__ __forceinline__ void z_store(const Params& p, uint32_t src, int rb, int cb, int q) {
  uint8_t* dst = p.scr->z2 + (size_t)(cb * 32 + q * 16 + (rb >> 2)) * B_SLOT + (rb & 3) * 6144;
  bulk_s2g(dst, src + q * 12288, 6144);
  bulk_s2g(dst + 8 * B_SLOT, src + q * 12288 + 6144, 6144);
  asm volatile("cp.async.bulk.commit_group;\ncp.async.bulk.wait_group 0;" ::: "memory");
}
__device__ __forceinline__ void y_store(const Params& p, uint32_t sb, int h, int ch, uint32_t par) {
  uint8_t* dst = p.scr->y + (size_t)y_row(ch, par) * 4096;
  if (elect_one()) {
    bulk_s2g(dst, sb + OFF_A + 9 * A_SLOT + h * 4096, 4096);
    asm volatile("cp.async.bulk.commit_group;\ncp.async.bulk.wait_group 0;" ::: "memory");
  }
  __syncwarp();
}
__device__ __forceinline__ void conv_service(const Params& p, uint32_t sb, int h, int ch, bool first) {
  bar_sync(NB_WGA + 8 + h, 160);
  const bool now = !first || __all_sync(0xffffffff, mbar_test(sb + BAR_KV, 0));
  if (now) { acquire_fence(); if (elect_one()) load_convx(p, sb + OFF_CV + (1 - h) * CV_SZ, sb + BAR_XF + 8 * h, ch + 128); }
  bar_sync(NB_WGA + 8 + h, 160);
  y_store(p, sb, h, ch, 0);
  if (!now) {
    mbar_wait(sb + BAR_KV, 0);
    acquire_fence();
    if (elect_one()) load_convx(p, sb + OFF_CV + (1 - h) * CV_SZ, sb + BAR_XF + 8 * h, ch + 128);
  }
}
__device__ __forceinline__ uint32_t y_tile(int h) { return OFF_CV + (1 - h) * 13312; }
__device__ __forceinline__ void load_late_y(const Params& p, uint32_t sb, int h, int rb, int cb, uint32_t par) {
  mbar_expect(sb + BAR_YL + 16 * h, 4096);
  tma2d(sb + y_tile(h) + 6144, &p.tmY, rb * 64, 384 + par * 256 + cb * 64 + h * 32, sb + BAR_YL + 16 * h);
  tma2d(sb + y_tile(h) + 8192, &p.tmY, rb * 64, 400 + par * 256 + cb * 64 + h * 32, sb + BAR_YL + 16 * h);
}
__device__ __forceinline__ void held_service(const Params& p, uint32_t sb, int h, int ch, int rb, int cb, uint32_t tag, int lane) {
#pragma unroll 1
  for (int i = 0; i < 8; i++) sts128(sb + OFF_A + 9 * A_SLOT + h * 4096 + i * 512 + lane * 16, 0, 0, 0, 0);
  fence_async_smem();
  __syncwarp();
  y_store(p, sb, h, ch, ~tag & 1);
  mbar_wait(sb + BAR_YT, 1);
  acquire_fence();
  bar_sync(NB_WGA + 8 + h, 160);
  bar_sync(NB_WGA + 8 + h, 160);
  uint8_t* dst = p.scr->y + (size_t)y_row(ch, tag & 1) * 4096;
  if (elect_one()) {
    bulk_s2g(dst, sb + OFF_A + 9 * A_SLOT + h * 4096, 4096);
    asm volatile("cp.async.bulk.commit_group;" ::: "memory");
    mbar_expect(sb + BAR_XF + 8 * h, 6144);
#pragma unroll 1
    for (int i = 0; i < 3; i++) tma2d(sb + y_tile(h) + i * 2048, &p.tmY, rb * 64, cb * 96 + h * 48 + i * 16, sb + BAR_XF + 8 * h);
  }
  mbar_wait(sb + BAR_AE + 8 * (LL_AT - 1), 1);
  if (elect_one()) { load_late_y(p, sb, h, rb, cb, tag & 1); asm volatile("cp.async.bulk.wait_group 0;" ::: "memory"); }
}
__device__ __forceinline__ void conv_worker(const Params& p, Taps& k, uint32_t cv, uint32_t yb0,
                                            uint32_t xbar, int nbar, int ch0, int n, uint32_t holdbar, int w, int lane,
                                            int tid, int st0, int rb, int cb) {
  const int g = lane >> 2, t = lane & 3, w0 = w & 1, w1 = w >> 1;
  const uint32_t ab = cv + ((g & 1) ? CV_KE : CV_KO) + 32 + 2 * (64 * w0 + 8 * w1 + ((g - 15) & ~1) + 2 * t);
  const uint32_t scA = cv + (w1 ? CV_KO : CV_KE) + 32, scB = scA + 2048;
  const int dl = (t >> 1) ^ 1;
  if (n == 2 || CPRE0 == 2) mbar_wait(xbar, 0);
  STAMPW(st0 + 3);
#pragma unroll 1
  for (int i = 0; i < n; i++) {
    if (tid == 0) {
      k.r0.x = (k.r0.x & 0xffff0000u) | (pack2(bf_lo(k.r0.x) + bf_lo(k.dd), 0.f) & 0xffffu);
      sts32(cv + CV_KO + 28, k.r0.x << 16);
    }
    sts128(cv + CV_KE + 32 + tid * 16, k.r0.x, k.r0.y, k.r0.z, k.r0.w);
    sts128(cv + CV_KO + 32 + tid * 16, prmt(k.r0.x, k.r0.y, 0x5432), prmt(k.r0.y, k.r0.z, 0x5432), prmt(k.r0.z, k.r0.w, 0x5432), prmt(k.r0.w, k.n0, 0x5432));
    sts128(cv + CV_KE + 2080 + tid * 16, k.r1.x, k.r1.y, k.r1.z, k.r1.w);
    sts128(cv + CV_KO + 2080 + tid * 16, prmt(k.r1.x, k.r1.y, 0x5432), prmt(k.r1.y, k.r1.z, 0x5432), prmt(k.r1.z, k.r1.w, 0x5432), prmt(k.r1.w, k.n1, 0x5432));
    if (i + 1 < n) load_taps(k, p, ch0 + (i + 1) * 128, tid);
    bar_sync(nbar, 128);
    CSTAMP(0);
    const uint64_t db = mkdesc(cv + (i & 0x1000), XB_PL, 128, 0);
    float d[64];
    uint32_t a[8][16];
    if (CPRE0 == 1 && i == 0) mbar_wait(xbar, 0);
    conv_load<7>(a[7], ab); conv_load<6>(a[6], ab); conv_load<5>(a[5], ab); conv_load<4>(a[4], ab);
#pragma unroll
    for (int j = 0; j < 64; j++) d[j] = 0.f;
    mbar_wait(xbar, i & 1);
    if (i + 1 == n) mbar_wait(holdbar, 1);
    CSTAMP(1);
    conv_step<7, -1>(d, a, ab, db); conv_step<6, -1>(d, a, ab, db); conv_step<5, -1>(d, a, ab, db); conv_step<4, 3>(d, a, ab, db);
    conv_step<3, 2>(d, a, ab, db);
    conv_step<2, 1>(d, a, ab, db);
    conv_step<1, 0>(d, a, ab, db);
    conv_step<0, -1>(d, a, ab, db);
    acc_fence<64>(d);
    CSTAMP(2);
    bar_sync(nbar + 8, 160);
    float E[16][2];
#pragma unroll
    for (int j = 0; j < 15; j++) { E[j][0] = d[4 * j] + d[4 * j + 6]; E[j][1] = d[4 * j + 1] + d[4 * j + 7]; }
    E[15][0] = d[60]; E[15][1] = d[61];
    if (w0 == 0) {
#pragma unroll
      for (int j = 8; j < 16; j++) sts64f(scA + (j - 8) * 256 + lane * 8, E[j][0], E[j][1]);
    } else {
      const uint32_t a = scB - dl * 256 + (lane ^ 2) * 8;
#pragma unroll
      for (int j = 1; j < 8; j++) sts64f(a + j * 256, E[j][0], E[j][1]);
      sts64f(scB + (dl ? 7 * 256 : 0) + (lane ^ 2) * 8, dl ? E[8][0] : E[0][0], dl ? E[8][1] : E[0][1]);
    }
    bar_sync(nbar, 128);
    CSTAMP(3);
    uint32_t pk[8];
    if (w0 == 0) {
#pragma unroll
      for (int j = 0; j < 8; j++) { const float2 v = lds64f(scB + j * 256 + lane * 8); pk[j] = pack2(E[j][0] + v.x, E[j][1] + v.y); }
    } else {
      const uint32_t a0 = scA - dl * 256 + (lane ^ 2) * 8;
#pragma unroll
      for (int j = 9; j < 16; j++) { const float2 v = lds64f(a0 + (j - 8) * 256); pk[j - 8] = pack2(E[j][0] + v.x, E[j][1] + v.y); }
      const float2 v = lds64f(scA + (dl ? 7 * 256 : 0) + (lane ^ 2) * 8);
      pk[0] = pack2((dl ? 0.f : E[8][0]) + v.x, (dl ? 0.f : E[8][1]) + v.y);
    }
    CSTAMP(4);
    if (i + 1 == n) {
#pragma unroll
      for (int j = 0; j < 8; j++) pk[j] = ~pk[j];
    }
    const int c1 = (w0 ? 35 : 95) - lane, c0 = (w0 && lane < 4) ? c1 - 32 : c1 + 32;
    stsm4t(yb0 + 128 * (c0 & 31) + (((2 * (c0 >> 5) + w1) ^ (c0 & 7)) << 4), pk[0], pk[1], pk[2], pk[3]);
    stsm4t(yb0 + 128 * (c1 & 31) + (((2 * (c1 >> 5) + w1) ^ (c1 & 7)) << 4), pk[4], pk[5], pk[6], pk[7]);
    fence_async_smem();
    bar_sync(nbar + 8, 160);
    CSTAMP(5);
    STAMPW(st0 + i);
    if (n == 2 && i == 0) {
      const int u = (tid >> 3) % 5, kg = rb * 3 + (tid < 120 ? (tid >> 3) / 5 : 0), c = u < 4 ? (u >> 1) * 10 + (u & 1) * 4 : 8, o2 = u < 4 ? 2 : 10;
      const uint4* wp = (const uint4*)p.wout + (uint32_t)((kg * 8 + (tid & 7)) * (kD / 8) + (seg_col(cb, 0) >> 3) + (u < 4 ? (u >> 1) * 8 + (u & 1) * 24 : 16));
      const uint4 w0 = ldg4(wp), w1 = ldg4(wp + 1), w2 = ldg4(wp + 2), w3 = ldg4(wp + 3);
      uint8_t* dst = p.scr->wo + (uint32_t)(cb * (12 * 20480) + kg * 2560 + c * 128 + (tid & 7) * 16);
      const bool f = u < 4, on = tid < 120;
      stg4_if(dst, w0.x, f ? w1.x : w0.z, f ? w2.x : w1.x, f ? w3.x : w1.z, on);
      stg4_if(dst + 128, w0.y, f ? w1.y : w0.w, f ? w2.y : w1.y, f ? w3.y : w1.w, on);
      stg4_if(dst + o2 * 128, f ? w0.z : w2.x, f ? w1.z : w2.z, f ? w2.z : w3.x, w3.z, on);
      stg4_if(dst + o2 * 128 + 128, f ? w0.w : w2.y, f ? w1.w : w2.w, f ? w2.w : w3.y, w3.w, on);
      bar_arrive(NB_WO, 160);
    }
  }
}

struct KvRegs { uint32_t k[11], v[8]; uint4 sh; };
__device__ __forceinline__ void kv_load(KvRegs& q, const __nv_bfloat16* kp, const __nv_bfloat16* vp, const __nv_bfloat16* sp, bool halo) {
#pragma unroll
  for (int i = 0; i < 11; i++) q.k[i] = (i >= 3 || halo) ? ldg1(kp + i * kD) : 0u;
#pragma unroll
  for (int i = 0; i < 8; i++) q.v[i] = ldg1(vp + i * kD);
  q.sh = ldg4(sp);
}
__device__ __forceinline__ void kv_unit(const KvRegs& q, uint32_t oa) {
  const uint32_t w0 = prmt(q.sh.x, q.sh.z, 0x5410), w1 = prmt(q.sh.x, q.sh.z, 0x7632), w2 = prmt(q.sh.y, q.sh.w, 0x5410), w3 = prmt(q.sh.y, q.sh.w, 0x7632);
  uint32_t r[8];
#pragma unroll
  for (int i = 0; i < 8; i++) r[i] = hmul2(hfma2(q.k[i + 3], w0, hfma2(q.k[i + 2], w1, hfma2(q.k[i + 1], w2, hmul2(q.k[i], w3)))), q.v[i]);
  sts128(oa, prmt(r[7], r[6], 0x5410), prmt(r[5], r[4], 0x5410), prmt(r[3], r[2], 0x5410), prmt(r[1], r[0], 0x5410));
  sts128(oa + 2048, prmt(r[7], r[6], 0x7632), prmt(r[5], r[4], 0x7632), prmt(r[3], r[2], 0x7632), prmt(r[1], r[0], 0x7632));
}

__device__ __forceinline__ void gather_colsum(const Params& p, uint32_t sb, int cb, int part, uint32_t tag, int lane) {
  uint4 v[3];
  uint32_t t0 = 0;
#pragma unroll 1
  while (true) {
    bool ok = true;
#pragma unroll
    for (int i = 0; i < 3; i++) {
      v[i] = ld_ll4(&p.scr->colsum[(part ? 0 : 768) + cb * 192 + i * 64 + lane * 2]);
      ok = ok && v[i].y == tag && v[i].w == tag;
    }
    if (__all_sync(0xffffffff, ok)) break;
    spin_guard(t0);
  }
#pragma unroll
  for (int i = 0; i < 3; i++) {
    const uint32_t hi = pack2(__uint_as_float(v[i].x), __uint_as_float(v[i].z)), ca = sb + OFF_CS + (1 - part) * 768 + i * 256 + (lane >> 2) * 32 + (lane & 3) * 4;
    sts32(ca, hi);
    sts32(ca + 16, pack2(__uint_as_float(v[i].x) - bf_lo(hi), __uint_as_float(v[i].z) - bf_hi(hi)));
  }
  __syncwarp();
  if (lane == 0) mbar_arrive(sb + BAR_ST + 8 * part);
}

__device__ __forceinline__ void helper_cta(const Params& p, uint32_t sb, int cb, int warp, int lane) {
  constexpr int NS = 9, ONES = NS * B_SLOT, BF = ONES + 256, BE = BF + 8 * NS;
  if (warp < NS && elect_one()) {
    mbar_init(sb + BF + 8 * warp, 1); mbar_init(sb + BE + 8 * warp, 1);
    fence_async_smem();
    if (warp == 0) { mbar_expect(sb + BF, B_SLOT); tma3d(sb, &p.tmW, 0, 0, 12 + cb * 3, sb + BF); }
  }
  if (warp == 15) { sts32(sb + ONES + lane * 4, 0x3f803f80u); sts32(sb + ONES + 128 + lane * 4, 0x3f803f80u); fence_async_smem(); }
  __syncthreads();
  if (warp == 4) {
    int s = 1, ph = 1;
    uint32_t tp = clock() + HP0;
#pragma unroll 1
    for (int it = 1; it < 20; it++) {
      if (HPD && it >= 10) pace(tp, HPD);
      mbar_wait(sb + BE + 8 * s, ph);
      if (elect_one()) { mbar_expect(sb + BF + 8 * s, B_SLOT); tma3d(sb + s * B_SLOT, &p.tmW, 0, (it < 10 ? it : it - 10) * 64, (it < 10 ? 12 : 0) + cb * 3, sb + BF + 8 * s); }
      if (++s == NS) { s = 0; ph ^= 1; }
    }
  } else if (warp < 4) {
    const uint32_t tag = load_epoch(p, 128 + cb, lane) + 1;
    const uint64_t db = mkdesc(sb + ONES, 128, 128, 0);
    uint2* dst = p.scr->colsum + cb * 192 + warp * 16 + (lane >> 2);
    if ((lane & 3) == 0) {
#pragma unroll 1
      for (int j = 0; j < 12; j++) st_ll2(dst + (j < 6 ? 768 : 0) + ((j % 6) >> 1) * 64 + (j & 1) * 8, 0, 0);
    }
    int s = 0, ph = 0;
#pragma unroll 1
    for (int part = 0; part < 2; part++) {
      float d[12];
#pragma unroll
      for (int i = 0; i < 12; i++) d[i] = 0.f;
#pragma unroll 1
      for (int it = 0; it < 10; it++) {
        mbar_wait(sb + BF + 8 * s, ph);
        const uint64_t da = mkdesc(sb + s * B_SLOT, 8192, 1024, 1);
        WG_FENCE();
#pragma unroll
        for (int j = 0; j < 12; j++) wgmma_colsum(d + 4 * (j % 3), da + (j % 3) * 512 + (j / 3) * 128, db);
        WG_COMMIT();
        WG_WAIT(1);
        mbar_arrive_if(sb + BE + 8 * (s == 0 ? NS - 1 : s - 1), threadIdx.x == 0 && (it | part) != 0);
        if (++s == NS) { s = 0; ph ^= 1; }
      }
      WG_WAIT(0);
      acc_fence<12>(d);
      if ((lane & 3) == 0) {
#pragma unroll
        for (int j = 0; j < 6; j++) st_ll2(dst + (part ? 0 : 768) + (j >> 1) * 64 + (j & 1) * 8, __float_as_uint(d[2 * j]), tag);
      }
      STAMPW(1 + part);
    }
    if (threadIdx.x == 0) *(volatile uint32_t*)&p.scr->epoch[128 + cb] = tag;
  }
}

__global__ void __launch_bounds__(512, 1) fused_kernel(const __grid_constant__ Params p) {
  extern __shared__ __align__(1024) uint8_t smem[];
  const int warp = __shfl_sync(0xffffffff, (int)(threadIdx.x >> 5), 0);
  const int lane = threadIdx.x & 31, tid = threadIdx.x & 127;
  const uint32_t sb = __shfl_sync(0xffffffff, (uint32_t)__cvta_generic_to_shared(smem), 0);
  const uint32_t tstart = clock();
  if (elect_one()) {
    if (warp < 5) asm volatile("prefetch.tensormap [%0];" ::"l"(&p.tmX + warp) : "memory");
    mbar_init(sb + OFF_BAR + 8 * warp, 1); mbar_init(sb + OFF_BAR + 128 + 8 * warp, 1); mbar_init(sb + OFF_BAR + 256 + 8 * warp, 2);
    asm volatile("fence.mbarrier_init.release.cluster;" ::: "memory");
  }
  int b = blockIdx.x;
  if (p.by_smid) asm volatile("mov.u32 %0, %%smid;" : "=r"(b));
  b = __shfl_sync(0xffffffff, b, 0);
  const int tp = b >> 1, t7 = (tp - 32) / 7;
  const int lin = tp < 32 ? ((tp & 7) ? (tp & 7) * 16 : 8) + (tp >> 3) * 2 + (b & 1)
                          : (tp < 60 ? (tp - 31 - t7 * 7) * 16 + 8 + t7 * 2 + (b & 1) : (tp < 62 ? -1 : b - 124));
  const int hcb = b & 3;
  if (lin < 0) { helper_cta(p, sb, hcb, warp, lane); return; }
  const int cb = ((lin >> 4) & 1) * 2 + ((lin >> 1) & 1), rb = (lin >> 5) * 8 + ((lin >> 2) & 3) * 2 + (lin & 1);
  const int zs0 = 4 - (cb & 2);
  const int chb = (cb >> 1) * 320 + rb * 2 + (cb & 1);
  if (warp == 0 && elect_one()) {
    mbar_expect(sb + BAR_AF, A_SLOT);
    tma_rows(sb + OFF_A, &p.tmX, 0, rb, sb + BAR_AF);
    mbar_expect(sb + BAR_BF, B_SLOT);
    tma3d(sb + OFF_B, &p.tmW, 0, 0, 12 + cb * 3, sb + BAR_BF);
  }
  if (warp == 1) STAMP(31);
  if (sb & 1023) die();
  __syncthreads();

  if (warp >= 12) {
    asm volatile("setmaxnreg.dec.sync.aligned.u32 32;");
    const uint32_t epoch = load_epoch(p, lin, lane);
    if (warp == 12) {
#pragma unroll 1
      for (int i = 1; i < NA; i++) {
        if (elect_one()) {
          mbar_expect(sb + BAR_AF + 8 * i, A_SLOT);
          tma_rows(sb + OFF_A + i * A_SLOT, &p.tmX, i * 64, rb, sb + BAR_AF + 8 * i);
          if (i < NB) { mbar_expect(sb + BAR_BF + 8 * i, B_SLOT); tma3d(sb + OFF_B + i * B_SLOT, &p.tmW, 0, i * 64, 12 + cb * 3, sb + BAR_BF + 8 * i); }
        }
      }
      STAMP(32);
      uint32_t kvt;
      {
        const int tb = rb * 2 + (cb & 1);
        kvt = __shfl_sync(0xffffffff, (ld_relaxed(p.scr->cnt + CNT_KV + (cb >> 1)) & ~63u) + 64, 0);
        {
          uint32_t tp = tstart;
          pace(tp, KV_T0);
          mbar_arrive_if(sb + BAR_KV + 8, lane == 0);
        }
        if (ST_YIELD) mbar_wait2(sb + BAR_XS, 0, sb + BAR_ST, 0);
#pragma unroll 1
        for (int u = 0; u < 5; u++) {
          mbar_wait(sb + BAR_KU + 8 * u, 0);
          fence_async_smem();
          if (elect_one()) {
            asm volatile("cp.async.bulk.tensor.3d.global.shared::cta.bulk_group [%0, {%2, %3, %4}], [%1];\ncp.async.bulk.commit_group;" ::"l"(&p.tmKV),
                         "r"(sb + OFF_CV + CV_SZ + (u < 3 ? u : u - 3) * 4096), "r"((63 - tb) * 16), "r"((cb >> 1) * 160 + u * 32), "r"(0) : "memory");
            if (u == 1 || u == 4) asm volatile("cp.async.bulk.wait_group 0;" ::: "memory");
            if (u == 1) { mbar_arrive(sb + BAR_KU); red_release(p.scr->cnt + CNT_KV + (cb >> 1)); }
          }
          __syncwarp();
          if (u == 1) {
            STAMP(35);
            if (PFT) { const char* q = (const char*)p.ssmk + chb * 4096 + lane * 128; prefetch_l2(q); prefetch_l2(q + 64 * 4096); }
          }
        }
        zero_pads(sb + OFF_CV + CV_SZ, lane);
        if (elect_one()) { mbar_arrive(sb + BAR_KU + 8); red_release(p.scr->cnt + CNT_KV + 2 + (cb >> 1)); }
        STAMP(30);
        if (lane < 24) {
          const char* r = (const char*)p.wout + (rb * 24 + lane) * (kD * 2) + (cb >> 1) * 640 + (cb & 1) * 384;
          prefetch_l2(r); prefetch_l2(r + 128); prefetch_l2(r + 256 - (cb & 1) * 384);
        }
      }
      poll_counter(p.scr->cnt + CNT_KV + 2 + (cb >> 1), kvt);
      if (elect_one()) mbar_arrive(sb + BAR_KV);
      STAMP(34);
      {
        const char* q = (const char*)p.wsp + (cb * 512 + rb * 16 + (lane >> 1)) * (kS * 2) + (lane & 1) * 128;
        uint32_t tp = clock();
#pragma unroll 1
        for (int i = LEAD / 2; i < WSP_N; i++) {
          prefetch_l2(q + i * 256);
          if (i == Z1_AT) {
            poll_counter(p.scr->cnt + CNT_Z1, (epoch + 1) * 128);
            if (elect_one()) mbar_arrive(sb + BAR_Z1);
            STAMP(24);
          }
          pace(tp, WSP_D);
        }
      }
      const uint32_t tag = epoch + 1;
      mbar_wait(sb + BAR_G2, 0);
      if (elect_one()) {
        bulk_s2g(p.scr->h + (size_t)(rb * 12 + cb * 3) * A_SLOT, sb + OFF_A + 5 * A_SLOT, 3 * A_SLOT);
        asm volatile("cp.async.bulk.commit_group;\ncp.async.bulk.wait_group 0;" ::: "memory");
        red_release(&p.scr->hcnt[(rb >> HGRP) * 32]);
      }
      __syncwarp();
      STAMP(20);
      mbar_wait(sb + BAR_AE + 56, 0);
      STAMP(39);
      poll_counter(&p.scr->hcnt[(rb >> HGRP) * 32], tag * (4 << HGRP));
      STAMP(37);
      if (elect_one()) {
        uint32_t tp = clock();
#pragma unroll 1
        for (int it = 3; it < 12; it++) {
          if (HPACE && it > 3) { tp += HPACE; while ((int32_t)((uint32_t)clock() - tp) < 0) {} }
          bulk_g2s(sb + OFF_A + ((it + 5) % 9) * A_SLOT, p.scr->h + (size_t)(rb * 12 + g3_block(cb, it)) * A_SLOT, A_SLOT, sb + BAR_AF + 8 * ((it + 5) % 9));
        }
      }
      STAMP(21);
    } else if (warp == 13) {
      const uint32_t ztarget = __shfl_sync(0xffffffff, ld_relaxed(p.scr->cnt + CNT_Z), 0);
      int s = 0, ph = 0;
#pragma unroll 1
      for (int it = NB; it < 20; it++) {
        mbar_wait(sb + BAR_BE + 8 * s, ph);
        if (elect_one()) { mbar_expect(sb + BAR_BF + 8 * s, B_SLOT); tma3d(sb + OFF_B + s * B_SLOT, &p.tmW, 0, (it < 10 ? it : (it + zs0) % 10) * 64, (it < 10 ? 12 : 0) + cb * 3, sb + BAR_BF + 8 * s); }
        STAMP2(32 + it);
        if (++s == NB) { s = 0; ph ^= 1; }
      }
      mbar_wait(sb + BAR_XC, 0);
#pragma unroll 1
      for (int i = 0; i < LEAD; i++) {
        mbar_wait(sb + BAR_AE + 8 * i, 0);
        if (elect_one()) { mbar_expect(sb + BAR_AF + 8 * i, A_SLOT); tma_rows(sb + OFF_A + i * A_SLOT, &p.tmWsp, i * 64, rb, sb + BAR_AF + 8 * i); }
      }
      if (ZP_AT < 0) mbar_wait(sb + BAR_ZP, 0);
      poll_counter(p.scr->cnt + CNT_Z, (ztarget & ~127u) + 128);
      STAMP(22);
      int sa = LEAD, pa = 0, ia = LEAD;
#pragma unroll 1
      for (int it = 0; it < 32; it++) {
        if (it == ZP_AT) mbar_wait(sb + BAR_ZP, 0);
        if (it == 16) { mbar_wait(sb + BAR_Z1, 1); acquire_fence(); }
        mbar_wait2(sb + BAR_BE + 8 * s, ph, sb + BAR_AE + 8 * sa, pa);
        if (elect_one()) {
          mbar_expect(sb + BAR_BF + 8 * s, B_SLOT);
          bulk_g2s(sb + OFF_B + s * B_SLOT, p.scr->z2 + (size_t)(cb * 32 + it) * B_SLOT, B_SLOT, sb + BAR_BF + 8 * s);
        }
#pragma unroll 1
        for (int j = (it < RAMP ? 0 : (it == 4 ? 1 + RAMP : 1)); j > 0 && ia < 32; j--, ia++) {
          if (it == 4) mbar_wait(sb + BAR_AE + 8 * sa, pa);
          if (elect_one()) { mbar_expect(sb + BAR_AF + 8 * sa, A_SLOT); tma_rows(sb + OFF_A + sa * A_SLOT, &p.tmWsp, ia * 64, rb, sb + BAR_AF + 8 * sa); }
          if (++sa == NA2) { sa = 0; pa ^= 1; }
        }
        STAMP2(52 + it);
        if (++s == NB) { s = 0; ph ^= 1; }
      }
      mbar_wait(sb + BAR_WO, 0);
      acquire_fence();
#pragma unroll 1
      for (int it = 0; it < 12; it++) {
        if (it < 6) mbar_wait(sb + BAR_BE + 8 * ((0x110443 >> (4 * it)) & 7), it < 3 ? 1 : 0);
        else mbar_wait(sb + BAR_BE + 8 * s, ph);
        if (elect_one()) {
          mbar_expect(sb + BAR_BF + 8 * s, 20480);
          bulk_g2s(sb + OFF_B + (s == 5 ? 0 : s + 1) * 20480, p.scr->wo + (size_t)(cb * 12 + g3_block(cb, it)) * 20480, 20480, sb + BAR_BF + 8 * s);
        }
        STAMP2(84 + it);
        if (++s == 6) { s = 0; ph ^= 1; }
      }
    } else if (warp == 14) {
      const uint32_t tag = epoch + 1;
      mbar_wait(sb + BAR_AF + 8 * (NA - 1), 0);
#pragma unroll 1
      for (int part = 0; part < 2 - CS1BY; part++) {
        gather_colsum(p, sb, cb, part, tag, lane);
        if (part == 0) STAMP(27);
      }
      if (!CS1BY) STAMP(38);
      bar_sync(NB_Z, ZORD ? 160 : 96);
      if (elect_one()) {
        z_store(p, sb + OFF_A + zs0 * A_SLOT, rb, cb, 0);
        STAMP(7);
        red_release(p.scr->cnt + CNT_Z);
      }
      STAMP(25);
      bar_sync(NB_Z2, 96);
      if (elect_one()) {
        z_store(p, sb + OFF_A + zs0 * A_SLOT, rb, cb, 1);
        mbar_arrive(sb + BAR_ZP);
        red_release(p.scr->cnt + CNT_Z1);
      }
      STAMP(28);
      mbar_wait(sb + BAR_AE + 72, 0);
      conv_service(p, sb, 0, chb + 64, true);
      bar_sync(NB_WO, 160);
      bar_sync(NB_CD, 64);
      if (elect_one()) { red_release(p.scr->cnt + CNT_WO + cb); red_relaxed(p.scr->cnt + CNT_Y + (cb >> 1)); }
      STAMP(49);
      poll_counter(p.scr->cnt + CNT_WO + cb, tag * 32);
      if (elect_one()) mbar_arrive(sb + BAR_WO);
      STAMP(46);
      held_service(p, sb, 0, chb + 192, rb, cb, tag, lane);
    } else {
      const uint32_t tag = epoch + 1;
      sts32(sb + OFF_BIAS + lane * 4, ldg1(p.bsp + (lane >> 3) * 512 + rb * 16 + (lane & 7) * 2));
      if (lane < 2) sts32(sb + OFF_TAG + lane * 4, lane ? 0 : tag);
      fence_async_smem();
      uint32_t t0 = 0;
      mbar_wait(sb + BAR_AF + 8 * (NA - 1), 0);
#pragma unroll 1
      while (true) {
        const uint4 u = ld_ll4(&p.scr->xstat[rb * 64 + lane]), v = ld_ll4(&p.scr->xstat[rb * 64 + 32 + lane]);
        sts64f(sb + OFF_XS + lane * 8, __uint_as_float(u.x), __uint_as_float(u.z));
        sts64f(sb + OFF_XS + 256 + lane * 8, __uint_as_float(v.x), __uint_as_float(v.z));
        if (__all_sync(0xffffffff, u.y == tag && u.w == tag && v.y == tag && v.w == tag)) break;
        spin_guard(t0);
      }
      STAMP(26);
      __syncwarp();
      if (lane == 0) mbar_arrive(sb + BAR_XS);
      if (CS1BY) { uint32_t tp = tstart; pace(tp, CS1_T); gather_colsum(p, sb, cb, 1, tag, lane); STAMP(38); }
      mbar_wait(sb + BAR_KU, 1);
      poll_counter(p.scr->cnt + CNT_KV + (cb >> 1), tag * 64);
      if (elect_one()) load_convx(p, sb + OFF_CV, sb + BAR_XF + 8, chb);
      mbar_wait(sb + BAR_KU + 8, 1);
      if (elect_one()) load_convx(p, sb + OFF_CV + CV_SZ, sb + BAR_XF, chb + 64);
      STAMP(48);
      mbar_wait(sb + BAR_AE + 72, 0);
#pragma unroll 1
      for (int i = 0; i < 2; i++) conv_service(p, sb, 1, chb + i * 128, i == 0);
      bar_arrive(NB_CD, 64);
      mbar_wait(sb + BAR_WO, 0);
      poll_counter(p.scr->cnt + CNT_Y + (cb >> 1), tag * 64);
      STAMP(47);
      if (elect_one()) mbar_arrive(sb + BAR_YT);
      held_service(p, sb, 1, chb + 256, rb, cb, tag, lane);
      if (lane == 0) *(volatile uint32_t*)&p.scr->epoch[lin] = tag;
      STAMP(23);
    }
  } else {
    if (warp == 7) STAMP(36);
    const int wg = warp >> 2, w = warp & 3, g = lane >> 2, t = lane & 3;
    Taps k;
    uint32_t xw[2][10];
    if (wg == 2) {
      asm volatile("setmaxnreg.inc.sync.aligned.u32 160;");
      const int tb = rb * 2 + (cb & 1), c0 = (cb >> 1) * 320;
      const uint32_t cv = sb + OFF_CV + CV_SZ;
      if (w == 0) zero_pads(sb + OFF_CV, lane);
      mbar_wait(sb + BAR_KV + 8, 0);
      const int t0 = tb * 32 + w * 8;
      const __nv_bfloat16* kp = p.k + (size_t)(t0 - 3) * kD + c0 + lane * 2;
      const __nv_bfloat16* vp = p.v + (size_t)t0 * kD + c0 + lane * 2;
      const __nv_bfloat16* sp = p.shift + (c0 + lane * 2) * 4;
      const uint32_t oa = cv + ((3 - w) & 1) * 1024 + lane * 32 + ((((3 - w) >> 1) ^ (lane >> 2)) & 1) * 16;
#pragma unroll 1
      for (int r = 0; r < 2; r++) {
        KvRegs n0, n1, n2;
        kv_load(n0, kp + r * 128, vp + r * 128, sp + r * 512, t0 > 0);
        kv_load(n1, kp + r * 128 + 64, vp + r * 128 + 64, sp + r * 512 + 256, t0 > 0);
        if (r) kv_load(n2, kp + 256, vp + 256, sp + 1024, t0 > 0);
        kv_unit(n0, oa + r * 8192);
        bar_sync(NB_WGC, 128);
        mbar_arrive_if(sb + BAR_KU + 16 * r, tid == 0);
        if (r) mbar_wait(sb + BAR_KU, 1);
        kv_unit(n1, oa + (r ? 0 : 4096));
        bar_sync(NB_WGC, 128);
        mbar_arrive_if(sb + BAR_KU + 16 * r + 8, tid == 0);
        if (r) {
          kv_unit(n2, oa + 4096);
          bar_sync(NB_WGC, 128);
          mbar_arrive_if(sb + BAR_KU + 32, tid == 0);
        } else {
          mbar_wait(sb + BAR_AF + 8 * ((cb >> 1) * 5 + 1), 0);
          mbar_wait2(sb + BAR_AF + 8 * ((cb >> 1) * 5 + 2), 0, sb + BAR_AF + 8 * ((cb >> 1) * 5 + 4), 0);
          final_load_x(xw, sb + OFF_A, cb, 1, w, lane);
          fence_async_smem();
          bar_sync(NB_WGC, 128);
          mbar_arrive_if(sb + BAR_XC, tid == 0);
        }
      }
      STAMPW(13);
      load_taps(k, p, chb, tid);
    } else {
      float d[96];
      if (wg == 0) st_ll2(&p.scr->zstat[(rb * 256 + cb * 64 + w * 16 + g + (t >> 1) * 8) * 2 + (t & 1)], 0, 0);
      else if ((tid & 7) == 0) st_ll4(&p.scr->xstat[rb * 64 + cb * 16 + (tid >> 3)], 0, 0, 0, 0);
      {
        #pragma unroll
        for (int i = 0; i < 96; i++) d[i] = 0.f;
        {
          if (__builtin_expect(wg == 1, 0)) {
            const int tid = tid_now();
            const uint32_t epoch = load_epoch(p, lin, lane);
            float s = 0.f, q = 0.f;
#pragma unroll 1
            for (int i = 0; i < 10; i++) {
              mbar_wait(sb + BAR_AF + 8 * i, 0);
              const uint4 x4 = lds128(sb + OFF_A + i * A_SLOT + cb * 2048 + tid * 16);
              const uint32_t u[4] = {x4.x, x4.y, x4.z, x4.w};
#pragma unroll
              for (int e = 0; e < 4; e++) { const float a = bf_lo(u[e]), c = bf_hi(u[e]); s += a + c; q = fmaf(a, a, q); q = fmaf(c, c, q); }
            }
#pragma unroll
            for (int o = 1; o <= 4; o <<= 1) { s += __shfl_xor_sync(0xffffffff, s, o); q += __shfl_xor_sync(0xffffffff, q, o); }
            const float m = s * (1.f / kD);
            const float r = rsqrtf(fmaxf(fmaf(-m, m, q * (1.f / kD)), 0.f) + 1e-5f);
            if ((tid & 7) == 0) st_ll4(&p.scr->xstat[rb * 64 + cb * 16 + (tid >> 3)], __float_as_uint(m), epoch + 1, __float_as_uint(r), epoch + 1);
            STAMPW(12);
            bar_sync(NB_G1, 256);
          }
          gemm_loop<192, true, 0, D1>(d, sb, 10, wg ? zs0 : 0, 0, 0, 0, wg, 2, tid_now(), [&]() { if (G1_AT == 0 && wg == 0) bar_arrive(NB_G1, 256); }, [](int) {});
          asm volatile("setmaxnreg.inc.sync.aligned.u32 160;");
          STAMPW(wg ? 14 : 1);
          if (wg == 0) ZS(0);
          mbar_wait2(sb + BAR_XS, 0, sb + BAR_ST + 8 * wg, 0);
          if (wg == 0) ZS(1);
        }
        const int t1 = tid_now();
        const uint32_t xa1 = sb + OFF_XS + (w * 16 + ((t1 & 31) >> 2)) * 8;
        const float2 s0 = lds64f(xa1), s1 = lds64f(xa1 + 64);
        uint32_t z[48];
        float st[4];
        fence_async_smem();
        fold_mean(d, sb + OFF_CS + (1 - wg) * 768, s0.x, s1.x, t1 & 3);
        if (G1_AT == 1 && wg == 0) bar_arrive(NB_G1, 256);
        WG_WAIT(0);
        acc_fence<96>(d);
        if (wg == 0) ZS(2);
        gelu_tile(d, z, st, s0.y, s1.y);
        const int tid = tid_now(), lane = tid & 31, g = lane >> 2, t = lane & 3;
        if (wg == 1) {
          uint32_t bra, brb;
          asm volatile("ld.shared.u16 %0, [%1];" : "=r"(bra) : "r"(sb + OFF_BIAS + (w * 16 + g) * 2));
          asm volatile("ld.shared.u16 %0, [%1+16];" : "=r"(brb) : "r"(sb + OFF_BIAS + (w * 16 + g) * 2));
#pragma unroll
          for (int j = 0; j < 96; j++) d[j] = bf_lo((j & 2) ? brb : bra);
          STAMPW(15);
          gemm_loop<192, true, 1, D2>(d, sb, 32, 0, 1, 20, 0, 2, 2, tid, [&]() { if (HOLD_AT < 32) mbar_arrive_if(sb + BAR_GO, tid == 0); }, [](int) {});
          if (HOLD_AT == 32) mbar_arrive_if(sb + BAR_GO, tid == 0);
          STAMPW(16);
          const int t2 = tid_now(), l2 = t2 & 31;
          const uint32_t ha = sb + OFF_A + 5 * A_SLOT + (l2 >> 4) * 1024 + (2 * w + ((l2 >> 3) & 1)) * 128 + (l2 & 7) * 16;
#pragma unroll
          for (int j = 0; j < 24; j += 2) {
#pragma unroll
            for (int e = 0; e < 4; e++) z[2 * j + e] = hmul2(z[2 * j + e], pack2(d[4 * j + 2 * e], d[4 * j + 2 * e + 1]));
            stsm4(ha + j * 1024, z[2 * j], z[2 * j + 1], z[2 * j + 2], z[2 * j + 3]);
          }
          fence_async_smem();
          bar_sync(NB_WGB, 128);
          mbar_arrive_if(sb + BAR_AF + 8 * (t2 == 3 ? (BAR_G2 - BAR_AF) / 8 : (t2 == 4 ? (BAR_GO - BAR_AF) / 8 : 5 + t2)), t2 < (HOLD_AT == 33 ? 5 : 4));
          STAMPW(17);
          {
            float e[80];
#pragma unroll
            for (int j = 0; j < 80; j++) e[j] = 0.f;
            gemm_loop<160, false, 2, DB>(e, sb, 12, 5, 0, 2, 0, 2, 2, tid_now(), []() {}, [](int) {});
            STAMPW(10);
            const int t3 = tid_now();
#pragma unroll
            for (int j = 0; j < 10; j++) {
              sts128(sb + OFF_A + j * 2048 + t3 * 16, pack2(e[8 * j], e[8 * j + 1]), pack2(e[8 * j + 2], e[8 * j + 3]), pack2(e[8 * j + 4], e[8 * j + 5]),
                     pack2(e[8 * j + 6], e[8 * j + 7]));
              if (j == 4) bar_arrive(NB_WO, 256);
            }
            bar_arrive(NB_Z, 256);
            STAMPW(45);
          }
          return;
        }
        ZS(3);
        const bool hi = t & 2;
        float a0 = (hi ? st[2] : st[0]) + __shfl_xor_sync(0xffffffff, hi ? st[0] : st[2], 2);
        float a1 = (hi ? st[3] : st[1]) + __shfl_xor_sync(0xffffffff, hi ? st[1] : st[3], 2);
        a0 = ((t & 1) ? a1 : a0) + __shfl_xor_sync(0xffffffff, (t & 1) ? a0 : a1, 1);
        const uint32_t tag = lds32<0>(sb + OFF_TAG);
        uint2* zs = p.scr->zstat + (rb * 256 + w * 16 + g + (t >> 1) * 8) * 2 + (t & 1);
        st_ll2(zs + cb * 128, __float_as_uint(a0), tag);
        STAMPW(2); ZS(4);
        uint2 u[4];
#pragma unroll
        for (int i = 0; i < 4; i++) u[i] = ld_ll2(zs + i * 128);
        const uint32_t keep = (cb & 2) ? 13 << 5 : 13;
        mbar_arrive_if(sb + BAR_AE + 8 * tid, tid < NA && !((keep >> tid) & 1));
        const uint32_t za = sb + OFF_A + zs0 * A_SLOT + (2 * w + ((lane >> 3) & 1)) * 3072 + (lane >> 4) * 128 + (lane & 7) * 16;
        const float ca = 0.5f * (hi ? s1.y : s0.y), inv = 1.f / 768.f;
        mbar_wait2(sb + BAR_AE + 8 * (zs0 + 2), 0, sb + BAR_XC, 0);
        ZS(6);
        uint32_t t0 = 0;
#pragma unroll 1
        while (!__all_sync(0xffffffff, u[0].y == tag && u[1].y == tag && u[2].y == tag && u[3].y == tag)) {
          spin_guard(t0);
#pragma unroll
          for (int i = 0; i < 4; i++) u[i] = ld_ll2(zs + i * 128);
        }
        STAMPW(3); ZS(7);
        a0 = ((__uint_as_float(u[0].x) + __uint_as_float(u[1].x)) + (__uint_as_float(u[2].x) + __uint_as_float(u[3].x))) * inv;
        a1 = __shfl_xor_sync(0xffffffff, a0, 1);
        const float m = (t & 1) ? a1 : a0, q = (t & 1) ? a0 : a1;
        const float r = bf_lo(pack2(ca * rsqrtf(fmaf(fmaxf(fmaf(-m, m, q), 0.f), ca * ca, 1e-5f)), 0.f));
        const uint32_t rn = pack2(r, -m * r), ro = __shfl_xor_sync(0xffffffff, rn, 2);
        const uint32_t ra2 = prmt(hi ? ro : rn, 0, 0x1010), n2a = prmt(hi ? ro : rn, 0, 0x3232), rb2 = prmt(hi ? rn : ro, 0, 0x1010), n2b = prmt(hi ? rn : ro, 0, 0x3232);
        if (ZORD && w >= 2) bar_sync(NB_Z, 160);
#pragma unroll
        for (int j = 0; j < 24; j += 2)
          stsm4(za + j * 128, hfma2(z[2 * j], ra2, n2a), hfma2(z[2 * j + 1], rb2, n2b), hfma2(z[2 * j + 2], ra2, n2a), hfma2(z[2 * j + 3], rb2, n2b));
        ZS(8);
        fence_async_smem();
        ZS(9);
        if (w < 2) bar_arrive(NB_Z, ZORD ? 160 : 96);
        else bar_arrive(NB_Z2, 96);
        final_load_x(xw, sb + OFF_A, cb, 0, w, lane);
        fence_async_smem();
        bar_sync(NB_WGA, 128);
        mbar_arrive_if(sb + BAR_AE + 8 * tid, tid < NA && ((keep >> tid) & 1));
      }
      {
        const uint32_t zero = lds32<0>(sb + OFF_TAG + 4);
#pragma unroll
        for (int i = 0; i < 20; i++) xw[i / 10][i % 10] |= zero;
      }
      load_taps(k, p, chb + 64, tid_now());
      STAMPW(4);
    }
    const int h = wg >> 1;
    {
    const int tid = tid_now(), lane = tid & 31;
    conv_worker(p, k, sb + OFF_CV + (1 - h) * CV_SZ, sb + OFF_A + 9 * A_SLOT + h * 4096, sb + BAR_XF + 8 * h, NB_WGA + h,
                chb + (h ? 0 : 64), 2 + h, sb + BAR_GO, w, lane, tid, h ? 40 : 5, rb, cb);
    {
      const int t3 = tid_now(), l3 = t3 & 31;
      const uint32_t xs_addr = sb + OFF_XS + (w * 16 + (l3 >> 2)) * 8;
      const float2 s0 = lds64f(xs_addr), s1 = lds64f(xs_addr + 64);
      const uint32_t ya = sb + y_tile(h) + ((l3 >> 4) * 8 + (l3 & 7)) * 128 + (((2 * w + ((l3 >> 3) & 1)) ^ (l3 & 7) ^ (rb & 7)) << 4);
      uint32_t sw[2][10];
      mbar_wait(sb + BAR_XF + 8 * h, h);
      final_s_early(sw, xw, ya, s0, s1);
      uint32_t ph = 1, t0 = 0, y[8];
#pragma unroll 1
      while (true) {
        mbar_wait(sb + BAR_YL + 16 * h, ph);
        if (bar_all(NB_WGA + h, 128, final_late(y, ya))) break;
        spin_guard(t0);
        ph ^= 1;
        if (t3 == 0) load_late_y(p, sb, h, rb, cb, lds32<0>(sb + OFF_TAG) & 1);
      }
#pragma unroll
      for (int e = 0; e < 8; e++) sw[e & 1][4 + (e >> 1)] = hmul2(sw[e & 1][4 + (e >> 1)], ~y[e]);
      __nv_bfloat16* o0 = p.out + (size_t)(w * 512 + rb * 16 + (l3 >> 2)) * kD + seg_col(cb, h);
      STAMPW(h ? 44 : 9);
      bar_sync(h ? NB_Z : NB_WO, 256);
      float d[40];
#pragma unroll
      for (int j = 0; j < 5; j++) {
        const uint4 v = lds128(sb + OFF_A + (h * 5 + j) * 2048 + t3 * 16);
        d[8 * j] = bf_lo(v.x); d[8 * j + 1] = bf_hi(v.x); d[8 * j + 2] = bf_lo(v.y); d[8 * j + 3] = bf_hi(v.y);
        d[8 * j + 4] = bf_lo(v.z); d[8 * j + 5] = bf_hi(v.z); d[8 * j + 6] = bf_lo(v.w); d[8 * j + 7] = bf_hi(v.w);
      }
      final_out(d, xw, sw, s0.y, s1.y, o0, h, l3 & 3);
    }
    }
  }
}

typedef CUresult (*EncodeFn)(CUtensorMap*, CUtensorMapDataType, cuuint32_t, void*, const cuuint64_t*, const cuuint64_t*, const cuuint32_t*,
                             const cuuint32_t*, CUtensorMapInterleave, CUtensorMapSwizzle, CUtensorMapL2promotion, CUtensorMapFloatOOBfill);

void encode(EncodeFn fn, CUtensorMap* m, const void* ptr, int rank, const cuuint64_t* dims, const cuuint64_t* strides, const cuuint32_t* box,
            CUtensorMapSwizzle swz = CU_TENSOR_MAP_SWIZZLE_128B) {
  const cuuint32_t es[3] = {1, 1, 1};
  fn(m, CU_TENSOR_MAP_DATA_TYPE_BFLOAT16, rank, const_cast<void*>(ptr), dims, strides, box, es, CU_TENSOR_MAP_INTERLEAVE_NONE,
     swz, CU_TENSOR_MAP_L2_PROMOTION_L2_128B, CU_TENSOR_MAP_FLOAT_OOB_FILL_NONE);
}

}

extern "C" void kernel_launch(void* const* d_in, const int* in_sizes, int n_in, void* d_out, int out_size) {
  (void)in_sizes; (void)n_in; (void)out_size;
  static EncodeFn enc = nullptr;
  static Scratch* scr = nullptr;
  static int sms = 0;
  if (!enc) {
    void* fn = nullptr;
    cudaDriverEntryPointQueryResult qr;
    cudaGetDriverEntryPoint("cuTensorMapEncodeTiled", &fn, cudaEnableDefault, &qr);
    enc = (EncodeFn)fn;
    cudaFuncSetAttribute(fused_kernel, cudaFuncAttributeMaxDynamicSharedMemorySize, SMEM_BYTES);
    cudaGetSymbolAddress((void**)&scr, g_scr);
    int dev = 0;
    cudaGetDevice(&dev);
    cudaDeviceGetAttribute(&sms, cudaDevAttrMultiProcessorCount, dev);
  }
  Params p;
  p.scr = scr;
  p.by_smid = sms == 132;
  p.k = (const __nv_bfloat16*)d_in[1];
  p.v = (const __nv_bfloat16*)d_in[2];
  p.shift = (const __nv_bfloat16*)d_in[3];
  p.ssmk = (const __nv_bfloat16*)d_in[4];
  p.ssmD = (const __nv_bfloat16*)d_in[5];
  p.wsp = (const __nv_bfloat16*)d_in[8];
  p.bsp = (const __nv_bfloat16*)d_in[9];
  p.wout = (const __nv_bfloat16*)d_in[10];
  p.out = (__nv_bfloat16*)d_out;
  for (int i = 0; i < 2; i++) {
    const cuuint64_t n = i ? kS : kD, dims[3] = {n, 512, 4}, st[2] = {n * 2, n * 1024};
    const cuuint32_t box[3] = {64, 16, 4};
    encode(enc, i ? &p.tmWsp : &p.tmX, d_in[i ? 8 : 0], 3, dims, st, box);
  }
  {
    const cuuint64_t dims[3] = {64, kD, kF / 64}, st[2] = {kF * 2, 128};
    const cuuint32_t box[3] = {64, 64, 3};
    encode(enc, &p.tmW, d_in[7], 3, dims, st, box);
  }
  {
    const cuuint64_t dims[2] = {kS, 896}, st[1] = {kS * 2};
    const cuuint32_t box[2] = {64, 16};
    encode(enc, &p.tmY, scr->y, 2, dims, st, box);
  }
  {
    const cuuint64_t dims[3] = {1024, kD / 2, 4}, st[2] = {8192, 2048};
    const cuuint32_t box[3] = {16, 32, 4};
    encode(enc, &p.tmKV, scr->kvx, 3, dims, st, box, CU_TENSOR_MAP_SWIZZLE_32B);
  }
  fused_kernel<<<132, 512, SMEM_BYTES, cudaStreamPerThread>>>(p);
}
```

```cpp
#include <cuda_runtime.h>
#include <cuda.h>
#include <cuda_bf16.h>
#include <stdint.h>

template <int N> struct WG;
template <> struct WG<16> {
  static __device__ __forceinline__ void rs(float* d, const uint32_t* a, uint64_t db) {
    asm volatile("{\n.reg .pred p;\nsetp.ne.b32 p, 1, 0;\nwgmma.mma_async.sync.aligned.m64n16k16.f32.bf16.bf16 {"
      "%0, %1, %2, %3, %4, %5, %6, %7"
      "}, {%8, %9, %10, %11}, %12, p, 1, 1, 0;\n}\n"
      :
      "+f"(d[0]), "+f"(d[1]), "+f"(d[2]), "+f"(d[3]), "+f"(d[4]), "+f"(d[5]), "+f"(d[6]), "+f"(d[7])
      : "r"(a[0]), "r"(a[1]), "r"(a[2]), "r"(a[3]), "l"(db));
  }
};
template <> struct WG<32> {
  static __device__ __forceinline__ void rs(float* d, const uint32_t* a, uint64_t db) {
    asm volatile("{\n.reg .pred p;\nsetp.ne.b32 p, 1, 0;\nwgmma.mma_async.sync.aligned.m64n32k16.f32.bf16.bf16 {"
      "%0, %1, %2, %3, %4, %5, %6, %7, %8, %9, %10, %11, %12, %13, %14, %15"
      "}, {%16, %17, %18, %19}, %20, p, 1, 1, 0;\n}\n"
      :
      "+f"(d[0]), "+f"(d[1]), "+f"(d[2]), "+f"(d[3]), "+f"(d[4]), "+f"(d[5]), "+f"(d[6]), "+f"(d[7]),
      "+f"(d[8]), "+f"(d[9]), "+f"(d[10]), "+f"(d[11]), "+f"(d[12]), "+f"(d[13]), "+f"(d[14]), "+f"(d[15])
      : "r"(a[0]), "r"(a[1]), "r"(a[2]), "r"(a[3]), "l"(db));
  }
};
template <> struct WG<48> {
  static __device__ __forceinline__ void rs(float* d, const uint32_t* a, uint64_t db) {
    asm volatile("{\n.reg .pred p;\nsetp.ne.b32 p, 1, 0;\nwgmma.mma_async.sync.aligned.m64n48k16.f32.bf16.bf16 {"
      "%0, %1, %2, %3, %4, %5, %6, %7, %8, %9, %10, %11, %12, %13, %14, %15, "
      "%16, %17, %18, %19, %20, %21, %22, %23"
      "}, {%24, %25, %26, %27}, %28, p, 1, 1, 0;\n}\n"
      :
      "+f"(d[0]), "+f"(d[1]), "+f"(d[2]), "+f"(d[3]), "+f"(d[4]), "+f"(d[5]), "+f"(d[6]), "+f"(d[7]),
      "+f"(d[8]), "+f"(d[9]), "+f"(d[10]), "+f"(d[11]), "+f"(d[12]), "+f"(d[13]), "+f"(d[14]), "+f"(d[15]),
      "+f"(d[16]), "+f"(d[17]), "+f"(d[18]), "+f"(d[19]), "+f"(d[20]), "+f"(d[21]), "+f"(d[22]), "+f"(d[23])
      : "r"(a[0]), "r"(a[1]), "r"(a[2]), "r"(a[3]), "l"(db));
  }
};
template <> struct WG<64> {
  static __device__ __forceinline__ void rs(float* d, const uint32_t* a, uint64_t db) {
    asm volatile("{\n.reg .pred p;\nsetp.ne.b32 p, 1, 0;\nwgmma.mma_async.sync.aligned.m64n64k16.f32.bf16.bf16 {"
      "%0, %1, %2, %3, %4, %5, %6, %7, %8, %9, %10, %11, %12, %13, %14, %15, "
      "%16, %17, %18, %19, %20, %21, %22, %23, %24, %25, %26, %27, %28, %29, %30, %31"
      "}, {%32, %33, %34, %35}, %36, p, 1, 1, 0;\n}\n"
      :
      "+f"(d[0]), "+f"(d[1]), "+f"(d[2]), "+f"(d[3]), "+f"(d[4]), "+f"(d[5]), "+f"(d[6]), "+f"(d[7]),
      "+f"(d[8]), "+f"(d[9]), "+f"(d[10]), "+f"(d[11]), "+f"(d[12]), "+f"(d[13]), "+f"(d[14]), "+f"(d[15]),
      "+f"(d[16]), "+f"(d[17]), "+f"(d[18]), "+f"(d[19]), "+f"(d[20]), "+f"(d[21]), "+f"(d[22]), "+f"(d[23]),
      "+f"(d[24]), "+f"(d[25]), "+f"(d[26]), "+f"(d[27]), "+f"(d[28]), "+f"(d[29]), "+f"(d[30]), "+f"(d[31])
      : "r"(a[0]), "r"(a[1]), "r"(a[2]), "r"(a[3]), "l"(db));
  }
};
template <> struct WG<80> {
  static __device__ __forceinline__ void rs(float* d, const uint32_t* a, uint64_t db) {
    asm volatile("{\n.reg .pred p;\nsetp.ne.b32 p, 1, 0;\nwgmma.mma_async.sync.aligned.m64n80k16.f32.bf16.bf16 {"
      "%0, %1, %2, %3, %4, %5, %6, %7, %8, %9, %10, %11, %12, %13, %14, %15, "
      "%16, %17, %18, %19, %20, %21, %22, %23, %24, %25, %26, %27, %28, %29, %30, %31, "
      "%32, %33, %34, %35, %36, %37, %38, %39"
      "}, {%40, %41, %42, %43}, %44, p, 1, 1, 0;\n}\n"
      :
      "+f"(d[0]), "+f"(d[1]), "+f"(d[2]), "+f"(d[3]), "+f"(d[4]), "+f"(d[5]), "+f"(d[6]), "+f"(d[7]),
      "+f"(d[8]), "+f"(d[9]), "+f"(d[10]), "+f"(d[11]), "+f"(d[12]), "+f"(d[13]), "+f"(d[14]), "+f"(d[15]),
      "+f"(d[16]), "+f"(d[17]), "+f"(d[18]), "+f"(d[19]), "+f"(d[20]), "+f"(d[21]), "+f"(d[22]), "+f"(d[23]),
      "+f"(d[24]), "+f"(d[25]), "+f"(d[26]), "+f"(d[27]), "+f"(d[28]), "+f"(d[29]), "+f"(d[30]), "+f"(d[31]),
      "+f"(d[32]), "+f"(d[33]), "+f"(d[34]), "+f"(d[35]), "+f"(d[36]), "+f"(d[37]), "+f"(d[38]), "+f"(d[39])
      : "r"(a[0]), "r"(a[1]), "r"(a[2]), "r"(a[3]), "l"(db));
  }
};
template <> struct WG<96> {
  static __device__ __forceinline__ void rs(float* d, const uint32_t* a, uint64_t db) {
    asm volatile("{\n.reg .pred p;\nsetp.ne.b32 p, 1, 0;\nwgmma.mma_async.sync.aligned.m64n96k16.f32.bf16.bf16 {"
      "%0, %1, %2, %3, %4, %5, %6, %7, %8, %9, %10, %11, %12, %13, %14, %15, "
      "%16, %17, %18, %19, %20, %21, %22, %23, %24, %25, %26, %27, %28, %29, %30, %31, "
      "%32, %33, %34, %35, %36, %37, %38, %39, %40, %41, %42, %43, %44, %45, %46, %47"
      "}, {%48, %49, %50, %51}, %52, p, 1, 1, 0;\n}\n"
      :
      "+f"(d[0]), "+f"(d[1]), "+f"(d[2]), "+f"(d[3]), "+f"(d[4]), "+f"(d[5]), "+f"(d[6]), "+f"(d[7]),
      "+f"(d[8]), "+f"(d[9]), "+f"(d[10]), "+f"(d[11]), "+f"(d[12]), "+f"(d[13]), "+f"(d[14]), "+f"(d[15]),
      "+f"(d[16]), "+f"(d[17]), "+f"(d[18]), "+f"(d[19]), "+f"(d[20]), "+f"(d[21]), "+f"(d[22]), "+f"(d[23]),
      "+f"(d[24]), "+f"(d[25]), "+f"(d[26]), "+f"(d[27]), "+f"(d[28]), "+f"(d[29]), "+f"(d[30]), "+f"(d[31]),
      "+f"(d[32]), "+f"(d[33]), "+f"(d[34]), "+f"(d[35]), "+f"(d[36]), "+f"(d[37]), "+f"(d[38]), "+f"(d[39]),
      "+f"(d[40]), "+f"(d[41]), "+f"(d[42]), "+f"(d[43]), "+f"(d[44]), "+f"(d[45]), "+f"(d[46]), "+f"(d[47])
      : "r"(a[0]), "r"(a[1]), "r"(a[2]), "r"(a[3]), "l"(db));
  }
};
template <> struct WG<112> {
  static __device__ __forceinline__ void rs(float* d, const uint32_t* a, uint64_t db) {
    asm volatile("{\n.reg .pred p;\nsetp.ne.b32 p, 1, 0;\nwgmma.mma_async.sync.aligned.m64n112k16.f32.bf16.bf16 {"
      "%0, %1, %2, %3, %4, %5, %6, %7, %8, %9, %10, %11, %12, %13, %14, %15, "
      "%16, %17, %18, %19, %20, %21, %22, %23, %24, %25, %26, %27, %28, %29, %30, %31, "
      "%32, %33, %34, %35, %36, %37, %38, %39, %40, %41, %42, %43, %44, %45, %46, %47, "
      "%48, %49, %50, %51, %52, %53, %54, %55"
      "}, {%56, %57, %58, %59}, %60, p, 1, 1, 0;\n}\n"
      :
      "+f"(d[0]), "+f"(d[1]), "+f"(d[2]), "+f"(d[3]), "+f"(d[4]), "+f"(d[5]), "+f"(d[6]), "+f"(d[7]),
      "+f"(d[8]), "+f"(d[9]), "+f"(d[10]), "+f"(d[11]), "+f"(d[12]), "+f"(d[13]), "+f"(d[14]), "+f"(d[15]),
      "+f"(d[16]), "+f"(d[17]), "+f"(d[18]), "+f"(d[19]), "+f"(d[20]), "+f"(d[21]), "+f"(d[22]), "+f"(d[23]),
      "+f"(d[24]), "+f"(d[25]), "+f"(d[26]), "+f"(d[27]), "+f"(d[28]), "+f"(d[29]), "+f"(d[30]), "+f"(d[31]),
      "+f"(d[32]), "+f"(d[33]), "+f"(d[34]), "+f"(d[35]), "+f"(d[36]), "+f"(d[37]), "+f"(d[38]), "+f"(d[39]),
      "+f"(d[40]), "+f"(d[41]), "+f"(d[42]), "+f"(d[43]), "+f"(d[44]), "+f"(d[45]), "+f"(d[46]), "+f"(d[47]),
      "+f"(d[48]), "+f"(d[49]), "+f"(d[50]), "+f"(d[51]), "+f"(d[52]), "+f"(d[53]), "+f"(d[54]), "+f"(d[55])
      : "r"(a[0]), "r"(a[1]), "r"(a[2]), "r"(a[3]), "l"(db));
  }
};
template <> struct WG<128> {
  static __device__ __forceinline__ void rs(float* d, const uint32_t* a, uint64_t db) {
    asm volatile("{\n.reg .pred p;\nsetp.ne.b32 p, 1, 0;\nwgmma.mma_async.sync.aligned.m64n128k16.f32.bf16.bf16 {"
      "%0, %1, %2, %3, %4, %5, %6, %7, %8, %9, %10, %11, %12, %13, %14, %15, "
      "%16, %17, %18, %19, %20, %21, %22, %23, %24, %25, %26, %27, %28, %29, %30, %31, "
      "%32, %33, %34, %35, %36, %37, %38, %39, %40, %41, %42, %43, %44, %45, %46, %47, "
      "%48, %49, %50, %51, %52, %53, %54, %55, %56, %57, %58, %59, %60, %61, %62, %63"
      "}, {%64, %65, %66, %67}, %68, p, 1, 1, 0;\n}\n"
      :
      "+f"(d[0]), "+f"(d[1]), "+f"(d[2]), "+f"(d[3]), "+f"(d[4]), "+f"(d[5]), "+f"(d[6]), "+f"(d[7]),
      "+f"(d[8]), "+f"(d[9]), "+f"(d[10]), "+f"(d[11]), "+f"(d[12]), "+f"(d[13]), "+f"(d[14]), "+f"(d[15]),
      "+f"(d[16]), "+f"(d[17]), "+f"(d[18]), "+f"(d[19]), "+f"(d[20]), "+f"(d[21]), "+f"(d[22]), "+f"(d[23]),
      "+f"(d[24]), "+f"(d[25]), "+f"(d[26]), "+f"(d[27]), "+f"(d[28]), "+f"(d[29]), "+f"(d[30]), "+f"(d[31]),
      "+f"(d[32]), "+f"(d[33]), "+f"(d[34]), "+f"(d[35]), "+f"(d[36]), "+f"(d[37]), "+f"(d[38]), "+f"(d[39]),
      "+f"(d[40]), "+f"(d[41]), "+f"(d[42]), "+f"(d[43]), "+f"(d[44]), "+f"(d[45]), "+f"(d[46]), "+f"(d[47]),
      "+f"(d[48]), "+f"(d[49]), "+f"(d[50]), "+f"(d[51]), "+f"(d[52]), "+f"(d[53]), "+f"(d[54]), "+f"(d[55]),
      "+f"(d[56]), "+f"(d[57]), "+f"(d[58]), "+f"(d[59]), "+f"(d[60]), "+f"(d[61]), "+f"(d[62]), "+f"(d[63])
      : "r"(a[0]), "r"(a[1]), "r"(a[2]), "r"(a[3]), "l"(db));
  }
};
template <> struct WG<160> {
  static __device__ __forceinline__ void ss(float* d, uint64_t da, uint64_t db, int sd) {
    asm volatile("{\n.reg .pred p;\nsetp.ne.b32 p, %82, 0;\nwgmma.mma_async.sync.aligned.m64n160k16.f32.bf16.bf16 {"
      "%0, %1, %2, %3, %4, %5, %6, %7, %8, %9, %10, %11, %12, %13, %14, %15, "
      "%16, %17, %18, %19, %20, %21, %22, %23, %24, %25, %26, %27, %28, %29, %30, %31, "
      "%32, %33, %34, %35, %36, %37, %38, %39, %40, %41, %42, %43, %44, %45, %46, %47, "
      "%48, %49, %50, %51, %52, %53, %54, %55, %56, %57, %58, %59, %60, %61, %62, %63, "
      "%64, %65, %66, %67, %68, %69, %70, %71, %72, %73, %74, %75, %76, %77, %78, %79"
      "}, %80, %81, p, 1, 1, 0, 1;\n}\n"
      :
      "+f"(d[0]), "+f"(d[1]), "+f"(d[2]), "+f"(d[3]), "+f"(d[4]), "+f"(d[5]), "+f"(d[6]), "+f"(d[7]),
      "+f"(d[8]), "+f"(d[9]), "+f"(d[10]), "+f"(d[11]), "+f"(d[12]), "+f"(d[13]), "+f"(d[14]), "+f"(d[15]),
      "+f"(d[16]), "+f"(d[17]), "+f"(d[18]), "+f"(d[19]), "+f"(d[20]), "+f"(d[21]), "+f"(d[22]), "+f"(d[23]),
      "+f"(d[24]), "+f"(d[25]), "+f"(d[26]), "+f"(d[27]), "+f"(d[28]), "+f"(d[29]), "+f"(d[30]), "+f"(d[31]),
      "+f"(d[32]), "+f"(d[33]), "+f"(d[34]), "+f"(d[35]), "+f"(d[36]), "+f"(d[37]), "+f"(d[38]), "+f"(d[39]),
      "+f"(d[40]), "+f"(d[41]), "+f"(d[42]), "+f"(d[43]), "+f"(d[44]), "+f"(d[45]), "+f"(d[46]), "+f"(d[47]),
      "+f"(d[48]), "+f"(d[49]), "+f"(d[50]), "+f"(d[51]), "+f"(d[52]), "+f"(d[53]), "+f"(d[54]), "+f"(d[55]),
      "+f"(d[56]), "+f"(d[57]), "+f"(d[58]), "+f"(d[59]), "+f"(d[60]), "+f"(d[61]), "+f"(d[62]), "+f"(d[63]),
      "+f"(d[64]), "+f"(d[65]), "+f"(d[66]), "+f"(d[67]), "+f"(d[68]), "+f"(d[69]), "+f"(d[70]), "+f"(d[71]),
      "+f"(d[72]), "+f"(d[73]), "+f"(d[74]), "+f"(d[75]), "+f"(d[76]), "+f"(d[77]), "+f"(d[78]), "+f"(d[79])
      : "l"(da), "l"(db), "r"(sd));
  }
};
template <> struct WG<192> {
  static __device__ __forceinline__ void ss(float* d, uint64_t da, uint64_t db, int sd) {
    asm volatile("{\n.reg .pred p;\nsetp.ne.b32 p, %98, 0;\nwgmma.mma_async.sync.aligned.m64n192k16.f32.bf16.bf16 {"
      "%0, %1, %2, %3, %4, %5, %6, %7, %8, %9, %10, %11, %12, %13, %14, %15, "
      "%16, %17, %18, %19, %20, %21, %22, %23, %24, %25, %26, %27, %28, %29, %30, %31, "
      "%32, %33, %34, %35, %36, %37, %38, %39, %40, %41, %42, %43, %44, %45, %46, %47, "
      "%48, %49, %50, %51, %52, %53, %54, %55, %56, %57, %58, %59, %60, %61, %62, %63, "
      "%64, %65, %66, %67, %68, %69, %70, %71, %72, %73, %74, %75, %76, %77, %78, %79, "
      "%80, %81, %82, %83, %84, %85, %86, %87, %88, %89, %90, %91, %92, %93, %94, %95"
      "}, %96, %97, p, 1, 1, 0, 1;\n}\n"
      :
      "+f"(d[0]), "+f"(d[1]), "+f"(d[2]), "+f"(d[3]), "+f"(d[4]), "+f"(d[5]), "+f"(d[6]), "+f"(d[7]),
      "+f"(d[8]), "+f"(d[9]), "+f"(d[10]), "+f"(d[11]), "+f"(d[12]), "+f"(d[13]), "+f"(d[14]), "+f"(d[15]),
      "+f"(d[16]), "+f"(d[17]), "+f"(d[18]), "+f"(d[19]), "+f"(d[20]), "+f"(d[21]), "+f"(d[22]), "+f"(d[23]),
      "+f"(d[24]), "+f"(d[25]), "+f"(d[26]), "+f"(d[27]), "+f"(d[28]), "+f"(d[29]), "+f"(d[30]), "+f"(d[31]),
      "+f"(d[32]), "+f"(d[33]), "+f"(d[34]), "+f"(d[35]), "+f"(d[36]), "+f"(d[37]), "+f"(d[38]), "+f"(d[39]),
      "+f"(d[40]), "+f"(d[41]), "+f"(d[42]), "+f"(d[43]), "+f"(d[44]), "+f"(d[45]), "+f"(d[46]), "+f"(d[47]),
      "+f"(d[48]), "+f"(d[49]), "+f"(d[50]), "+f"(d[51]), "+f"(d[52]), "+f"(d[53]), "+f"(d[54]), "+f"(d[55]),
      "+f"(d[56]), "+f"(d[57]), "+f"(d[58]), "+f"(d[59]), "+f"(d[60]), "+f"(d[61]), "+f"(d[62]), "+f"(d[63]),
      "+f"(d[64]), "+f"(d[65]), "+f"(d[66]), "+f"(d[67]), "+f"(d[68]), "+f"(d[69]), "+f"(d[70]), "+f"(d[71]),
      "+f"(d[72]), "+f"(d[73]), "+f"(d[74]), "+f"(d[75]), "+f"(d[76]), "+f"(d[77]), "+f"(d[78]), "+f"(d[79]),
      "+f"(d[80]), "+f"(d[81]), "+f"(d[82]), "+f"(d[83]), "+f"(d[84]), "+f"(d[85]), "+f"(d[86]), "+f"(d[87]),
      "+f"(d[88]), "+f"(d[89]), "+f"(d[90]), "+f"(d[91]), "+f"(d[92]), "+f"(d[93]), "+f"(d[94]), "+f"(d[95])
      : "l"(da), "l"(db), "r"(sd));
  }
  static __device__ __forceinline__ void rst(float* d, const uint32_t* a, uint64_t db) {
    asm volatile("{\n.reg .pred p;\nsetp.ne.b32 p, 1, 0;\nwgmma.mma_async.sync.aligned.m64n192k16.f32.bf16.bf16 {"
      "%0, %1, %2, %3, %4, %5, %6, %7, %8, %9, %10, %11, %12, %13, %14, %15, "
      "%16, %17, %18, %19, %20, %21, %22, %23, %24, %25, %26, %27, %28, %29, %30, %31, "
      "%32, %33, %34, %35, %36, %37, %38, %39, %40, %41, %42, %43, %44, %45, %46, %47, "
      "%48, %49, %50, %51, %52, %53, %54, %55, %56, %57, %58, %59, %60, %61, %62, %63, "
      "%64, %65, %66, %67, %68, %69, %70, %71, %72, %73, %74, %75, %76, %77, %78, %79, "
      "%80, %81, %82, %83, %84, %85, %86, %87, %88, %89, %90, %91, %92, %93, %94, %95"
      "}, {%96, %97, %98, %99}, %100, p, 1, 1, 1;\n}\n"
      :
      "+f"(d[0]), "+f"(d[1]), "+f"(d[2]), "+f"(d[3]), "+f"(d[4]), "+f"(d[5]), "+f"(d[6]), "+f"(d[7]),
      "+f"(d[8]), "+f"(d[9]), "+f"(d[10]), "+f"(d[11]), "+f"(d[12]), "+f"(d[13]), "+f"(d[14]), "+f"(d[15]),
      "+f"(d[16]), "+f"(d[17]), "+f"(d[18]), "+f"(d[19]), "+f"(d[20]), "+f"(d[21]), "+f"(d[22]), "+f"(d[23]),
      "+f"(d[24]), "+f"(d[25]), "+f"(d[26]), "+f"(d[27]), "+f"(d[28]), "+f"(d[29]), "+f"(d[30]), "+f"(d[31]),
      "+f"(d[32]), "+f"(d[33]), "+f"(d[34]), "+f"(d[35]), "+f"(d[36]), "+f"(d[37]), "+f"(d[38]), "+f"(d[39]),
      "+f"(d[40]), "+f"(d[41]), "+f"(d[42]), "+f"(d[43]), "+f"(d[44]), "+f"(d[45]), "+f"(d[46]), "+f"(d[47]),
      "+f"(d[48]), "+f"(d[49]), "+f"(d[50]), "+f"(d[51]), "+f"(d[52]), "+f"(d[53]), "+f"(d[54]), "+f"(d[55]),
      "+f"(d[56]), "+f"(d[57]), "+f"(d[58]), "+f"(d[59]), "+f"(d[60]), "+f"(d[61]), "+f"(d[62]), "+f"(d[63]),
      "+f"(d[64]), "+f"(d[65]), "+f"(d[66]), "+f"(d[67]), "+f"(d[68]), "+f"(d[69]), "+f"(d[70]), "+f"(d[71]),
      "+f"(d[72]), "+f"(d[73]), "+f"(d[74]), "+f"(d[75]), "+f"(d[76]), "+f"(d[77]), "+f"(d[78]), "+f"(d[79]),
      "+f"(d[80]), "+f"(d[81]), "+f"(d[82]), "+f"(d[83]), "+f"(d[84]), "+f"(d[85]), "+f"(d[86]), "+f"(d[87]),
      "+f"(d[88]), "+f"(d[89]), "+f"(d[90]), "+f"(d[91]), "+f"(d[92]), "+f"(d[93]), "+f"(d[94]), "+f"(d[95])
      : "r"(a[0]), "r"(a[1]), "r"(a[2]), "r"(a[3]), "l"(db));
  }
};

#define ZSH 1
#define ZP_AT 1
#define CPRE0 1
#define ZORD 1
#define CS1BY 1
#define CS1_T 9500
#define Z1_AT 4
#define G1_AT 0
#define HGRP 3
#define HPACE 200
#define DB 0
#define HOLD_AT 33
#define LL_AT 4
#define KV_T0 2300
#define ST_YIELD 1
#define HP0 0
#define HPD 0
#define RAMP 1
#define LEAD 2
#define WSP_N 16
#define EARLY 0
#define CPIN 1
#define CW0 0
#define PFT 1
#define WSP_D 600
#define D1 4
#define D2 4
#define NSLEEP 32

static_assert(ZP_AT <= RAMP && LEAD <= 2, "staging slots");

namespace {

constexpr int kS = 2048, kD = 640, kF = 1536;
constexpr int NA = 10, NA2 = 9, NB = 5;
constexpr int A_SLOT = 8192, B_SLOT = 24576;
constexpr int OFF_A = 0;
constexpr int OFF_B = OFF_A + NA * A_SLOT;
constexpr int XB_PL = 2112;
constexpr int CV_KE = 4224, CV_KO = CV_KE + 4160;
constexpr int CV_SZ = CV_KO + 4160;
constexpr int OFF_CV = OFF_B + NB * B_SLOT;
constexpr int OFF_CS = OFF_CV + 2 * CV_SZ;
constexpr int OFF_BIAS = OFF_CS + 1536;
constexpr int OFF_XS = OFF_BIAS + 128;
constexpr int OFF_BAR = OFF_XS + 512;
constexpr int BAR_AF = OFF_BAR, BAR_ST = BAR_AF + 8 * NA, BAR_XF = BAR_ST + 16, BAR_KV = BAR_XF + 16;
constexpr int BAR_BF = OFF_BAR + 128, BAR_G2 = BAR_BF + 8 * (NB + 1), BAR_XS = BAR_G2 + 8, BAR_KU = BAR_XS + 8, BAR_ZP = BAR_KU + 40, BAR_XC = BAR_ZP + 8, BAR_WO = BAR_XC + 8;
constexpr int BAR_AE = OFF_BAR + 256, BAR_BE = BAR_AE + 8 * NA;
constexpr int BAR_YT = BAR_KU + 24;
constexpr int BAR_Z1 = BAR_ST;
constexpr int BAR_GO = BAR_XS;
constexpr int BAR_YL = BAR_KU + 16;
constexpr int OFF_TAG = OFF_CS - 32;
constexpr int SMEM_BYTES = OFF_BAR + 384;
static_assert(SMEM_BYTES <= 232448, "smem");
constexpr int NB_WGA = 1, NB_WGC = 2, NB_G1 = 3, NB_WO = 4, NB_CD = 5, NB_Z = 6, NB_WGB = 7, NB_Z2 = 8;

constexpr int CNT_Y = 1, CNT_Z1 = 3, CNT_KV = 32, CNT_WO = 36;
struct Scratch {
  uint8_t kvx[kD * 4096];
  uint8_t z2[4 * 32 * 24576];
  uint8_t h[32 * 12 * 8192];
  uint8_t wo[4 * 12 * 20480];
  uint8_t y[896 * 4096];
  uint4 xstat[kS];
  uint2 zstat[kS * 8];
  uint2 colsum[kF];
  uint32_t zcnt[4 * 32];
  uint32_t cnt[2 * 32];
  uint32_t hcnt[32 * 32];
  uint32_t epoch[136];
};
__device__ __align__(1024) Scratch g_scr;
#define ZS(i)
#define STAMP(i)
#define STAMP2(i)
#define STAMPW(i)

struct Params {
  Scratch* scr;
  int by_smid;
  const __nv_bfloat16 *k, *v, *shift, *ssmk, *ssmD, *wsp, *bsp, *wout;
  __nv_bfloat16* out;
  CUtensorMap tmX, tmW, tmWsp, tmY, tmKV;
};

__device__ __forceinline__ uint64_t mkdesc(uint32_t addr, uint32_t lbo, uint32_t sbo, uint32_t swz) {
  return (uint64_t)((addr & 0x3FFFF) >> 4) | ((uint64_t)(lbo >> 4) << 16) | ((uint64_t)(sbo >> 4) << 32) | ((uint64_t)swz << 62);
}
#define WG_FENCE() asm volatile("wgmma.fence.sync.aligned;" ::: "memory")
#define WG_COMMIT() asm volatile("wgmma.commit_group.sync.aligned;" ::: "memory")
#define WG_WAIT(n) asm volatile("wgmma.wait_group.sync.aligned %0;" ::"n"(n) : "memory")
template <int N> __device__ __forceinline__ void acc_fence(float* d) {
#pragma unroll
  for (int i = 0; i < N; i++) asm volatile("" : "+f"(d[i])::"memory");
}
__device__ __forceinline__ void mbar_init(uint32_t bar, int cnt) { asm volatile("mbarrier.init.shared::cta.b64 [%0], %1;" ::"r"(bar), "r"(cnt) : "memory"); }
__device__ __forceinline__ void mbar_expect(uint32_t bar, uint32_t bytes) { asm volatile("mbarrier.arrive.expect_tx.shared::cta.b64 _, [%0], %1;" ::"r"(bar), "r"(bytes) : "memory"); }
__device__ __forceinline__ void mbar_arrive(uint32_t bar) { asm volatile("mbarrier.arrive.shared::cta.b64 _, [%0];" ::"r"(bar) : "memory"); }
__device__ __forceinline__ void mbar_arrive_if(uint32_t bar, bool c) {
  asm volatile("{\n.reg .pred p;\nsetp.ne.u32 p, %1, 0;\n@p mbarrier.arrive.shared::cta.b64 _, [%0];\n}\n" ::"r"(bar), "r"((uint32_t)c) : "memory");
}
__device__ __forceinline__ void mbar_expect_if(uint32_t bar, uint32_t bytes, bool c) {
  asm volatile("{\n.reg .pred p;\nsetp.ne.u32 p, %2, 0;\n@p mbarrier.arrive.expect_tx.shared::cta.b64 _, [%0], %1;\n}\n" ::"r"(bar), "r"(bytes), "r"((uint32_t)c) : "memory");
}
__device__ __forceinline__ bool mbar_try(uint32_t bar, uint32_t parity) {
  uint32_t ok;
  asm volatile("{\n.reg .pred p;\nmbarrier.try_wait.parity.shared::cta.b64 p, [%1], %2;\nselp.u32 %0, 1, 0, p;\n}\n" : "=r"(ok) : "r"(bar), "r"(parity) : "memory");
  return ok;
}
__device__ __forceinline__ bool mbar_test(uint32_t bar, uint32_t parity) {
  uint32_t ok;
  asm volatile("{\n.reg .pred p;\nmbarrier.test_wait.parity.shared::cta.b64 p, [%1], %2;\nselp.u32 %0, 1, 0, p;\n}\n" : "=r"(ok) : "r"(bar), "r"(parity) : "memory");
  return ok;
}
__device__ __forceinline__ void die() { asm volatile("st.volatile.global.u32 [%0], %1;" ::"l"(0ull), "r"(0) : "memory"); }
__device__ __forceinline__ void spin_guard(uint32_t& n) { if (++n == (1u << 22)) die(); }
__device__ __forceinline__ void mbar_wait(uint32_t bar, uint32_t parity) {
  uint32_t t0 = 0;
#pragma unroll 1
  while (!mbar_try(bar, parity)) spin_guard(t0);
}
__device__ __forceinline__ void mbar_wait2(uint32_t b0, uint32_t p0, uint32_t b1, uint32_t p1) {
  uint32_t t0 = 0;
#pragma unroll 1
  while (true) {
    const bool r0 = mbar_try(b0, p0), r1 = mbar_try(b1, p1);
    if (r0 && r1) break;
    spin_guard(t0);
  }
}
__device__ __forceinline__ int tid_now() { int v; asm volatile("mov.u32 %0, %%tid.x;" : "=r"(v)); return v & 127; }
__device__ __forceinline__ bool elect_one() {
  uint32_t p;
  asm volatile("{\n.reg .pred P;\nelect.sync _|P, 0xffffffff;\nselp.u32 %0, 1, 0, P;\n}\n" : "=r"(p));
  return p;
}
__device__ __forceinline__ void bar_sync(int id, int n) { asm volatile("bar.sync %0, %1;" ::"r"(id), "r"(n) : "memory"); }
__device__ __forceinline__ void bar_arrive(int id, int n) { asm volatile("bar.arrive %0, %1;" ::"r"(id), "r"(n) : "memory"); }
__device__ __forceinline__ void fence_async_smem() { asm volatile("fence.proxy.async.shared::cta;" ::: "memory"); }
__device__ __forceinline__ void bulk_g2s(uint32_t dst, const void* src, uint32_t bytes, uint32_t bar) {
  asm volatile("cp.async.bulk.shared::cluster.global.mbarrier::complete_tx::bytes [%0], [%1], %2, [%3];" ::"r"(dst), "l"(src), "r"(bytes), "r"(bar) : "memory");
}
__device__ __forceinline__ void bulk_s2g(void* dst, uint32_t src, uint32_t bytes) {
  asm volatile("cp.async.bulk.global.shared::cta.bulk_group [%0], [%1], %2;" ::"l"(dst), "r"(src), "r"(bytes) : "memory");
}
__device__ __forceinline__ void tma2d(uint32_t dst, const CUtensorMap* m, int c0, int c1, uint32_t bar) {
  asm volatile("cp.async.bulk.tensor.2d.shared::cluster.global.mbarrier::complete_tx::bytes [%0], [%1, {%3, %4}], [%2];" ::"r"(dst), "l"(m), "r"(bar), "r"(c0), "r"(c1) : "memory");
}
__device__ __forceinline__ void tma3d(uint32_t dst, const CUtensorMap* m, int c0, int c1, int c2, uint32_t bar) {
  asm volatile("cp.async.bulk.tensor.3d.shared::cluster.global.mbarrier::complete_tx::bytes [%0], [%1, {%3, %4, %5}], [%2];" ::"r"(dst), "l"(m), "r"(bar), "r"(c0), "r"(c1), "r"(c2) : "memory");
}
__device__ __forceinline__ void tma_rows(uint32_t dst, const CUtensorMap* m, int c0, int rb, uint32_t bar) { tma3d(dst, m, c0, rb * 16, 0, bar); }
__device__ __forceinline__ uint4 ld_ll4(const void* p) {
  uint64_t a, b;
  asm volatile("ld.relaxed.gpu.global.v2.u64 {%0,%1}, [%2];" : "=l"(a), "=l"(b) : "l"(p) : "memory");
  return make_uint4((uint32_t)a, (uint32_t)(a >> 32), (uint32_t)b, (uint32_t)(b >> 32));
}
__device__ __forceinline__ void st_ll4(void* p, uint32_t a, uint32_t b, uint32_t c, uint32_t d) {
  asm volatile("st.relaxed.gpu.global.v2.u64 [%0], {%1,%2};" ::"l"(p), "l"(a | ((uint64_t)b << 32)), "l"(c | ((uint64_t)d << 32)) : "memory");
}
__device__ __forceinline__ void st_ll2(void* p, uint32_t a, uint32_t b) { asm volatile("st.relaxed.gpu.global.u64 [%0], %1;" ::"l"(p), "l"(a | ((uint64_t)b << 32)) : "memory"); }
__device__ __forceinline__ uint2 ld_ll2(const void* p) {
  uint64_t a;
  asm volatile("ld.relaxed.gpu.global.u64 %0, [%1];" : "=l"(a) : "l"(p) : "memory");
  return make_uint2((uint32_t)a, (uint32_t)(a >> 32));
}
__device__ __forceinline__ void wgmma_colsum(float* d, uint64_t da, uint64_t db) {
  asm volatile("{\n.reg .pred p;\nsetp.ne.b32 p, 1, 0;\nwgmma.mma_async.sync.aligned.m64n8k16.f32.bf16.bf16 {%0, %1, %2, %3}, %4, %5, p, 1, 1, 1, 0;\n}\n"
               : "+f"(d[0]), "+f"(d[1]), "+f"(d[2]), "+f"(d[3]) : "l"(da), "l"(db));
}
__device__ __forceinline__ void prefetch_l2(const void* p) { asm volatile("prefetch.global.L2 [%0];" ::"l"(p)); }
__device__ __forceinline__ void pace(uint32_t& t, uint32_t dt) {
  t += dt;
  while ((int32_t)((uint32_t)clock() - t) < 0) { if (NSLEEP) __nanosleep(NSLEEP); }
}
__device__ __forceinline__ void red_relaxed(uint32_t* p) { asm volatile("red.relaxed.gpu.global.add.u32 [%0], 1;" ::"l"(p) : "memory"); }
__device__ __forceinline__ void red_release(uint32_t* p) { asm volatile("red.release.gpu.global.add.u32 [%0], 1;" ::"l"(p) : "memory"); }
__device__ __forceinline__ uint4 ldg4(const void* p) { uint4 v; asm volatile("ld.global.v4.u32 {%0,%1,%2,%3}, [%4];" : "=r"(v.x), "=r"(v.y), "=r"(v.z), "=r"(v.w) : "l"(p) : "memory"); return v; }
__device__ __forceinline__ uint32_t ldg1(const void* p) { uint32_t v; asm volatile("ld.global.u32 %0, [%1];" : "=r"(v) : "l"(p) : "memory"); return v; }
__device__ __forceinline__ void stg4_if(void* p, uint32_t a, uint32_t b, uint32_t c, uint32_t d, bool on) {
  asm volatile("{\n.reg .pred p;\nsetp.ne.u32 p, %5, 0;\n@p st.global.v4.u32 [%0], {%1,%2,%3,%4};\n}\n" ::"l"(p), "r"(a), "r"(b), "r"(c), "r"(d), "r"((uint32_t)on) : "memory");
}
template <int OFF> __device__ __forceinline__ uint32_t lds32(uint32_t a) { uint32_t v; asm volatile("ld.shared.u32 %0, [%1+%2];" : "=r"(v) : "r"(a), "n"(OFF)); return v; }
__device__ __forceinline__ uint4 lds128(uint32_t a) { uint4 v; asm volatile("ld.shared.v4.u32 {%0,%1,%2,%3}, [%4];" : "=r"(v.x), "=r"(v.y), "=r"(v.z), "=r"(v.w) : "r"(a) : "memory"); return v; }
__device__ __forceinline__ float2 lds64f(uint32_t a) { float2 v; asm volatile("ld.shared.v2.f32 {%0,%1}, [%2];" : "=f"(v.x), "=f"(v.y) : "r"(a) : "memory"); return v; }
__device__ __forceinline__ void sts64f(uint32_t a, float x, float y) { asm volatile("st.shared.v2.f32 [%0], {%1,%2};" ::"r"(a), "f"(x), "f"(y) : "memory"); }
__device__ __forceinline__ void sts32(uint32_t a, uint32_t x) { asm volatile("st.shared.u32 [%0], %1;" ::"r"(a), "r"(x) : "memory"); }
__device__ __forceinline__ void sts128(uint32_t a, uint32_t x, uint32_t y, uint32_t z, uint32_t w) { asm volatile("st.shared.v4.u32 [%0], {%1,%2,%3,%4};" ::"r"(a), "r"(x), "r"(y), "r"(z), "r"(w) : "memory"); }
__device__ __forceinline__ void stsm4(uint32_t a, uint32_t r0, uint32_t r1, uint32_t r2, uint32_t r3) {
  asm volatile("stmatrix.sync.aligned.m8n8.x4.shared.b16 [%0], {%1,%2,%3,%4};" ::"r"(a), "r"(r0), "r"(r1), "r"(r2), "r"(r3) : "memory");
}
__device__ __forceinline__ void stsm4t(uint32_t a, uint32_t r0, uint32_t r1, uint32_t r2, uint32_t r3) {
  asm volatile("stmatrix.sync.aligned.m8n8.x4.trans.shared.b16 [%0], {%1,%2,%3,%4};" ::"r"(a), "r"(r0), "r"(r1), "r"(r2), "r"(r3) : "memory");
}
__device__ __forceinline__ void ldsm4t(uint32_t* r, uint32_t a) {
  asm volatile("ldmatrix.sync.aligned.m8n8.x4.trans.shared.b16 {%0,%1,%2,%3}, [%4];" : "=r"(r[0]), "=r"(r[1]), "=r"(r[2]), "=r"(r[3]) : "r"(a) : "memory");
}
__device__ __forceinline__ uint32_t pack2(float lo, float hi) { uint32_t r; asm("cvt.rn.bf16x2.f32 %0, %1, %2;" : "=r"(r) : "f"(hi), "f"(lo)); return r; }
__device__ __forceinline__ float bf_lo(uint32_t u) { return __uint_as_float(u << 16); }
__device__ __forceinline__ float bf_hi(uint32_t u) { return __uint_as_float(u & 0xffff0000u); }
__device__ __forceinline__ float tanh_fast(float x) { float y; asm("tanh.approx.f32 %0, %1;" : "=f"(y) : "f"(x)); return y; }
__device__ __forceinline__ uint32_t hmul2(uint32_t a, uint32_t b) { uint32_t r; asm("mul.rn.bf16x2 %0, %1, %2;" : "=r"(r) : "r"(a), "r"(b)); return r; }
__device__ __forceinline__ uint32_t hfma2(uint32_t a, uint32_t b, uint32_t c) { uint32_t r; asm("fma.rn.bf16x2 %0, %1, %2, %3;" : "=r"(r) : "r"(a), "r"(b), "r"(c)); return r; }
__device__ __forceinline__ uint32_t prmt(uint32_t a, uint32_t b, uint32_t s) { return __byte_perm(a, b, s); }

__device__ __forceinline__ uint32_t ld_relaxed(const uint32_t* p) { uint32_t v; asm volatile("ld.relaxed.gpu.global.u32 %0, [%1];" : "=r"(v) : "l"(p) : "memory"); return v; }
__device__ __forceinline__ void acquire_fence() { asm volatile("fence.acquire.gpu;\nfence.proxy.async.global;" ::: "memory"); }
__device__ __forceinline__ uint32_t load_epoch(const Params& p, int idx, int lane) { return ld_relaxed(&p.scr->epoch[idx + (((lane * lane) & 3) == 2 ? 1 : 0)]); }
__device__ __forceinline__ void poll_counter(const uint32_t* cnt, uint32_t target) {
  uint32_t t0 = 0;
#pragma unroll 1
  while (!__all_sync(0xffffffff, ld_relaxed(cnt) == target)) spin_guard(t0);
  acquire_fence();
}

__device__ __forceinline__ int g3_block(int cb, int it) { return it < 3 ? cb * 3 + it : (it - 3 < cb * 3 ? it - 3 : it); }

template <int N, bool A_SWZ, int B_MODE, int DEPTH, class Hook, class Mid>
__device__ __forceinline__ void gemm_loop(float* d, uint32_t sb, int nkb, int sa, int pa, int b0, uint32_t boff, int relA, int relB, int tid, Hook hook, Mid mid) {
  constexpr uint32_t A_STEP = A_SWZ ? 2 : 128;
  constexpr uint32_t B_STEP = B_MODE == 0 ? 128 : (B_MODE == 1 ? 384 : 320);
  const uint64_t da0 = A_SWZ ? mkdesc(sb + OFF_A, 16, 1024, 1) : mkdesc(sb + OFF_A, 1024, 128, 0);
  const uint64_t db0 = B_MODE == 0 ? mkdesc(sb + OFF_B + boff, 8192, 1024, 1) : mkdesc(sb + OFF_B + boff, B_MODE == 1 ? 3072 : 2560, 128, 0);
  constexpr int MODA = B_MODE == 0 ? NA : NA2;
  constexpr int MODB = B_MODE == 2 ? 6 : NB;
  int sbk = b0 % MODB, pb = (b0 / MODB) & 1;
  auto boffs = [](int s_) { return B_MODE == 2 ? (s_ == 5 ? 0 : s_ + 1) * (20480 >> 4) : s_ * (B_SLOT >> 4); };
  uint32_t rel = 0;
  uint64_t da = da0 + sa * (A_SLOT >> 4), db = db0 + boffs(sbk);
  const bool doR = tid < 2 ? tid < relA : tid - 2 < relB;
  mbar_wait2(sb + BAR_AF + 8 * sa, pa, sb + BAR_BF + 8 * sbk, pb);
  if constexpr (DEPTH == 0) {
    acc_fence<N / 2>(d);
#pragma unroll 1
    for (int it = 0; it < nkb; it++) {
      WG_FENCE();
#pragma unroll
      for (int j = 0; j < 4; j++) WG<N>::ss(d, da + j * A_STEP, db + j * B_STEP, 1);
      WG_COMMIT();
      const uint32_t prel = rel;
      rel = sb + BAR_AE + 8 * (tid < 2 ? sa : sbk + NA);
      if (++sa == MODA) { sa = 0; pa ^= 1; }
      if (++sbk == MODB) { sbk = 0; pb ^= 1; }
      da = da0 + sa * (A_SLOT >> 4); db = db0 + boffs(sbk);
      const bool r0 = mbar_test(sb + BAR_AF + 8 * sa, pa), r1 = mbar_test(sb + BAR_BF + 8 * sbk, pb);
      WG_WAIT(1);
      mbar_arrive_if(prel, doR && prel != 0);
      if (it == 2) {
        WG_WAIT(0);
        mbar_expect_if(sb + BAR_AF + 8 * (tid == 8 ? 8 : tid), A_SLOT, tid < 9);
        mbar_arrive_if(rel, doR);
        rel = 0;
      }
      mid(it);
      if (it + 1 < nkb && !(r0 && r1)) {
        mbar_wait2(sb + BAR_AF + 8 * sa, pa, sb + BAR_BF + 8 * sbk, pb);
      }
    }
  } else
#pragma unroll 1
  for (int it = 0; it < nkb; it++) {
    WG_FENCE();
    WG<N>::ss(d, da, db, 1);
    const uint32_t prel = rel;
    rel = sb + BAR_AE + 8 * (tid < 2 ? sa : sbk + NA);
    if (++sa == MODA) { sa = 0; if (B_MODE) pa ^= 1; }
    if (++sbk == MODB) { sbk = 0; pb ^= 1; }
    if (DEPTH == 1) { WG_COMMIT(); WG_WAIT(1); }
    WG<N>::ss(d, da + A_STEP, db + B_STEP, 1);
    WG_COMMIT();
    WG_WAIT(1);
    if (EARLY == 1) mbar_arrive_if(prel, doR && it != 0);
    WG<N>::ss(d, da + 2 * A_STEP, db + 2 * B_STEP, 1);
    if (DEPTH == 1) WG_COMMIT();
    if (EARLY != 1) mbar_arrive_if(prel, doR && it != 0);
    const bool r0 = mbar_test(sb + BAR_AF + 8 * sa, pa), r1 = mbar_test(sb + BAR_BF + 8 * sbk, pb);
    const uint64_t da3 = da + 3 * A_STEP, db3 = db + 3 * B_STEP;
    da = da0 + sa * (A_SLOT >> 4); db = db0 + boffs(sbk);
    if (DEPTH == 1) WG_WAIT(1);
    WG<N>::ss(d, da3, db3, 1);
    WG_COMMIT();
    mid(it);
    if (it + 1 < nkb) {
      if (!(r0 && r1)) {
        mbar_wait2(sb + BAR_AF + 8 * sa, pa, sb + BAR_BF + 8 * sbk, pb);
      }
    }
    if (DEPTH == 2) WG_WAIT(1);
  }
  hook();
  WG_WAIT(0);
  acc_fence<N / 2>(d);
  mbar_arrive_if(rel, doR);
}

__device__ __forceinline__ void fold_mean(float* d, uint32_t cs, float ma, float mb, int t) {
  const uint32_t ha = pack2(-ma, -ma), hb = pack2(-mb, -mb);
  const float la = -ma - bf_lo(ha), lb = -mb - bf_lo(hb);
  const uint32_t a[4] = {t ? 0u : ha, t ? 0u : hb, t ? 0u : pack2(la, la), t ? 0u : pack2(lb, lb)};
  WG_FENCE();
  WG<192>::rst(d, a, mkdesc(cs, 0, 32, 0));
  WG_COMMIT();
}
__device__ __forceinline__ void gelu_tile(const float* d, uint32_t* z, float* st, float ra, float rb) {
  const float kA = 0.7978845608028654f, kB = 0.7978845608028654f * 0.044715f;
  const float c1a = kA * ra, c3a = kB * ra * ra * ra, c1b = kA * rb, c3b = kB * rb * rb * rb;
  float acc[8];
#pragma unroll
  for (int i = 0; i < 8; i++) acc[i] = 0.f;
#pragma unroll
  for (int j = 0; j < 24; j++) {
    float r[4];
#pragma unroll
    for (int e = 0; e < 4; e++) {
      const float v = d[4 * j + e];
      const float a = v * fmaf(v * v, e < 2 ? c3a : c3b, e < 2 ? c1a : c1b);
      r[e] = fmaf(v, tanh_fast(a), v);
      acc[e] += r[e];
      acc[4 + e] = fmaf(r[e], r[e], acc[4 + e]);
    }
    z[2 * j] = pack2(r[0], r[1]);
    z[2 * j + 1] = pack2(r[2], r[3]);
  }
  st[0] = acc[0] + acc[1]; st[1] = acc[4] + acc[5]; st[2] = acc[2] + acc[3]; st[3] = acc[6] + acc[7];
}

template <int Q> __device__ __forceinline__ void conv_load(uint32_t* a, uint32_t ab) {
  a[0] = lds32<512 * Q>(ab);       a[1] = lds32<512 * Q + 256>(ab);  a[2] = lds32<512 * Q + 16>(ab);   a[3] = lds32<512 * Q + 272>(ab);
  a[4] = lds32<512 * Q + 32>(ab);  a[5] = lds32<512 * Q + 288>(ab);  a[6] = lds32<512 * Q + 48>(ab);   a[7] = lds32<512 * Q + 304>(ab);
  a[8] = lds32<512 * Q + 64>(ab);  a[9] = lds32<512 * Q + 320>(ab);  a[10] = lds32<512 * Q + 80>(ab);  a[11] = lds32<512 * Q + 336>(ab);
  a[12] = lds32<512 * Q + 96>(ab); a[13] = lds32<512 * Q + 352>(ab); a[14] = lds32<512 * Q + 112>(ab); a[15] = lds32<512 * Q + 368>(ab);
}
template <int Q, int L> __device__ __forceinline__ void conv_step(float* d, uint32_t (*a)[16], uint32_t ab, uint64_t db) {
  WG_FENCE();
#pragma unroll
  for (int s = 0; s < 4; s++) WG<128 - 16 * Q>::rs(d, a[Q] + 4 * s, db + s + 16 * Q);
  WG_COMMIT();
  if (CPIN) WG_WAIT(1);
  if (L >= 0) conv_load<(L >= 0 ? L : 0)>(a[L >= 0 ? L : 0], ab);
  if (CW0 || Q == 0) WG_WAIT(0);
}

__device__ __forceinline__ int seg_col(int cb, int h) { return (cb >> 1) * 320 + (cb & 1) * 32 + h * 64; }
__device__ __forceinline__ void final_load_x(uint32_t (*xw)[10], uint32_t xt, int cb, int h, int w, int lane) {
  const int g = lane >> 2, t = lane & 3, cc = seg_col(cb, h) >> 3;
  const int c0 = cc + t, c1 = c0 + 24, c2 = cc + 16 - 6 * h + (t >> 1);
  const uint32_t r0 = xt + (w * 16 + g) * 128;
#pragma unroll
  for (int r = 0; r < 2; r++) {
    const uint4 u = lds128(r0 + r * 1024 + (c0 >> 3) * A_SLOT + (((c0 ^ g) & 7) << 4)), v = lds128(r0 + r * 1024 + (c1 >> 3) * A_SLOT + (((c1 ^ g) & 7) << 4));
    const float2 z = lds64f(r0 + r * 1024 + (c2 >> 3) * A_SLOT + (((c2 ^ g) & 7) << 4) + (t & 1) * 8);
    xw[r][0] = u.x; xw[r][1] = u.y; xw[r][2] = u.z; xw[r][3] = u.w;
    xw[r][4] = v.x; xw[r][5] = v.y; xw[r][6] = v.z; xw[r][7] = v.w;
    xw[r][8] = __float_as_uint(z.x); xw[r][9] = __float_as_uint(z.y);
  }
}
__device__ __forceinline__ void final_s_early(uint32_t (*sw)[10], const uint32_t (*xw)[10], uint32_t ya, float2 s0, float2 s1) {
  const uint32_t r2[2] = {pack2(s0.y, s0.y), pack2(s1.y, s1.y)};
  const float na = -s0.x * bf_lo(r2[0]), nb = -s1.x * bf_lo(r2[1]);
  const uint32_t n2[2] = {pack2(na, na), pack2(nb, nb)};
#pragma unroll
  for (int j = 0; j < 10; j += 2) {
    uint32_t y[4];
    if (j < 4 || j == 8) ldsm4t(y, ya + (j < 4 ? j : 4) * 1024);
#pragma unroll
    for (int e = 0; e < 4; e++) {
      const uint32_t xn = hfma2(xw[e & 1][j + (e >> 1)], r2[e & 1], n2[e & 1]);
      sw[e & 1][j + (e >> 1)] = (j < 4 || j == 8) ? hmul2(xn, y[e]) : xn;
    }
  }
}
__device__ __forceinline__ bool final_late(uint32_t* y, uint32_t ya) {
  ldsm4t(y, ya + 6144);
  ldsm4t(y + 4, ya + 8192);
  uint32_t zero = 0;
#pragma unroll
  for (int e = 0; e < 8; e++) zero |= (y[e] - 0x00010001u) & ~y[e];
  return (zero & 0x80008000u) == 0;
}
__device__ __forceinline__ bool bar_all(int id, int n, bool c) {
  uint32_t r;
  asm volatile("{\n.reg .pred p, q;\nsetp.ne.u32 p, %3, 0;\nbar.red.and.pred q, %1, %2, p;\nselp.u32 %0, 1, 0, q;\n}\n" : "=r"(r) : "r"(id), "r"(n), "r"((uint32_t)c) : "memory");
  return r;
}
__device__ __forceinline__ void final_out(const float* d, const uint32_t (*xw)[10], const uint32_t (*sw)[10], float ra, float rb, __nv_bfloat16* o0, int h, int t) {
  const float ca = 0.25f * ra, cb = 0.25f * rb;
  uint32_t o[2][10];
#pragma unroll
  for (int j = 0; j < 10; j++) {
#pragma unroll
    for (int r = 0; r < 2; r++) {
      const float h0 = d[4 * j + 2 * r] * (r ? cb : ca), h1 = d[4 * j + 2 * r + 1] * (r ? cb : ca);
      o[r][j] = hfma2(pack2(fmaf(h0, tanh_fast(h0), h0), fmaf(h1, tanh_fast(h1), h1)), sw[r][j], xw[r][j]);
      __nv_bfloat16* q = o0 + r * 8 * kD;
      if (j == 3) stg4_if(q + t * 8, o[r][0], o[r][1], o[r][2], o[r][3], true);
      if (j == 7) stg4_if(q + 192 + t * 8, o[r][4], o[r][5], o[r][6], o[r][7], true);
      if (j == 9) asm volatile("st.global.v2.u32 [%0], {%1,%2};" ::"l"(q + 128 - 48 * h + t * 4), "r"(o[r][8]), "r"(o[r][9]) : "memory");
    }
  }
}

struct Taps { uint4 r0, r1; uint32_t n0, n1, dd; };
__device__ __forceinline__ void load_taps(Taps& k, const Params& p, int ch, int tid) {
  const uint4* kp = (const uint4*)(p.ssmk + (size_t)ch * kS);
  k.r0 = ldg4(kp + tid); k.r1 = ldg4(kp + 128 + tid);
  k.n0 = ldg1(kp + tid + 1); k.n1 = tid < 127 ? ldg1(kp + 129 + tid) : 0u;
  k.dd = __bfloat16_as_ushort(p.ssmD[ch]);
}
__device__ __forceinline__ void load_convx(const Params& p, uint32_t cv, uint32_t bar, int ch) {
  mbar_expect(bar, 4096);
  bulk_g2s(cv, p.scr->kvx + (size_t)ch * 4096, 2048, bar);
  bulk_g2s(cv + XB_PL, p.scr->kvx + (size_t)ch * 4096 + 2048, 2048, bar);
}
#define CW 3
#define CSTAMP(j)
__device__ __forceinline__ void zero_pads(uint32_t cv, int lane) {
  if (lane < 8) sts128(cv + (lane >> 2) * XB_PL + 2048 + (lane & 3) * 16, 0, 0, 0, 0);
  else if (lane < 12) sts128(cv + ((lane & 2) ? CV_KO : CV_KE) + (lane & 1) * 16, 0, 0, 0, 0);
  fence_async_smem();
  __syncwarp();
}
__device__ __forceinline__ int y_row(int c, uint32_t par) {
  const int hf = c >= 320, cc = c - hf * 320, u = cc >> 6, cb = hf * 2 + ((cc >> 5) & 1);
  if (u == 2) return cb * 96 + ((cc >> 4) & 1) * 48 + 32 + (cc & 1) + ((cc >> 1) & 1) * 8 + ((cc >> 2) & 3) * 2;
  return (u < 2 ? cb * 96 + u * 48 : 384 + par * 256 + cb * 64 + (u - 3) * 32) + (cc & 1) + ((cc >> 1) & 3) * 8 + ((cc >> 3) & 3) * 2;
}
__device__ __forceinline__ void z_store(const Params& p, uint32_t src, int rb, int cb, int q) {
  uint8_t* dst = p.scr->z2 + (size_t)(cb * 32 + q * 16 + (rb >> 2)) * B_SLOT + (rb & 3) * 6144;
  bulk_s2g(dst, src + q * 12288, 6144);
  bulk_s2g(dst + 8 * B_SLOT, src + q * 12288 + 6144, 6144);
  asm volatile("cp.async.bulk.commit_group;\ncp.async.bulk.wait_group 0;" ::: "memory");
}
__device__ __forceinline__ void y_store(const Params& p, uint32_t sb, int h, int ch, uint32_t par) {
  uint8_t* dst = p.scr->y + (size_t)y_row(ch, par) * 4096;
  if (elect_one()) {
    bulk_s2g(dst, sb + OFF_A + 9 * A_SLOT + h * 4096, 4096);
    asm volatile("cp.async.bulk.commit_group;\ncp.async.bulk.wait_group 0;" ::: "memory");
  }
  __syncwarp();
}
__device__ __forceinline__ void conv_service(const Params& p, uint32_t sb, int h, int ch, bool first) {
  bar_sync(NB_WGA + 8 + h, 160);
  const bool now = !first || __all_sync(0xffffffff, mbar_test(sb + BAR_KV, 0));
  if (now) { acquire_fence(); if (elect_one()) load_convx(p, sb + OFF_CV + (1 - h) * CV_SZ, sb + BAR_XF + 8 * h, ch + 128); }
  bar_sync(NB_WGA + 8 + h, 160);
  y_store(p, sb, h, ch, 0);
  if (!now) {
    mbar_wait(sb + BAR_KV, 0);
    acquire_fence();
    if (elect_one()) load_convx(p, sb + OFF_CV + (1 - h) * CV_SZ, sb + BAR_XF + 8 * h, ch + 128);
  }
}
__device__ __forceinline__ uint32_t y_tile(int h) { return OFF_CV + (1 - h) * 13312; }
__device__ __forceinline__ void load_late_y(const Params& p, uint32_t sb, int h, int rb, int cb, uint32_t par) {
  mbar_expect(sb + BAR_YL + 16 * h, 4096);
  tma2d(sb + y_tile(h) + 6144, &p.tmY, rb * 64, 384 + par * 256 + cb * 64 + h * 32, sb + BAR_YL + 16 * h);
  tma2d(sb + y_tile(h) + 8192, &p.tmY, rb * 64, 400 + par * 256 + cb * 64 + h * 32, sb + BAR_YL + 16 * h);
}
__device__ __forceinline__ void held_service(const Params& p, uint32_t sb, int h, int ch, int rb, int cb, uint32_t tag, int lane) {
#pragma unroll 1
  for (int i = 0; i < 8; i++) sts128(sb + OFF_A + 9 * A_SLOT + h * 4096 + i * 512 + lane * 16, 0, 0, 0, 0);
  fence_async_smem();
  __syncwarp();
  y_store(p, sb, h, ch, ~tag & 1);
  mbar_wait(sb + BAR_YT, 1);
  acquire_fence();
  bar_sync(NB_WGA + 8 + h, 160);
  bar_sync(NB_WGA + 8 + h, 160);
  uint8_t* dst = p.scr->y + (size_t)y_row(ch, tag & 1) * 4096;
  if (elect_one()) {
    bulk_s2g(dst, sb + OFF_A + 9 * A_SLOT + h * 4096, 4096);
    asm volatile("cp.async.bulk.commit_group;" ::: "memory");
    mbar_expect(sb + BAR_XF + 8 * h, 6144);
#pragma unroll 1
    for (int i = 0; i < 3; i++) tma2d(sb + y_tile(h) + i * 2048, &p.tmY, rb * 64, cb * 96 + h * 48 + i * 16, sb + BAR_XF + 8 * h);
  }
  mbar_wait(sb + BAR_AE + 8 * (LL_AT - 1), 1);
  if (elect_one()) { load_late_y(p, sb, h, rb, cb, tag & 1); asm volatile("cp.async.bulk.wait_group 0;" ::: "memory"); }
}
__device__ __forceinline__ void conv_worker(const Params& p, Taps& k, uint32_t cv, uint32_t yb0,
                                            uint32_t xbar, int nbar, int ch0, int n, uint32_t holdbar, int w, int lane,
                                            int tid, int st0, int rb, int cb) {
  const int g = lane >> 2, t = lane & 3, w0 = w & 1, w1 = w >> 1;
  const uint32_t ab = cv + ((g & 1) ? CV_KE : CV_KO) + 32 + 2 * (64 * w0 + 8 * w1 + ((g - 15) & ~1) + 2 * t);
  const uint32_t scA = cv + (w1 ? CV_KO : CV_KE) + 32, scB = scA + 2048;
  const int dl = (t >> 1) ^ 1;
  if (n == 2 || CPRE0 == 2) mbar_wait(xbar, 0);
  STAMPW(st0 + 3);
#pragma unroll 1
  for (int i = 0; i < n; i++) {
    if (tid == 0) {
      k.r0.x = (k.r0.x & 0xffff0000u) | (pack2(bf_lo(k.r0.x) + bf_lo(k.dd), 0.f) & 0xffffu);
      sts32(cv + CV_KO + 28, k.r0.x << 16);
    }
    sts128(cv + CV_KE + 32 + tid * 16, k.r0.x, k.r0.y, k.r0.z, k.r0.w);
    sts128(cv + CV_KO + 32 + tid * 16, prmt(k.r0.x, k.r0.y, 0x5432), prmt(k.r0.y, k.r0.z, 0x5432), prmt(k.r0.z, k.r0.w, 0x5432), prmt(k.r0.w, k.n0, 0x5432));
    sts128(cv + CV_KE + 2080 + tid * 16, k.r1.x, k.r1.y, k.r1.z, k.r1.w);
    sts128(cv + CV_KO + 2080 + tid * 16, prmt(k.r1.x, k.r1.y, 0x5432), prmt(k.r1.y, k.r1.z, 0x5432), prmt(k.r1.z, k.r1.w, 0x5432), prmt(k.r1.w, k.n1, 0x5432));
    if (i + 1 < n) load_taps(k, p, ch0 + (i + 1) * 128, tid);
    bar_sync(nbar, 128);
    CSTAMP(0);
    const uint64_t db = mkdesc(cv + (i & 0x1000), XB_PL, 128, 0);
    float d[64];
    uint32_t a[8][16];
    if (CPRE0 == 1 && i == 0) mbar_wait(xbar, 0);
    conv_load<7>(a[7], ab); conv_load<6>(a[6], ab); conv_load<5>(a[5], ab); conv_load<4>(a[4], ab);
#pragma unroll
    for (int j = 0; j < 64; j++) d[j] = 0.f;
    mbar_wait(xbar, i & 1);
    if (i + 1 == n) mbar_wait(holdbar, 1);
    CSTAMP(1);
    conv_step<7, -1>(d, a, ab, db); conv_step<6, -1>(d, a, ab, db); conv_step<5, -1>(d, a, ab, db); conv_step<4, 3>(d, a, ab, db);
    conv_step<3, 2>(d, a, ab, db);
    conv_step<2, 1>(d, a, ab, db);
    conv_step<1, 0>(d, a, ab, db);
    conv_step<0, -1>(d, a, ab, db);
    acc_fence<64>(d);
    CSTAMP(2);
    bar_sync(nbar + 8, 160);
    float E[16][2];
#pragma unroll
    for (int j = 0; j < 15; j++) { E[j][0] = d[4 * j] + d[4 * j + 6]; E[j][1] = d[4 * j + 1] + d[4 * j + 7]; }
    E[15][0] = d[60]; E[15][1] = d[61];
    if (w0 == 0) {
#pragma unroll
      for (int j = 8; j < 16; j++) sts64f(scA + (j - 8) * 256 + lane * 8, E[j][0], E[j][1]);
    } else {
      const uint32_t a = scB - dl * 256 + (lane ^ 2) * 8;
#pragma unroll
      for (int j = 1; j < 8; j++) sts64f(a + j * 256, E[j][0], E[j][1]);
      sts64f(scB + (dl ? 7 * 256 : 0) + (lane ^ 2) * 8, dl ? E[8][0] : E[0][0], dl ? E[8][1] : E[0][1]);
    }
    bar_sync(nbar, 128);
    CSTAMP(3);
    uint32_t pk[8];
    if (w0 == 0) {
#pragma unroll
      for (int j = 0; j < 8; j++) { const float2 v = lds64f(scB + j * 256 + lane * 8); pk[j] = pack2(E[j][0] + v.x, E[j][1] + v.y); }
    } else {
      const uint32_t a0 = scA - dl * 256 + (lane ^ 2) * 8;
#pragma unroll
      for (int j = 9; j < 16; j++) { const float2 v = lds64f(a0 + (j - 8) * 256); pk[j - 8] = pack2(E[j][0] + v.x, E[j][1] + v.y); }
      const float2 v = lds64f(scA + (dl ? 7 * 256 : 0) + (lane ^ 2) * 8);
      pk[0] = pack2((dl ? 0.f : E[8][0]) + v.x, (dl ? 0.f : E[8][1]) + v.y);
    }
    CSTAMP(4);
    if (i + 1 == n) {
#pragma unroll
      for (int j = 0; j < 8; j++) pk[j] = ~pk[j];
    }
    const int c1 = (w0 ? 35 : 95) - lane, c0 = (w0 && lane < 4) ? c1 - 32 : c1 + 32;
    stsm4t(yb0 + 128 * (c0 & 31) + (((2 * (c0 >> 5) + w1) ^ (c0 & 7)) << 4), pk[0], pk[1], pk[2], pk[3]);
    stsm4t(yb0 + 128 * (c1 & 31) + (((2 * (c1 >> 5) + w1) ^ (c1 & 7)) << 4), pk[4], pk[5], pk[6], pk[7]);
    fence_async_smem();
    bar_sync(nbar + 8, 160);
    CSTAMP(5);
    STAMPW(st0 + i);
    if (n == 2 && i == 0) {
      const int u = (tid >> 3) % 5, kg = rb * 3 + (tid < 120 ? (tid >> 3) / 5 : 0), c = u < 4 ? (u >> 1) * 10 + (u & 1) * 4 : 8, o2 = u < 4 ? 2 : 10;
      const uint4* wp = (const uint4*)p.wout + (uint32_t)((kg * 8 + (tid & 7)) * (kD / 8) + (seg_col(cb, 0) >> 3) + (u < 4 ? (u >> 1) * 8 + (u & 1) * 24 : 16));
      const uint4 w0 = ldg4(wp), w1 = ldg4(wp + 1), w2 = ldg4(wp + 2), w3 = ldg4(wp + 3);
      uint8_t* dst = p.scr->wo + (uint32_t)(cb * (12 * 20480) + kg * 2560 + c * 128 + (tid & 7) * 16);
      const bool f = u < 4, on = tid < 120;
      stg4_if(dst, w0.x, f ? w1.x : w0.z, f ? w2.x : w1.x, f ? w3.x : w1.z, on);
      stg4_if(dst + 128, w0.y, f ? w1.y : w0.w, f ? w2.y : w1.y, f ? w3.y : w1.w, on);
      stg4_if(dst + o2 * 128, f ? w0.z : w2.x, f ? w1.z : w2.z, f ? w2.z : w3.x, w3.z, on);
      stg4_if(dst + o2 * 128 + 128, f ? w0.w : w2.y, f ? w1.w : w2.w, f ? w2.w : w3.y, w3.w, on);
      bar_arrive(NB_WO, 160);
    }
  }
}

struct KvRegs { uint32_t k[11], v[8]; uint4 sh; };
__device__ __forceinline__ void kv_load(KvRegs& q, const __nv_bfloat16* kp, const __nv_bfloat16* vp, const __nv_bfloat16* sp, bool halo) {
#pragma unroll
  for (int i = 0; i < 11; i++) q.k[i] = (i >= 3 || halo) ? ldg1(kp + i * kD) : 0u;
#pragma unroll
  for (int i = 0; i < 8; i++) q.v[i] = ldg1(vp + i * kD);
  q.sh = ldg4(sp);
}
__device__ __forceinline__ void kv_unit(const KvRegs& q, uint32_t oa) {
  const uint32_t w0 = prmt(q.sh.x, q.sh.z, 0x5410), w1 = prmt(q.sh.x, q.sh.z, 0x7632), w2 = prmt(q.sh.y, q.sh.w, 0x5410), w3 = prmt(q.sh.y, q.sh.w, 0x7632);
  uint32_t r[8];
#pragma unroll
  for (int i = 0; i < 8; i++) r[i] = hmul2(hfma2(q.k[i + 3], w0, hfma2(q.k[i + 2], w1, hfma2(q.k[i + 1], w2, hmul2(q.k[i], w3)))), q.v[i]);
  sts128(oa, prmt(r[7], r[6], 0x5410), prmt(r[5], r[4], 0x5410), prmt(r[3], r[2], 0x5410), prmt(r[1], r[0], 0x5410));
  sts128(oa + 2048, prmt(r[7], r[6], 0x7632), prmt(r[5], r[4], 0x7632), prmt(r[3], r[2], 0x7632), prmt(r[1], r[0], 0x7632));
}

__device__ __forceinline__ void gather_colsum(const Params& p, uint32_t sb, int cb, int part, uint32_t tag, int lane) {
  uint4 v[3];
  uint32_t t0 = 0;
#pragma unroll 1
  while (true) {
    bool ok = true;
#pragma unroll
    for (int i = 0; i < 3; i++) {
      v[i] = ld_ll4(&p.scr->colsum[(part ? 0 : 768) + cb * 192 + i * 64 + lane * 2]);
      ok = ok && v[i].y == tag && v[i].w == tag;
    }
    if (__all_sync(0xffffffff, ok)) break;
    spin_guard(t0);
  }
#pragma unroll
  for (int i = 0; i < 3; i++) {
    const uint32_t hi = pack2(__uint_as_float(v[i].x), __uint_as_float(v[i].z)), ca = sb + OFF_CS + (1 - part) * 768 + i * 256 + (lane >> 2) * 32 + (lane & 3) * 4;
    sts32(ca, hi);
    sts32(ca + 16, pack2(__uint_as_float(v[i].x) - bf_lo(hi), __uint_as_float(v[i].z) - bf_hi(hi)));
  }
  __syncwarp();
  if (lane == 0) mbar_arrive(sb + BAR_ST + 8 * part);
}

__device__ __forceinline__ void helper_cta(const Params& p, uint32_t sb, int cb, int warp, int lane) {
  constexpr int NS = 9, ONES = NS * B_SLOT, BF = ONES + 256, BE = BF + 8 * NS;
  if (warp < NS && elect_one()) {
    mbar_init(sb + BF + 8 * warp, 1); mbar_init(sb + BE + 8 * warp, 1);
    fence_async_smem();
    if (warp == 0) { mbar_expect(sb + BF, B_SLOT); tma3d(sb, &p.tmW, 0, 0, 12 + cb * 3, sb + BF); }
  }
  if (warp == 15) { sts32(sb + ONES + lane * 4, 0x3f803f80u); sts32(sb + ONES + 128 + lane * 4, 0x3f803f80u); fence_async_smem(); }
  __syncthreads();
  if (warp == 4) {
    int s = 1, ph = 1;
    uint32_t tp = clock() + HP0;
#pragma unroll 1
    for (int it = 1; it < 20; it++) {
      if (HPD && it >= 10) pace(tp, HPD);
      mbar_wait(sb + BE + 8 * s, ph);
      if (elect_one()) { mbar_expect(sb + BF + 8 * s, B_SLOT); tma3d(sb + s * B_SLOT, &p.tmW, 0, (it < 10 ? it : it - 10) * 64, (it < 10 ? 12 : 0) + cb * 3, sb + BF + 8 * s); }
      if (++s == NS) { s = 0; ph ^= 1; }
    }
  } else if (warp < 4) {
    const uint32_t tag = load_epoch(p, 128 + cb, lane) + 1;
    const uint64_t db = mkdesc(sb + ONES, 128, 128, 0);
    uint2* dst = p.scr->colsum + cb * 192 + warp * 16 + (lane >> 2);
    if ((lane & 3) == 0) {
#pragma unroll 1
      for (int j = 0; j < 12; j++) st_ll2(dst + (j < 6 ? 768 : 0) + ((j % 6) >> 1) * 64 + (j & 1) * 8, 0, 0);
    }
    int s = 0, ph = 0;
#pragma unroll 1
    for (int part = 0; part < 2; part++) {
      float d[12];
#pragma unroll
      for (int i = 0; i < 12; i++) d[i] = 0.f;
#pragma unroll 1
      for (int it = 0; it < 10; it++) {
        mbar_wait(sb + BF + 8 * s, ph);
        const uint64_t da = mkdesc(sb + s * B_SLOT, 8192, 1024, 1);
        WG_FENCE();
#pragma unroll
        for (int j = 0; j < 12; j++) wgmma_colsum(d + 4 * (j % 3), da + (j % 3) * 512 + (j / 3) * 128, db);
        WG_COMMIT();
        WG_WAIT(1);
        mbar_arrive_if(sb + BE + 8 * (s == 0 ? NS - 1 : s - 1), threadIdx.x == 0 && (it | part) != 0);
        if (++s == NS) { s = 0; ph ^= 1; }
      }
      WG_WAIT(0);
      acc_fence<12>(d);
      if ((lane & 3) == 0) {
#pragma unroll
        for (int j = 0; j < 6; j++) st_ll2(dst + (part ? 0 : 768) + (j >> 1) * 64 + (j & 1) * 8, __float_as_uint(d[2 * j]), tag);
      }
      STAMPW(1 + part);
    }
    if (threadIdx.x == 0) *(volatile uint32_t*)&p.scr->epoch[128 + cb] = tag;
  }
}

__global__ void __launch_bounds__(512, 1) fused_kernel(const __grid_constant__ Params p) {
  extern __shared__ __align__(1024) uint8_t smem[];
  const int warp = __shfl_sync(0xffffffff, (int)(threadIdx.x >> 5), 0);
  const int lane = threadIdx.x & 31, tid = threadIdx.x & 127;
  const uint32_t sb = __shfl_sync(0xffffffff, (uint32_t)__cvta_generic_to_shared(smem), 0);
  const uint32_t tstart = clock();
  if (elect_one()) {
    if (warp < 5) asm volatile("prefetch.tensormap [%0];" ::"l"(&p.tmX + warp) : "memory");
    mbar_init(sb + OFF_BAR + 8 * warp, 1); mbar_init(sb + OFF_BAR + 128 + 8 * warp, 1); mbar_init(sb + OFF_BAR + 256 + 8 * warp, 2);
    asm volatile("fence.mbarrier_init.release.cluster;" ::: "memory");
  }
  int b = blockIdx.x;
  if (p.by_smid) asm volatile("mov.u32 %0, %%smid;" : "=r"(b));
  b = __shfl_sync(0xffffffff, b, 0);
  const int tp = b >> 1, t7 = (tp - 32) / 7;
  const int lin = tp < 32 ? ((tp & 7) ? (tp & 7) * 16 : 8) + (tp >> 3) * 2 + (b & 1)
                          : (tp < 60 ? (tp - 31 - t7 * 7) * 16 + 8 + t7 * 2 + (b & 1) : (tp < 62 ? -1 : b - 124));
  const int hcb = b & 3;
  if (lin < 0) { helper_cta(p, sb, hcb, warp, lane); return; }
  const int cb = ((lin >> 4) & 1) * 2 + ((lin >> 1) & 1), rb = (lin >> 5) * 8 + ((lin >> 2) & 3) * 2 + (lin & 1);
  const int zs0 = 4 - (cb & 2);
  const int chb = (cb >> 1) * 320 + rb * 2 + (cb & 1);
  if (warp == 0 && elect_one()) {
    mbar_expect(sb + BAR_AF, A_SLOT);
    tma_rows(sb + OFF_A, &p.tmX, 0, rb, sb + BAR_AF);
    mbar_expect(sb + BAR_BF, B_SLOT);
    tma3d(sb + OFF_B, &p.tmW, 0, 0, 12 + cb * 3, sb + BAR_BF);
  }
  if (warp == 1) STAMP(31);
  if (sb & 1023) die();
  __syncthreads();

  if (warp >= 12) {
    asm volatile("setmaxnreg.dec.sync.aligned.u32 32;");
    const uint32_t epoch = load_epoch(p, lin, lane);
    if (warp == 12) {
#pragma unroll 1
      for (int i = 1; i < NA; i++) {
        if (elect_one()) {
          mbar_expect(sb + BAR_AF + 8 * i, A_SLOT);
          tma_rows(sb + OFF_A + i * A_SLOT, &p.tmX, i * 64, rb, sb + BAR_AF + 8 * i);
          if (i < NB) { mbar_expect(sb + BAR_BF + 8 * i, B_SLOT); tma3d(sb + OFF_B + i * B_SLOT, &p.tmW, 0, i * 64, 12 + cb * 3, sb + BAR_BF + 8 * i); }
        }
      }
      STAMP(32);
      uint32_t kvt;
      {
        const int tb = rb * 2 + (cb & 1);
        kvt = __shfl_sync(0xffffffff, (ld_relaxed(p.scr->cnt + CNT_KV + (cb >> 1)) & ~63u) + 64, 0);
        {
          uint32_t tp = tstart;
          pace(tp, KV_T0);
          mbar_arrive_if(sb + BAR_KV + 8, lane == 0);
        }
        if (ST_YIELD) mbar_wait2(sb + BAR_XS, 0, sb + BAR_ST, 0);
#pragma unroll 1
        for (int u = 0; u < 5; u++) {
          mbar_wait(sb + BAR_KU + 8 * u, 0);
          fence_async_smem();
          if (elect_one()) {
            asm volatile("cp.async.bulk.tensor.3d.global.shared::cta.bulk_group [%0, {%2, %3, %4}], [%1];\ncp.async.bulk.commit_group;" ::"l"(&p.tmKV),
                         "r"(sb + OFF_CV + CV_SZ + (u < 3 ? u : u - 3) * 4096), "r"((63 - tb) * 16), "r"((cb >> 1) * 160 + u * 32), "r"(0) : "memory");
            if (u == 1 || u == 4) asm volatile("cp.async.bulk.wait_group 0;" ::: "memory");
            if (u == 1) { mbar_arrive(sb + BAR_KU); red_release(p.scr->cnt + CNT_KV + (cb >> 1)); }
          }
          __syncwarp();
          if (u == 1) {
            STAMP(35);
            if (PFT) { const char* q = (const char*)p.ssmk + chb * 4096 + lane * 128; prefetch_l2(q); prefetch_l2(q + 64 * 4096); }
          }
        }
        zero_pads(sb + OFF_CV + CV_SZ, lane);
        if (elect_one()) { mbar_arrive(sb + BAR_KU + 8); red_release(p.scr->cnt + CNT_KV + 2 + (cb >> 1)); }
        STAMP(30);
        if (lane < 24) {
          const char* r = (const char*)p.wout + (rb * 24 + lane) * (kD * 2) + (cb >> 1) * 640 + (cb & 1) * 384;
          prefetch_l2(r); prefetch_l2(r + 128); prefetch_l2(r + 256 - (cb & 1) * 384);
        }
      }
      poll_counter(p.scr->cnt + CNT_KV + 2 + (cb >> 1), kvt);
      if (elect_one()) mbar_arrive(sb + BAR_KV);
      STAMP(34);
      {
        const char* q = (const char*)p.wsp + (cb * 512 + rb * 16 + (lane >> 1)) * (kS * 2) + (lane & 1) * 128;
        uint32_t tp = clock();
#pragma unroll 1
        for (int i = LEAD / 2; i < WSP_N; i++) {
          prefetch_l2(q + i * 256);
          if (i == Z1_AT) {
            poll_counter(p.scr->cnt + CNT_Z1, (epoch + 1) * 128);
            if (elect_one()) mbar_arrive(sb + BAR_Z1);
            STAMP(24);
          }
          pace(tp, WSP_D);
        }
      }
      const uint32_t tag = epoch + 1;
      mbar_wait(sb + BAR_G2, 0);
      if (elect_one()) {
        bulk_s2g(p.scr->h + (size_t)(rb * 12 + cb * 3) * A_SLOT, sb + OFF_A + 5 * A_SLOT, 3 * A_SLOT);
        asm volatile("cp.async.bulk.commit_group;\ncp.async.bulk.wait_group 0;" ::: "memory");
        red_release(&p.scr->hcnt[(rb >> HGRP) * 32]);
      }
      __syncwarp();
      STAMP(20);
      mbar_wait(sb + BAR_AE + 56, 0);
      STAMP(39);
      poll_counter(&p.scr->hcnt[(rb >> HGRP) * 32], tag * (4 << HGRP));
      STAMP(37);
      if (elect_one()) {
        uint32_t tp = clock();
#pragma unroll 1
        for (int it = 3; it < 12; it++) {
          if (HPACE && it > 3) { tp += HPACE; while ((int32_t)((uint32_t)clock() - tp) < 0) {} }
          bulk_g2s(sb + OFF_A + ((it + 5) % 9) * A_SLOT, p.scr->h + (size_t)(rb * 12 + g3_block(cb, it)) * A_SLOT, A_SLOT, sb + BAR_AF + 8 * ((it + 5) % 9));
        }
      }
      STAMP(21);
    } else if (warp == 13) {
      int s = 0, ph = 0;
#pragma unroll 1
      for (int it = NB; it < 20; it++) {
        mbar_wait(sb + BAR_BE + 8 * s, ph);
        if (elect_one()) { mbar_expect(sb + BAR_BF + 8 * s, B_SLOT); tma3d(sb + OFF_B + s * B_SLOT, &p.tmW, 0, (it < 10 ? it : (it + zs0) % 10) * 64, (it < 10 ? 12 : 0) + cb * 3, sb + BAR_BF + 8 * s); }
        STAMP2(32 + it);
        if (++s == NB) { s = 0; ph ^= 1; }
      }
      mbar_wait(sb + BAR_XC, 0);
#pragma unroll 1
      for (int i = 0; i < LEAD; i++) {
        mbar_wait(sb + BAR_AE + 8 * i, 0);
        if (elect_one()) { mbar_expect(sb + BAR_AF + 8 * i, A_SLOT); tma_rows(sb + OFF_A + i * A_SLOT, &p.tmWsp, i * 64, rb, sb + BAR_AF + 8 * i); }
      }
      if (ZP_AT < 0) mbar_wait(sb + BAR_ZP, 0);
      poll_counter(p.scr->zcnt + (cb >> ZSH) * 32, (epoch + 1) * (32 << ZSH));
      STAMP(22);
      int sa = LEAD, pa = 0, ia = LEAD;
#pragma unroll 1
      for (int it = 0; it < 32; it++) {
        if (it == ZP_AT) mbar_wait(sb + BAR_ZP, 0);
        if (it == 16) { mbar_wait(sb + BAR_Z1, 1); acquire_fence(); }
        mbar_wait2(sb + BAR_BE + 8 * s, ph, sb + BAR_AE + 8 * sa, pa);
        if (elect_one()) {
          mbar_expect(sb + BAR_BF + 8 * s, B_SLOT);
          bulk_g2s(sb + OFF_B + s * B_SLOT, p.scr->z2 + (size_t)(cb * 32 + it) * B_SLOT, B_SLOT, sb + BAR_BF + 8 * s);
        }
#pragma unroll 1
        for (int j = (it < RAMP ? 0 : (it == 4 ? 1 + RAMP : 1)); j > 0 && ia < 32; j--, ia++) {
          if (it == 4) mbar_wait(sb + BAR_AE + 8 * sa, pa);
          if (elect_one()) { mbar_expect(sb + BAR_AF + 8 * sa, A_SLOT); tma_rows(sb + OFF_A + sa * A_SLOT, &p.tmWsp, ia * 64, rb, sb + BAR_AF + 8 * sa); }
          if (++sa == NA2) { sa = 0; pa ^= 1; }
        }
        STAMP2(52 + it);
        if (++s == NB) { s = 0; ph ^= 1; }
      }
      mbar_wait(sb + BAR_WO, 0);
      acquire_fence();
#pragma unroll 1
      for (int it = 0; it < 12; it++) {
        if (it < 6) mbar_wait(sb + BAR_BE + 8 * ((0x110443 >> (4 * it)) & 7), it < 3 ? 1 : 0);
        else mbar_wait(sb + BAR_BE + 8 * s, ph);
        if (elect_one()) {
          mbar_expect(sb + BAR_BF + 8 * s, 20480);
          bulk_g2s(sb + OFF_B + (s == 5 ? 0 : s + 1) * 20480, p.scr->wo + (size_t)(cb * 12 + g3_block(cb, it)) * 20480, 20480, sb + BAR_BF + 8 * s);
        }
        STAMP2(84 + it);
        if (++s == 6) { s = 0; ph ^= 1; }
      }
    } else if (warp == 14) {
      const uint32_t tag = epoch + 1;
      mbar_wait(sb + BAR_AF + 8 * (NA - 1), 0);
#pragma unroll 1
      for (int part = 0; part < 2 - CS1BY; part++) {
        gather_colsum(p, sb, cb, part, tag, lane);
        if (part == 0) STAMP(27);
      }
      if (!CS1BY) STAMP(38);
      bar_sync(NB_Z, ZORD ? 160 : 96);
      if (elect_one()) {
        z_store(p, sb + OFF_A + zs0 * A_SLOT, rb, cb, 0);
        STAMP(7);
        red_release(p.scr->zcnt + (cb >> ZSH) * 32);
      }
      STAMP(25);
      bar_sync(NB_Z2, 96);
      if (elect_one()) {
        z_store(p, sb + OFF_A + zs0 * A_SLOT, rb, cb, 1);
        mbar_arrive(sb + BAR_ZP);
        red_release(p.scr->cnt + CNT_Z1);
      }
      STAMP(28);
      mbar_wait(sb + BAR_AE + 72, 0);
      conv_service(p, sb, 0, chb + 64, true);
      bar_sync(NB_WO, 160);
      bar_sync(NB_CD, 64);
      if (elect_one()) { red_release(p.scr->cnt + CNT_WO + cb); red_relaxed(p.scr->cnt + CNT_Y + (cb >> 1)); }
      STAMP(49);
      poll_counter(p.scr->cnt + CNT_WO + cb, tag * 32);
      if (elect_one()) mbar_arrive(sb + BAR_WO);
      STAMP(46);
      held_service(p, sb, 0, chb + 192, rb, cb, tag, lane);
    } else {
      const uint32_t tag = epoch + 1;
      sts32(sb + OFF_BIAS + lane * 4, ldg1(p.bsp + (lane >> 3) * 512 + rb * 16 + (lane & 7) * 2));
      if (lane < 2) sts32(sb + OFF_TAG + lane * 4, lane ? 0 : tag);
      fence_async_smem();
      uint32_t t0 = 0;
      mbar_wait(sb + BAR_AF + 8 * (NA - 1), 0);
#pragma unroll 1
      while (true) {
        const uint4 u = ld_ll4(&p.scr->xstat[rb * 64 + lane]), v = ld_ll4(&p.scr->xstat[rb * 64 + 32 + lane]);
        sts64f(sb + OFF_XS + lane * 8, __uint_as_float(u.x), __uint_as_float(u.z));
        sts64f(sb + OFF_XS + 256 + lane * 8, __uint_as_float(v.x), __uint_as_float(v.z));
        if (__all_sync(0xffffffff, u.y == tag && u.w == tag && v.y == tag && v.w == tag)) break;
        spin_guard(t0);
      }
      STAMP(26);
      __syncwarp();
      if (lane == 0) mbar_arrive(sb + BAR_XS);
      if (CS1BY) { uint32_t tp = tstart; pace(tp, CS1_T); gather_colsum(p, sb, cb, 1, tag, lane); STAMP(38); }
      mbar_wait(sb + BAR_KU, 1);
      poll_counter(p.scr->cnt + CNT_KV + (cb >> 1), tag * 64);
      if (elect_one()) load_convx(p, sb + OFF_CV, sb + BAR_XF + 8, chb);
      mbar_wait(sb + BAR_KU + 8, 1);
      if (elect_one()) load_convx(p, sb + OFF_CV + CV_SZ, sb + BAR_XF, chb + 64);
      STAMP(48);
      mbar_wait(sb + BAR_AE + 72, 0);
#pragma unroll 1
      for (int i = 0; i < 2; i++) conv_service(p, sb, 1, chb + i * 128, i == 0);
      bar_arrive(NB_CD, 64);
      mbar_wait(sb + BAR_WO, 0);
      poll_counter(p.scr->cnt + CNT_Y + (cb >> 1), tag * 64);
      STAMP(47);
      if (elect_one()) mbar_arrive(sb + BAR_YT);
      held_service(p, sb, 1, chb + 256, rb, cb, tag, lane);
      if (lane == 0) *(volatile uint32_t*)&p.scr->epoch[lin] = tag;
      STAMP(23);
    }
  } else {
    if (warp == 7) STAMP(36);
    const int wg = warp >> 2, w = warp & 3, g = lane >> 2, t = lane & 3;
    Taps k;
    uint32_t xw[2][10];
    if (wg == 2) {
      asm volatile("setmaxnreg.inc.sync.aligned.u32 160;");
      const int tb = rb * 2 + (cb & 1), c0 = (cb >> 1) * 320;
      const uint32_t cv = sb + OFF_CV + CV_SZ;
      if (w == 0) zero_pads(sb + OFF_CV, lane);
      mbar_wait(sb + BAR_KV + 8, 0);
      const int t0 = tb * 32 + w * 8;
      const __nv_bfloat16* kp = p.k + (size_t)(t0 - 3) * kD + c0 + lane * 2;
      const __nv_bfloat16* vp = p.v + (size_t)t0 * kD + c0 + lane * 2;
      const __nv_bfloat16* sp = p.shift + (c0 + lane * 2) * 4;
      const uint32_t oa = cv + ((3 - w) & 1) * 1024 + lane * 32 + ((((3 - w) >> 1) ^ (lane >> 2)) & 1) * 16;
#pragma unroll 1
      for (int r = 0; r < 2; r++) {
        KvRegs n0, n1, n2;
        kv_load(n0, kp + r * 128, vp + r * 128, sp + r * 512, t0 > 0);
        kv_load(n1, kp + r * 128 + 64, vp + r * 128 + 64, sp + r * 512 + 256, t0 > 0);
        if (r) kv_load(n2, kp + 256, vp + 256, sp + 1024, t0 > 0);
        kv_unit(n0, oa + r * 8192);
        bar_sync(NB_WGC, 128);
        mbar_arrive_if(sb + BAR_KU + 16 * r, tid == 0);
        if (r) mbar_wait(sb + BAR_KU, 1);
        kv_unit(n1, oa + (r ? 0 : 4096));
        bar_sync(NB_WGC, 128);
        mbar_arrive_if(sb + BAR_KU + 16 * r + 8, tid == 0);
        if (r) {
          kv_unit(n2, oa + 4096);
          bar_sync(NB_WGC, 128);
          mbar_arrive_if(sb + BAR_KU + 32, tid == 0);
        } else {
          mbar_wait(sb + BAR_AF + 8 * ((cb >> 1) * 5 + 1), 0);
          mbar_wait2(sb + BAR_AF + 8 * ((cb >> 1) * 5 + 2), 0, sb + BAR_AF + 8 * ((cb >> 1) * 5 + 4), 0);
          final_load_x(xw, sb + OFF_A, cb, 1, w, lane);
          fence_async_smem();
          bar_sync(NB_WGC, 128);
          mbar_arrive_if(sb + BAR_XC, tid == 0);
        }
      }
      STAMPW(13);
      load_taps(k, p, chb, tid);
    } else {
      float d[96];
      if (wg == 0) st_ll2(&p.scr->zstat[(rb * 256 + cb * 64 + w * 16 + g + (t >> 1) * 8) * 2 + (t & 1)], 0, 0);
      else if ((tid & 7) == 0) st_ll4(&p.scr->xstat[rb * 64 + cb * 16 + (tid >> 3)], 0, 0, 0, 0);
      {
        #pragma unroll
        for (int i = 0; i < 96; i++) d[i] = 0.f;
        {
          if (__builtin_expect(wg == 1, 0)) {
            const int tid = tid_now();
            const uint32_t epoch = load_epoch(p, lin, lane);
            float s = 0.f, q = 0.f;
#pragma unroll 1
            for (int i = 0; i < 10; i++) {
              mbar_wait(sb + BAR_AF + 8 * i, 0);
              const uint4 x4 = lds128(sb + OFF_A + i * A_SLOT + cb * 2048 + tid * 16);
              const uint32_t u[4] = {x4.x, x4.y, x4.z, x4.w};
#pragma unroll
              for (int e = 0; e < 4; e++) { const float a = bf_lo(u[e]), c = bf_hi(u[e]); s += a + c; q = fmaf(a, a, q); q = fmaf(c, c, q); }
            }
#pragma unroll
            for (int o = 1; o <= 4; o <<= 1) { s += __shfl_xor_sync(0xffffffff, s, o); q += __shfl_xor_sync(0xffffffff, q, o); }
            const float m = s * (1.f / kD);
            const float r = rsqrtf(fmaxf(fmaf(-m, m, q * (1.f / kD)), 0.f) + 1e-5f);
            if ((tid & 7) == 0) st_ll4(&p.scr->xstat[rb * 64 + cb * 16 + (tid >> 3)], __float_as_uint(m), epoch + 1, __float_as_uint(r), epoch + 1);
            STAMPW(12);
            bar_sync(NB_G1, 256);
          }
          gemm_loop<192, true, 0, D1>(d, sb, 10, wg ? zs0 : 0, 0, 0, 0, wg, 2, tid_now(), [&]() { if (G1_AT == 0 && wg == 0) bar_arrive(NB_G1, 256); }, [](int) {});
          asm volatile("setmaxnreg.inc.sync.aligned.u32 160;");
          STAMPW(wg ? 14 : 1);
          if (wg == 0) ZS(0);
          mbar_wait2(sb + BAR_XS, 0, sb + BAR_ST + 8 * wg, 0);
          if (wg == 0) ZS(1);
        }
        const int t1 = tid_now();
        const uint32_t xa1 = sb + OFF_XS + (w * 16 + ((t1 & 31) >> 2)) * 8;
        const float2 s0 = lds64f(xa1), s1 = lds64f(xa1 + 64);
        uint32_t z[48];
        float st[4];
        fence_async_smem();
        fold_mean(d, sb + OFF_CS + (1 - wg) * 768, s0.x, s1.x, t1 & 3);
        if (G1_AT == 1 && wg == 0) bar_arrive(NB_G1, 256);
        WG_WAIT(0);
        acc_fence<96>(d);
        if (wg == 0) ZS(2);
        gelu_tile(d, z, st, s0.y, s1.y);
        const int tid = tid_now(), lane = tid & 31, g = lane >> 2, t = lane & 3;
        if (wg == 1) {
          uint32_t bra, brb;
          asm volatile("ld.shared.u16 %0, [%1];" : "=r"(bra) : "r"(sb + OFF_BIAS + (w * 16 + g) * 2));
          asm volatile("ld.shared.u16 %0, [%1+16];" : "=r"(brb) : "r"(sb + OFF_BIAS + (w * 16 + g) * 2));
#pragma unroll
          for (int j = 0; j < 96; j++) d[j] = bf_lo((j & 2) ? brb : bra);
          STAMPW(15);
          gemm_loop<192, true, 1, D2>(d, sb, 32, 0, 1, 20, 0, 2, 2, tid, [&]() { if (HOLD_AT < 32) mbar_arrive_if(sb + BAR_GO, tid == 0); }, [](int) {});
          if (HOLD_AT == 32) mbar_arrive_if(sb + BAR_GO, tid == 0);
          STAMPW(16);
          const int t2 = tid_now(), l2 = t2 & 31;
          const uint32_t ha = sb + OFF_A + 5 * A_SLOT + (l2 >> 4) * 1024 + (2 * w + ((l2 >> 3) & 1)) * 128 + (l2 & 7) * 16;
#pragma unroll
          for (int j = 0; j < 24; j += 2) {
#pragma unroll
            for (int e = 0; e < 4; e++) z[2 * j + e] = hmul2(z[2 * j + e], pack2(d[4 * j + 2 * e], d[4 * j + 2 * e + 1]));
            stsm4(ha + j * 1024, z[2 * j], z[2 * j + 1], z[2 * j + 2], z[2 * j + 3]);
          }
          fence_async_smem();
          bar_sync(NB_WGB, 128);
          mbar_arrive_if(sb + BAR_AF + 8 * (t2 == 3 ? (BAR_G2 - BAR_AF) / 8 : (t2 == 4 ? (BAR_GO - BAR_AF) / 8 : 5 + t2)), t2 < (HOLD_AT == 33 ? 5 : 4));
          STAMPW(17);
          {
            float e[80];
#pragma unroll
            for (int j = 0; j < 80; j++) e[j] = 0.f;
            gemm_loop<160, false, 2, DB>(e, sb, 12, 5, 0, 2, 0, 2, 2, tid_now(), []() {}, [](int) {});
            STAMPW(10);
            const int t3 = tid_now();
#pragma unroll
            for (int j = 0; j < 10; j++) {
              sts128(sb + OFF_A + j * 2048 + t3 * 16, pack2(e[8 * j], e[8 * j + 1]), pack2(e[8 * j + 2], e[8 * j + 3]), pack2(e[8 * j + 4], e[8 * j + 5]),
                     pack2(e[8 * j + 6], e[8 * j + 7]));
              if (j == 4) bar_arrive(NB_WO, 256);
            }
            bar_arrive(NB_Z, 256);
            STAMPW(45);
          }
          return;
        }
        ZS(3);
        const bool hi = t & 2;
        float a0 = (hi ? st[2] : st[0]) + __shfl_xor_sync(0xffffffff, hi ? st[0] : st[2], 2);
        float a1 = (hi ? st[3] : st[1]) + __shfl_xor_sync(0xffffffff, hi ? st[1] : st[3], 2);
        a0 = ((t & 1) ? a1 : a0) + __shfl_xor_sync(0xffffffff, (t & 1) ? a0 : a1, 1);
        const uint32_t tag = lds32<0>(sb + OFF_TAG);
        uint2* zs = p.scr->zstat + (rb * 256 + w * 16 + g + (t >> 1) * 8) * 2 + (t & 1);
        st_ll2(zs + cb * 128, __float_as_uint(a0), tag);
        STAMPW(2); ZS(4);
        uint2 u[4];
#pragma unroll
        for (int i = 0; i < 4; i++) u[i] = ld_ll2(zs + i * 128);
        const uint32_t keep = (cb & 2) ? 13 << 5 : 13;
        mbar_arrive_if(sb + BAR_AE + 8 * tid, tid < NA && !((keep >> tid) & 1));
        const uint32_t za = sb + OFF_A + zs0 * A_SLOT + (2 * w + ((lane >> 3) & 1)) * 3072 + (lane >> 4) * 128 + (lane & 7) * 16;
        const float ca = 0.5f * (hi ? s1.y : s0.y), inv = 1.f / 768.f;
        mbar_wait2(sb + BAR_AE + 8 * (zs0 + 2), 0, sb + BAR_XC, 0);
        ZS(6);
        uint32_t t0 = 0;
#pragma unroll 1
        while (!__all_sync(0xffffffff, u[0].y == tag && u[1].y == tag && u[2].y == tag && u[3].y == tag)) {
          spin_guard(t0);
#pragma unroll
          for (int i = 0; i < 4; i++) u[i] = ld_ll2(zs + i * 128);
        }
        STAMPW(3); ZS(7);
        a0 = ((__uint_as_float(u[0].x) + __uint_as_float(u[1].x)) + (__uint_as_float(u[2].x) + __uint_as_float(u[3].x))) * inv;
        a1 = __shfl_xor_sync(0xffffffff, a0, 1);
        const float m = (t & 1) ? a1 : a0, q = (t & 1) ? a0 : a1;
        const float r = bf_lo(pack2(ca * rsqrtf(fmaf(fmaxf(fmaf(-m, m, q), 0.f), ca * ca, 1e-5f)), 0.f));
        const uint32_t rn = pack2(r, -m * r), ro = __shfl_xor_sync(0xffffffff, rn, 2);
        const uint32_t ra2 = prmt(hi ? ro : rn, 0, 0x1010), n2a = prmt(hi ? ro : rn, 0, 0x3232), rb2 = prmt(hi ? rn : ro, 0, 0x1010), n2b = prmt(hi ? rn : ro, 0, 0x3232);
        if (ZORD && w >= 2) bar_sync(NB_Z, 160);
#pragma unroll
        for (int j = 0; j < 24; j += 2)
          stsm4(za + j * 128, hfma2(z[2 * j], ra2, n2a), hfma2(z[2 * j + 1], rb2, n2b), hfma2(z[2 * j + 2], ra2, n2a), hfma2(z[2 * j + 3], rb2, n2b));
        ZS(8);
        fence_async_smem();
        ZS(9);
        if (w < 2) bar_arrive(NB_Z, ZORD ? 160 : 96);
        else bar_arrive(NB_Z2, 96);
        final_load_x(xw, sb + OFF_A, cb, 0, w, lane);
        fence_async_smem();
        bar_sync(NB_WGA, 128);
        mbar_arrive_if(sb + BAR_AE + 8 * tid, tid < NA && ((keep >> tid) & 1));
      }
      {
        const uint32_t zero = lds32<0>(sb + OFF_TAG + 4);
#pragma unroll
        for (int i = 0; i < 20; i++) xw[i / 10][i % 10] |= zero;
      }
      load_taps(k, p, chb + 64, tid_now());
      STAMPW(4);
    }
    const int h = wg >> 1;
    {
    const int tid = tid_now(), lane = tid & 31;
    conv_worker(p, k, sb + OFF_CV + (1 - h) * CV_SZ, sb + OFF_A + 9 * A_SLOT + h * 4096, sb + BAR_XF + 8 * h, NB_WGA + h,
                chb + (h ? 0 : 64), 2 + h, sb + BAR_GO, w, lane, tid, h ? 40 : 5, rb, cb);
    {
      const int t3 = tid_now(), l3 = t3 & 31;
      const uint32_t xs_addr = sb + OFF_XS + (w * 16 + (l3 >> 2)) * 8;
      const float2 s0 = lds64f(xs_addr), s1 = lds64f(xs_addr + 64);
      const uint32_t ya = sb + y_tile(h) + ((l3 >> 4) * 8 + (l3 & 7)) * 128 + (((2 * w + ((l3 >> 3) & 1)) ^ (l3 & 7) ^ (rb & 7)) << 4);
      uint32_t sw[2][10];
      mbar_wait(sb + BAR_XF + 8 * h, h);
      final_s_early(sw, xw, ya, s0, s1);
      uint32_t ph = 1, t0 = 0, y[8];
#pragma unroll 1
      while (true) {
        mbar_wait(sb + BAR_YL + 16 * h, ph);
        if (bar_all(NB_WGA + h, 128, final_late(y, ya))) break;
        spin_guard(t0);
        ph ^= 1;
        if (t3 == 0) load_late_y(p, sb, h, rb, cb, lds32<0>(sb + OFF_TAG) & 1);
      }
#pragma unroll
      for (int e = 0; e < 8; e++) sw[e & 1][4 + (e >> 1)] = hmul2(sw[e & 1][4 + (e >> 1)], ~y[e]);
      __nv_bfloat16* o0 = p.out + (size_t)(w * 512 + rb * 16 + (l3 >> 2)) * kD + seg_col(cb, h);
      STAMPW(h ? 44 : 9);
      bar_sync(h ? NB_Z : NB_WO, 256);
      float d[40];
#pragma unroll
      for (int j = 0; j < 5; j++) {
        const uint4 v = lds128(sb + OFF_A + (h * 5 + j) * 2048 + t3 * 16);
        d[8 * j] = bf_lo(v.x); d[8 * j + 1] = bf_hi(v.x); d[8 * j + 2] = bf_lo(v.y); d[8 * j + 3] = bf_hi(v.y);
        d[8 * j + 4] = bf_lo(v.z); d[8 * j + 5] = bf_hi(v.z); d[8 * j + 6] = bf_lo(v.w); d[8 * j + 7] = bf_hi(v.w);
      }
      final_out(d, xw, sw, s0.y, s1.y, o0, h, l3 & 3);
    }
    }
  }
}

typedef CUresult (*EncodeFn)(CUtensorMap*, CUtensorMapDataType, cuuint32_t, void*, const cuuint64_t*, const cuuint64_t*, const cuuint32_t*,
                             const cuuint32_t*, CUtensorMapInterleave, CUtensorMapSwizzle, CUtensorMapL2promotion, CUtensorMapFloatOOBfill);

void encode(EncodeFn fn, CUtensorMap* m, const void* ptr, int rank, const cuuint64_t* dims, const cuuint64_t* strides, const cuuint32_t* box,
            CUtensorMapSwizzle swz = CU_TENSOR_MAP_SWIZZLE_128B) {
  const cuuint32_t es[3] = {1, 1, 1};
  fn(m, CU_TENSOR_MAP_DATA_TYPE_BFLOAT16, rank, const_cast<void*>(ptr), dims, strides, box, es, CU_TENSOR_MAP_INTERLEAVE_NONE,
     swz, CU_TENSOR_MAP_L2_PROMOTION_L2_128B, CU_TENSOR_MAP_FLOAT_OOB_FILL_NONE);
}

}

extern "C" void kernel_launch(void* const* d_in, const int* in_sizes, int n_in, void* d_out, int out_size) {
  (void)in_sizes; (void)n_in; (void)out_size;
  static EncodeFn enc = nullptr;
  static Scratch* scr = nullptr;
  static int sms = 0;
  if (!enc) {
    void* fn = nullptr;
    cudaDriverEntryPointQueryResult qr;
    cudaGetDriverEntryPoint("cuTensorMapEncodeTiled", &fn, cudaEnableDefault, &qr);
    enc = (EncodeFn)fn;
    cudaFuncSetAttribute(fused_kernel, cudaFuncAttributeMaxDynamicSharedMemorySize, SMEM_BYTES);
    cudaGetSymbolAddress((void**)&scr, g_scr);
    int dev = 0;
    cudaGetDevice(&dev);
    cudaDeviceGetAttribute(&sms, cudaDevAttrMultiProcessorCount, dev);
  }
  Params p;
  p.scr = scr;
  p.by_smid = sms == 132;
  p.k = (const __nv_bfloat16*)d_in[1];
  p.v = (const __nv_bfloat16*)d_in[2];
  p.shift = (const __nv_bfloat16*)d_in[3];
  p.ssmk = (const __nv_bfloat16*)d_in[4];
  p.ssmD = (const __nv_bfloat16*)d_in[5];
  p.wsp = (const __nv_bfloat16*)d_in[8];
  p.bsp = (const __nv_bfloat16*)d_in[9];
  p.wout = (const __nv_bfloat16*)d_in[10];
  p.out = (__nv_bfloat16*)d_out;
  for (int i = 0; i < 2; i++) {
    const cuuint64_t n = i ? kS : kD, dims[3] = {n, 512, 4}, st[2] = {n * 2, n * 1024};
    const cuuint32_t box[3] = {64, 16, 4};
    encode(enc, i ? &p.tmWsp : &p.tmX, d_in[i ? 8 : 0], 3, dims, st, box);
  }
  {
    const cuuint64_t dims[3] = {64, kD, kF / 64}, st[2] = {kF * 2, 128};
    const cuuint32_t box[3] = {64, 64, 3};
    encode(enc, &p.tmW, d_in[7], 3, dims, st, box);
  }
  {
    const cuuint64_t dims[2] = {kS, 896}, st[1] = {kS * 2};
    const cuuint32_t box[2] = {64, 16};
    encode(enc, &p.tmY, scr->y, 2, dims, st, box);
  }
  {
    const cuuint64_t dims[3] = {1024, kD / 2, 4}, st[2] = {8192, 2048};
    const cuuint32_t box[3] = {16, 32, 4};
    encode(enc, &p.tmKV, scr->kvx, 3, dims, st, box, CU_TENSOR_MAP_SWIZZLE_32B);
  }
  fused_kernel<<<132, 512, SMEM_BYTES, cudaStreamPerThread>>>(p);
}
```

```cpp
#include <cuda_runtime.h>
#include <cuda.h>
#include <cuda_bf16.h>
#include <stdint.h>

template <int N> struct WG;
template <> struct WG<16> {
  static __device__ __forceinline__ void rs(float* d, const uint32_t* a, uint64_t db) {
    asm volatile("{\n.reg .pred p;\nsetp.ne.b32 p, 1, 0;\nwgmma.mma_async.sync.aligned.m64n16k16.f32.bf16.bf16 {"
      "%0, %1, %2, %3, %4, %5, %6, %7"
      "}, {%8, %9, %10, %11}, %12, p, 1, 1, 0;\n}\n"
      :
      "+f"(d[0]), "+f"(d[1]), "+f"(d[2]), "+f"(d[3]), "+f"(d[4]), "+f"(d[5]), "+f"(d[6]), "+f"(d[7])
      : "r"(a[0]), "r"(a[1]), "r"(a[2]), "r"(a[3]), "l"(db));
  }
};
template <> struct WG<32> {
  static __device__ __forceinline__ void rs(float* d, const uint32_t* a, uint64_t db) {
    asm volatile("{\n.reg .pred p;\nsetp.ne.b32 p, 1, 0;\nwgmma.mma_async.sync.aligned.m64n32k16.f32.bf16.bf16 {"
      "%0, %1, %2, %3, %4, %5, %6, %7, %8, %9, %10, %11, %12, %13, %14, %15"
      "}, {%16, %17, %18, %19}, %20, p, 1, 1, 0;\n}\n"
      :
      "+f"(d[0]), "+f"(d[1]), "+f"(d[2]), "+f"(d[3]), "+f"(d[4]), "+f"(d[5]), "+f"(d[6]), "+f"(d[7]),
      "+f"(d[8]), "+f"(d[9]), "+f"(d[10]), "+f"(d[11]), "+f"(d[12]), "+f"(d[13]), "+f"(d[14]), "+f"(d[15])
      : "r"(a[0]), "r"(a[1]), "r"(a[2]), "r"(a[3]), "l"(db));
  }
};
template <> struct WG<48> {
  static __device__ __forceinline__ void rs(float* d, const uint32_t* a, uint64_t db) {
    asm volatile("{\n.reg .pred p;\nsetp.ne.b32 p, 1, 0;\nwgmma.mma_async.sync.aligned.m64n48k16.f32.bf16.bf16 {"
      "%0, %1, %2, %3, %4, %5, %6, %7, %8, %9, %10, %11, %12, %13, %14, %15, "
      "%16, %17, %18, %19, %20, %21, %22, %23"
      "}, {%24, %25, %26, %27}, %28, p, 1, 1, 0;\n}\n"
      :
      "+f"(d[0]), "+f"(d[1]), "+f"(d[2]), "+f"(d[3]), "+f"(d[4]), "+f"(d[5]), "+f"(d[6]), "+f"(d[7]),
      "+f"(d[8]), "+f"(d[9]), "+f"(d[10]), "+f"(d[11]), "+f"(d[12]), "+f"(d[13]), "+f"(d[14]), "+f"(d[15]),
      "+f"(d[16]), "+f"(d[17]), "+f"(d[18]), "+f"(d[19]), "+f"(d[20]), "+f"(d[21]), "+f"(d[22]), "+f"(d[23])
      : "r"(a[0]), "r"(a[1]), "r"(a[2]), "r"(a[3]), "l"(db));
  }
};
template <> struct WG<64> {
  static __device__ __forceinline__ void rs(float* d, const uint32_t* a, uint64_t db) {
    asm volatile("{\n.reg .pred p;\nsetp.ne.b32 p, 1, 0;\nwgmma.mma_async.sync.aligned.m64n64k16.f32.bf16.bf16 {"
      "%0, %1, %2, %3, %4, %5, %6, %7, %8, %9, %10, %11, %12, %13, %14, %15, "
      "%16, %17, %18, %19, %20, %21, %22, %23, %24, %25, %26, %27, %28, %29, %30, %31"
      "}, {%32, %33, %34, %35}, %36, p, 1, 1, 0;\n}\n"
      :
      "+f"(d[0]), "+f"(d[1]), "+f"(d[2]), "+f"(d[3]), "+f"(d[4]), "+f"(d[5]), "+f"(d[6]), "+f"(d[7]),
      "+f"(d[8]), "+f"(d[9]), "+f"(d[10]), "+f"(d[11]), "+f"(d[12]), "+f"(d[13]), "+f"(d[14]), "+f"(d[15]),
      "+f"(d[16]), "+f"(d[17]), "+f"(d[18]), "+f"(d[19]), "+f"(d[20]), "+f"(d[21]), "+f"(d[22]), "+f"(d[23]),
      "+f"(d[24]), "+f"(d[25]), "+f"(d[26]), "+f"(d[27]), "+f"(d[28]), "+f"(d[29]), "+f"(d[30]), "+f"(d[31])
      : "r"(a[0]), "r"(a[1]), "r"(a[2]), "r"(a[3]), "l"(db));
  }
};
template <> struct WG<80> {
  static __device__ __forceinline__ void rs(float* d, const uint32_t* a, uint64_t db) {
    asm volatile("{\n.reg .pred p;\nsetp.ne.b32 p, 1, 0;\nwgmma.mma_async.sync.aligned.m64n80k16.f32.bf16.bf16 {"
      "%0, %1, %2, %3, %4, %5, %6, %7, %8, %9, %10, %11, %12, %13, %14, %15, "
      "%16, %17, %18, %19, %20, %21, %22, %23, %24, %25, %26, %27, %28, %29, %30, %31, "
      "%32, %33, %34, %35, %36, %37, %38, %39"
      "}, {%40, %41, %42, %43}, %44, p, 1, 1, 0;\n}\n"
      :
      "+f"(d[0]), "+f"(d[1]), "+f"(d[2]), "+f"(d[3]), "+f"(d[4]), "+f"(d[5]), "+f"(d[6]), "+f"(d[7]),
      "+f"(d[8]), "+f"(d[9]), "+f"(d[10]), "+f"(d[11]), "+f"(d[12]), "+f"(d[13]), "+f"(d[14]), "+f"(d[15]),
      "+f"(d[16]), "+f"(d[17]), "+f"(d[18]), "+f"(d[19]), "+f"(d[20]), "+f"(d[21]), "+f"(d[22]), "+f"(d[23]),
      "+f"(d[24]), "+f"(d[25]), "+f"(d[26]), "+f"(d[27]), "+f"(d[28]), "+f"(d[29]), "+f"(d[30]), "+f"(d[31]),
      "+f"(d[32]), "+f"(d[33]), "+f"(d[34]), "+f"(d[35]), "+f"(d[36]), "+f"(d[37]), "+f"(d[38]), "+f"(d[39])
      : "r"(a[0]), "r"(a[1]), "r"(a[2]), "r"(a[3]), "l"(db));
  }
};
template <> struct WG<96> {
  static __device__ __forceinline__ void rs(float* d, const uint32_t* a, uint64_t db) {
    asm volatile("{\n.reg .pred p;\nsetp.ne.b32 p, 1, 0;\nwgmma.mma_async.sync.aligned.m64n96k16.f32.bf16.bf16 {"
      "%0, %1, %2, %3, %4, %5, %6, %7, %8, %9, %10, %11, %12, %13, %14, %15, "
      "%16, %17, %18, %19, %20, %21, %22, %23, %24, %25, %26, %27, %28, %29, %30, %31, "
      "%32, %33, %34, %35, %36, %37, %38, %39, %40, %41, %42, %43, %44, %45, %46, %47"
      "}, {%48, %49, %50, %51}, %52, p, 1, 1, 0;\n}\n"
      :
      "+f"(d[0]), "+f"(d[1]), "+f"(d[2]), "+f"(d[3]), "+f"(d[4]), "+f"(d[5]), "+f"(d[6]), "+f"(d[7]),
      "+f"(d[8]), "+f"(d[9]), "+f"(d[10]), "+f"(d[11]), "+f"(d[12]), "+f"(d[13]), "+f"(d[14]), "+f"(d[15]),
      "+f"(d[16]), "+f"(d[17]), "+f"(d[18]), "+f"(d[19]), "+f"(d[20]), "+f"(d[21]), "+f"(d[22]), "+f"(d[23]),
      "+f"(d[24]), "+f"(d[25]), "+f"(d[26]), "+f"(d[27]), "+f"(d[28]), "+f"(d[29]), "+f"(d[30]), "+f"(d[31]),
      "+f"(d[32]), "+f"(d[33]), "+f"(d[34]), "+f"(d[35]), "+f"(d[36]), "+f"(d[37]), "+f"(d[38]), "+f"(d[39]),
      "+f"(d[40]), "+f"(d[41]), "+f"(d[42]), "+f"(d[43]), "+f"(d[44]), "+f"(d[45]), "+f"(d[46]), "+f"(d[47])
      : "r"(a[0]), "r"(a[1]), "r"(a[2]), "r"(a[3]), "l"(db));
  }
};
template <> struct WG<112> {
  static __device__ __forceinline__ void rs(float* d, const uint32_t* a, uint64_t db) {
    asm volatile("{\n.reg .pred p;\nsetp.ne.b32 p, 1, 0;\nwgmma.mma_async.sync.aligned.m64n112k16.f32.bf16.bf16 {"
      "%0, %1, %2, %3, %4, %5, %6, %7, %8, %9, %10, %11, %12, %13, %14, %15, "
      "%16, %17, %18, %19, %20, %21, %22, %23, %24, %25, %26, %27, %28, %29, %30, %31, "
      "%32, %33, %34, %35, %36, %37, %38, %39, %40, %41, %42, %43, %44, %45, %46, %47, "
      "%48, %49, %50, %51, %52, %53, %54, %55"
      "}, {%56, %57, %58, %59}, %60, p, 1, 1, 0;\n}\n"
      :
      "+f"(d[0]), "+f"(d[1]), "+f"(d[2]), "+f"(d[3]), "+f"(d[4]), "+f"(d[5]), "+f"(d[6]), "+f"(d[7]),
      "+f"(d[8]), "+f"(d[9]), "+f"(d[10]), "+f"(d[11]), "+f"(d[12]), "+f"(d[13]), "+f"(d[14]), "+f"(d[15]),
      "+f"(d[16]), "+f"(d[17]), "+f"(d[18]), "+f"(d[19]), "+f"(d[20]), "+f"(d[21]), "+f"(d[22]), "+f"(d[23]),
      "+f"(d[24]), "+f"(d[25]), "+f"(d[26]), "+f"(d[27]), "+f"(d[28]), "+f"(d[29]), "+f"(d[30]), "+f"(d[31]),
      "+f"(d[32]), "+f"(d[33]), "+f"(d[34]), "+f"(d[35]), "+f"(d[36]), "+f"(d[37]), "+f"(d[38]), "+f"(d[39]),
      "+f"(d[40]), "+f"(d[41]), "+f"(d[42]), "+f"(d[43]), "+f"(d[44]), "+f"(d[45]), "+f"(d[46]), "+f"(d[47]),
      "+f"(d[48]), "+f"(d[49]), "+f"(d[50]), "+f"(d[51]), "+f"(d[52]), "+f"(d[53]), "+f"(d[54]), "+f"(d[55])
      : "r"(a[0]), "r"(a[1]), "r"(a[2]), "r"(a[3]), "l"(db));
  }
};
template <> struct WG<128> {
  static __device__ __forceinline__ void rs(float* d, const uint32_t* a, uint64_t db) {
    asm volatile("{\n.reg .pred p;\nsetp.ne.b32 p, 1, 0;\nwgmma.mma_async.sync.aligned.m64n128k16.f32.bf16.bf16 {"
      "%0, %1, %2, %3, %4, %5, %6, %7, %8, %9, %10, %11, %12, %13, %14, %15, "
      "%16, %17, %18, %19, %20, %21, %22, %23, %24, %25, %26, %27, %28, %29, %30, %31, "
      "%32, %33, %34, %35, %36, %37, %38, %39, %40, %41, %42, %43, %44, %45, %46, %47, "
      "%48, %49, %50, %51, %52, %53, %54, %55, %56, %57, %58, %59, %60, %61, %62, %63"
      "}, {%64, %65, %66, %67}, %68, p, 1, 1, 0;\n}\n"
      :
      "+f"(d[0]), "+f"(d[1]), "+f"(d[2]), "+f"(d[3]), "+f"(d[4]), "+f"(d[5]), "+f"(d[6]), "+f"(d[7]),
      "+f"(d[8]), "+f"(d[9]), "+f"(d[10]), "+f"(d[11]), "+f"(d[12]), "+f"(d[13]), "+f"(d[14]), "+f"(d[15]),
      "+f"(d[16]), "+f"(d[17]), "+f"(d[18]), "+f"(d[19]), "+f"(d[20]), "+f"(d[21]), "+f"(d[22]), "+f"(d[23]),
      "+f"(d[24]), "+f"(d[25]), "+f"(d[26]), "+f"(d[27]), "+f"(d[28]), "+f"(d[29]), "+f"(d[30]), "+f"(d[31]),
      "+f"(d[32]), "+f"(d[33]), "+f"(d[34]), "+f"(d[35]), "+f"(d[36]), "+f"(d[37]), "+f"(d[38]), "+f"(d[39]),
      "+f"(d[40]), "+f"(d[41]), "+f"(d[42]), "+f"(d[43]), "+f"(d[44]), "+f"(d[45]), "+f"(d[46]), "+f"(d[47]),
      "+f"(d[48]), "+f"(d[49]), "+f"(d[50]), "+f"(d[51]), "+f"(d[52]), "+f"(d[53]), "+f"(d[54]), "+f"(d[55]),
      "+f"(d[56]), "+f"(d[57]), "+f"(d[58]), "+f"(d[59]), "+f"(d[60]), "+f"(d[61]), "+f"(d[62]), "+f"(d[63])
      : "r"(a[0]), "r"(a[1]), "r"(a[2]), "r"(a[3]), "l"(db));
  }
};
template <> struct WG<160> {
  static __device__ __forceinline__ void ss(float* d, uint64_t da, uint64_t db, int sd) {
    asm volatile("{\n.reg .pred p;\nsetp.ne.b32 p, %82, 0;\nwgmma.mma_async.sync.aligned.m64n160k16.f32.bf16.bf16 {"
      "%0, %1, %2, %3, %4, %5, %6, %7, %8, %9, %10, %11, %12, %13, %14, %15, "
      "%16, %17, %18, %19, %20, %21, %22, %23, %24, %25, %26, %27, %28, %29, %30, %31, "
      "%32, %33, %34, %35, %36, %37, %38, %39, %40, %41, %42, %43, %44, %45, %46, %47, "
      "%48, %49, %50, %51, %52, %53, %54, %55, %56, %57, %58, %59, %60, %61, %62, %63, "
      "%64, %65, %66, %67, %68, %69, %70, %71, %72, %73, %74, %75, %76, %77, %78, %79"
      "}, %80, %81, p, 1, 1, 0, 1;\n}\n"
      :
      "+f"(d[0]), "+f"(d[1]), "+f"(d[2]), "+f"(d[3]), "+f"(d[4]), "+f"(d[5]), "+f"(d[6]), "+f"(d[7]),
      "+f"(d[8]), "+f"(d[9]), "+f"(d[10]), "+f"(d[11]), "+f"(d[12]), "+f"(d[13]), "+f"(d[14]), "+f"(d[15]),
      "+f"(d[16]), "+f"(d[17]), "+f"(d[18]), "+f"(d[19]), "+f"(d[20]), "+f"(d[21]), "+f"(d[22]), "+f"(d[23]),
      "+f"(d[24]), "+f"(d[25]), "+f"(d[26]), "+f"(d[27]), "+f"(d[28]), "+f"(d[29]), "+f"(d[30]), "+f"(d[31]),
      "+f"(d[32]), "+f"(d[33]), "+f"(d[34]), "+f"(d[35]), "+f"(d[36]), "+f"(d[37]), "+f"(d[38]), "+f"(d[39]),
      "+f"(d[40]), "+f"(d[41]), "+f"(d[42]), "+f"(d[43]), "+f"(d[44]), "+f"(d[45]), "+f"(d[46]), "+f"(d[47]),
      "+f"(d[48]), "+f"(d[49]), "+f"(d[50]), "+f"(d[51]), "+f"(d[52]), "+f"(d[53]), "+f"(d[54]), "+f"(d[55]),
      "+f"(d[56]), "+f"(d[57]), "+f"(d[58]), "+f"(d[59]), "+f"(d[60]), "+f"(d[61]), "+f"(d[62]), "+f"(d[63]),
      "+f"(d[64]), "+f"(d[65]), "+f"(d[66]), "+f"(d[67]), "+f"(d[68]), "+f"(d[69]), "+f"(d[70]), "+f"(d[71]),
      "+f"(d[72]), "+f"(d[73]), "+f"(d[74]), "+f"(d[75]), "+f"(d[76]), "+f"(d[77]), "+f"(d[78]), "+f"(d[79])
      : "l"(da), "l"(db), "r"(sd));
  }
};
template <> struct WG<192> {
  static __device__ __forceinline__ void ss(float* d, uint64_t da, uint64_t db, int sd) {
    asm volatile("{\n.reg .pred p;\nsetp.ne.b32 p, %98, 0;\nwgmma.mma_async.sync.aligned.m64n192k16.f32.bf16.bf16 {"
      "%0, %1, %2, %3, %4, %5, %6, %7, %8, %9, %10, %11, %12, %13, %14, %15, "
      "%16, %17, %18, %19, %20, %21, %22, %23, %24, %25, %26, %27, %28, %29, %30, %31, "
      "%32, %33, %34, %35, %36, %37, %38, %39, %40, %41, %42, %43, %44, %45, %46, %47, "
      "%48, %49, %50, %51, %52, %53, %54, %55, %56, %57, %58, %59, %60, %61, %62, %63, "
      "%64, %65, %66, %67, %68, %69, %70, %71, %72, %73, %74, %75, %76, %77, %78, %79, "
      "%80, %81, %82, %83, %84, %85, %86, %87, %88, %89, %90, %91, %92, %93, %94, %95"
      "}, %96, %97, p, 1, 1, 0, 1;\n}\n"
      :
      "+f"(d[0]), "+f"(d[1]), "+f"(d[2]), "+f"(d[3]), "+f"(d[4]), "+f"(d[5]), "+f"(d[6]), "+f"(d[7]),
      "+f"(d[8]), "+f"(d[9]), "+f"(d[10]), "+f"(d[11]), "+f"(d[12]), "+f"(d[13]), "+f"(d[14]), "+f"(d[15]),
      "+f"(d[16]), "+f"(d[17]), "+f"(d[18]), "+f"(d[19]), "+f"(d[20]), "+f"(d[21]), "+f"(d[22]), "+f"(d[23]),
      "+f"(d[24]), "+f"(d[25]), "+f"(d[26]), "+f"(d[27]), "+f"(d[28]), "+f"(d[29]), "+f"(d[30]), "+f"(d[31]),
      "+f"(d[32]), "+f"(d[33]), "+f"(d[34]), "+f"(d[35]), "+f"(d[36]), "+f"(d[37]), "+f"(d[38]), "+f"(d[39]),
      "+f"(d[40]), "+f"(d[41]), "+f"(d[42]), "+f"(d[43]), "+f"(d[44]), "+f"(d[45]), "+f"(d[46]), "+f"(d[47]),
      "+f"(d[48]), "+f"(d[49]), "+f"(d[50]), "+f"(d[51]), "+f"(d[52]), "+f"(d[53]), "+f"(d[54]), "+f"(d[55]),
      "+f"(d[56]), "+f"(d[57]), "+f"(d[58]), "+f"(d[59]), "+f"(d[60]), "+f"(d[61]), "+f"(d[62]), "+f"(d[63]),
      "+f"(d[64]), "+f"(d[65]), "+f"(d[66]), "+f"(d[67]), "+f"(d[68]), "+f"(d[69]), "+f"(d[70]), "+f"(d[71]),
      "+f"(d[72]), "+f"(d[73]), "+f"(d[74]), "+f"(d[75]), "+f"(d[76]), "+f"(d[77]), "+f"(d[78]), "+f"(d[79]),
      "+f"(d[80]), "+f"(d[81]), "+f"(d[82]), "+f"(d[83]), "+f"(d[84]), "+f"(d[85]), "+f"(d[86]), "+f"(d[87]),
      "+f"(d[88]), "+f"(d[89]), "+f"(d[90]), "+f"(d[91]), "+f"(d[92]), "+f"(d[93]), "+f"(d[94]), "+f"(d[95])
      : "l"(da), "l"(db), "r"(sd));
  }
  static __device__ __forceinline__ void rst(float* d, const uint32_t* a, uint64_t db) {
    asm volatile("{\n.reg .pred p;\nsetp.ne.b32 p, 1, 0;\nwgmma.mma_async.sync.aligned.m64n192k16.f32.bf16.bf16 {"
      "%0, %1, %2, %3, %4, %5, %6, %7, %8, %9, %10, %11, %12, %13, %14, %15, "
      "%16, %17, %18, %19, %20, %21, %22, %23, %24, %25, %26, %27, %28, %29, %30, %31, "
      "%32, %33, %34, %35, %36, %37, %38, %39, %40, %41, %42, %43, %44, %45, %46, %47, "
      "%48, %49, %50, %51, %52, %53, %54, %55, %56, %57, %58, %59, %60, %61, %62, %63, "
      "%64, %65, %66, %67, %68, %69, %70, %71, %72, %73, %74, %75, %76, %77, %78, %79, "
      "%80, %81, %82, %83, %84, %85, %86, %87, %88, %89, %90, %91, %92, %93, %94, %95"
      "}, {%96, %97, %98, %99}, %100, p, 1, 1, 1;\n}\n"
      :
      "+f"(d[0]), "+f"(d[1]), "+f"(d[2]), "+f"(d[3]), "+f"(d[4]), "+f"(d[5]), "+f"(d[6]), "+f"(d[7]),
      "+f"(d[8]), "+f"(d[9]), "+f"(d[10]), "+f"(d[11]), "+f"(d[12]), "+f"(d[13]), "+f"(d[14]), "+f"(d[15]),
      "+f"(d[16]), "+f"(d[17]), "+f"(d[18]), "+f"(d[19]), "+f"(d[20]), "+f"(d[21]), "+f"(d[22]), "+f"(d[23]),
      "+f"(d[24]), "+f"(d[25]), "+f"(d[26]), "+f"(d[27]), "+f"(d[28]), "+f"(d[29]), "+f"(d[30]), "+f"(d[31]),
      "+f"(d[32]), "+f"(d[33]), "+f"(d[34]), "+f"(d[35]), "+f"(d[36]), "+f"(d[37]), "+f"(d[38]), "+f"(d[39]),
      "+f"(d[40]), "+f"(d[41]), "+f"(d[42]), "+f"(d[43]), "+f"(d[44]), "+f"(d[45]), "+f"(d[46]), "+f"(d[47]),
      "+f"(d[48]), "+f"(d[49]), "+f"(d[50]), "+f"(d[51]), "+f"(d[52]), "+f"(d[53]), "+f"(d[54]), "+f"(d[55]),
      "+f"(d[56]), "+f"(d[57]), "+f"(d[58]), "+f"(d[59]), "+f"(d[60]), "+f"(d[61]), "+f"(d[62]), "+f"(d[63]),
      "+f"(d[64]), "+f"(d[65]), "+f"(d[66]), "+f"(d[67]), "+f"(d[68]), "+f"(d[69]), "+f"(d[70]), "+f"(d[71]),
      "+f"(d[72]), "+f"(d[73]), "+f"(d[74]), "+f"(d[75]), "+f"(d[76]), "+f"(d[77]), "+f"(d[78]), "+f"(d[79]),
      "+f"(d[80]), "+f"(d[81]), "+f"(d[82]), "+f"(d[83]), "+f"(d[84]), "+f"(d[85]), "+f"(d[86]), "+f"(d[87]),
      "+f"(d[88]), "+f"(d[89]), "+f"(d[90]), "+f"(d[91]), "+f"(d[92]), "+f"(d[93]), "+f"(d[94]), "+f"(d[95])
      : "r"(a[0]), "r"(a[1]), "r"(a[2]), "r"(a[3]), "l"(db));
  }
};

#define REFENCE 0
#define KWT 0
#define HPC 0
#define ZSH 1
#define ZP_AT 1
#define CPRE0 1
#define ZORD 1
#define CS1BY 1
#define CS1_T 9500
#define Z1_AT -1
#define G1_AT 0
#define HGRP 3
#define HPACE 200
#define DB 0
#define HOLD_AT 33
#define LL_AT 4
#define KV_T0 2300
#define ST_YIELD 1
#define HP0 0
#define HPD 0
#define RAMP 1
#define LEAD 2
#define WSP_N 16
#define EARLY 0
#define CPIN 1
#define CW0 0
#define PFT 1
#define WSP_D 600
#define D1 4
#define D2 4
#define NSLEEP 32

static_assert(ZP_AT <= RAMP && LEAD <= 2, "staging slots");

namespace {

constexpr int kS = 2048, kD = 640, kF = 1536;
constexpr int NA = 10, NA2 = 9, NB = 5;
constexpr int A_SLOT = 8192, B_SLOT = 24576;
constexpr int OFF_A = 0;
constexpr int OFF_B = OFF_A + NA * A_SLOT;
constexpr int XB_PL = 2112;
constexpr int CV_KE = 4224, CV_KO = CV_KE + 4160;
constexpr int CV_SZ = CV_KO + 4160;
constexpr int OFF_CV = OFF_B + NB * B_SLOT;
constexpr int OFF_CS = OFF_CV + 2 * CV_SZ;
constexpr int OFF_BIAS = OFF_CS + 1536;
constexpr int OFF_XS = OFF_BIAS + 128;
constexpr int OFF_BAR = OFF_XS + 512;
constexpr int BAR_AF = OFF_BAR, BAR_ST = BAR_AF + 8 * NA, BAR_XF = BAR_ST + 16, BAR_KV = BAR_XF + 16;
constexpr int BAR_BF = OFF_BAR + 128, BAR_G2 = BAR_BF + 8 * (NB + 1), BAR_XS = BAR_G2 + 8, BAR_KU = BAR_XS + 8, BAR_ZP = BAR_KU + 40, BAR_XC = BAR_ZP + 8, BAR_WO = BAR_XC + 8;
constexpr int BAR_AE = OFF_BAR + 256, BAR_BE = BAR_AE + 8 * NA;
constexpr int BAR_YT = BAR_KU + 24;
constexpr int BAR_Z1 = BAR_ST;
constexpr int BAR_GO = BAR_XS;
constexpr int BAR_YL = BAR_KU + 16;
constexpr int OFF_TAG = OFF_CS - 32;
constexpr int SMEM_BYTES = OFF_BAR + 384;
static_assert(SMEM_BYTES <= 232448, "smem");
constexpr int NB_WGA = 1, NB_WGC = 2, NB_G1 = 3, NB_WO = 4, NB_CD = 5, NB_Z = 6, NB_WGB = 7, NB_Z2 = 8;

constexpr int CNT_Y = 1, CNT_Z1 = 3, CNT_KV = 32, CNT_WO = 36;
struct Scratch {
  uint8_t kvx[kD * 4096];
  uint8_t z2[4 * 32 * 24576];
  uint8_t h[32 * 12 * 8192];
  uint8_t wo[4 * 12 * 20480];
  uint8_t y[896 * 4096];
  uint4 xstat[kS];
  uint2 zstat[kS * 8];
  uint2 colsum[kF];
  uint32_t zcnt[4 * 32];
  uint32_t cnt[2 * 32];
  uint32_t hcnt[32 * 32];
  uint32_t epoch[136];
};
__device__ __align__(1024) Scratch g_scr;
#define ZS(i)
#define STAMP(i)
#define STAMP2(i)
#define STAMPW(i)

struct Params {
  Scratch* scr;
  int by_smid;
  const __nv_bfloat16 *k, *v, *shift, *ssmk, *ssmD, *wsp, *bsp, *wout;
  __nv_bfloat16* out;
  CUtensorMap tmX, tmW, tmWsp, tmY, tmKV;
};

__device__ __forceinline__ uint64_t mkdesc(uint32_t addr, uint32_t lbo, uint32_t sbo, uint32_t swz) {
  return (uint64_t)((addr & 0x3FFFF) >> 4) | ((uint64_t)(lbo >> 4) << 16) | ((uint64_t)(sbo >> 4) << 32) | ((uint64_t)swz << 62);
}
#define WG_FENCE() asm volatile("wgmma.fence.sync.aligned;" ::: "memory")
#define WG_COMMIT() asm volatile("wgmma.commit_group.sync.aligned;" ::: "memory")
#define WG_WAIT(n) asm volatile("wgmma.wait_group.sync.aligned %0;" ::"n"(n) : "memory")
template <int N> __device__ __forceinline__ void acc_fence(float* d) {
#pragma unroll
  for (int i = 0; i < N; i++) asm volatile("" : "+f"(d[i])::"memory");
}
__device__ __forceinline__ void mbar_init(uint32_t bar, int cnt) { asm volatile("mbarrier.init.shared::cta.b64 [%0], %1;" ::"r"(bar), "r"(cnt) : "memory"); }
__device__ __forceinline__ void mbar_expect(uint32_t bar, uint32_t bytes) { asm volatile("mbarrier.arrive.expect_tx.shared::cta.b64 _, [%0], %1;" ::"r"(bar), "r"(bytes) : "memory"); }
__device__ __forceinline__ void mbar_arrive(uint32_t bar) { asm volatile("mbarrier.arrive.shared::cta.b64 _, [%0];" ::"r"(bar) : "memory"); }
__device__ __forceinline__ void mbar_arrive_if(uint32_t bar, bool c) {
  asm volatile("{\n.reg .pred p;\nsetp.ne.u32 p, %1, 0;\n@p mbarrier.arrive.shared::cta.b64 _, [%0];\n}\n" ::"r"(bar), "r"((uint32_t)c) : "memory");
}
__device__ __forceinline__ void mbar_expect_if(uint32_t bar, uint32_t bytes, bool c) {
  asm volatile("{\n.reg .pred p;\nsetp.ne.u32 p, %2, 0;\n@p mbarrier.arrive.expect_tx.shared::cta.b64 _, [%0], %1;\n}\n" ::"r"(bar), "r"(bytes), "r"((uint32_t)c) : "memory");
}
__device__ __forceinline__ bool mbar_try(uint32_t bar, uint32_t parity) {
  uint32_t ok;
  asm volatile("{\n.reg .pred p;\nmbarrier.try_wait.parity.shared::cta.b64 p, [%1], %2;\nselp.u32 %0, 1, 0, p;\n}\n" : "=r"(ok) : "r"(bar), "r"(parity) : "memory");
  return ok;
}
__device__ __forceinline__ bool mbar_test(uint32_t bar, uint32_t parity) {
  uint32_t ok;
  asm volatile("{\n.reg .pred p;\nmbarrier.test_wait.parity.shared::cta.b64 p, [%1], %2;\nselp.u32 %0, 1, 0, p;\n}\n" : "=r"(ok) : "r"(bar), "r"(parity) : "memory");
  return ok;
}
__device__ __forceinline__ void die() { asm volatile("st.volatile.global.u32 [%0], %1;" ::"l"(0ull), "r"(0) : "memory"); }
__device__ __forceinline__ void spin_guard(uint32_t& n) { if (++n == (1u << 22)) die(); }
__device__ __forceinline__ void mbar_wait(uint32_t bar, uint32_t parity) {
  uint32_t t0 = 0;
#pragma unroll 1
  while (!mbar_try(bar, parity)) spin_guard(t0);
}
__device__ __forceinline__ void mbar_wait2(uint32_t b0, uint32_t p0, uint32_t b1, uint32_t p1) {
  uint32_t t0 = 0;
#pragma unroll 1
  while (true) {
    const bool r0 = mbar_try(b0, p0), r1 = mbar_try(b1, p1);
    if (r0 && r1) break;
    spin_guard(t0);
  }
}
__device__ __forceinline__ int tid_now() { int v; asm volatile("mov.u32 %0, %%tid.x;" : "=r"(v)); return v & 127; }
__device__ __forceinline__ bool elect_one() {
  uint32_t p;
  asm volatile("{\n.reg .pred P;\nelect.sync _|P, 0xffffffff;\nselp.u32 %0, 1, 0, P;\n}\n" : "=r"(p));
  return p;
}
__device__ __forceinline__ void bar_sync(int id, int n) { asm volatile("bar.sync %0, %1;" ::"r"(id), "r"(n) : "memory"); }
__device__ __forceinline__ void bar_arrive(int id, int n) { asm volatile("bar.arrive %0, %1;" ::"r"(id), "r"(n) : "memory"); }
__device__ __forceinline__ void fence_async_smem() { asm volatile("fence.proxy.async.shared::cta;" ::: "memory"); }
__device__ __forceinline__ void bulk_g2s(uint32_t dst, const void* src, uint32_t bytes, uint32_t bar) {
  asm volatile("cp.async.bulk.shared::cluster.global.mbarrier::complete_tx::bytes [%0], [%1], %2, [%3];" ::"r"(dst), "l"(src), "r"(bytes), "r"(bar) : "memory");
}
__device__ __forceinline__ void bulk_s2g(void* dst, uint32_t src, uint32_t bytes) {
  asm volatile("cp.async.bulk.global.shared::cta.bulk_group [%0], [%1], %2;" ::"l"(dst), "r"(src), "r"(bytes) : "memory");
}
__device__ __forceinline__ void tma2d(uint32_t dst, const CUtensorMap* m, int c0, int c1, uint32_t bar) {
  asm volatile("cp.async.bulk.tensor.2d.shared::cluster.global.mbarrier::complete_tx::bytes [%0], [%1, {%3, %4}], [%2];" ::"r"(dst), "l"(m), "r"(bar), "r"(c0), "r"(c1) : "memory");
}
__device__ __forceinline__ void tma3d(uint32_t dst, const CUtensorMap* m, int c0, int c1, int c2, uint32_t bar) {
  asm volatile("cp.async.bulk.tensor.3d.shared::cluster.global.mbarrier::complete_tx::bytes [%0], [%1, {%3, %4, %5}], [%2];" ::"r"(dst), "l"(m), "r"(bar), "r"(c0), "r"(c1), "r"(c2) : "memory");
}
__device__ __forceinline__ void tma_rows(uint32_t dst, const CUtensorMap* m, int c0, int rb, uint32_t bar) { tma3d(dst, m, c0, rb * 16, 0, bar); }
__device__ __forceinline__ uint4 ld_ll4(const void* p) {
  uint64_t a, b;
  asm volatile("ld.relaxed.gpu.global.v2.u64 {%0,%1}, [%2];" : "=l"(a), "=l"(b) : "l"(p) : "memory");
  return make_uint4((uint32_t)a, (uint32_t)(a >> 32), (uint32_t)b, (uint32_t)(b >> 32));
}
__device__ __forceinline__ void st_ll4(void* p, uint32_t a, uint32_t b, uint32_t c, uint32_t d) {
  asm volatile("st.relaxed.gpu.global.v2.u64 [%0], {%1,%2};" ::"l"(p), "l"(a | ((uint64_t)b << 32)), "l"(c | ((uint64_t)d << 32)) : "memory");
}
__device__ __forceinline__ void st_ll2(void* p, uint32_t a, uint32_t b) { asm volatile("st.relaxed.gpu.global.u64 [%0], %1;" ::"l"(p), "l"(a | ((uint64_t)b << 32)) : "memory"); }
__device__ __forceinline__ uint2 ld_ll2(const void* p) {
  uint64_t a;
  asm volatile("ld.relaxed.gpu.global.u64 %0, [%1];" : "=l"(a) : "l"(p) : "memory");
  return make_uint2((uint32_t)a, (uint32_t)(a >> 32));
}
__device__ __forceinline__ void wgmma_colsum(float* d, uint64_t da, uint64_t db) {
  asm volatile("{\n.reg .pred p;\nsetp.ne.b32 p, 1, 0;\nwgmma.mma_async.sync.aligned.m64n8k16.f32.bf16.bf16 {%0, %1, %2, %3}, %4, %5, p, 1, 1, 1, 0;\n}\n"
               : "+f"(d[0]), "+f"(d[1]), "+f"(d[2]), "+f"(d[3]) : "l"(da), "l"(db));
}
__device__ __forceinline__ void prefetch_l2(const void* p) { asm volatile("prefetch.global.L2 [%0];" ::"l"(p)); }
__device__ __forceinline__ void pace(uint32_t& t, uint32_t dt) {
  t += dt;
  while ((int32_t)((uint32_t)clock() - t) < 0) { if (NSLEEP) __nanosleep(NSLEEP); }
}
__device__ __forceinline__ void red_relaxed(uint32_t* p) { asm volatile("red.relaxed.gpu.global.add.u32 [%0], 1;" ::"l"(p) : "memory"); }
__device__ __forceinline__ void red_release(uint32_t* p) { asm volatile("red.release.gpu.global.add.u32 [%0], 1;" ::"l"(p) : "memory"); }
__device__ __forceinline__ uint4 ldg4(const void* p) { uint4 v; asm volatile("ld.global.v4.u32 {%0,%1,%2,%3}, [%4];" : "=r"(v.x), "=r"(v.y), "=r"(v.z), "=r"(v.w) : "l"(p) : "memory"); return v; }
__device__ __forceinline__ uint32_t ldg1(const void* p) { uint32_t v; asm volatile("ld.global.u32 %0, [%1];" : "=r"(v) : "l"(p) : "memory"); return v; }
__device__ __forceinline__ void stg4_if(void* p, uint32_t a, uint32_t b, uint32_t c, uint32_t d, bool on) {
  asm volatile("{\n.reg .pred p;\nsetp.ne.u32 p, %5, 0;\n@p st.global.v4.u32 [%0], {%1,%2,%3,%4};\n}\n" ::"l"(p), "r"(a), "r"(b), "r"(c), "r"(d), "r"((uint32_t)on) : "memory");
}
template <int OFF> __device__ __forceinline__ uint32_t lds32(uint32_t a) { uint32_t v; asm volatile("ld.shared.u32 %0, [%1+%2];" : "=r"(v) : "r"(a), "n"(OFF)); return v; }
__device__ __forceinline__ uint4 lds128(uint32_t a) { uint4 v; asm volatile("ld.shared.v4.u32 {%0,%1,%2,%3}, [%4];" : "=r"(v.x), "=r"(v.y), "=r"(v.z), "=r"(v.w) : "r"(a) : "memory"); return v; }
__device__ __forceinline__ float2 lds64f(uint32_t a) { float2 v; asm volatile("ld.shared.v2.f32 {%0,%1}, [%2];" : "=f"(v.x), "=f"(v.y) : "r"(a) : "memory"); return v; }
__device__ __forceinline__ void sts64f(uint32_t a, float x, float y) { asm volatile("st.shared.v2.f32 [%0], {%1,%2};" ::"r"(a), "f"(x), "f"(y) : "memory"); }
__device__ __forceinline__ void sts32(uint32_t a, uint32_t x) { asm volatile("st.shared.u32 [%0], %1;" ::"r"(a), "r"(x) : "memory"); }
__device__ __forceinline__ void sts128(uint32_t a, uint32_t x, uint32_t y, uint32_t z, uint32_t w) { asm volatile("st.shared.v4.u32 [%0], {%1,%2,%3,%4};" ::"r"(a), "r"(x), "r"(y), "r"(z), "r"(w) : "memory"); }
__device__ __forceinline__ void stsm4(uint32_t a, uint32_t r0, uint32_t r1, uint32_t r2, uint32_t r3) {
  asm volatile("stmatrix.sync.aligned.m8n8.x4.shared.b16 [%0], {%1,%2,%3,%4};" ::"r"(a), "r"(r0), "r"(r1), "r"(r2), "r"(r3) : "memory");
}
__device__ __forceinline__ void stsm4t(uint32_t a, uint32_t r0, uint32_t r1, uint32_t r2, uint32_t r3) {
  asm volatile("stmatrix.sync.aligned.m8n8.x4.trans.shared.b16 [%0], {%1,%2,%3,%4};" ::"r"(a), "r"(r0), "r"(r1), "r"(r2), "r"(r3) : "memory");
}
__device__ __forceinline__ void ldsm4t(uint32_t* r, uint32_t a) {
  asm volatile("ldmatrix.sync.aligned.m8n8.x4.trans.shared.b16 {%0,%1,%2,%3}, [%4];" : "=r"(r[0]), "=r"(r[1]), "=r"(r[2]), "=r"(r[3]) : "r"(a) : "memory");
}
__device__ __forceinline__ uint32_t pack2(float lo, float hi) { uint32_t r; asm("cvt.rn.bf16x2.f32 %0, %1, %2;" : "=r"(r) : "f"(hi), "f"(lo)); return r; }
__device__ __forceinline__ float bf_lo(uint32_t u) { return __uint_as_float(u << 16); }
__device__ __forceinline__ float bf_hi(uint32_t u) { return __uint_as_float(u & 0xffff0000u); }
__device__ __forceinline__ float tanh_fast(float x) { float y; asm("tanh.approx.f32 %0, %1;" : "=f"(y) : "f"(x)); return y; }
__device__ __forceinline__ uint32_t hmul2(uint32_t a, uint32_t b) { uint32_t r; asm("mul.rn.bf16x2 %0, %1, %2;" : "=r"(r) : "r"(a), "r"(b)); return r; }
__device__ __forceinline__ uint32_t hfma2(uint32_t a, uint32_t b, uint32_t c) { uint32_t r; asm("fma.rn.bf16x2 %0, %1, %2, %3;" : "=r"(r) : "r"(a), "r"(b), "r"(c)); return r; }
__device__ __forceinline__ uint32_t prmt(uint32_t a, uint32_t b, uint32_t s) { return __byte_perm(a, b, s); }

__device__ __forceinline__ uint32_t ld_relaxed(const uint32_t* p) { uint32_t v; asm volatile("ld.relaxed.gpu.global.u32 %0, [%1];" : "=r"(v) : "l"(p) : "memory"); return v; }
__device__ __forceinline__ void acquire_fence() { asm volatile("fence.acquire.gpu;\nfence.proxy.async.global;" ::: "memory"); }
__device__ __forceinline__ uint32_t load_epoch(const Params& p, int idx, int lane) { return ld_relaxed(&p.scr->epoch[idx + (((lane * lane) & 3) == 2 ? 1 : 0)]); }
__device__ __forceinline__ void poll_counter(const uint32_t* cnt, uint32_t target) {
  uint32_t t0 = 0;
#pragma unroll 1
  while (!__all_sync(0xffffffff, ld_relaxed(cnt) == target)) spin_guard(t0);
  acquire_fence();
}

__device__ __forceinline__ int g3_block(int cb, int it) { return it < 3 ? cb * 3 + it : (it - 3 < cb * 3 ? it - 3 : it); }

template <int N, bool A_SWZ, int B_MODE, int DEPTH, class Hook, class Mid>
__device__ __forceinline__ void gemm_loop(float* d, uint32_t sb, int nkb, int sa, int pa, int b0, uint32_t boff, int relA, int relB, int tid, Hook hook, Mid mid) {
  constexpr uint32_t A_STEP = A_SWZ ? 2 : 128;
  constexpr uint32_t B_STEP = B_MODE == 0 ? 128 : (B_MODE == 1 ? 384 : 320);
  const uint64_t da0 = A_SWZ ? mkdesc(sb + OFF_A, 16, 1024, 1) : mkdesc(sb + OFF_A, 1024, 128, 0);
  const uint64_t db0 = B_MODE == 0 ? mkdesc(sb + OFF_B + boff, 8192, 1024, 1) : mkdesc(sb + OFF_B + boff, B_MODE == 1 ? 3072 : 2560, 128, 0);
  constexpr int MODA = B_MODE == 0 ? NA : NA2;
  constexpr int MODB = B_MODE == 2 ? 6 : NB;
  int sbk = b0 % MODB, pb = (b0 / MODB) & 1;
  auto boffs = [](int s_) { return B_MODE == 2 ? (s_ == 5 ? 0 : s_ + 1) * (20480 >> 4) : s_ * (B_SLOT >> 4); };
  uint32_t rel = 0;
  uint64_t da = da0 + sa * (A_SLOT >> 4), db = db0 + boffs(sbk);
  const bool doR = tid < 2 ? tid < relA : tid - 2 < relB;
  mbar_wait2(sb + BAR_AF + 8 * sa, pa, sb + BAR_BF + 8 * sbk, pb);
  if constexpr (DEPTH == 0) {
    acc_fence<N / 2>(d);
#pragma unroll 1
    for (int it = 0; it < nkb; it++) {
      WG_FENCE();
#pragma unroll
      for (int j = 0; j < 4; j++) WG<N>::ss(d, da + j * A_STEP, db + j * B_STEP, 1);
      WG_COMMIT();
      const uint32_t prel = rel;
      rel = sb + BAR_AE + 8 * (tid < 2 ? sa : sbk + NA);
      if (++sa == MODA) { sa = 0; pa ^= 1; }
      if (++sbk == MODB) { sbk = 0; pb ^= 1; }
      da = da0 + sa * (A_SLOT >> 4); db = db0 + boffs(sbk);
      const bool r0 = mbar_test(sb + BAR_AF + 8 * sa, pa), r1 = mbar_test(sb + BAR_BF + 8 * sbk, pb);
      WG_WAIT(1);
      mbar_arrive_if(prel, doR && prel != 0);
      if (it == 2) {
        WG_WAIT(0);
        mbar_expect_if(sb + BAR_AF + 8 * (tid == 8 ? 8 : tid), A_SLOT, tid < 9);
        mbar_arrive_if(rel, doR);
        rel = 0;
      }
      mid(it);
      if (it + 1 < nkb && !(r0 && r1)) {
        mbar_wait2(sb + BAR_AF + 8 * sa, pa, sb + BAR_BF + 8 * sbk, pb);
      }
    }
  } else
#pragma unroll 1
  for (int it = 0; it < nkb; it++) {
    WG_FENCE();
    WG<N>::ss(d, da, db, 1);
    const uint32_t prel = rel;
    rel = sb + BAR_AE + 8 * (tid < 2 ? sa : sbk + NA);
    if (++sa == MODA) { sa = 0; if (B_MODE) pa ^= 1; }
    if (++sbk == MODB) { sbk = 0; pb ^= 1; }
    if (DEPTH == 1) { WG_COMMIT(); WG_WAIT(1); }
    WG<N>::ss(d, da + A_STEP, db + B_STEP, 1);
    WG_COMMIT();
    WG_WAIT(1);
    if (EARLY == 1) mbar_arrive_if(prel, doR && it != 0);
    WG<N>::ss(d, da + 2 * A_STEP, db + 2 * B_STEP, 1);
    if (DEPTH == 1) WG_COMMIT();
    if (EARLY != 1) mbar_arrive_if(prel, doR && it != 0);
    const bool r0 = mbar_test(sb + BAR_AF + 8 * sa, pa), r1 = mbar_test(sb + BAR_BF + 8 * sbk, pb);
    const uint64_t da3 = da + 3 * A_STEP, db3 = db + 3 * B_STEP;
    da = da0 + sa * (A_SLOT >> 4); db = db0 + boffs(sbk);
    if (DEPTH == 1) WG_WAIT(1);
    WG<N>::ss(d, da3, db3, 1);
    WG_COMMIT();
    mid(it);
    if (it + 1 < nkb) {
      if (!(r0 && r1)) {
        mbar_wait2(sb + BAR_AF + 8 * sa, pa, sb + BAR_BF + 8 * sbk, pb);
      }
    }
    if (DEPTH == 2) WG_WAIT(1);
  }
  hook();
  WG_WAIT(0);
  acc_fence<N / 2>(d);
  mbar_arrive_if(rel, doR);
}

__device__ __forceinline__ void fold_mean(float* d, uint32_t cs, float ma, float mb, int t) {
  const uint32_t ha = pack2(-ma, -ma), hb = pack2(-mb, -mb);
  const float la = -ma - bf_lo(ha), lb = -mb - bf_lo(hb);
  const uint32_t a[4] = {t ? 0u : ha, t ? 0u : hb, t ? 0u : pack2(la, la), t ? 0u : pack2(lb, lb)};
  WG_FENCE();
  WG<192>::rst(d, a, mkdesc(cs, 0, 32, 0));
  WG_COMMIT();
}
__device__ __forceinline__ void gelu_tile(const float* d, uint32_t* z, float* st, float ra, float rb) {
  const float kA = 0.7978845608028654f, kB = 0.7978845608028654f * 0.044715f;
  const float c1a = kA * ra, c3a = kB * ra * ra * ra, c1b = kA * rb, c3b = kB * rb * rb * rb;
  float acc[8];
#pragma unroll
  for (int i = 0; i < 8; i++) acc[i] = 0.f;
#pragma unroll
  for (int j = 0; j < 24; j++) {
    float r[4];
#pragma unroll
    for (int e = 0; e < 4; e++) {
      const float v = d[4 * j + e];
      const float a = v * fmaf(v * v, e < 2 ? c3a : c3b, e < 2 ? c1a : c1b);
      r[e] = fmaf(v, tanh_fast(a), v);
      acc[e] += r[e];
      acc[4 + e] = fmaf(r[e], r[e], acc[4 + e]);
    }
    z[2 * j] = pack2(r[0], r[1]);
    z[2 * j + 1] = pack2(r[2], r[3]);
  }
  st[0] = acc[0] + acc[1]; st[1] = acc[4] + acc[5]; st[2] = acc[2] + acc[3]; st[3] = acc[6] + acc[7];
}

template <int Q> __device__ __forceinline__ void conv_load(uint32_t* a, uint32_t ab) {
  a[0] = lds32<512 * Q>(ab);       a[1] = lds32<512 * Q + 256>(ab);  a[2] = lds32<512 * Q + 16>(ab);   a[3] = lds32<512 * Q + 272>(ab);
  a[4] = lds32<512 * Q + 32>(ab);  a[5] = lds32<512 * Q + 288>(ab);  a[6] = lds32<512 * Q + 48>(ab);   a[7] = lds32<512 * Q + 304>(ab);
  a[8] = lds32<512 * Q + 64>(ab);  a[9] = lds32<512 * Q + 320>(ab);  a[10] = lds32<512 * Q + 80>(ab);  a[11] = lds32<512 * Q + 336>(ab);
  a[12] = lds32<512 * Q + 96>(ab); a[13] = lds32<512 * Q + 352>(ab); a[14] = lds32<512 * Q + 112>(ab); a[15] = lds32<512 * Q + 368>(ab);
}
template <int Q, int L> __device__ __forceinline__ void conv_step(float* d, uint32_t (*a)[16], uint32_t ab, uint64_t db) {
  WG_FENCE();
#pragma unroll
  for (int s = 0; s < 4; s++) WG<128 - 16 * Q>::rs(d, a[Q] + 4 * s, db + s + 16 * Q);
  WG_COMMIT();
  if (CPIN) WG_WAIT(1);
  if (L >= 0) conv_load<(L >= 0 ? L : 0)>(a[L >= 0 ? L : 0], ab);
  if (CW0 || Q == 0) WG_WAIT(0);
}

__device__ __forceinline__ int seg_col(int cb, int h) { return (cb >> 1) * 320 + (cb & 1) * 32 + h * 64; }
__device__ __forceinline__ void final_load_x(uint32_t (*xw)[10], uint32_t xt, int cb, int h, int w, int lane) {
  const int g = lane >> 2, t = lane & 3, cc = seg_col(cb, h) >> 3;
  const int c0 = cc + t, c1 = c0 + 24, c2 = cc + 16 - 6 * h + (t >> 1);
  const uint32_t r0 = xt + (w * 16 + g) * 128;
#pragma unroll
  for (int r = 0; r < 2; r++) {
    const uint4 u = lds128(r0 + r * 1024 + (c0 >> 3) * A_SLOT + (((c0 ^ g) & 7) << 4)), v = lds128(r0 + r * 1024 + (c1 >> 3) * A_SLOT + (((c1 ^ g) & 7) << 4));
    const float2 z = lds64f(r0 + r * 1024 + (c2 >> 3) * A_SLOT + (((c2 ^ g) & 7) << 4) + (t & 1) * 8);
    xw[r][0] = u.x; xw[r][1] = u.y; xw[r][2] = u.z; xw[r][3] = u.w;
    xw[r][4] = v.x; xw[r][5] = v.y; xw[r][6] = v.z; xw[r][7] = v.w;
    xw[r][8] = __float_as_uint(z.x); xw[r][9] = __float_as_uint(z.y);
  }
}
__device__ __forceinline__ void final_s_early(uint32_t (*sw)[10], const uint32_t (*xw)[10], uint32_t ya, float2 s0, float2 s1) {
  const uint32_t r2[2] = {pack2(s0.y, s0.y), pack2(s1.y, s1.y)};
  const float na = -s0.x * bf_lo(r2[0]), nb = -s1.x * bf_lo(r2[1]);
  const uint32_t n2[2] = {pack2(na, na), pack2(nb, nb)};
#pragma unroll
  for (int j = 0; j < 10; j += 2) {
    uint32_t y[4];
    if (j < 4 || j == 8) ldsm4t(y, ya + (j < 4 ? j : 4) * 1024);
#pragma unroll
    for (int e = 0; e < 4; e++) {
      const uint32_t xn = hfma2(xw[e & 1][j + (e >> 1)], r2[e & 1], n2[e & 1]);
      sw[e & 1][j + (e >> 1)] = (j < 4 || j == 8) ? hmul2(xn, y[e]) : xn;
    }
  }
}
__device__ __forceinline__ bool final_late(uint32_t* y, uint32_t ya) {
  ldsm4t(y, ya + 6144);
  ldsm4t(y + 4, ya + 8192);
  uint32_t zero = 0;
#pragma unroll
  for (int e = 0; e < 8; e++) zero |= (y[e] - 0x00010001u) & ~y[e];
  return (zero & 0x80008000u) == 0;
}
__device__ __forceinline__ bool bar_all(int id, int n, bool c) {
  uint32_t r;
  asm volatile("{\n.reg .pred p, q;\nsetp.ne.u32 p, %3, 0;\nbar.red.and.pred q, %1, %2, p;\nselp.u32 %0, 1, 0, q;\n}\n" : "=r"(r) : "r"(id), "r"(n), "r"((uint32_t)c) : "memory");
  return r;
}
__device__ __forceinline__ void final_out(const float* d, const uint32_t (*xw)[10], const uint32_t (*sw)[10], float ra, float rb, __nv_bfloat16* o0, int h, int t) {
  const float ca = 0.25f * ra, cb = 0.25f * rb;
  uint32_t o[2][10];
#pragma unroll
  for (int j = 0; j < 10; j++) {
#pragma unroll
    for (int r = 0; r < 2; r++) {
      const float h0 = d[4 * j + 2 * r] * (r ? cb : ca), h1 = d[4 * j + 2 * r + 1] * (r ? cb : ca);
      o[r][j] = hfma2(pack2(fmaf(h0, tanh_fast(h0), h0), fmaf(h1, tanh_fast(h1), h1)), sw[r][j], xw[r][j]);
      __nv_bfloat16* q = o0 + r * 8 * kD;
      if (j == 3) stg4_if(q + t * 8, o[r][0], o[r][1], o[r][2], o[r][3], true);
      if (j == 7) stg4_if(q + 192 + t * 8, o[r][4], o[r][5], o[r][6], o[r][7], true);
      if (j == 9) asm volatile("st.global.v2.u32 [%0], {%1,%2};" ::"l"(q + 128 - 48 * h + t * 4), "r"(o[r][8]), "r"(o[r][9]) : "memory");
    }
  }
}

struct Taps { uint4 r0, r1; uint32_t n0, n1, dd; };
__device__ __forceinline__ void load_taps(Taps& k, const Params& p, int ch, int tid) {
  const uint4* kp = (const uint4*)(p.ssmk + (size_t)ch * kS);
  k.r0 = ldg4(kp + tid); k.r1 = ldg4(kp + 128 + tid);
  k.n0 = ldg1(kp + tid + 1); k.n1 = tid < 127 ? ldg1(kp + 129 + tid) : 0u;
  k.dd = __bfloat16_as_ushort(p.ssmD[ch]);
}
__device__ __forceinline__ void load_convx(const Params& p, uint32_t cv, uint32_t bar, int ch) {
  mbar_expect(bar, 4096);
  bulk_g2s(cv, p.scr->kvx + (size_t)ch * 4096, 2048, bar);
  bulk_g2s(cv + XB_PL, p.scr->kvx + (size_t)ch * 4096 + 2048, 2048, bar);
}
#define CW 3
#define CSTAMP(j)
__device__ __forceinline__ void zero_pads(uint32_t cv, int lane) {
  if (lane < 8) sts128(cv + (lane >> 2) * XB_PL + 2048 + (lane & 3) * 16, 0, 0, 0, 0);
  else if (lane < 12) sts128(cv + ((lane & 2) ? CV_KO : CV_KE) + (lane & 1) * 16, 0, 0, 0, 0);
  fence_async_smem();
  __syncwarp();
}
__device__ __forceinline__ int y_row(int c, uint32_t par) {
  const int hf = c >= 320, cc = c - hf * 320, u = cc >> 6, cb = hf * 2 + ((cc >> 5) & 1);
  if (u == 2) return cb * 96 + ((cc >> 4) & 1) * 48 + 32 + (cc & 1) + ((cc >> 1) & 1) * 8 + ((cc >> 2) & 3) * 2;
  return (u < 2 ? cb * 96 + u * 48 : 384 + par * 256 + cb * 64 + (u - 3) * 32) + (cc & 1) + ((cc >> 1) & 3) * 8 + ((cc >> 3) & 3) * 2;
}
__device__ __forceinline__ void z_store(const Params& p, uint32_t src, int rb, int cb, int q) {
  uint8_t* dst = p.scr->z2 + (size_t)(cb * 32 + q * 16 + (rb >> 2)) * B_SLOT + (rb & 3) * 6144;
  bulk_s2g(dst, src + q * 12288, 6144);
  bulk_s2g(dst + 8 * B_SLOT, src + q * 12288 + 6144, 6144);
  asm volatile("cp.async.bulk.commit_group;\ncp.async.bulk.wait_group 0;" ::: "memory");
}
__device__ __forceinline__ void y_store(const Params& p, uint32_t sb, int h, int ch, uint32_t par) {
  uint8_t* dst = p.scr->y + (size_t)y_row(ch, par) * 4096;
  if (elect_one()) {
    bulk_s2g(dst, sb + OFF_A + 9 * A_SLOT + h * 4096, 4096);
    asm volatile("cp.async.bulk.commit_group;\ncp.async.bulk.wait_group 0;" ::: "memory");
  }
  __syncwarp();
}
__device__ __forceinline__ void conv_service(const Params& p, uint32_t sb, int h, int ch, bool first) {
  bar_sync(NB_WGA + 8 + h, 160);
  const bool now = !first || __all_sync(0xffffffff, mbar_test(sb + BAR_KV, 0));
  if (now) { if (REFENCE & 4) acquire_fence(); if (elect_one()) load_convx(p, sb + OFF_CV + (1 - h) * CV_SZ, sb + BAR_XF + 8 * h, ch + 128); }
  bar_sync(NB_WGA + 8 + h, 160);
  y_store(p, sb, h, ch, 0);
  if (!now) {
    mbar_wait(sb + BAR_KV, 0);
    if (REFENCE & 4) acquire_fence();
    if (elect_one()) load_convx(p, sb + OFF_CV + (1 - h) * CV_SZ, sb + BAR_XF + 8 * h, ch + 128);
  }
}
__device__ __forceinline__ uint32_t y_tile(int h) { return OFF_CV + (1 - h) * 13312; }
__device__ __forceinline__ void load_late_y(const Params& p, uint32_t sb, int h, int rb, int cb, uint32_t par) {
  mbar_expect(sb + BAR_YL + 16 * h, 4096);
  tma2d(sb + y_tile(h) + 6144, &p.tmY, rb * 64, 384 + par * 256 + cb * 64 + h * 32, sb + BAR_YL + 16 * h);
  tma2d(sb + y_tile(h) + 8192, &p.tmY, rb * 64, 400 + par * 256 + cb * 64 + h * 32, sb + BAR_YL + 16 * h);
}
__device__ __forceinline__ void held_service(const Params& p, uint32_t sb, int h, int ch, int rb, int cb, uint32_t tag, int lane) {
#pragma unroll 1
  for (int i = 0; i < 8; i++) sts128(sb + OFF_A + 9 * A_SLOT + h * 4096 + i * 512 + lane * 16, 0, 0, 0, 0);
  fence_async_smem();
  __syncwarp();
  y_store(p, sb, h, ch, ~tag & 1);
  mbar_wait(sb + BAR_YT, 1);
  if (REFENCE & 4) acquire_fence();
  bar_sync(NB_WGA + 8 + h, 160);
  bar_sync(NB_WGA + 8 + h, 160);
  uint8_t* dst = p.scr->y + (size_t)y_row(ch, tag & 1) * 4096;
  if (elect_one()) {
    bulk_s2g(dst, sb + OFF_A + 9 * A_SLOT + h * 4096, 4096);
    asm volatile("cp.async.bulk.commit_group;" ::: "memory");
    mbar_expect(sb + BAR_XF + 8 * h, 6144);
#pragma unroll 1
    for (int i = 0; i < 3; i++) tma2d(sb + y_tile(h) + i * 2048, &p.tmY, rb * 64, cb * 96 + h * 48 + i * 16, sb + BAR_XF + 8 * h);
  }
  mbar_wait(sb + BAR_AE + 8 * (LL_AT - 1), 1);
  if (elect_one()) { load_late_y(p, sb, h, rb, cb, tag & 1); asm volatile("cp.async.bulk.wait_group 0;" ::: "memory"); }
}
__device__ __forceinline__ void conv_worker(const Params& p, Taps& k, uint32_t cv, uint32_t yb0,
                                            uint32_t xbar, int nbar, int ch0, int n, uint32_t holdbar, int w, int lane,
                                            int tid, int st0, int rb, int cb) {
  const int g = lane >> 2, t = lane & 3, w0 = w & 1, w1 = w >> 1;
  const uint32_t ab = cv + ((g & 1) ? CV_KE : CV_KO) + 32 + 2 * (64 * w0 + 8 * w1 + ((g - 15) & ~1) + 2 * t);
  const uint32_t scA = cv + (w1 ? CV_KO : CV_KE) + 32, scB = scA + 2048;
  const int dl = (t >> 1) ^ 1;
  if (n == 2 || CPRE0 == 2) mbar_wait(xbar, 0);
  STAMPW(st0 + 3);
#pragma unroll 1
  for (int i = 0; i < n; i++) {
    if (tid == 0) {
      k.r0.x = (k.r0.x & 0xffff0000u) | (pack2(bf_lo(k.r0.x) + bf_lo(k.dd), 0.f) & 0xffffu);
      sts32(cv + CV_KO + 28, k.r0.x << 16);
    }
    sts128(cv + CV_KE + 32 + tid * 16, k.r0.x, k.r0.y, k.r0.z, k.r0.w);
    sts128(cv + CV_KO + 32 + tid * 16, prmt(k.r0.x, k.r0.y, 0x5432), prmt(k.r0.y, k.r0.z, 0x5432), prmt(k.r0.z, k.r0.w, 0x5432), prmt(k.r0.w, k.n0, 0x5432));
    sts128(cv + CV_KE + 2080 + tid * 16, k.r1.x, k.r1.y, k.r1.z, k.r1.w);
    sts128(cv + CV_KO + 2080 + tid * 16, prmt(k.r1.x, k.r1.y, 0x5432), prmt(k.r1.y, k.r1.z, 0x5432), prmt(k.r1.z, k.r1.w, 0x5432), prmt(k.r1.w, k.n1, 0x5432));
    if (i + 1 < n) load_taps(k, p, ch0 + (i + 1) * 128, tid);
    bar_sync(nbar, 128);
    CSTAMP(0);
    const uint64_t db = mkdesc(cv + (i & 0x1000), XB_PL, 128, 0);
    float d[64];
    uint32_t a[8][16];
    if (CPRE0 == 1 && i == 0) mbar_wait(xbar, 0);
    conv_load<7>(a[7], ab); conv_load<6>(a[6], ab); conv_load<5>(a[5], ab); conv_load<4>(a[4], ab);
#pragma unroll
    for (int j = 0; j < 64; j++) d[j] = 0.f;
    mbar_wait(xbar, i & 1);
    if (i + 1 == n) mbar_wait(holdbar, 1);
    CSTAMP(1);
    conv_step<7, -1>(d, a, ab, db); conv_step<6, -1>(d, a, ab, db); conv_step<5, -1>(d, a, ab, db); conv_step<4, 3>(d, a, ab, db);
    conv_step<3, 2>(d, a, ab, db);
    conv_step<2, 1>(d, a, ab, db);
    conv_step<1, 0>(d, a, ab, db);
    conv_step<0, -1>(d, a, ab, db);
    acc_fence<64>(d);
    CSTAMP(2);
    bar_sync(nbar + 8, 160);
    float E[16][2];
#pragma unroll
    for (int j = 0; j < 15; j++) { E[j][0] = d[4 * j] + d[4 * j + 6]; E[j][1] = d[4 * j + 1] + d[4 * j + 7]; }
    E[15][0] = d[60]; E[15][1] = d[61];
    if (w0 == 0) {
#pragma unroll
      for (int j = 8; j < 16; j++) sts64f(scA + (j - 8) * 256 + lane * 8, E[j][0], E[j][1]);
    } else {
      const uint32_t a = scB - dl * 256 + (lane ^ 2) * 8;
#pragma unroll
      for (int j = 1; j < 8; j++) sts64f(a + j * 256, E[j][0], E[j][1]);
      sts64f(scB + (dl ? 7 * 256 : 0) + (lane ^ 2) * 8, dl ? E[8][0] : E[0][0], dl ? E[8][1] : E[0][1]);
    }
    bar_sync(nbar, 128);
    CSTAMP(3);
    uint32_t pk[8];
    if (w0 == 0) {
#pragma unroll
      for (int j = 0; j < 8; j++) { const float2 v = lds64f(scB + j * 256 + lane * 8); pk[j] = pack2(E[j][0] + v.x, E[j][1] + v.y); }
    } else {
      const uint32_t a0 = scA - dl * 256 + (lane ^ 2) * 8;
#pragma unroll
      for (int j = 9; j < 16; j++) { const float2 v = lds64f(a0 + (j - 8) * 256); pk[j - 8] = pack2(E[j][0] + v.x, E[j][1] + v.y); }
      const float2 v = lds64f(scA + (dl ? 7 * 256 : 0) + (lane ^ 2) * 8);
      pk[0] = pack2((dl ? 0.f : E[8][0]) + v.x, (dl ? 0.f : E[8][1]) + v.y);
    }
    CSTAMP(4);
    if (i + 1 == n) {
#pragma unroll
      for (int j = 0; j < 8; j++) pk[j] = ~pk[j];
    }
    const int c1 = (w0 ? 35 : 95) - lane, c0 = (w0 && lane < 4) ? c1 - 32 : c1 + 32;
    stsm4t(yb0 + 128 * (c0 & 31) + (((2 * (c0 >> 5) + w1) ^ (c0 & 7)) << 4), pk[0], pk[1], pk[2], pk[3]);
    stsm4t(yb0 + 128 * (c1 & 31) + (((2 * (c1 >> 5) + w1) ^ (c1 & 7)) << 4), pk[4], pk[5], pk[6], pk[7]);
    fence_async_smem();
    bar_sync(nbar + 8, 160);
    CSTAMP(5);
    STAMPW(st0 + i);
    if (n == 2 && i == 0) {
      const int u = (tid >> 3) % 5, kg = rb * 3 + (tid < 120 ? (tid >> 3) / 5 : 0), c = u < 4 ? (u >> 1) * 10 + (u & 1) * 4 : 8, o2 = u < 4 ? 2 : 10;
      const uint4* wp = (const uint4*)p.wout + (uint32_t)((kg * 8 + (tid & 7)) * (kD / 8) + (seg_col(cb, 0) >> 3) + (u < 4 ? (u >> 1) * 8 + (u & 1) * 24 : 16));
      const uint4 w0 = ldg4(wp), w1 = ldg4(wp + 1), w2 = ldg4(wp + 2), w3 = ldg4(wp + 3);
      uint8_t* dst = p.scr->wo + (uint32_t)(cb * (12 * 20480) + kg * 2560 + c * 128 + (tid & 7) * 16);
      const bool f = u < 4, on = tid < 120;
      stg4_if(dst, w0.x, f ? w1.x : w0.z, f ? w2.x : w1.x, f ? w3.x : w1.z, on);
      stg4_if(dst + 128, w0.y, f ? w1.y : w0.w, f ? w2.y : w1.y, f ? w3.y : w1.w, on);
      stg4_if(dst + o2 * 128, f ? w0.z : w2.x, f ? w1.z : w2.z, f ? w2.z : w3.x, w3.z, on);
      stg4_if(dst + o2 * 128 + 128, f ? w0.w : w2.y, f ? w1.w : w2.w, f ? w2.w : w3.y, w3.w, on);
      bar_arrive(NB_WO, 160);
    }
  }
}

struct KvRegs { uint32_t k[11], v[8]; uint4 sh; };
__device__ __forceinline__ void kv_load(KvRegs& q, const __nv_bfloat16* kp, const __nv_bfloat16* vp, const __nv_bfloat16* sp, bool halo) {
#pragma unroll
  for (int i = 0; i < 11; i++) q.k[i] = (i >= 3 || halo) ? ldg1(kp + i * kD) : 0u;
#pragma unroll
  for (int i = 0; i < 8; i++) q.v[i] = ldg1(vp + i * kD);
  q.sh = ldg4(sp);
}
__device__ __forceinline__ void kv_unit(const KvRegs& q, uint32_t oa) {
  const uint32_t w0 = prmt(q.sh.x, q.sh.z, 0x5410), w1 = prmt(q.sh.x, q.sh.z, 0x7632), w2 = prmt(q.sh.y, q.sh.w, 0x5410), w3 = prmt(q.sh.y, q.sh.w, 0x7632);
  uint32_t r[8];
#pragma unroll
  for (int i = 0; i < 8; i++) r[i] = hmul2(hfma2(q.k[i + 3], w0, hfma2(q.k[i + 2], w1, hfma2(q.k[i + 1], w2, hmul2(q.k[i], w3)))), q.v[i]);
  sts128(oa, prmt(r[7], r[6], 0x5410), prmt(r[5], r[4], 0x5410), prmt(r[3], r[2], 0x5410), prmt(r[1], r[0], 0x5410));
  sts128(oa + 2048, prmt(r[7], r[6], 0x7632), prmt(r[5], r[4], 0x7632), prmt(r[3], r[2], 0x7632), prmt(r[1], r[0], 0x7632));
}

__device__ __forceinline__ void gather_colsum(const Params& p, uint32_t sb, int cb, int part, uint32_t tag, int lane) {
  uint4 v[3];
  uint32_t t0 = 0;
#pragma unroll 1
  while (true) {
    bool ok = true;
#pragma unroll
    for (int i = 0; i < 3; i++) {
      v[i] = ld_ll4(&p.scr->colsum[(part ? 0 : 768) + cb * 192 + i * 64 + lane * 2]);
      ok = ok && v[i].y == tag && v[i].w == tag;
    }
    if (__all_sync(0xffffffff, ok)) break;
    spin_guard(t0);
  }
#pragma unroll
  for (int i = 0; i < 3; i++) {
    const uint32_t hi = pack2(__uint_as_float(v[i].x), __uint_as_float(v[i].z)), ca = sb + OFF_CS + (1 - part) * 768 + i * 256 + (lane >> 2) * 32 + (lane & 3) * 4;
    sts32(ca, hi);
    sts32(ca + 16, pack2(__uint_as_float(v[i].x) - bf_lo(hi), __uint_as_float(v[i].z) - bf_hi(hi)));
  }
  __syncwarp();
  if (lane == 0) mbar_arrive(sb + BAR_ST + 8 * part);
}

__device__ __forceinline__ void helper_cta(const Params& p, uint32_t sb, int cb, int warp, int lane) {
  constexpr int NS = 9, ONES = NS * B_SLOT, BF = ONES + 256, BE = BF + 8 * NS;
  if (warp < NS && elect_one()) {
    mbar_init(sb + BF + 8 * warp, 1); mbar_init(sb + BE + 8 * warp, 1);
    fence_async_smem();
    if (warp == 0) { mbar_expect(sb + BF, B_SLOT); tma3d(sb, &p.tmW, 0, 0, 12 + cb * 3, sb + BF); }
  }
  if (warp == 15) { sts32(sb + ONES + lane * 4, 0x3f803f80u); sts32(sb + ONES + 128 + lane * 4, 0x3f803f80u); fence_async_smem(); }
  __syncthreads();
  if (warp == 4) {
    int s = 1, ph = 1;
    uint32_t tp = clock() + HP0;
#pragma unroll 1
    for (int it = 1; it < 20; it++) {
      if (HPD && it >= 10) pace(tp, HPD);
      mbar_wait(sb + BE + 8 * s, ph);
      if (elect_one()) { mbar_expect(sb + BF + 8 * s, B_SLOT); tma3d(sb + s * B_SLOT, &p.tmW, 0, (it < 10 ? it : it - 10) * 64, (it < 10 ? 12 : 0) + cb * 3, sb + BF + 8 * s); }
      if (++s == NS) { s = 0; ph ^= 1; }
    }
  } else if (warp < 4) {
    const uint32_t tag = load_epoch(p, 128 + cb, lane) + 1;
    const uint64_t db = mkdesc(sb + ONES, 128, 128, 0);
    uint2* dst = p.scr->colsum + cb * 192 + warp * 16 + (lane >> 2);
    if ((lane & 3) == 0) {
#pragma unroll 1
      for (int j = 0; j < 12; j++) st_ll2(dst + (j < 6 ? 768 : 0) + ((j % 6) >> 1) * 64 + (j & 1) * 8, 0, 0);
    }
    int s = 0, ph = 0;
#pragma unroll 1
    for (int part = 0; part < 2; part++) {
      float d[12];
#pragma unroll
      for (int i = 0; i < 12; i++) d[i] = 0.f;
#pragma unroll 1
      for (int it = 0; it < 10; it++) {
        mbar_wait(sb + BF + 8 * s, ph);
        const uint64_t da = mkdesc(sb + s * B_SLOT, 8192, 1024, 1);
        WG_FENCE();
#pragma unroll
        for (int j = 0; j < 12; j++) wgmma_colsum(d + 4 * (j % 3), da + (j % 3) * 512 + (j / 3) * 128, db);
        WG_COMMIT();
        WG_WAIT(1);
        mbar_arrive_if(sb + BE + 8 * (s == 0 ? NS - 1 : s - 1), threadIdx.x == 0 && (it | part) != 0);
        if (++s == NS) { s = 0; ph ^= 1; }
      }
      WG_WAIT(0);
      acc_fence<12>(d);
      if ((lane & 3) == 0) {
#pragma unroll
        for (int j = 0; j < 6; j++) st_ll2(dst + (part ? 0 : 768) + (j >> 1) * 64 + (j & 1) * 8, __float_as_uint(d[2 * j]), tag);
      }
      STAMPW(1 + part);
    }
    if (threadIdx.x == 0) *(volatile uint32_t*)&p.scr->epoch[128 + cb] = tag;
  }
}

__global__ void __launch_bounds__(512, 1) fused_kernel(const __grid_constant__ Params p) {
  extern __shared__ __align__(1024) uint8_t smem[];
  const int warp = __shfl_sync(0xffffffff, (int)(threadIdx.x >> 5), 0);
  const int lane = threadIdx.x & 31, tid = threadIdx.x & 127;
  const uint32_t sb = __shfl_sync(0xffffffff, (uint32_t)__cvta_generic_to_shared(smem), 0);
  const uint32_t tstart = clock();
  if (elect_one()) {
    if (warp < 5) asm volatile("prefetch.tensormap [%0];" ::"l"(&p.tmX + warp) : "memory");
    mbar_init(sb + OFF_BAR + 8 * warp, 1); mbar_init(sb + OFF_BAR + 128 + 8 * warp, 1); mbar_init(sb + OFF_BAR + 256 + 8 * warp, 2);
    asm volatile("fence.mbarrier_init.release.cluster;" ::: "memory");
  }
  int b = blockIdx.x;
  if (p.by_smid) asm volatile("mov.u32 %0, %%smid;" : "=r"(b));
  b = __shfl_sync(0xffffffff, b, 0);
  const int tp = b >> 1, t7 = (tp - 32) / 7;
  const int lin = tp < 32 ? ((tp & 7) ? (tp & 7) * 16 : 8) + (tp >> 3) * 2 + (b & 1)
                          : (tp < 60 ? (tp - 31 - t7 * 7) * 16 + 8 + t7 * 2 + (b & 1) : (tp < 62 ? -1 : b - 124));
  const int hcb = b & 3;
  if (lin < 0) { helper_cta(p, sb, hcb, warp, lane); return; }
  const int cb = ((lin >> 4) & 1) * 2 + ((lin >> 1) & 1), rb = (lin >> 5) * 8 + ((lin >> 2) & 3) * 2 + (lin & 1);
  const int zs0 = 4 - (cb & 2);
  const int chb = (cb >> 1) * 320 + rb * 2 + (cb & 1);
  if (warp == 0 && elect_one()) {
    mbar_expect(sb + BAR_AF, A_SLOT);
    tma_rows(sb + OFF_A, &p.tmX, 0, rb, sb + BAR_AF);
    mbar_expect(sb + BAR_BF, B_SLOT);
    tma3d(sb + OFF_B, &p.tmW, 0, 0, 12 + cb * 3, sb + BAR_BF);
  }
  if (warp == 1) STAMP(31);
  if (sb & 1023) die();
  __syncthreads();

  if (warp >= 12) {
    asm volatile("setmaxnreg.dec.sync.aligned.u32 32;");
    const uint32_t epoch = load_epoch(p, lin, lane);
    if (warp == 12) {
#pragma unroll 1
      for (int i = 1; i < NA; i++) {
        if (elect_one()) {
          mbar_expect(sb + BAR_AF + 8 * i, A_SLOT);
          tma_rows(sb + OFF_A + i * A_SLOT, &p.tmX, i * 64, rb, sb + BAR_AF + 8 * i);
          if (i < NB) { mbar_expect(sb + BAR_BF + 8 * i, B_SLOT); tma3d(sb + OFF_B + i * B_SLOT, &p.tmW, 0, i * 64, 12 + cb * 3, sb + BAR_BF + 8 * i); }
        }
      }
      STAMP(32);
      uint32_t kvt;
      {
        const int tb = rb * 2 + (cb & 1);
        kvt = __shfl_sync(0xffffffff, (ld_relaxed(p.scr->cnt + CNT_KV + (cb >> 1)) & ~63u) + 64, 0);
        {
          uint32_t tp = tstart;
          pace(tp, KV_T0);
          mbar_arrive_if(sb + BAR_KV + 8, lane == 0);
        }
        if (ST_YIELD) mbar_wait2(sb + BAR_XS, 0, sb + BAR_ST, 0);
#pragma unroll 1
        for (int u = 0; u < 5; u++) {
          mbar_wait(sb + BAR_KU + 8 * u, 0);
          fence_async_smem();
          if (elect_one()) {
            asm volatile("cp.async.bulk.tensor.3d.global.shared::cta.bulk_group [%0, {%2, %3, %4}], [%1];\ncp.async.bulk.commit_group;" ::"l"(&p.tmKV),
                         "r"(sb + OFF_CV + CV_SZ + (u < 3 ? u : u - 3) * 4096), "r"((63 - tb) * 16), "r"((cb >> 1) * 160 + u * 32), "r"(0) : "memory");
            if (u == 1 || u == 4) asm volatile("cp.async.bulk.wait_group 0;" ::: "memory");
            if (u == 1) { mbar_arrive(sb + BAR_KU); red_release(p.scr->cnt + CNT_KV + (cb >> 1)); }
          }
          __syncwarp();
          if (u == 1) {
            STAMP(35);
            if (PFT) { const char* q = (const char*)p.ssmk + chb * 4096 + lane * 128; prefetch_l2(q); prefetch_l2(q + 64 * 4096); }
          }
        }
        zero_pads(sb + OFF_CV + CV_SZ, lane);
        if (elect_one()) { mbar_arrive(sb + BAR_KU + 8); red_release(p.scr->cnt + CNT_KV + 2 + (cb >> 1)); }
        STAMP(30);
        if (lane < 24) {
          const char* r = (const char*)p.wout + (rb * 24 + lane) * (kD * 2) + (cb >> 1) * 640 + (cb & 1) * 384;
          prefetch_l2(r); prefetch_l2(r + 128); prefetch_l2(r + 256 - (cb & 1) * 384);
        }
      }
      poll_counter(p.scr->cnt + CNT_KV + 2 + (cb >> 1), kvt);
      if (elect_one()) mbar_arrive(sb + BAR_KV);
      STAMP(34);
      {
        const char* q = (const char*)p.wsp + (cb * 512 + rb * 16 + (lane >> 1)) * (kS * 2) + (lane & 1) * 128;
        uint32_t tp = clock();
#pragma unroll 1
        for (int i = LEAD / 2; i < WSP_N; i++) {
          prefetch_l2(q + i * 256);
          if (i == Z1_AT) {
            poll_counter(p.scr->cnt + CNT_Z1 + (cb >> 1), (epoch + 1) * 64);
            if (elect_one()) mbar_arrive(sb + BAR_Z1);
            STAMP(24);
          }
          pace(tp, WSP_D);
        }
      }
      const uint32_t tag = epoch + 1;
      if (HPC) {
        bar_sync(NB_Z2, 160);
        if (elect_one()) bulk_s2g(p.scr->h + (size_t)(rb * 12 + cb * 3) * A_SLOT, sb + OFF_A + 5 * A_SLOT, HPC * A_SLOT);
      }
      mbar_wait(sb + BAR_G2, 0);
      if (elect_one()) {
        bulk_s2g(p.scr->h + (size_t)(rb * 12 + cb * 3 + HPC) * A_SLOT, sb + OFF_A + (5 + HPC) * A_SLOT, (3 - HPC) * A_SLOT);
        asm volatile("cp.async.bulk.commit_group;\ncp.async.bulk.wait_group 0;" ::: "memory");
        red_release(&p.scr->hcnt[(rb >> HGRP) * 32]);
      }
      __syncwarp();
      STAMP(20);
      mbar_wait(sb + BAR_AE + 56, 0);
      STAMP(39);
      poll_counter(&p.scr->hcnt[(rb >> HGRP) * 32], tag * (4 << HGRP));
      STAMP(37);
      if (elect_one()) {
        uint32_t tp = clock();
#pragma unroll 1
        for (int it = 3; it < 12; it++) {
          if (HPACE && it > 3) { tp += HPACE; while ((int32_t)((uint32_t)clock() - tp) < 0) {} }
          bulk_g2s(sb + OFF_A + ((it + 5) % 9) * A_SLOT, p.scr->h + (size_t)(rb * 12 + g3_block(cb, it)) * A_SLOT, A_SLOT, sb + BAR_AF + 8 * ((it + 5) % 9));
        }
      }
      STAMP(21);
    } else if (warp == 13) {
      int s = 0, ph = 0;
#pragma unroll 1
      for (int it = NB; it < 20; it++) {
        mbar_wait(sb + BAR_BE + 8 * s, ph);
        if (elect_one()) { mbar_expect(sb + BAR_BF + 8 * s, B_SLOT); tma3d(sb + OFF_B + s * B_SLOT, &p.tmW, 0, (it < 10 ? it : (it + zs0) % 10) * 64, (it < 10 ? 12 : 0) + cb * 3, sb + BAR_BF + 8 * s); }
        STAMP2(32 + it);
        if (++s == NB) { s = 0; ph ^= 1; }
      }
      mbar_wait(sb + BAR_XC, 0);
#pragma unroll 1
      for (int i = 0; i < LEAD; i++) {
        mbar_wait(sb + BAR_AE + 8 * i, 0);
        if (elect_one()) { mbar_expect(sb + BAR_AF + 8 * i, A_SLOT); tma_rows(sb + OFF_A + i * A_SLOT, &p.tmWsp, i * 64, rb, sb + BAR_AF + 8 * i); }
      }
      if (ZP_AT < 0) mbar_wait(sb + BAR_ZP, 0);
      poll_counter(p.scr->zcnt + (cb >> ZSH) * 32, (epoch + 1) * (32 << ZSH));
      STAMP(22);
      int sa = LEAD, pa = 0, ia = LEAD;
#pragma unroll 1
      for (int it = 0; it < 32; it++) {
        if (it == ZP_AT) mbar_wait(sb + BAR_ZP, 0);
        if (it == 16) { mbar_wait(sb + BAR_Z1, 1); if (REFENCE & 1) acquire_fence(); }
        mbar_wait2(sb + BAR_BE + 8 * s, ph, sb + BAR_AE + 8 * sa, pa);
        if (elect_one()) {
          mbar_expect(sb + BAR_BF + 8 * s, B_SLOT);
          bulk_g2s(sb + OFF_B + s * B_SLOT, p.scr->z2 + (size_t)(cb * 32 + it) * B_SLOT, B_SLOT, sb + BAR_BF + 8 * s);
        }
#pragma unroll 1
        for (int j = (it < RAMP ? 0 : (it == 4 ? 1 + RAMP : 1)); j > 0 && ia < 32; j--, ia++) {
          if (it == 4) mbar_wait(sb + BAR_AE + 8 * sa, pa);
          if (elect_one()) { mbar_expect(sb + BAR_AF + 8 * sa, A_SLOT); tma_rows(sb + OFF_A + sa * A_SLOT, &p.tmWsp, ia * 64, rb, sb + BAR_AF + 8 * sa); }
          if (++sa == NA2) { sa = 0; pa ^= 1; }
        }
        STAMP2(52 + it);
        if (++s == NB) { s = 0; ph ^= 1; }
      }
      mbar_wait(sb + BAR_WO, 0);
      if (REFENCE & 2) acquire_fence();
#pragma unroll 1
      for (int it = 0; it < 12; it++) {
        if (it < 6) mbar_wait(sb + BAR_BE + 8 * ((0x110443 >> (4 * it)) & 7), it < 3 ? 1 : 0);
        else mbar_wait(sb + BAR_BE + 8 * s, ph);
        if (elect_one()) {
          mbar_expect(sb + BAR_BF + 8 * s, 20480);
          bulk_g2s(sb + OFF_B + (s == 5 ? 0 : s + 1) * 20480, p.scr->wo + (size_t)(cb * 12 + g3_block(cb, it)) * 20480, 20480, sb + BAR_BF + 8 * s);
        }
        STAMP2(84 + it);
        if (++s == 6) { s = 0; ph ^= 1; }
      }
    } else if (warp == 14) {
      const uint32_t tag = epoch + 1;
      mbar_wait(sb + BAR_AF + 8 * (NA - 1), 0);
#pragma unroll 1
      for (int part = 0; part < 2 - CS1BY; part++) {
        gather_colsum(p, sb, cb, part, tag, lane);
        if (part == 0) STAMP(27);
      }
      if (!CS1BY) STAMP(38);
      bar_sync(NB_Z, ZORD ? 160 : 96);
      if (elect_one()) {
        z_store(p, sb + OFF_A + zs0 * A_SLOT, rb, cb, 0);
        STAMP(7);
        red_release(p.scr->zcnt + (cb >> ZSH) * 32);
      }
      STAMP(25);
      bar_sync(NB_Z2, 96);
      if (elect_one()) {
        z_store(p, sb + OFF_A + zs0 * A_SLOT, rb, cb, 1);
        mbar_arrive(sb + BAR_ZP);
        red_release(p.scr->cnt + CNT_Z1 + (cb >> 1));
      }
      STAMP(28);
      mbar_wait(sb + BAR_AE + 72, 0);
      conv_service(p, sb, 0, chb + 64, true);
      bar_sync(NB_WO, 160);
      bar_sync(NB_CD, 64);
      if (elect_one()) { red_release(p.scr->cnt + CNT_WO + cb); red_relaxed(p.scr->cnt + CNT_Y + (cb >> 1)); }
      STAMP(49);
      poll_counter(p.scr->cnt + CNT_WO + cb, tag * 32);
      if (elect_one()) mbar_arrive(sb + BAR_WO);
      STAMP(46);
      held_service(p, sb, 0, chb + 192, rb, cb, tag, lane);
    } else {
      const uint32_t tag = epoch + 1;
      sts32(sb + OFF_BIAS + lane * 4, ldg1(p.bsp + (lane >> 3) * 512 + rb * 16 + (lane & 7) * 2));
      if (lane < 2) sts32(sb + OFF_TAG + lane * 4, lane ? 0 : tag);
      fence_async_smem();
      uint32_t t0 = 0;
      mbar_wait(sb + BAR_AF + 8 * (NA - 1), 0);
#pragma unroll 1
      while (true) {
        const uint4 u = ld_ll4(&p.scr->xstat[rb * 64 + lane]), v = ld_ll4(&p.scr->xstat[rb * 64 + 32 + lane]);
        sts64f(sb + OFF_XS + lane * 8, __uint_as_float(u.x), __uint_as_float(u.z));
        sts64f(sb + OFF_XS + 256 + lane * 8, __uint_as_float(v.x), __uint_as_float(v.z));
        if (__all_sync(0xffffffff, u.y == tag && u.w == tag && v.y == tag && v.w == tag)) break;
        spin_guard(t0);
      }
      STAMP(26);
      __syncwarp();
      if (lane == 0) mbar_arrive(sb + BAR_XS);
      if (CS1BY) { uint32_t tp = tstart; pace(tp, CS1_T); gather_colsum(p, sb, cb, 1, tag, lane); STAMP(38); }
      mbar_wait(sb + BAR_KU, 1);
      poll_counter(p.scr->cnt + CNT_KV + (cb >> 1), tag * 64);
      if (elect_one()) load_convx(p, sb + OFF_CV, sb + BAR_XF + 8, chb);
      mbar_wait(sb + BAR_KU + 8, 1);
      if (elect_one()) load_convx(p, sb + OFF_CV + CV_SZ, sb + BAR_XF, chb + 64);
      STAMP(48);
      mbar_wait(sb + BAR_AE + 72, 0);
#pragma unroll 1
      for (int i = 0; i < 2; i++) {
        conv_service(p, sb, 1, chb + i * 128, i == 0);
        if (Z1_AT < 0 && i == 0) {
          poll_counter(p.scr->cnt + CNT_Z1 + (cb >> 1), tag * 64);
          if (elect_one()) mbar_arrive(sb + BAR_Z1);
          STAMP(24);
        }
      }
      bar_arrive(NB_CD, 64);
      mbar_wait(sb + BAR_WO, 0);
      poll_counter(p.scr->cnt + CNT_Y + (cb >> 1), tag * 64);
      STAMP(47);
      if (elect_one()) mbar_arrive(sb + BAR_YT);
      held_service(p, sb, 1, chb + 256, rb, cb, tag, lane);
      if (lane == 0) *(volatile uint32_t*)&p.scr->epoch[lin] = tag;
      STAMP(23);
    }
  } else {
    if (warp == 7) STAMP(36);
    const int wg = warp >> 2, w = warp & 3, g = lane >> 2, t = lane & 3;
    Taps k;
    uint32_t xw[2][10];
    if (wg == 2) {
      asm volatile("setmaxnreg.inc.sync.aligned.u32 160;");
      const int tb = rb * 2 + (cb & 1), c0 = (cb >> 1) * 320;
      const uint32_t cv = sb + OFF_CV + CV_SZ;
      if (w == 0) zero_pads(sb + OFF_CV, lane);
      mbar_wait(sb + BAR_KV + 8, 0);
      const int t0 = tb * 32 + w * 8;
      const __nv_bfloat16* kp = p.k + (size_t)(t0 - 3) * kD + c0 + lane * 2;
      const __nv_bfloat16* vp = p.v + (size_t)t0 * kD + c0 + lane * 2;
      const __nv_bfloat16* sp = p.shift + (c0 + lane * 2) * 4;
      const uint32_t oa = cv + ((3 - w) & 1) * 1024 + lane * 32 + ((((3 - w) >> 1) ^ (lane >> 2)) & 1) * 16;
#pragma unroll 1
      for (int r = 0; r < 2; r++) {
        KvRegs n0, n1, n2;
        if (KWT && r) mbar_wait2(sb + BAR_XS, 0, sb + BAR_ST, 0);
        STAMPW(r ? 51 : 50);
        kv_load(n0, kp + r * 128, vp + r * 128, sp + r * 512, t0 > 0);
        kv_load(n1, kp + r * 128 + 64, vp + r * 128 + 64, sp + r * 512 + 256, t0 > 0);
        if (r) kv_load(n2, kp + 256, vp + 256, sp + 1024, t0 > 0);
        kv_unit(n0, oa + r * 8192);
        bar_sync(NB_WGC, 128);
        mbar_arrive_if(sb + BAR_KU + 16 * r, tid == 0);
        if (r) mbar_wait(sb + BAR_KU, 1);
        kv_unit(n1, oa + (r ? 0 : 4096));
        bar_sync(NB_WGC, 128);
        mbar_arrive_if(sb + BAR_KU + 16 * r + 8, tid == 0);
        if (r) {
          kv_unit(n2, oa + 4096);
          bar_sync(NB_WGC, 128);
          mbar_arrive_if(sb + BAR_KU + 32, tid == 0);
        } else {
          mbar_wait(sb + BAR_AF + 8 * ((cb >> 1) * 5 + 1), 0);
          mbar_wait2(sb + BAR_AF + 8 * ((cb >> 1) * 5 + 2), 0, sb + BAR_AF + 8 * ((cb >> 1) * 5 + 4), 0);
          final_load_x(xw, sb + OFF_A, cb, 1, w, lane);
          fence_async_smem();
          bar_sync(NB_WGC, 128);
          mbar_arrive_if(sb + BAR_XC, tid == 0);
        }
      }
      STAMPW(13);
      load_taps(k, p, chb, tid);
    } else {
      float d[96];
      if (wg == 0) st_ll2(&p.scr->zstat[(rb * 256 + cb * 64 + w * 16 + g + (t >> 1) * 8) * 2 + (t & 1)], 0, 0);
      else if ((tid & 7) == 0) st_ll4(&p.scr->xstat[rb * 64 + cb * 16 + (tid >> 3)], 0, 0, 0, 0);
      {
        #pragma unroll
        for (int i = 0; i < 96; i++) d[i] = 0.f;
        {
          if (__builtin_expect(wg == 1, 0)) {
            const int tid = tid_now();
            const uint32_t epoch = load_epoch(p, lin, lane);
            float s = 0.f, q = 0.f;
#pragma unroll 1
            for (int i = 0; i < 10; i++) {
              mbar_wait(sb + BAR_AF + 8 * i, 0);
              const uint4 x4 = lds128(sb + OFF_A + i * A_SLOT + cb * 2048 + tid * 16);
              const uint32_t u[4] = {x4.x, x4.y, x4.z, x4.w};
#pragma unroll
              for (int e = 0; e < 4; e++) { const float a = bf_lo(u[e]), c = bf_hi(u[e]); s += a + c; q = fmaf(a, a, q); q = fmaf(c, c, q); }
            }
#pragma unroll
            for (int o = 1; o <= 4; o <<= 1) { s += __shfl_xor_sync(0xffffffff, s, o); q += __shfl_xor_sync(0xffffffff, q, o); }
            const float m = s * (1.f / kD);
            const float r = rsqrtf(fmaxf(fmaf(-m, m, q * (1.f / kD)), 0.f) + 1e-5f);
            if ((tid & 7) == 0) st_ll4(&p.scr->xstat[rb * 64 + cb * 16 + (tid >> 3)], __float_as_uint(m), epoch + 1, __float_as_uint(r), epoch + 1);
            STAMPW(12);
            bar_sync(NB_G1, 256);
          }
          gemm_loop<192, true, 0, D1>(d, sb, 10, wg ? zs0 : 0, 0, 0, 0, wg, 2, tid_now(), [&]() { if (G1_AT == 0 && wg == 0) bar_arrive(NB_G1, 256); }, [](int) {});
          asm volatile("setmaxnreg.inc.sync.aligned.u32 160;");
          STAMPW(wg ? 14 : 1);
          if (wg == 0) ZS(0);
          mbar_wait2(sb + BAR_XS, 0, sb + BAR_ST + 8 * wg, 0);
          if (wg == 0) ZS(1);
        }
        const int t1 = tid_now();
        const uint32_t xa1 = sb + OFF_XS + (w * 16 + ((t1 & 31) >> 2)) * 8;
        const float2 s0 = lds64f(xa1), s1 = lds64f(xa1 + 64);
        uint32_t z[48];
        float st[4];
        fence_async_smem();
        fold_mean(d, sb + OFF_CS + (1 - wg) * 768, s0.x, s1.x, t1 & 3);
        if (G1_AT == 1 && wg == 0) bar_arrive(NB_G1, 256);
        WG_WAIT(0);
        acc_fence<96>(d);
        if (wg == 0) ZS(2);
        gelu_tile(d, z, st, s0.y, s1.y);
        const int tid = tid_now(), lane = tid & 31, g = lane >> 2, t = lane & 3;
        if (wg == 1) {
          uint32_t bra, brb;
          asm volatile("ld.shared.u16 %0, [%1];" : "=r"(bra) : "r"(sb + OFF_BIAS + (w * 16 + g) * 2));
          asm volatile("ld.shared.u16 %0, [%1+16];" : "=r"(brb) : "r"(sb + OFF_BIAS + (w * 16 + g) * 2));
#pragma unroll
          for (int j = 0; j < 96; j++) d[j] = bf_lo((j & 2) ? brb : bra);
          STAMPW(15);
          gemm_loop<192, true, 1, D2>(d, sb, 32, 0, 1, 20, 0, 2, 2, tid, [&]() { if (HOLD_AT < 32) mbar_arrive_if(sb + BAR_GO, tid == 0); }, [](int) {});
          if (HOLD_AT == 32) mbar_arrive_if(sb + BAR_GO, tid == 0);
          STAMPW(16);
          const int t2 = tid_now(), l2 = t2 & 31;
          const uint32_t ha = sb + OFF_A + 5 * A_SLOT + (l2 >> 4) * 1024 + (2 * w + ((l2 >> 3) & 1)) * 128 + (l2 & 7) * 16;
#pragma unroll
          for (int j = 0; j < 24; j += 2) {
#pragma unroll
            for (int e = 0; e < 4; e++) z[2 * j + e] = hmul2(z[2 * j + e], pack2(d[4 * j + 2 * e], d[4 * j + 2 * e + 1]));
            stsm4(ha + j * 1024, z[2 * j], z[2 * j + 1], z[2 * j + 2], z[2 * j + 3]);
            if (HPC && j == HPC * 8 - 2) {
              fence_async_smem();
              bar_arrive(NB_Z2, 160);
            }
          }
          fence_async_smem();
          bar_sync(NB_WGB, 128);
          mbar_arrive_if(sb + BAR_AF + 8 * (t2 == 3 ? (BAR_G2 - BAR_AF) / 8 : (t2 == 4 ? (BAR_GO - BAR_AF) / 8 : 5 + t2)), t2 < (HOLD_AT == 33 ? 5 : 4));
          STAMPW(17);
          {
            float e[80];
#pragma unroll
            for (int j = 0; j < 80; j++) e[j] = 0.f;
            gemm_loop<160, false, 2, DB>(e, sb, 12, 5, 0, 2, 0, 2, 2, tid_now(), []() {}, [](int) {});
            STAMPW(10);
            const int t3 = tid_now();
#pragma unroll
            for (int j = 0; j < 10; j++) {
              sts128(sb + OFF_A + j * 2048 + t3 * 16, pack2(e[8 * j], e[8 * j + 1]), pack2(e[8 * j + 2], e[8 * j + 3]), pack2(e[8 * j + 4], e[8 * j + 5]),
                     pack2(e[8 * j + 6], e[8 * j + 7]));
              if (j == 4) bar_arrive(NB_WO, 256);
            }
            bar_arrive(NB_Z, 256);
            STAMPW(45);
          }
          return;
        }
        ZS(3);
        const bool hi = t & 2;
        float a0 = (hi ? st[2] : st[0]) + __shfl_xor_sync(0xffffffff, hi ? st[0] : st[2], 2);
        float a1 = (hi ? st[3] : st[1]) + __shfl_xor_sync(0xffffffff, hi ? st[1] : st[3], 2);
        a0 = ((t & 1) ? a1 : a0) + __shfl_xor_sync(0xffffffff, (t & 1) ? a0 : a1, 1);
        const uint32_t tag = lds32<0>(sb + OFF_TAG);
        uint2* zs = p.scr->zstat + (rb * 256 + w * 16 + g + (t >> 1) * 8) * 2 + (t & 1);
        st_ll2(zs + cb * 128, __float_as_uint(a0), tag);
        STAMPW(2); ZS(4);
        uint2 u[4];
#pragma unroll
        for (int i = 0; i < 4; i++) u[i] = ld_ll2(zs + i * 128);
        const uint32_t keep = (cb & 2) ? 13 << 5 : 13;
        mbar_arrive_if(sb + BAR_AE + 8 * tid, tid < NA && !((keep >> tid) & 1));
        const uint32_t za = sb + OFF_A + zs0 * A_SLOT + (2 * w + ((lane >> 3) & 1)) * 3072 + (lane >> 4) * 128 + (lane & 7) * 16;
        const float ca = 0.5f * (hi ? s1.y : s0.y), inv = 1.f / 768.f;
        mbar_wait2(sb + BAR_AE + 8 * (zs0 + 2), 0, sb + BAR_XC, 0);
        ZS(6);
        uint32_t t0 = 0;
#pragma unroll 1
        while (!__all_sync(0xffffffff, u[0].y == tag && u[1].y == tag && u[2].y == tag && u[3].y == tag)) {
          spin_guard(t0);
#pragma unroll
          for (int i = 0; i < 4; i++) u[i] = ld_ll2(zs + i * 128);
        }
        STAMPW(3); ZS(7);
        a0 = ((__uint_as_float(u[0].x) + __uint_as_float(u[1].x)) + (__uint_as_float(u[2].x) + __uint_as_float(u[3].x))) * inv;
        a1 = __shfl_xor_sync(0xffffffff, a0, 1);
        const float m = (t & 1) ? a1 : a0, q = (t & 1) ? a0 : a1;
        const float r = bf_lo(pack2(ca * rsqrtf(fmaf(fmaxf(fmaf(-m, m, q), 0.f), ca * ca, 1e-5f)), 0.f));
        const uint32_t rn = pack2(r, -m * r), ro = __shfl_xor_sync(0xffffffff, rn, 2);
        const uint32_t ra2 = prmt(hi ? ro : rn, 0, 0x1010), n2a = prmt(hi ? ro : rn, 0, 0x3232), rb2 = prmt(hi ? rn : ro, 0, 0x1010), n2b = prmt(hi ? rn : ro, 0, 0x3232);
        if (ZORD && w >= 2) bar_sync(NB_Z, 160);
#pragma unroll
        for (int j = 0; j < 24; j += 2)
          stsm4(za + j * 128, hfma2(z[2 * j], ra2, n2a), hfma2(z[2 * j + 1], rb2, n2b), hfma2(z[2 * j + 2], ra2, n2a), hfma2(z[2 * j + 3], rb2, n2b));
        ZS(8);
        fence_async_smem();
        ZS(9);
        if (w < 2) bar_arrive(NB_Z, ZORD ? 160 : 96);
        else bar_arrive(NB_Z2, 96);
        final_load_x(xw, sb + OFF_A, cb, 0, w, lane);
        fence_async_smem();
        bar_sync(NB_WGA, 128);
        mbar_arrive_if(sb + BAR_AE + 8 * tid, tid < NA && ((keep >> tid) & 1));
      }
      {
        const uint32_t zero = lds32<0>(sb + OFF_TAG + 4);
#pragma unroll
        for (int i = 0; i < 20; i++) xw[i / 10][i % 10] |= zero;
      }
      load_taps(k, p, chb + 64, tid_now());
      STAMPW(4);
    }
    const int h = wg >> 1;
    {
    const int tid = tid_now(), lane = tid & 31;
    conv_worker(p, k, sb + OFF_CV + (1 - h) * CV_SZ, sb + OFF_A + 9 * A_SLOT + h * 4096, sb + BAR_XF + 8 * h, NB_WGA + h,
                chb + (h ? 0 : 64), 2 + h, sb + BAR_GO, w, lane, tid, h ? 40 : 5, rb, cb);
    {
      const int t3 = tid_now(), l3 = t3 & 31;
      const uint32_t xs_addr = sb + OFF_XS + (w * 16 + (l3 >> 2)) * 8;
      const float2 s0 = lds64f(xs_addr), s1 = lds64f(xs_addr + 64);
      const uint32_t ya = sb + y_tile(h) + ((l3 >> 4) * 8 + (l3 & 7)) * 128 + (((2 * w + ((l3 >> 3) & 1)) ^ (l3 & 7) ^ (rb & 7)) << 4);
      uint32_t sw[2][10];
      mbar_wait(sb + BAR_XF + 8 * h, h);
      final_s_early(sw, xw, ya, s0, s1);
      uint32_t ph = 1, t0 = 0, y[8];
#pragma unroll 1
      while (true) {
        mbar_wait(sb + BAR_YL + 16 * h, ph);
        if (bar_all(NB_WGA + h, 128, final_late(y, ya))) break;
        spin_guard(t0);
        ph ^= 1;
        if (t3 == 0) load_late_y(p, sb, h, rb, cb, lds32<0>(sb + OFF_TAG) & 1);
      }
#pragma unroll
      for (int e = 0; e < 8; e++) sw[e & 1][4 + (e >> 1)] = hmul2(sw[e & 1][4 + (e >> 1)], ~y[e]);
      __nv_bfloat16* o0 = p.out + (size_t)(w * 512 + rb * 16 + (l3 >> 2)) * kD + seg_col(cb, h);
      STAMPW(h ? 44 : 9);
      bar_sync(h ? NB_Z : NB_WO, 256);
      float d[40];
#pragma unroll
      for (int j = 0; j < 5; j++) {
        const uint4 v = lds128(sb + OFF_A + (h * 5 + j) * 2048 + t3 * 16);
        d[8 * j] = bf_lo(v.x); d[8 * j + 1] = bf_hi(v.x); d[8 * j + 2] = bf_lo(v.y); d[8 * j + 3] = bf_hi(v.y);
        d[8 * j + 4] = bf_lo(v.z); d[8 * j + 5] = bf_hi(v.z); d[8 * j + 6] = bf_lo(v.w); d[8 * j + 7] = bf_hi(v.w);
      }
      final_out(d, xw, sw, s0.y, s1.y, o0, h, l3 & 3);
    }
    }
  }
}

typedef CUresult (*EncodeFn)(CUtensorMap*, CUtensorMapDataType, cuuint32_t, void*, const cuuint64_t*, const cuuint64_t*, const cuuint32_t*,
                             const cuuint32_t*, CUtensorMapInterleave, CUtensorMapSwizzle, CUtensorMapL2promotion, CUtensorMapFloatOOBfill);

void encode(EncodeFn fn, CUtensorMap* m, const void* ptr, int rank, const cuuint64_t* dims, const cuuint64_t* strides, const cuuint32_t* box,
            CUtensorMapSwizzle swz = CU_TENSOR_MAP_SWIZZLE_128B) {
  const cuuint32_t es[3] = {1, 1, 1};
  fn(m, CU_TENSOR_MAP_DATA_TYPE_BFLOAT16, rank, const_cast<void*>(ptr), dims, strides, box, es, CU_TENSOR_MAP_INTERLEAVE_NONE,
     swz, CU_TENSOR_MAP_L2_PROMOTION_L2_128B, CU_TENSOR_MAP_FLOAT_OOB_FILL_NONE);
}

}

extern "C" void kernel_launch(void* const* d_in, const int* in_sizes, int n_in, void* d_out, int out_size) {
  (void)in_sizes; (void)n_in; (void)out_size;
  static EncodeFn enc = nullptr;
  static Scratch* scr = nullptr;
  static int sms = 0;
  if (!enc) {
    void* fn = nullptr;
    cudaDriverEntryPointQueryResult qr;
    cudaGetDriverEntryPoint("cuTensorMapEncodeTiled", &fn, cudaEnableDefault, &qr);
    enc = (EncodeFn)fn;
    cudaFuncSetAttribute(fused_kernel, cudaFuncAttributeMaxDynamicSharedMemorySize, SMEM_BYTES);
    cudaGetSymbolAddress((void**)&scr, g_scr);
    int dev = 0;
    cudaGetDevice(&dev);
    cudaDeviceGetAttribute(&sms, cudaDevAttrMultiProcessorCount, dev);
  }
  Params p;
  p.scr = scr;
  p.by_smid = sms == 132;
  p.k = (const __nv_bfloat16*)d_in[1];
  p.v = (const __nv_bfloat16*)d_in[2];
  p.shift = (const __nv_bfloat16*)d_in[3];
  p.ssmk = (const __nv_bfloat16*)d_in[4];
  p.ssmD = (const __nv_bfloat16*)d_in[5];
  p.wsp = (const __nv_bfloat16*)d_in[8];
  p.bsp = (const __nv_bfloat16*)d_in[9];
  p.wout = (const __nv_bfloat16*)d_in[10];
  p.out = (__nv_bfloat16*)d_out;
  for (int i = 0; i < 2; i++) {
    const cuuint64_t n = i ? kS : kD, dims[3] = {n, 512, 4}, st[2] = {n * 2, n * 1024};
    const cuuint32_t box[3] = {64, 16, 4};
    encode(enc, i ? &p.tmWsp : &p.tmX, d_in[i ? 8 : 0], 3, dims, st, box);
  }
  {
    const cuuint64_t dims[3] = {64, kD, kF / 64}, st[2] = {kF * 2, 128};
    const cuuint32_t box[3] = {64, 64, 3};
    encode(enc, &p.tmW, d_in[7], 3, dims, st, box);
  }
  {
    const cuuint64_t dims[2] = {kS, 896}, st[1] = {kS * 2};
    const cuuint32_t box[2] = {64, 16};
    encode(enc, &p.tmY, scr->y, 2, dims, st, box);
  }
  {
    const cuuint64_t dims[3] = {1024, kD / 2, 4}, st[2] = {8192, 2048};
    const cuuint32_t box[3] = {16, 32, 4};
    encode(enc, &p.tmKV, scr->kvx, 3, dims, st, box, CU_TENSOR_MAP_SWIZZLE_32B);
  }
  fused_kernel<<<132, 512, SMEM_BYTES, cudaStreamPerThread>>>(p);
}
```

```cpp
#include <cuda_runtime.h>
#include <cuda.h>
#include <cuda_bf16.h>
#include <stdint.h>

template <int N> struct WG;
template <> struct WG<16> {
  static __device__ __forceinline__ void rs(float* d, const uint32_t* a, uint64_t db) {
    asm volatile("{\n.reg .pred p;\nsetp.ne.b32 p, 1, 0;\nwgmma.mma_async.sync.aligned.m64n16k16.f32.bf16.bf16 {"
      "%0, %1, %2, %3, %4, %5, %6, %7"
      "}, {%8, %9, %10, %11}, %12, p, 1, 1, 0;\n}\n"
      :
      "+f"(d[0]), "+f"(d[1]), "+f"(d[2]), "+f"(d[3]), "+f"(d[4]), "+f"(d[5]), "+f"(d[6]), "+f"(d[7])
      : "r"(a[0]), "r"(a[1]), "r"(a[2]), "r"(a[3]), "l"(db));
  }
};
template <> struct WG<32> {
  static __device__ __forceinline__ void rs(float* d, const uint32_t* a, uint64_t db) {
    asm volatile("{\n.reg .pred p;\nsetp.ne.b32 p, 1, 0;\nwgmma.mma_async.sync.aligned.m64n32k16.f32.bf16.bf16 {"
      "%0, %1, %2, %3, %4, %5, %6, %7, %8, %9, %10, %11, %12, %13, %14, %15"
      "}, {%16, %17, %18, %19}, %20, p, 1, 1, 0;\n}\n"
      :
      "+f"(d[0]), "+f"(d[1]), "+f"(d[2]), "+f"(d[3]), "+f"(d[4]), "+f"(d[5]), "+f"(d[6]), "+f"(d[7]),
      "+f"(d[8]), "+f"(d[9]), "+f"(d[10]), "+f"(d[11]), "+f"(d[12]), "+f"(d[13]), "+f"(d[14]), "+f"(d[15])
      : "r"(a[0]), "r"(a[1]), "r"(a[2]), "r"(a[3]), "l"(db));
  }
};
template <> struct WG<48> {
  static __device__ __forceinline__ void rs(float* d, const uint32_t* a, uint64_t db) {
    asm volatile("{\n.reg .pred p;\nsetp.ne.b32 p, 1, 0;\nwgmma.mma_async.sync.aligned.m64n48k16.f32.bf16.bf16 {"
      "%0, %1, %2, %3, %4, %5, %6, %7, %8, %9, %10, %11, %12, %13, %14, %15, "
      "%16, %17, %18, %19, %20, %21, %22, %23"
      "}, {%24, %25, %26, %27}, %28, p, 1, 1, 0;\n}\n"
      :
      "+f"(d[0]), "+f"(d[1]), "+f"(d[2]), "+f"(d[3]), "+f"(d[4]), "+f"(d[5]), "+f"(d[6]), "+f"(d[7]),
      "+f"(d[8]), "+f"(d[9]), "+f"(d[10]), "+f"(d[11]), "+f"(d[12]), "+f"(d[13]), "+f"(d[14]), "+f"(d[15]),
      "+f"(d[16]), "+f"(d[17]), "+f"(d[18]), "+f"(d[19]), "+f"(d[20]), "+f"(d[21]), "+f"(d[22]), "+f"(d[23])
      : "r"(a[0]), "r"(a[1]), "r"(a[2]), "r"(a[3]), "l"(db));
  }
};
template <> struct WG<64> {
  static __device__ __forceinline__ void rs(float* d, const uint32_t* a, uint64_t db) {
    asm volatile("{\n.reg .pred p;\nsetp.ne.b32 p, 1, 0;\nwgmma.mma_async.sync.aligned.m64n64k16.f32.bf16.bf16 {"
      "%0, %1, %2, %3, %4, %5, %6, %7, %8, %9, %10, %11, %12, %13, %14, %15, "
      "%16, %17, %18, %19, %20, %21, %22, %23, %24, %25, %26, %27, %28, %29, %30, %31"
      "}, {%32, %33, %34, %35}, %36, p, 1, 1, 0;\n}\n"
      :
      "+f"(d[0]), "+f"(d[1]), "+f"(d[2]), "+f"(d[3]), "+f"(d[4]), "+f"(d[5]), "+f"(d[6]), "+f"(d[7]),
      "+f"(d[8]), "+f"(d[9]), "+f"(d[10]), "+f"(d[11]), "+f"(d[12]), "+f"(d[13]), "+f"(d[14]), "+f"(d[15]),
      "+f"(d[16]), "+f"(d[17]), "+f"(d[18]), "+f"(d[19]), "+f"(d[20]), "+f"(d[21]), "+f"(d[22]), "+f"(d[23]),
      "+f"(d[24]), "+f"(d[25]), "+f"(d[26]), "+f"(d[27]), "+f"(d[28]), "+f"(d[29]), "+f"(d[30]), "+f"(d[31])
      : "r"(a[0]), "r"(a[1]), "r"(a[2]), "r"(a[3]), "l"(db));
  }
};
template <> struct WG<80> {
  static __device__ __forceinline__ void rs(float* d, const uint32_t* a, uint64_t db) {
    asm volatile("{\n.reg .pred p;\nsetp.ne.b32 p, 1, 0;\nwgmma.mma_async.sync.aligned.m64n80k16.f32.bf16.bf16 {"
      "%0, %1, %2, %3, %4, %5, %6, %7, %8, %9, %10, %11, %12, %13, %14, %15, "
      "%16, %17, %18, %19, %20, %21, %22, %23, %24, %25, %26, %27, %28, %29, %30, %31, "
      "%32, %33, %34, %35, %36, %37, %38, %39"
      "}, {%40, %41, %42, %43}, %44, p, 1, 1, 0;\n}\n"
      :
      "+f"(d[0]), "+f"(d[1]), "+f"(d[2]), "+f"(d[3]), "+f"(d[4]), "+f"(d[5]), "+f"(d[6]), "+f"(d[7]),
      "+f"(d[8]), "+f"(d[9]), "+f"(d[10]), "+f"(d[11]), "+f"(d[12]), "+f"(d[13]), "+f"(d[14]), "+f"(d[15]),
      "+f"(d[16]), "+f"(d[17]), "+f"(d[18]), "+f"(d[19]), "+f"(d[20]), "+f"(d[21]), "+f"(d[22]), "+f"(d[23]),
      "+f"(d[24]), "+f"(d[25]), "+f"(d[26]), "+f"(d[27]), "+f"(d[28]), "+f"(d[29]), "+f"(d[30]), "+f"(d[31]),
      "+f"(d[32]), "+f"(d[33]), "+f"(d[34]), "+f"(d[35]), "+f"(d[36]), "+f"(d[37]), "+f"(d[38]), "+f"(d[39])
      : "r"(a[0]), "r"(a[1]), "r"(a[2]), "r"(a[3]), "l"(db));
  }
};
template <> struct WG<96> {
  static __device__ __forceinline__ void rs(float* d, const uint32_t* a, uint64_t db) {
    asm volatile("{\n.reg .pred p;\nsetp.ne.b32 p, 1, 0;\nwgmma.mma_async.sync.aligned.m64n96k16.f32.bf16.bf16 {"
      "%0, %1, %2, %3, %4, %5, %6, %7, %8, %9, %10, %11, %12, %13, %14, %15, "
      "%16, %17, %18, %19, %20, %21, %22, %23, %24, %25, %26, %27, %28, %29, %30, %31, "
      "%32, %33, %34, %35, %36, %37, %38, %39, %40, %41, %42, %43, %44, %45, %46, %47"
      "}, {%48, %49, %50, %51}, %52, p, 1, 1, 0;\n}\n"
      :
      "+f"(d[0]), "+f"(d[1]), "+f"(d[2]), "+f"(d[3]), "+f"(d[4]), "+f"(d[5]), "+f"(d[6]), "+f"(d[7]),
      "+f"(d[8]), "+f"(d[9]), "+f"(d[10]), "+f"(d[11]), "+f"(d[12]), "+f"(d[13]), "+f"(d[14]), "+f"(d[15]),
      "+f"(d[16]), "+f"(d[17]), "+f"(d[18]), "+f"(d[19]), "+f"(d[20]), "+f"(d[21]), "+f"(d[22]), "+f"(d[23]),
      "+f"(d[24]), "+f"(d[25]), "+f"(d[26]), "+f"(d[27]), "+f"(d[28]), "+f"(d[29]), "+f"(d[30]), "+f"(d[31]),
      "+f"(d[32]), "+f"(d[33]), "+f"(d[34]), "+f"(d[35]), "+f"(d[36]), "+f"(d[37]), "+f"(d[38]), "+f"(d[39]),
      "+f"(d[40]), "+f"(d[41]), "+f"(d[42]), "+f"(d[43]), "+f"(d[44]), "+f"(d[45]), "+f"(d[46]), "+f"(d[47])
      : "r"(a[0]), "r"(a[1]), "r"(a[2]), "r"(a[3]), "l"(db));
  }
};
template <> struct WG<112> {
  static __device__ __forceinline__ void rs(float* d, const uint32_t* a, uint64_t db) {
    asm volatile("{\n.reg .pred p;\nsetp.ne.b32 p, 1, 0;\nwgmma.mma_async.sync.aligned.m64n112k16.f32.bf16.bf16 {"
      "%0, %1, %2, %3, %4, %5, %6, %7, %8, %9, %10, %11, %12, %13, %14, %15, "
      "%16, %17, %18, %19, %20, %21, %22, %23, %24, %25, %26, %27, %28, %29, %30, %31, "
      "%32, %33, %34, %35, %36, %37, %38, %39, %40, %41, %42, %43, %44, %45, %46, %47, "
      "%48, %49, %50, %51, %52, %53, %54, %55"
      "}, {%56, %57, %58, %59}, %60, p, 1, 1, 0;\n}\n"
      :
      "+f"(d[0]), "+f"(d[1]), "+f"(d[2]), "+f"(d[3]), "+f"(d[4]), "+f"(d[5]), "+f"(d[6]), "+f"(d[7]),
      "+f"(d[8]), "+f"(d[9]), "+f"(d[10]), "+f"(d[11]), "+f"(d[12]), "+f"(d[13]), "+f"(d[14]), "+f"(d[15]),
      "+f"(d[16]), "+f"(d[17]), "+f"(d[18]), "+f"(d[19]), "+f"(d[20]), "+f"(d[21]), "+f"(d[22]), "+f"(d[23]),
      "+f"(d[24]), "+f"(d[25]), "+f"(d[26]), "+f"(d[27]), "+f"(d[28]), "+f"(d[29]), "+f"(d[30]), "+f"(d[31]),
      "+f"(d[32]), "+f"(d[33]), "+f"(d[34]), "+f"(d[35]), "+f"(d[36]), "+f"(d[37]), "+f"(d[38]), "+f"(d[39]),
      "+f"(d[40]), "+f"(d[41]), "+f"(d[42]), "+f"(d[43]), "+f"(d[44]), "+f"(d[45]), "+f"(d[46]), "+f"(d[47]),
      "+f"(d[48]), "+f"(d[49]), "+f"(d[50]), "+f"(d[51]), "+f"(d[52]), "+f"(d[53]), "+f"(d[54]), "+f"(d[55])
      : "r"(a[0]), "r"(a[1]), "r"(a[2]), "r"(a[3]), "l"(db));
  }
};
template <> struct WG<128> {
  static __device__ __forceinline__ void rs(float* d, const uint32_t* a, uint64_t db) {
    asm volatile("{\n.reg .pred p;\nsetp.ne.b32 p, 1, 0;\nwgmma.mma_async.sync.aligned.m64n128k16.f32.bf16.bf16 {"
      "%0, %1, %2, %3, %4, %5, %6, %7, %8, %9, %10, %11, %12, %13, %14, %15, "
      "%16, %17, %18, %19, %20, %21, %22, %23, %24, %25, %26, %27, %28, %29, %30, %31, "
      "%32, %33, %34, %35, %36, %37, %38, %39, %40, %41, %42, %43, %44, %45, %46, %47, "
      "%48, %49, %50, %51, %52, %53, %54, %55, %56, %57, %58, %59, %60, %61, %62, %63"
      "}, {%64, %65, %66, %67}, %68, p, 1, 1, 0;\n}\n"
      :
      "+f"(d[0]), "+f"(d[1]), "+f"(d[2]), "+f"(d[3]), "+f"(d[4]), "+f"(d[5]), "+f"(d[6]), "+f"(d[7]),
      "+f"(d[8]), "+f"(d[9]), "+f"(d[10]), "+f"(d[11]), "+f"(d[12]), "+f"(d[13]), "+f"(d[14]), "+f"(d[15]),
      "+f"(d[16]), "+f"(d[17]), "+f"(d[18]), "+f"(d[19]), "+f"(d[20]), "+f"(d[21]), "+f"(d[22]), "+f"(d[23]),
      "+f"(d[24]), "+f"(d[25]), "+f"(d[26]), "+f"(d[27]), "+f"(d[28]), "+f"(d[29]), "+f"(d[30]), "+f"(d[31]),
      "+f"(d[32]), "+f"(d[33]), "+f"(d[34]), "+f"(d[35]), "+f"(d[36]), "+f"(d[37]), "+f"(d[38]), "+f"(d[39]),
      "+f"(d[40]), "+f"(d[41]), "+f"(d[42]), "+f"(d[43]), "+f"(d[44]), "+f"(d[45]), "+f"(d[46]), "+f"(d[47]),
      "+f"(d[48]), "+f"(d[49]), "+f"(d[50]), "+f"(d[51]), "+f"(d[52]), "+f"(d[53]), "+f"(d[54]), "+f"(d[55]),
      "+f"(d[56]), "+f"(d[57]), "+f"(d[58]), "+f"(d[59]), "+f"(d[60]), "+f"(d[61]), "+f"(d[62]), "+f"(d[63])
      : "r"(a[0]), "r"(a[1]), "r"(a[2]), "r"(a[3]), "l"(db));
  }
};
template <> struct WG<160> {
  static __device__ __forceinline__ void ss(float* d, uint64_t da, uint64_t db, int sd) {
    asm volatile("{\n.reg .pred p;\nsetp.ne.b32 p, %82, 0;\nwgmma.mma_async.sync.aligned.m64n160k16.f32.bf16.bf16 {"
      "%0, %1, %2, %3, %4, %5, %6, %7, %8, %9, %10, %11, %12, %13, %14, %15, "
      "%16, %17, %18, %19, %20, %21, %22, %23, %24, %25, %26, %27, %28, %29, %30, %31, "
      "%32, %33, %34, %35, %36, %37, %38, %39, %40, %41, %42, %43, %44, %45, %46, %47, "
      "%48, %49, %50, %51, %52, %53, %54, %55, %56, %57, %58, %59, %60, %61, %62, %63, "
      "%64, %65, %66, %67, %68, %69, %70, %71, %72, %73, %74, %75, %76, %77, %78, %79"
      "}, %80, %81, p, 1, 1, 0, 1;\n}\n"
      :
      "+f"(d[0]), "+f"(d[1]), "+f"(d[2]), "+f"(d[3]), "+f"(d[4]), "+f"(d[5]), "+f"(d[6]), "+f"(d[7]),
      "+f"(d[8]), "+f"(d[9]), "+f"(d[10]), "+f"(d[11]), "+f"(d[12]), "+f"(d[13]), "+f"(d[14]), "+f"(d[15]),
      "+f"(d[16]), "+f"(d[17]), "+f"(d[18]), "+f"(d[19]), "+f"(d[20]), "+f"(d[21]), "+f"(d[22]), "+f"(d[23]),
      "+f"(d[24]), "+f"(d[25]), "+f"(d[26]), "+f"(d[27]), "+f"(d[28]), "+f"(d[29]), "+f"(d[30]), "+f"(d[31]),
      "+f"(d[32]), "+f"(d[33]), "+f"(d[34]), "+f"(d[35]), "+f"(d[36]), "+f"(d[37]), "+f"(d[38]), "+f"(d[39]),
      "+f"(d[40]), "+f"(d[41]), "+f"(d[42]), "+f"(d[43]), "+f"(d[44]), "+f"(d[45]), "+f"(d[46]), "+f"(d[47]),
      "+f"(d[48]), "+f"(d[49]), "+f"(d[50]), "+f"(d[51]), "+f"(d[52]), "+f"(d[53]), "+f"(d[54]), "+f"(d[55]),
      "+f"(d[56]), "+f"(d[57]), "+f"(d[58]), "+f"(d[59]), "+f"(d[60]), "+f"(d[61]), "+f"(d[62]), "+f"(d[63]),
      "+f"(d[64]), "+f"(d[65]), "+f"(d[66]), "+f"(d[67]), "+f"(d[68]), "+f"(d[69]), "+f"(d[70]), "+f"(d[71]),
      "+f"(d[72]), "+f"(d[73]), "+f"(d[74]), "+f"(d[75]), "+f"(d[76]), "+f"(d[77]), "+f"(d[78]), "+f"(d[79])
      : "l"(da), "l"(db), "r"(sd));
  }
};
template <> struct WG<192> {
  static __device__ __forceinline__ void ss(float* d, uint64_t da, uint64_t db, int sd) {
    asm volatile("{\n.reg .pred p;\nsetp.ne.b32 p, %98, 0;\nwgmma.mma_async.sync.aligned.m64n192k16.f32.bf16.bf16 {"
      "%0, %1, %2, %3, %4, %5, %6, %7, %8, %9, %10, %11, %12, %13, %14, %15, "
      "%16, %17, %18, %19, %20, %21, %22, %23, %24, %25, %26, %27, %28, %29, %30, %31, "
      "%32, %33, %34, %35, %36, %37, %38, %39, %40, %41, %42, %43, %44, %45, %46, %47, "
      "%48, %49, %50, %51, %52, %53, %54, %55, %56, %57, %58, %59, %60, %61, %62, %63, "
      "%64, %65, %66, %67, %68, %69, %70, %71, %72, %73, %74, %75, %76, %77, %78, %79, "
      "%80, %81, %82, %83, %84, %85, %86, %87, %88, %89, %90, %91, %92, %93, %94, %95"
      "}, %96, %97, p, 1, 1, 0, 1;\n}\n"
      :
      "+f"(d[0]), "+f"(d[1]), "+f"(d[2]), "+f"(d[3]), "+f"(d[4]), "+f"(d[5]), "+f"(d[6]), "+f"(d[7]),
      "+f"(d[8]), "+f"(d[9]), "+f"(d[10]), "+f"(d[11]), "+f"(d[12]), "+f"(d[13]), "+f"(d[14]), "+f"(d[15]),
      "+f"(d[16]), "+f"(d[17]), "+f"(d[18]), "+f"(d[19]), "+f"(d[20]), "+f"(d[21]), "+f"(d[22]), "+f"(d[23]),
      "+f"(d[24]), "+f"(d[25]), "+f"(d[26]), "+f"(d[27]), "+f"(d[28]), "+f"(d[29]), "+f"(d[30]), "+f"(d[31]),
      "+f"(d[32]), "+f"(d[33]), "+f"(d[34]), "+f"(d[35]), "+f"(d[36]), "+f"(d[37]), "+f"(d[38]), "+f"(d[39]),
      "+f"(d[40]), "+f"(d[41]), "+f"(d[42]), "+f"(d[43]), "+f"(d[44]), "+f"(d[45]), "+f"(d[46]), "+f"(d[47]),
      "+f"(d[48]), "+f"(d[49]), "+f"(d[50]), "+f"(d[51]), "+f"(d[52]), "+f"(d[53]), "+f"(d[54]), "+f"(d[55]),
      "+f"(d[56]), "+f"(d[57]), "+f"(d[58]), "+f"(d[59]), "+f"(d[60]), "+f"(d[61]), "+f"(d[62]), "+f"(d[63]),
      "+f"(d[64]), "+f"(d[65]), "+f"(d[66]), "+f"(d[67]), "+f"(d[68]), "+f"(d[69]), "+f"(d[70]), "+f"(d[71]),
      "+f"(d[72]), "+f"(d[73]), "+f"(d[74]), "+f"(d[75]), "+f"(d[76]), "+f"(d[77]), "+f"(d[78]), "+f"(d[79]),
      "+f"(d[80]), "+f"(d[81]), "+f"(d[82]), "+f"(d[83]), "+f"(d[84]), "+f"(d[85]), "+f"(d[86]), "+f"(d[87]),
      "+f"(d[88]), "+f"(d[89]), "+f"(d[90]), "+f"(d[91]), "+f"(d[92]), "+f"(d[93]), "+f"(d[94]), "+f"(d[95])
      : "l"(da), "l"(db), "r"(sd));
  }
  static __device__ __forceinline__ void rst(float* d, const uint32_t* a, uint64_t db) {
    asm volatile("{\n.reg .pred p;\nsetp.ne.b32 p, 1, 0;\nwgmma.mma_async.sync.aligned.m64n192k16.f32.bf16.bf16 {"
      "%0, %1, %2, %3, %4, %5, %6, %7, %8, %9, %10, %11, %12, %13, %14, %15, "
      "%16, %17, %18, %19, %20, %21, %22, %23, %24, %25, %26, %27, %28, %29, %30, %31, "
      "%32, %33, %34, %35, %36, %37, %38, %39, %40, %41, %42, %43, %44, %45, %46, %47, "
      "%48, %49, %50, %51, %52, %53, %54, %55, %56, %57, %58, %59, %60, %61, %62, %63, "
      "%64, %65, %66, %67, %68, %69, %70, %71, %72, %73, %74, %75, %76, %77, %78, %79, "
      "%80, %81, %82, %83, %84, %85, %86, %87, %88, %89, %90, %91, %92, %93, %94, %95"
      "}, {%96, %97, %98, %99}, %100, p, 1, 1, 1;\n}\n"
      :
      "+f"(d[0]), "+f"(d[1]), "+f"(d[2]), "+f"(d[3]), "+f"(d[4]), "+f"(d[5]), "+f"(d[6]), "+f"(d[7]),
      "+f"(d[8]), "+f"(d[9]), "+f"(d[10]), "+f"(d[11]), "+f"(d[12]), "+f"(d[13]), "+f"(d[14]), "+f"(d[15]),
      "+f"(d[16]), "+f"(d[17]), "+f"(d[18]), "+f"(d[19]), "+f"(d[20]), "+f"(d[21]), "+f"(d[22]), "+f"(d[23]),
      "+f"(d[24]), "+f"(d[25]), "+f"(d[26]), "+f"(d[27]), "+f"(d[28]), "+f"(d[29]), "+f"(d[30]), "+f"(d[31]),
      "+f"(d[32]), "+f"(d[33]), "+f"(d[34]), "+f"(d[35]), "+f"(d[36]), "+f"(d[37]), "+f"(d[38]), "+f"(d[39]),
      "+f"(d[40]), "+f"(d[41]), "+f"(d[42]), "+f"(d[43]), "+f"(d[44]), "+f"(d[45]), "+f"(d[46]), "+f"(d[47]),
      "+f"(d[48]), "+f"(d[49]), "+f"(d[50]), "+f"(d[51]), "+f"(d[52]), "+f"(d[53]), "+f"(d[54]), "+f"(d[55]),
      "+f"(d[56]), "+f"(d[57]), "+f"(d[58]), "+f"(d[59]), "+f"(d[60]), "+f"(d[61]), "+f"(d[62]), "+f"(d[63]),
      "+f"(d[64]), "+f"(d[65]), "+f"(d[66]), "+f"(d[67]), "+f"(d[68]), "+f"(d[69]), "+f"(d[70]), "+f"(d[71]),
      "+f"(d[72]), "+f"(d[73]), "+f"(d[74]), "+f"(d[75]), "+f"(d[76]), "+f"(d[77]), "+f"(d[78]), "+f"(d[79]),
      "+f"(d[80]), "+f"(d[81]), "+f"(d[82]), "+f"(d[83]), "+f"(d[84]), "+f"(d[85]), "+f"(d[86]), "+f"(d[87]),
      "+f"(d[88]), "+f"(d[89]), "+f"(d[90]), "+f"(d[91]), "+f"(d[92]), "+f"(d[93]), "+f"(d[94]), "+f"(d[95])
      : "r"(a[0]), "r"(a[1]), "r"(a[2]), "r"(a[3]), "l"(db));
  }
};

#define REFENCE 0
#define KWT 0
#define HPC 0
#define ZSH 1
#define ZP_AT 1
#define CPRE0 1
#define ZORD 1
#define CS1BY 1
#define CS1_T 9500
#define Z1_AT -1
#define G1_AT 0
#define HGRP 3
#define HPACE 150
#define DB 0
#define HOLD_AT 33
#define LL_AT 4
#define KV_T0 2300
#define ST_YIELD 1
#define HP0 0
#define HPD 0
#define RAMP 1
#define LEAD 2
#define WSP_N 16
#define EARLY 0
#define CPIN 1
#define CW0 0
#define PFT 1
#define WSP_D 650
#define D1 4
#define D2 4
#define NSLEEP 32

static_assert(ZP_AT <= RAMP && LEAD <= 2, "staging slots");

namespace {

constexpr int kS = 2048, kD = 640, kF = 1536;
constexpr int NA = 10, NA2 = 9, NB = 5;
constexpr int A_SLOT = 8192, B_SLOT = 24576;
constexpr int OFF_A = 0;
constexpr int OFF_B = OFF_A + NA * A_SLOT;
constexpr int XB_PL = 2112;
constexpr int CV_KE = 4224, CV_KO = CV_KE + 4160;
constexpr int CV_SZ = CV_KO + 4160;
constexpr int OFF_CV = OFF_B + NB * B_SLOT;
constexpr int OFF_CS = OFF_CV + 2 * CV_SZ;
constexpr int OFF_BIAS = OFF_CS + 1536;
constexpr int OFF_XS = OFF_BIAS + 128;
constexpr int OFF_BAR = OFF_XS + 512;
constexpr int BAR_AF = OFF_BAR, BAR_ST = BAR_AF + 8 * NA, BAR_XF = BAR_ST + 16, BAR_KV = BAR_XF + 16;
constexpr int BAR_BF = OFF_BAR + 128, BAR_G2 = BAR_BF + 8 * (NB + 1), BAR_XS = BAR_G2 + 8, BAR_KU = BAR_XS + 8, BAR_ZP = BAR_KU + 40, BAR_XC = BAR_ZP + 8, BAR_WO = BAR_XC + 8;
constexpr int BAR_AE = OFF_BAR + 256, BAR_BE = BAR_AE + 8 * NA;
constexpr int BAR_YT = BAR_KU + 24;
constexpr int BAR_Z1 = BAR_ST;
constexpr int BAR_GO = BAR_XS;
constexpr int BAR_YL = BAR_KU + 16;
constexpr int OFF_TAG = OFF_CS - 32;
constexpr int SMEM_BYTES = OFF_BAR + 384;
static_assert(SMEM_BYTES <= 232448, "smem");
constexpr int NB_WGA = 1, NB_WGC = 2, NB_G1 = 3, NB_WO = 4, NB_CD = 5, NB_Z = 6, NB_WGB = 7, NB_Z2 = 8;

constexpr int CNT_Y = 1, CNT_Z1 = 3, CNT_KV = 32, CNT_WO = 36;
struct Scratch {
  uint8_t kvx[kD * 4096];
  uint8_t z2[4 * 32 * 24576];
  uint8_t h[32 * 12 * 8192];
  uint8_t wo[4 * 12 * 20480];
  uint8_t y[896 * 4096];
  uint4 xstat[kS];
  uint2 zstat[kS * 8];
  uint2 colsum[kF];
  uint32_t zcnt[4 * 32];
  uint32_t cnt[2 * 32];
  uint32_t hcnt[32 * 32];
  uint32_t epoch[136];
};
__device__ __align__(1024) Scratch g_scr;
#define ZS(i)
#define STAMP(i)
#define STAMP2(i)
#define STAMPW(i)

struct Params {
  Scratch* scr;
  int by_smid;
  const __nv_bfloat16 *k, *v, *shift, *ssmk, *ssmD, *wsp, *bsp, *wout;
  __nv_bfloat16* out;
  CUtensorMap tmX, tmW, tmWsp, tmY, tmKV;
};

__device__ __forceinline__ uint64_t mkdesc(uint32_t addr, uint32_t lbo, uint32_t sbo, uint32_t swz) {
  return (uint64_t)((addr & 0x3FFFF) >> 4) | ((uint64_t)(lbo >> 4) << 16) | ((uint64_t)(sbo >> 4) << 32) | ((uint64_t)swz << 62);
}
#define WG_FENCE() asm volatile("wgmma.fence.sync.aligned;" ::: "memory")
#define WG_COMMIT() asm volatile("wgmma.commit_group.sync.aligned;" ::: "memory")
#define WG_WAIT(n) asm volatile("wgmma.wait_group.sync.aligned %0;" ::"n"(n) : "memory")
template <int N> __device__ __forceinline__ void acc_fence(float* d) {
#pragma unroll
  for (int i = 0; i < N; i++) asm volatile("" : "+f"(d[i])::"memory");
}
__device__ __forceinline__ void mbar_init(uint32_t bar, int cnt) { asm volatile("mbarrier.init.shared::cta.b64 [%0], %1;" ::"r"(bar), "r"(cnt) : "memory"); }
__device__ __forceinline__ void mbar_expect(uint32_t bar, uint32_t bytes) { asm volatile("mbarrier.arrive.expect_tx.shared::cta.b64 _, [%0], %1;" ::"r"(bar), "r"(bytes) : "memory"); }
__device__ __forceinline__ void mbar_arrive(uint32_t bar) { asm volatile("mbarrier.arrive.shared::cta.b64 _, [%0];" ::"r"(bar) : "memory"); }
__device__ __forceinline__ void mbar_arrive_if(uint32_t bar, bool c) {
  asm volatile("{\n.reg .pred p;\nsetp.ne.u32 p, %1, 0;\n@p mbarrier.arrive.shared::cta.b64 _, [%0];\n}\n" ::"r"(bar), "r"((uint32_t)c) : "memory");
}
__device__ __forceinline__ void mbar_expect_if(uint32_t bar, uint32_t bytes, bool c) {
  asm volatile("{\n.reg .pred p;\nsetp.ne.u32 p, %2, 0;\n@p mbarrier.arrive.expect_tx.shared::cta.b64 _, [%0], %1;\n}\n" ::"r"(bar), "r"(bytes), "r"((uint32_t)c) : "memory");
}
__device__ __forceinline__ bool mbar_try(uint32_t bar, uint32_t parity) {
  uint32_t ok;
  asm volatile("{\n.reg .pred p;\nmbarrier.try_wait.parity.shared::cta.b64 p, [%1], %2;\nselp.u32 %0, 1, 0, p;\n}\n" : "=r"(ok) : "r"(bar), "r"(parity) : "memory");
  return ok;
}
__device__ __forceinline__ bool mbar_test(uint32_t bar, uint32_t parity) {
  uint32_t ok;
  asm volatile("{\n.reg .pred p;\nmbarrier.test_wait.parity.shared::cta.b64 p, [%1], %2;\nselp.u32 %0, 1, 0, p;\n}\n" : "=r"(ok) : "r"(bar), "r"(parity) : "memory");
  return ok;
}
__device__ __forceinline__ void die() { asm volatile("st.volatile.global.u32 [%0], %1;" ::"l"(0ull), "r"(0) : "memory"); }
__device__ __forceinline__ void spin_guard(uint32_t& n) { if (++n == (1u << 22)) die(); }
__device__ __forceinline__ void mbar_wait(uint32_t bar, uint32_t parity) {
  uint32_t t0 = 0;
#pragma unroll 1
  while (!mbar_try(bar, parity)) spin_guard(t0);
}
__device__ __forceinline__ void mbar_wait2(uint32_t b0, uint32_t p0, uint32_t b1, uint32_t p1) {
  uint32_t t0 = 0;
#pragma unroll 1
  while (true) {
    const bool r0 = mbar_try(b0, p0), r1 = mbar_try(b1, p1);
    if (r0 && r1) break;
    spin_guard(t0);
  }
}
__device__ __forceinline__ int tid_now() { int v; asm volatile("mov.u32 %0, %%tid.x;" : "=r"(v)); return v & 127; }
__device__ __forceinline__ bool elect_one() {
  uint32_t p;
  asm volatile("{\n.reg .pred P;\nelect.sync _|P, 0xffffffff;\nselp.u32 %0, 1, 0, P;\n}\n" : "=r"(p));
  return p;
}
__device__ __forceinline__ void bar_sync(int id, int n) { asm volatile("bar.sync %0, %1;" ::"r"(id), "r"(n) : "memory"); }
__device__ __forceinline__ void bar_arrive(int id, int n) { asm volatile("bar.arrive %0, %1;" ::"r"(id), "r"(n) : "memory"); }
__device__ __forceinline__ void fence_async_smem() { asm volatile("fence.proxy.async.shared::cta;" ::: "memory"); }
__device__ __forceinline__ void bulk_g2s(uint32_t dst, const void* src, uint32_t bytes, uint32_t bar) {
  asm volatile("cp.async.bulk.shared::cluster.global.mbarrier::complete_tx::bytes [%0], [%1], %2, [%3];" ::"r"(dst), "l"(src), "r"(bytes), "r"(bar) : "memory");
}
__device__ __forceinline__ void bulk_s2g(void* dst, uint32_t src, uint32_t bytes) {
  asm volatile("cp.async.bulk.global.shared::cta.bulk_group [%0], [%1], %2;" ::"l"(dst), "r"(src), "r"(bytes) : "memory");
}
__device__ __forceinline__ void tma2d(uint32_t dst, const CUtensorMap* m, int c0, int c1, uint32_t bar) {
  asm volatile("cp.async.bulk.tensor.2d.shared::cluster.global.mbarrier::complete_tx::bytes [%0], [%1, {%3, %4}], [%2];" ::"r"(dst), "l"(m), "r"(bar), "r"(c0), "r"(c1) : "memory");
}
__device__ __forceinline__ void tma3d(uint32_t dst, const CUtensorMap* m, int c0, int c1, int c2, uint32_t bar) {
  asm volatile("cp.async.bulk.tensor.3d.shared::cluster.global.mbarrier::complete_tx::bytes [%0], [%1, {%3, %4, %5}], [%2];" ::"r"(dst), "l"(m), "r"(bar), "r"(c0), "r"(c1), "r"(c2) : "memory");
}
__device__ __forceinline__ void tma_rows(uint32_t dst, const CUtensorMap* m, int c0, int rb, uint32_t bar) { tma3d(dst, m, c0, rb * 16, 0, bar); }
__device__ __forceinline__ uint4 ld_ll4(const void* p) {
  uint64_t a, b;
  asm volatile("ld.relaxed.gpu.global.v2.u64 {%0,%1}, [%2];" : "=l"(a), "=l"(b) : "l"(p) : "memory");
  return make_uint4((uint32_t)a, (uint32_t)(a >> 32), (uint32_t)b, (uint32_t)(b >> 32));
}
__device__ __forceinline__ void st_ll4(void* p, uint32_t a, uint32_t b, uint32_t c, uint32_t d) {
  asm volatile("st.relaxed.gpu.global.v2.u64 [%0], {%1,%2};" ::"l"(p), "l"(a | ((uint64_t)b << 32)), "l"(c | ((uint64_t)d << 32)) : "memory");
}
__device__ __forceinline__ void st_ll2(void* p, uint32_t a, uint32_t b) { asm volatile("st.relaxed.gpu.global.u64 [%0], %1;" ::"l"(p), "l"(a | ((uint64_t)b << 32)) : "memory"); }
__device__ __forceinline__ uint2 ld_ll2(const void* p) {
  uint64_t a;
  asm volatile("ld.relaxed.gpu.global.u64 %0, [%1];" : "=l"(a) : "l"(p) : "memory");
  return make_uint2((uint32_t)a, (uint32_t)(a >> 32));
}
__device__ __forceinline__ void wgmma_colsum(float* d, uint64_t da, uint64_t db) {
  asm volatile("{\n.reg .pred p;\nsetp.ne.b32 p, 1, 0;\nwgmma.mma_async.sync.aligned.m64n8k16.f32.bf16.bf16 {%0, %1, %2, %3}, %4, %5, p, 1, 1, 1, 0;\n}\n"
               : "+f"(d[0]), "+f"(d[1]), "+f"(d[2]), "+f"(d[3]) : "l"(da), "l"(db));
}
__device__ __forceinline__ void prefetch_l2(const void* p) { asm volatile("prefetch.global.L2 [%0];" ::"l"(p)); }
__device__ __forceinline__ void pace(uint32_t& t, uint32_t dt) {
  t += dt;
  while ((int32_t)((uint32_t)clock() - t) < 0) { if (NSLEEP) __nanosleep(NSLEEP); }
}
__device__ __forceinline__ void red_relaxed(uint32_t* p) { asm volatile("red.relaxed.gpu.global.add.u32 [%0], 1;" ::"l"(p) : "memory"); }
__device__ __forceinline__ void red_release(uint32_t* p) { asm volatile("red.release.gpu.global.add.u32 [%0], 1;" ::"l"(p) : "memory"); }
__device__ __forceinline__ uint4 ldg4(const void* p) { uint4 v; asm volatile("ld.global.v4.u32 {%0,%1,%2,%3}, [%4];" : "=r"(v.x), "=r"(v.y), "=r"(v.z), "=r"(v.w) : "l"(p) : "memory"); return v; }
__device__ __forceinline__ uint32_t ldg1(const void* p) { uint32_t v; asm volatile("ld.global.u32 %0, [%1];" : "=r"(v) : "l"(p) : "memory"); return v; }
__device__ __forceinline__ void stg4_if(void* p, uint32_t a, uint32_t b, uint32_t c, uint32_t d, bool on) {
  asm volatile("{\n.reg .pred p;\nsetp.ne.u32 p, %5, 0;\n@p st.global.v4.u32 [%0], {%1,%2,%3,%4};\n}\n" ::"l"(p), "r"(a), "r"(b), "r"(c), "r"(d), "r"((uint32_t)on) : "memory");
}
template <int OFF> __device__ __forceinline__ uint32_t lds32(uint32_t a) { uint32_t v; asm volatile("ld.shared.u32 %0, [%1+%2];" : "=r"(v) : "r"(a), "n"(OFF)); return v; }
__device__ __forceinline__ uint4 lds128(uint32_t a) { uint4 v; asm volatile("ld.shared.v4.u32 {%0,%1,%2,%3}, [%4];" : "=r"(v.x), "=r"(v.y), "=r"(v.z), "=r"(v.w) : "r"(a) : "memory"); return v; }
__device__ __forceinline__ float2 lds64f(uint32_t a) { float2 v; asm volatile("ld.shared.v2.f32 {%0,%1}, [%2];" : "=f"(v.x), "=f"(v.y) : "r"(a) : "memory"); return v; }
__device__ __forceinline__ void sts64f(uint32_t a, float x, float y) { asm volatile("st.shared.v2.f32 [%0], {%1,%2};" ::"r"(a), "f"(x), "f"(y) : "memory"); }
__device__ __forceinline__ void sts32(uint32_t a, uint32_t x) { asm volatile("st.shared.u32 [%0], %1;" ::"r"(a), "r"(x) : "memory"); }
__device__ __forceinline__ void sts128(uint32_t a, uint32_t x, uint32_t y, uint32_t z, uint32_t w) { asm volatile("st.shared.v4.u32 [%0], {%1,%2,%3,%4};" ::"r"(a), "r"(x), "r"(y), "r"(z), "r"(w) : "memory"); }
__device__ __forceinline__ void stsm4(uint32_t a, uint32_t r0, uint32_t r1, uint32_t r2, uint32_t r3) {
  asm volatile("stmatrix.sync.aligned.m8n8.x4.shared.b16 [%0], {%1,%2,%3,%4};" ::"r"(a), "r"(r0), "r"(r1), "r"(r2), "r"(r3) : "memory");
}
__device__ __forceinline__ void stsm4t(uint32_t a, uint32_t r0, uint32_t r1, uint32_t r2, uint32_t r3) {
  asm volatile("stmatrix.sync.aligned.m8n8.x4.trans.shared.b16 [%0], {%1,%2,%3,%4};" ::"r"(a), "r"(r0), "r"(r1), "r"(r2), "r"(r3) : "memory");
}
__device__ __forceinline__ void ldsm4t(uint32_t* r, uint32_t a) {
  asm volatile("ldmatrix.sync.aligned.m8n8.x4.trans.shared.b16 {%0,%1,%2,%3}, [%4];" : "=r"(r[0]), "=r"(r[1]), "=r"(r[2]), "=r"(r[3]) : "r"(a) : "memory");
}
__device__ __forceinline__ uint32_t pack2(float lo, float hi) { uint32_t r; asm("cvt.rn.bf16x2.f32 %0, %1, %2;" : "=r"(r) : "f"(hi), "f"(lo)); return r; }
__device__ __forceinline__ float bf_lo(uint32_t u) { return __uint_as_float(u << 16); }
__device__ __forceinline__ float bf_hi(uint32_t u) { return __uint_as_float(u & 0xffff0000u); }
__device__ __forceinline__ float tanh_fast(float x) { float y; asm("tanh.approx.f32 %0, %1;" : "=f"(y) : "f"(x)); return y; }
__device__ __forceinline__ uint32_t hmul2(uint32_t a, uint32_t b) { uint32_t r; asm("mul.rn.bf16x2 %0, %1, %2;" : "=r"(r) : "r"(a), "r"(b)); return r; }
__device__ __forceinline__ uint32_t hfma2(uint32_t a, uint32_t b, uint32_t c) { uint32_t r; asm("fma.rn.bf16x2 %0, %1, %2, %3;" : "=r"(r) : "r"(a), "r"(b), "r"(c)); return r; }
__device__ __forceinline__ uint32_t prmt(uint32_t a, uint32_t b, uint32_t s) { return __byte_perm(a, b, s); }

__device__ __forceinline__ uint32_t ld_relaxed(const uint32_t* p) { uint32_t v; asm volatile("ld.relaxed.gpu.global.u32 %0, [%1];" : "=r"(v) : "l"(p) : "memory"); return v; }
#define AQF 3
__device__ __forceinline__ void acquire_fence() {
  if (AQF & 1) asm volatile("fence.acquire.gpu;" ::: "memory");
  if (AQF & 2) asm volatile("fence.proxy.async.global;" ::: "memory");
}
__device__ __forceinline__ uint32_t load_epoch(const Params& p, int idx, int lane) { return ld_relaxed(&p.scr->epoch[idx + (((lane * lane) & 3) == 2 ? 1 : 0)]); }
__device__ __forceinline__ void poll_counter(const uint32_t* cnt, uint32_t target) {
  uint32_t t0 = 0;
#pragma unroll 1
  while (!__all_sync(0xffffffff, ld_relaxed(cnt) == target)) spin_guard(t0);
  acquire_fence();
}

__device__ __forceinline__ int g3_block(int cb, int it) { return it < 3 ? cb * 3 + it : (it - 3 < cb * 3 ? it - 3 : it); }

template <int N, bool A_SWZ, int B_MODE, int DEPTH, class Hook, class Mid>
__device__ __forceinline__ void gemm_loop(float* d, uint32_t sb, int nkb, int sa, int pa, int b0, uint32_t boff, int relA, int relB, int tid, Hook hook, Mid mid) {
  constexpr uint32_t A_STEP = A_SWZ ? 2 : 128;
  constexpr uint32_t B_STEP = B_MODE == 0 ? 128 : (B_MODE == 1 ? 384 : 320);
  const uint64_t da0 = A_SWZ ? mkdesc(sb + OFF_A, 16, 1024, 1) : mkdesc(sb + OFF_A, 1024, 128, 0);
  const uint64_t db0 = B_MODE == 0 ? mkdesc(sb + OFF_B + boff, 8192, 1024, 1) : mkdesc(sb + OFF_B + boff, B_MODE == 1 ? 3072 : 2560, 128, 0);
  constexpr int MODA = B_MODE == 0 ? NA : NA2;
  constexpr int MODB = B_MODE == 2 ? 6 : NB;
  int sbk = b0 % MODB, pb = (b0 / MODB) & 1;
  auto boffs = [](int s_) { return B_MODE == 2 ? (s_ == 5 ? 0 : s_ + 1) * (20480 >> 4) : s_ * (B_SLOT >> 4); };
  uint32_t rel = 0;
  uint64_t da = da0 + sa * (A_SLOT >> 4), db = db0 + boffs(sbk);
  const bool doR = tid < 2 ? tid < relA : tid - 2 < relB;
  mbar_wait2(sb + BAR_AF + 8 * sa, pa, sb + BAR_BF + 8 * sbk, pb);
  if constexpr (DEPTH == 0) {
    acc_fence<N / 2>(d);
#pragma unroll 1
    for (int it = 0; it < nkb; it++) {
      WG_FENCE();
#pragma unroll
      for (int j = 0; j < 4; j++) WG<N>::ss(d, da + j * A_STEP, db + j * B_STEP, 1);
      WG_COMMIT();
      const uint32_t prel = rel;
      rel = sb + BAR_AE + 8 * (tid < 2 ? sa : sbk + NA);
      if (++sa == MODA) { sa = 0; pa ^= 1; }
      if (++sbk == MODB) { sbk = 0; pb ^= 1; }
      da = da0 + sa * (A_SLOT >> 4); db = db0 + boffs(sbk);
      const bool r0 = mbar_test(sb + BAR_AF + 8 * sa, pa), r1 = mbar_test(sb + BAR_BF + 8 * sbk, pb);
      WG_WAIT(1);
      mbar_arrive_if(prel, doR && prel != 0);
      if (it == 2) {
        WG_WAIT(0);
        mbar_expect_if(sb + BAR_AF + 8 * (tid == 8 ? 8 : tid), A_SLOT, tid < 9);
        mbar_arrive_if(rel, doR);
        rel = 0;
      }
      mid(it);
      if (it + 1 < nkb && !(r0 && r1)) {
        mbar_wait2(sb + BAR_AF + 8 * sa, pa, sb + BAR_BF + 8 * sbk, pb);
      }
    }
  } else
#pragma unroll 1
  for (int it = 0; it < nkb; it++) {
    WG_FENCE();
    WG<N>::ss(d, da, db, 1);
    const uint32_t prel = rel;
    rel = sb + BAR_AE + 8 * (tid < 2 ? sa : sbk + NA);
    if (++sa == MODA) { sa = 0; if (B_MODE) pa ^= 1; }
    if (++sbk == MODB) { sbk = 0; pb ^= 1; }
    if (DEPTH == 1) { WG_COMMIT(); WG_WAIT(1); }
    WG<N>::ss(d, da + A_STEP, db + B_STEP, 1);
    WG_COMMIT();
    WG_WAIT(1);
    if (EARLY == 1) mbar_arrive_if(prel, doR && it != 0);
    WG<N>::ss(d, da + 2 * A_STEP, db + 2 * B_STEP, 1);
    if (DEPTH == 1) WG_COMMIT();
    if (EARLY != 1) mbar_arrive_if(prel, doR && it != 0);
    const bool r0 = mbar_test(sb + BAR_AF + 8 * sa, pa), r1 = mbar_test(sb + BAR_BF + 8 * sbk, pb);
    const uint64_t da3 = da + 3 * A_STEP, db3 = db + 3 * B_STEP;
    da = da0 + sa * (A_SLOT >> 4); db = db0 + boffs(sbk);
    if (DEPTH == 1) WG_WAIT(1);
    WG<N>::ss(d, da3, db3, 1);
    WG_COMMIT();
    mid(it);
    if (it + 1 < nkb) {
      if (!(r0 && r1)) {
        mbar_wait2(sb + BAR_AF + 8 * sa, pa, sb + BAR_BF + 8 * sbk, pb);
      }
    }
    if (DEPTH == 2) WG_WAIT(1);
  }
  hook();
  WG_WAIT(0);
  acc_fence<N / 2>(d);
  mbar_arrive_if(rel, doR);
}

__device__ __forceinline__ void fold_mean(float* d, uint32_t cs, float ma, float mb, int t) {
  const uint32_t ha = pack2(-ma, -ma), hb = pack2(-mb, -mb);
  const float la = -ma - bf_lo(ha), lb = -mb - bf_lo(hb);
  const uint32_t a[4] = {t ? 0u : ha, t ? 0u : hb, t ? 0u : pack2(la, la), t ? 0u : pack2(lb, lb)};
  WG_FENCE();
  WG<192>::rst(d, a, mkdesc(cs, 0, 32, 0));
  WG_COMMIT();
}
__device__ __forceinline__ void gelu_tile(const float* d, uint32_t* z, float* st, float ra, float rb) {
  const float kA = 0.7978845608028654f, kB = 0.7978845608028654f * 0.044715f;
  const float c1a = kA * ra, c3a = kB * ra * ra * ra, c1b = kA * rb, c3b = kB * rb * rb * rb;
  float acc[8];
#pragma unroll
  for (int i = 0; i < 8; i++) acc[i] = 0.f;
#pragma unroll
  for (int j = 0; j < 24; j++) {
    float r[4];
#pragma unroll
    for (int e = 0; e < 4; e++) {
      const float v = d[4 * j + e];
      const float a = v * fmaf(v * v, e < 2 ? c3a : c3b, e < 2 ? c1a : c1b);
      r[e] = fmaf(v, tanh_fast(a), v);
      acc[e] += r[e];
      acc[4 + e] = fmaf(r[e], r[e], acc[4 + e]);
    }
    z[2 * j] = pack2(r[0], r[1]);
    z[2 * j + 1] = pack2(r[2], r[3]);
  }
  st[0] = acc[0] + acc[1]; st[1] = acc[4] + acc[5]; st[2] = acc[2] + acc[3]; st[3] = acc[6] + acc[7];
}

template <int Q> __device__ __forceinline__ void conv_load(uint32_t* a, uint32_t ab) {
  a[0] = lds32<512 * Q>(ab);       a[1] = lds32<512 * Q + 256>(ab);  a[2] = lds32<512 * Q + 16>(ab);   a[3] = lds32<512 * Q + 272>(ab);
  a[4] = lds32<512 * Q + 32>(ab);  a[5] = lds32<512 * Q + 288>(ab);  a[6] = lds32<512 * Q + 48>(ab);   a[7] = lds32<512 * Q + 304>(ab);
  a[8] = lds32<512 * Q + 64>(ab);  a[9] = lds32<512 * Q + 320>(ab);  a[10] = lds32<512 * Q + 80>(ab);  a[11] = lds32<512 * Q + 336>(ab);
  a[12] = lds32<512 * Q + 96>(ab); a[13] = lds32<512 * Q + 352>(ab); a[14] = lds32<512 * Q + 112>(ab); a[15] = lds32<512 * Q + 368>(ab);
}
template <int Q, int L> __device__ __forceinline__ void conv_step(float* d, uint32_t (*a)[16], uint32_t ab, uint64_t db) {
  WG_FENCE();
#pragma unroll
  for (int s = 0; s < 4; s++) WG<128 - 16 * Q>::rs(d, a[Q] + 4 * s, db + s + 16 * Q);
  WG_COMMIT();
  if (CPIN) WG_WAIT(1);
  if (L >= 0) conv_load<(L >= 0 ? L : 0)>(a[L >= 0 ? L : 0], ab);
  if (CW0 || Q == 0) WG_WAIT(0);
}

__device__ __forceinline__ int seg_col(int cb, int h) { return (cb >> 1) * 320 + (cb & 1) * 32 + h * 64; }
__device__ __forceinline__ void final_load_x(uint32_t (*xw)[10], uint32_t xt, int cb, int h, int w, int lane) {
  const int g = lane >> 2, t = lane & 3, cc = seg_col(cb, h) >> 3;
  const int c0 = cc + t, c1 = c0 + 24, c2 = cc + 16 - 6 * h + (t >> 1);
  const uint32_t r0 = xt + (w * 16 + g) * 128;
#pragma unroll
  for (int r = 0; r < 2; r++) {
    const uint4 u = lds128(r0 + r * 1024 + (c0 >> 3) * A_SLOT + (((c0 ^ g) & 7) << 4)), v = lds128(r0 + r * 1024 + (c1 >> 3) * A_SLOT + (((c1 ^ g) & 7) << 4));
    const float2 z = lds64f(r0 + r * 1024 + (c2 >> 3) * A_SLOT + (((c2 ^ g) & 7) << 4) + (t & 1) * 8);
    xw[r][0] = u.x; xw[r][1] = u.y; xw[r][2] = u.z; xw[r][3] = u.w;
    xw[r][4] = v.x; xw[r][5] = v.y; xw[r][6] = v.z; xw[r][7] = v.w;
    xw[r][8] = __float_as_uint(z.x); xw[r][9] = __float_as_uint(z.y);
  }
}
__device__ __forceinline__ void final_s_early(uint32_t (*sw)[10], const uint32_t (*xw)[10], uint32_t ya, float2 s0, float2 s1) {
  const uint32_t r2[2] = {pack2(s0.y, s0.y), pack2(s1.y, s1.y)};
  const float na = -s0.x * bf_lo(r2[0]), nb = -s1.x * bf_lo(r2[1]);
  const uint32_t n2[2] = {pack2(na, na), pack2(nb, nb)};
#pragma unroll
  for (int j = 0; j < 10; j += 2) {
    uint32_t y[4];
    if (j < 4 || j == 8) ldsm4t(y, ya + (j < 4 ? j : 4) * 1024);
#pragma unroll
    for (int e = 0; e < 4; e++) {
      const uint32_t xn = hfma2(xw[e & 1][j + (e >> 1)], r2[e & 1], n2[e & 1]);
      sw[e & 1][j + (e >> 1)] = (j < 4 || j == 8) ? hmul2(xn, y[e]) : xn;
    }
  }
}
__device__ __forceinline__ bool final_late(uint32_t* y, uint32_t ya) {
  ldsm4t(y, ya + 6144);
  ldsm4t(y + 4, ya + 8192);
  uint32_t zero = 0;
#pragma unroll
  for (int e = 0; e < 8; e++) zero |= (y[e] - 0x00010001u) & ~y[e];
  return (zero & 0x80008000u) == 0;
}
__device__ __forceinline__ bool bar_all(int id, int n, bool c) {
  uint32_t r;
  asm volatile("{\n.reg .pred p, q;\nsetp.ne.u32 p, %3, 0;\nbar.red.and.pred q, %1, %2, p;\nselp.u32 %0, 1, 0, q;\n}\n" : "=r"(r) : "r"(id), "r"(n), "r"((uint32_t)c) : "memory");
  return r;
}
__device__ __forceinline__ void final_out(const float* d, const uint32_t (*xw)[10], const uint32_t (*sw)[10], float ra, float rb, __nv_bfloat16* o0, int h, int t) {
  const float ca = 0.25f * ra, cb = 0.25f * rb;
  uint32_t o[2][10];
#pragma unroll
  for (int j = 0; j < 10; j++) {
#pragma unroll
    for (int r = 0; r < 2; r++) {
      const float h0 = d[4 * j + 2 * r] * (r ? cb : ca), h1 = d[4 * j + 2 * r + 1] * (r ? cb : ca);
      o[r][j] = hfma2(pack2(fmaf(h0, tanh_fast(h0), h0), fmaf(h1, tanh_fast(h1), h1)), sw[r][j], xw[r][j]);
      __nv_bfloat16* q = o0 + r * 8 * kD;
      if (j == 3) stg4_if(q + t * 8, o[r][0], o[r][1], o[r][2], o[r][3], true);
      if (j == 7) stg4_if(q + 192 + t * 8, o[r][4], o[r][5], o[r][6], o[r][7], true);
      if (j == 9) asm volatile("st.global.v2.u32 [%0], {%1,%2};" ::"l"(q + 128 - 48 * h + t * 4), "r"(o[r][8]), "r"(o[r][9]) : "memory");
    }
  }
}

struct Taps { uint4 r0, r1; uint32_t n0, n1, dd; };
__device__ __forceinline__ void load_taps(Taps& k, const Params& p, int ch, int tid) {
  const uint4* kp = (const uint4*)(p.ssmk + (size_t)ch * kS);
  k.r0 = ldg4(kp + tid); k.r1 = ldg4(kp + 128 + tid);
  k.n0 = ldg1(kp + tid + 1); k.n1 = tid < 127 ? ldg1(kp + 129 + tid) : 0u;
  k.dd = __bfloat16_as_ushort(p.ssmD[ch]);
}
__device__ __forceinline__ void load_convx(const Params& p, uint32_t cv, uint32_t bar, int ch) {
  mbar_expect(bar, 4096);
  bulk_g2s(cv, p.scr->kvx + (size_t)ch * 4096, 2048, bar);
  bulk_g2s(cv + XB_PL, p.scr->kvx + (size_t)ch * 4096 + 2048, 2048, bar);
}
#define CW 3
#define CSTAMP(j)
__device__ __forceinline__ void zero_pads(uint32_t cv, int lane) {
  if (lane < 8) sts128(cv + (lane >> 2) * XB_PL + 2048 + (lane & 3) * 16, 0, 0, 0, 0);
  else if (lane < 12) sts128(cv + ((lane & 2) ? CV_KO : CV_KE) + (lane & 1) * 16, 0, 0, 0, 0);
  fence_async_smem();
  __syncwarp();
}
__device__ __forceinline__ int y_row(int c, uint32_t par) {
  const int hf = c >= 320, cc = c - hf * 320, u = cc >> 6, cb = hf * 2 + ((cc >> 5) & 1);
  if (u == 2) return cb * 96 + ((cc >> 4) & 1) * 48 + 32 + (cc & 1) + ((cc >> 1) & 1) * 8 + ((cc >> 2) & 3) * 2;
  return (u < 2 ? cb * 96 + u * 48 : 384 + par * 256 + cb * 64 + (u - 3) * 32) + (cc & 1) + ((cc >> 1) & 3) * 8 + ((cc >> 3) & 3) * 2;
}
__device__ __forceinline__ void z_store(const Params& p, uint32_t src, int rb, int cb, int q) {
  uint8_t* dst = p.scr->z2 + (size_t)(cb * 32 + q * 16 + (rb >> 2)) * B_SLOT + (rb & 3) * 6144;
  bulk_s2g(dst, src + q * 12288, 6144);
  bulk_s2g(dst + 8 * B_SLOT, src + q * 12288 + 6144, 6144);
  asm volatile("cp.async.bulk.commit_group;\ncp.async.bulk.wait_group 0;" ::: "memory");
}
__device__ __forceinline__ void y_store(const Params& p, uint32_t sb, int h, int ch, uint32_t par) {
  uint8_t* dst = p.scr->y + (size_t)y_row(ch, par) * 4096;
  if (elect_one()) {
    bulk_s2g(dst, sb + OFF_A + 9 * A_SLOT + h * 4096, 4096);
    asm volatile("cp.async.bulk.commit_group;\ncp.async.bulk.wait_group 0;" ::: "memory");
  }
  __syncwarp();
}
__device__ __forceinline__ void conv_service(const Params& p, uint32_t sb, int h, int ch, bool first) {
  bar_sync(NB_WGA + 8 + h, 160);
  const bool now = !first || __all_sync(0xffffffff, mbar_test(sb + BAR_KV, 0));
  if (now) { if (REFENCE & 4) acquire_fence(); if (elect_one()) load_convx(p, sb + OFF_CV + (1 - h) * CV_SZ, sb + BAR_XF + 8 * h, ch + 128); }
  bar_sync(NB_WGA + 8 + h, 160);
  y_store(p, sb, h, ch, 0);
  if (!now) {
    mbar_wait(sb + BAR_KV, 0);
    if (REFENCE & 4) acquire_fence();
    if (elect_one()) load_convx(p, sb + OFF_CV + (1 - h) * CV_SZ, sb + BAR_XF + 8 * h, ch + 128);
  }
}
__device__ __forceinline__ uint32_t y_tile(int h) { return OFF_CV + (1 - h) * 13312; }
__device__ __forceinline__ void load_late_y(const Params& p, uint32_t sb, int h, int rb, int cb, uint32_t par) {
  mbar_expect(sb + BAR_YL + 16 * h, 4096);
  tma2d(sb + y_tile(h) + 6144, &p.tmY, rb * 64, 384 + par * 256 + cb * 64 + h * 32, sb + BAR_YL + 16 * h);
  tma2d(sb + y_tile(h) + 8192, &p.tmY, rb * 64, 400 + par * 256 + cb * 64 + h * 32, sb + BAR_YL + 16 * h);
}
__device__ __forceinline__ void held_service(const Params& p, uint32_t sb, int h, int ch, int rb, int cb, uint32_t tag, int lane) {
#pragma unroll 1
  for (int i = 0; i < 8; i++) sts128(sb + OFF_A + 9 * A_SLOT + h * 4096 + i * 512 + lane * 16, 0, 0, 0, 0);
  fence_async_smem();
  __syncwarp();
  y_store(p, sb, h, ch, ~tag & 1);
  mbar_wait(sb + BAR_YT, 1);
  if (REFENCE & 4) acquire_fence();
  bar_sync(NB_WGA + 8 + h, 160);
  bar_sync(NB_WGA + 8 + h, 160);
  uint8_t* dst = p.scr->y + (size_t)y_row(ch, tag & 1) * 4096;
  if (elect_one()) {
    bulk_s2g(dst, sb + OFF_A + 9 * A_SLOT + h * 4096, 4096);
    asm volatile("cp.async.bulk.commit_group;" ::: "memory");
    mbar_expect(sb + BAR_XF + 8 * h, 6144);
#pragma unroll 1
    for (int i = 0; i < 3; i++) tma2d(sb + y_tile(h) + i * 2048, &p.tmY, rb * 64, cb * 96 + h * 48 + i * 16, sb + BAR_XF + 8 * h);
  }
  mbar_wait(sb + BAR_AE + 8 * (LL_AT - 1), 1);
  if (elect_one()) { load_late_y(p, sb, h, rb, cb, tag & 1); asm volatile("cp.async.bulk.wait_group 0;" ::: "memory"); }
}
__device__ __forceinline__ void conv_worker(const Params& p, Taps& k, uint32_t cv, uint32_t yb0,
                                            uint32_t xbar, int nbar, int ch0, int n, uint32_t holdbar, int w, int lane,
                                            int tid, int st0, int rb, int cb) {
  const int g = lane >> 2, t = lane & 3, w0 = w & 1, w1 = w >> 1;
  const uint32_t ab = cv + ((g & 1) ? CV_KE : CV_KO) + 32 + 2 * (64 * w0 + 8 * w1 + ((g - 15) & ~1) + 2 * t);
  const uint32_t scA = cv + (w1 ? CV_KO : CV_KE) + 32, scB = scA + 2048;
  const int dl = (t >> 1) ^ 1;
  if (n == 2 || CPRE0 == 2) mbar_wait(xbar, 0);
  STAMPW(st0 + 3);
#pragma unroll 1
  for (int i = 0; i < n; i++) {
    if (tid == 0) {
      k.r0.x = (k.r0.x & 0xffff0000u) | (pack2(bf_lo(k.r0.x) + bf_lo(k.dd), 0.f) & 0xffffu);
      sts32(cv + CV_KO + 28, k.r0.x << 16);
    }
    sts128(cv + CV_KE + 32 + tid * 16, k.r0.x, k.r0.y, k.r0.z, k.r0.w);
    sts128(cv + CV_KO + 32 + tid * 16, prmt(k.r0.x, k.r0.y, 0x5432), prmt(k.r0.y, k.r0.z, 0x5432), prmt(k.r0.z, k.r0.w, 0x5432), prmt(k.r0.w, k.n0, 0x5432));
    sts128(cv + CV_KE + 2080 + tid * 16, k.r1.x, k.r1.y, k.r1.z, k.r1.w);
    sts128(cv + CV_KO + 2080 + tid * 16, prmt(k.r1.x, k.r1.y, 0x5432), prmt(k.r1.y, k.r1.z, 0x5432), prmt(k.r1.z, k.r1.w, 0x5432), prmt(k.r1.w, k.n1, 0x5432));
    if (i + 1 < n) load_taps(k, p, ch0 + (i + 1) * 128, tid);
    bar_sync(nbar, 128);
    CSTAMP(0);
    const uint64_t db = mkdesc(cv + (i & 0x1000), XB_PL, 128, 0);
    float d[64];
    uint32_t a[8][16];
    if (CPRE0 == 1 && i == 0) mbar_wait(xbar, 0);
    conv_load<7>(a[7], ab); conv_load<6>(a[6], ab); conv_load<5>(a[5], ab); conv_load<4>(a[4], ab);
#pragma unroll
    for (int j = 0; j < 64; j++) d[j] = 0.f;
    mbar_wait(xbar, i & 1);
    if (i + 1 == n) mbar_wait(holdbar, 1);
    CSTAMP(1);
    conv_step<7, -1>(d, a, ab, db); conv_step<6, -1>(d, a, ab, db); conv_step<5, -1>(d, a, ab, db); conv_step<4, 3>(d, a, ab, db);
    conv_step<3, 2>(d, a, ab, db);
    conv_step<2, 1>(d, a, ab, db);
    conv_step<1, 0>(d, a, ab, db);
    conv_step<0, -1>(d, a, ab, db);
    acc_fence<64>(d);
    CSTAMP(2);
    bar_sync(nbar + 8, 160);
    float E[16][2];
#pragma unroll
    for (int j = 0; j < 15; j++) { E[j][0] = d[4 * j] + d[4 * j + 6]; E[j][1] = d[4 * j + 1] + d[4 * j + 7]; }
    E[15][0] = d[60]; E[15][1] = d[61];
    if (w0 == 0) {
#pragma unroll
      for (int j = 8; j < 16; j++) sts64f(scA + (j - 8) * 256 + lane * 8, E[j][0], E[j][1]);
    } else {
      const uint32_t a = scB - dl * 256 + (lane ^ 2) * 8;
#pragma unroll
      for (int j = 1; j < 8; j++) sts64f(a + j * 256, E[j][0], E[j][1]);
      sts64f(scB + (dl ? 7 * 256 : 0) + (lane ^ 2) * 8, dl ? E[8][0] : E[0][0], dl ? E[8][1] : E[0][1]);
    }
    bar_sync(nbar, 128);
    CSTAMP(3);
    uint32_t pk[8];
    if (w0 == 0) {
#pragma unroll
      for (int j = 0; j < 8; j++) { const float2 v = lds64f(scB + j * 256 + lane * 8); pk[j] = pack2(E[j][0] + v.x, E[j][1] + v.y); }
    } else {
      const uint32_t a0 = scA - dl * 256 + (lane ^ 2) * 8;
#pragma unroll
      for (int j = 9; j < 16; j++) { const float2 v = lds64f(a0 + (j - 8) * 256); pk[j - 8] = pack2(E[j][0] + v.x, E[j][1] + v.y); }
      const float2 v = lds64f(scA + (dl ? 7 * 256 : 0) + (lane ^ 2) * 8);
      pk[0] = pack2((dl ? 0.f : E[8][0]) + v.x, (dl ? 0.f : E[8][1]) + v.y);
    }
    CSTAMP(4);
    if (i + 1 == n) {
#pragma unroll
      for (int j = 0; j < 8; j++) pk[j] = ~pk[j];
    }
    const int c1 = (w0 ? 35 : 95) - lane, c0 = (w0 && lane < 4) ? c1 - 32 : c1 + 32;
    stsm4t(yb0 + 128 * (c0 & 31) + (((2 * (c0 >> 5) + w1) ^ (c0 & 7)) << 4), pk[0], pk[1], pk[2], pk[3]);
    stsm4t(yb0 + 128 * (c1 & 31) + (((2 * (c1 >> 5) + w1) ^ (c1 & 7)) << 4), pk[4], pk[5], pk[6], pk[7]);
    fence_async_smem();
    bar_sync(nbar + 8, 160);
    CSTAMP(5);
    STAMPW(st0 + i);
    if (n == 2 && i == 0) {
      const int u = (tid >> 3) % 5, kg = rb * 3 + (tid < 120 ? (tid >> 3) / 5 : 0), c = u < 4 ? (u >> 1) * 10 + (u & 1) * 4 : 8, o2 = u < 4 ? 2 : 10;
      const uint4* wp = (const uint4*)p.wout + (uint32_t)((kg * 8 + (tid & 7)) * (kD / 8) + (seg_col(cb, 0) >> 3) + (u < 4 ? (u >> 1) * 8 + (u & 1) * 24 : 16));
      const uint4 w0 = ldg4(wp), w1 = ldg4(wp + 1), w2 = ldg4(wp + 2), w3 = ldg4(wp + 3);
      uint8_t* dst = p.scr->wo + (uint32_t)(cb * (12 * 20480) + kg * 2560 + c * 128 + (tid & 7) * 16);
      const bool f = u < 4, on = tid < 120;
      stg4_if(dst, w0.x, f ? w1.x : w0.z, f ? w2.x : w1.x, f ? w3.x : w1.z, on);
      stg4_if(dst + 128, w0.y, f ? w1.y : w0.w, f ? w2.y : w1.y, f ? w3.y : w1.w, on);
      stg4_if(dst + o2 * 128, f ? w0.z : w2.x, f ? w1.z : w2.z, f ? w2.z : w3.x, w3.z, on);
      stg4_if(dst + o2 * 128 + 128, f ? w0.w : w2.y, f ? w1.w : w2.w, f ? w2.w : w3.y, w3.w, on);
      bar_arrive(NB_WO, 160);
    }
  }
}

struct KvRegs { uint32_t k[11], v[8]; uint4 sh; };
__device__ __forceinline__ void kv_load(KvRegs& q, const __nv_bfloat16* kp, const __nv_bfloat16* vp, const __nv_bfloat16* sp, bool halo) {
#pragma unroll
  for (int i = 0; i < 11; i++) q.k[i] = (i >= 3 || halo) ? ldg1(kp + i * kD) : 0u;
#pragma unroll
  for (int i = 0; i < 8; i++) q.v[i] = ldg1(vp + i * kD);
  q.sh = ldg4(sp);
}
__device__ __forceinline__ void kv_unit(const KvRegs& q, uint32_t oa) {
  const uint32_t w0 = prmt(q.sh.x, q.sh.z, 0x5410), w1 = prmt(q.sh.x, q.sh.z, 0x7632), w2 = prmt(q.sh.y, q.sh.w, 0x5410), w3 = prmt(q.sh.y, q.sh.w, 0x7632);
  uint32_t r[8];
#pragma unroll
  for (int i = 0; i < 8; i++) r[i] = hmul2(hfma2(q.k[i + 3], w0, hfma2(q.k[i + 2], w1, hfma2(q.k[i + 1], w2, hmul2(q.k[i], w3)))), q.v[i]);
  sts128(oa, prmt(r[7], r[6], 0x5410), prmt(r[5], r[4], 0x5410), prmt(r[3], r[2], 0x5410), prmt(r[1], r[0], 0x5410));
  sts128(oa + 2048, prmt(r[7], r[6], 0x7632), prmt(r[5], r[4], 0x7632), prmt(r[3], r[2], 0x7632), prmt(r[1], r[0], 0x7632));
}

__device__ __forceinline__ void gather_colsum(const Params& p, uint32_t sb, int cb, int part, uint32_t tag, int lane) {
  uint4 v[3];
  uint32_t t0 = 0;
#pragma unroll 1
  while (true) {
    bool ok = true;
#pragma unroll
    for (int i = 0; i < 3; i++) {
      v[i] = ld_ll4(&p.scr->colsum[(part ? 0 : 768) + cb * 192 + i * 64 + lane * 2]);
      ok = ok && v[i].y == tag && v[i].w == tag;
    }
    if (__all_sync(0xffffffff, ok)) break;
    spin_guard(t0);
  }
#pragma unroll
  for (int i = 0; i < 3; i++) {
    const uint32_t hi = pack2(__uint_as_float(v[i].x), __uint_as_float(v[i].z)), ca = sb + OFF_CS + (1 - part) * 768 + i * 256 + (lane >> 2) * 32 + (lane & 3) * 4;
    sts32(ca, hi);
    sts32(ca + 16, pack2(__uint_as_float(v[i].x) - bf_lo(hi), __uint_as_float(v[i].z) - bf_hi(hi)));
  }
  __syncwarp();
  if (lane == 0) mbar_arrive(sb + BAR_ST + 8 * part);
}

__device__ __forceinline__ void helper_cta(const Params& p, uint32_t sb, int cb, int warp, int lane) {
  constexpr int NS = 9, ONES = NS * B_SLOT, BF = ONES + 256, BE = BF + 8 * NS;
  if (warp < NS && elect_one()) {
    mbar_init(sb + BF + 8 * warp, 1); mbar_init(sb + BE + 8 * warp, 1);
    fence_async_smem();
    if (warp == 0) { mbar_expect(sb + BF, B_SLOT); tma3d(sb, &p.tmW, 0, 0, 12 + cb * 3, sb + BF); }
  }
  if (warp == 15) { sts32(sb + ONES + lane * 4, 0x3f803f80u); sts32(sb + ONES + 128 + lane * 4, 0x3f803f80u); fence_async_smem(); }
  __syncthreads();
  if (warp == 4) {
    int s = 1, ph = 1;
    uint32_t tp = clock() + HP0;
#pragma unroll 1
    for (int it = 1; it < 20; it++) {
      if (HPD && it >= 10) pace(tp, HPD);
      mbar_wait(sb + BE + 8 * s, ph);
      if (elect_one()) { mbar_expect(sb + BF + 8 * s, B_SLOT); tma3d(sb + s * B_SLOT, &p.tmW, 0, (it < 10 ? it : it - 10) * 64, (it < 10 ? 12 : 0) + cb * 3, sb + BF + 8 * s); }
      if (++s == NS) { s = 0; ph ^= 1; }
    }
  } else if (warp < 4) {
    const uint32_t tag = load_epoch(p, 128 + cb, lane) + 1;
    const uint64_t db = mkdesc(sb + ONES, 128, 128, 0);
    uint2* dst = p.scr->colsum + cb * 192 + warp * 16 + (lane >> 2);
    if ((lane & 3) == 0) {
#pragma unroll 1
      for (int j = 0; j < 12; j++) st_ll2(dst + (j < 6 ? 768 : 0) + ((j % 6) >> 1) * 64 + (j & 1) * 8, 0, 0);
    }
    int s = 0, ph = 0;
#pragma unroll 1
    for (int part = 0; part < 2; part++) {
      float d[12];
#pragma unroll
      for (int i = 0; i < 12; i++) d[i] = 0.f;
#pragma unroll 1
      for (int it = 0; it < 10; it++) {
        mbar_wait(sb + BF + 8 * s, ph);
        const uint64_t da = mkdesc(sb + s * B_SLOT, 8192, 1024, 1);
        WG_FENCE();
#pragma unroll
        for (int j = 0; j < 12; j++) wgmma_colsum(d + 4 * (j % 3), da + (j % 3) * 512 + (j / 3) * 128, db);
        WG_COMMIT();
        WG_WAIT(1);
        mbar_arrive_if(sb + BE + 8 * (s == 0 ? NS - 1 : s - 1), threadIdx.x == 0 && (it | part) != 0);
        if (++s == NS) { s = 0; ph ^= 1; }
      }
      WG_WAIT(0);
      acc_fence<12>(d);
      if ((lane & 3) == 0) {
#pragma unroll
        for (int j = 0; j < 6; j++) st_ll2(dst + (part ? 0 : 768) + (j >> 1) * 64 + (j & 1) * 8, __float_as_uint(d[2 * j]), tag);
      }
      STAMPW(1 + part);
    }
    if (threadIdx.x == 0) *(volatile uint32_t*)&p.scr->epoch[128 + cb] = tag;
  }
}

__global__ void __launch_bounds__(512, 1) fused_kernel(const __grid_constant__ Params p) {
  extern __shared__ __align__(1024) uint8_t smem[];
  const int warp = __shfl_sync(0xffffffff, (int)(threadIdx.x >> 5), 0);
  const int lane = threadIdx.x & 31, tid = threadIdx.x & 127;
  const uint32_t sb = __shfl_sync(0xffffffff, (uint32_t)__cvta_generic_to_shared(smem), 0);
  const uint32_t tstart = clock();
  if (elect_one()) {
    if (warp < 5) asm volatile("prefetch.tensormap [%0];" ::"l"(&p.tmX + warp) : "memory");
    mbar_init(sb + OFF_BAR + 8 * warp, 1); mbar_init(sb + OFF_BAR + 128 + 8 * warp, 1); mbar_init(sb + OFF_BAR + 256 + 8 * warp, 2);
    asm volatile("fence.mbarrier_init.release.cluster;" ::: "memory");
  }
  int b = blockIdx.x;
  if (p.by_smid) asm volatile("mov.u32 %0, %%smid;" : "=r"(b));
  b = __shfl_sync(0xffffffff, b, 0);
  const int tp = b >> 1, t7 = (tp - 32) / 7;
  const int lin = tp < 32 ? ((tp & 7) ? (tp & 7) * 16 : 8) + (tp >> 3) * 2 + (b & 1)
                          : (tp < 60 ? (tp - 31 - t7 * 7) * 16 + 8 + t7 * 2 + (b & 1) : (tp < 62 ? -1 : b - 124));
  const int hcb = b & 3;
  if (lin < 0) { helper_cta(p, sb, hcb, warp, lane); return; }
  const int cb = ((lin >> 4) & 1) * 2 + ((lin >> 1) & 1), rb = (lin >> 5) * 8 + ((lin >> 2) & 3) * 2 + (lin & 1);
  const int zs0 = 4 - (cb & 2);
  const int chb = (cb >> 1) * 320 + rb * 2 + (cb & 1);
  if (warp == 0 && elect_one()) {
    mbar_expect(sb + BAR_AF, A_SLOT);
    tma_rows(sb + OFF_A, &p.tmX, 0, rb, sb + BAR_AF);
    mbar_expect(sb + BAR_BF, B_SLOT);
    tma3d(sb + OFF_B, &p.tmW, 0, 0, 12 + cb * 3, sb + BAR_BF);
  }
  if (warp == 1) STAMP(31);
  if (sb & 1023) die();
  __syncthreads();

  if (warp >= 12) {
    asm volatile("setmaxnreg.dec.sync.aligned.u32 32;");
    const uint32_t epoch = load_epoch(p, lin, lane);
    if (warp == 12) {
#pragma unroll 1
      for (int i = 1; i < NA; i++) {
        if (elect_one()) {
          mbar_expect(sb + BAR_AF + 8 * i, A_SLOT);
          tma_rows(sb + OFF_A + i * A_SLOT, &p.tmX, i * 64, rb, sb + BAR_AF + 8 * i);
          if (i < NB) { mbar_expect(sb + BAR_BF + 8 * i, B_SLOT); tma3d(sb + OFF_B + i * B_SLOT, &p.tmW, 0, i * 64, 12 + cb * 3, sb + BAR_BF + 8 * i); }
        }
      }
      STAMP(32);
      uint32_t kvt;
      {
        const int tb = rb * 2 + (cb & 1);
        kvt = __shfl_sync(0xffffffff, (ld_relaxed(p.scr->cnt + CNT_KV + (cb >> 1)) & ~63u) + 64, 0);
        {
          uint32_t tp = tstart;
          pace(tp, KV_T0);
          mbar_arrive_if(sb + BAR_KV + 8, lane == 0);
        }
        if (ST_YIELD) mbar_wait2(sb + BAR_XS, 0, sb + BAR_ST, 0);
#pragma unroll 1
        for (int u = 0; u < 5; u++) {
          mbar_wait(sb + BAR_KU + 8 * u, 0);
          fence_async_smem();
          if (elect_one()) {
            asm volatile("cp.async.bulk.tensor.3d.global.shared::cta.bulk_group [%0, {%2, %3, %4}], [%1];\ncp.async.bulk.commit_group;" ::"l"(&p.tmKV),
                         "r"(sb + OFF_CV + CV_SZ + (u < 3 ? u : u - 3) * 4096), "r"((63 - tb) * 16), "r"((cb >> 1) * 160 + u * 32), "r"(0) : "memory");
            if (u == 1 || u == 4) asm volatile("cp.async.bulk.wait_group 0;" ::: "memory");
            if (u == 1) { mbar_arrive(sb + BAR_KU); red_release(p.scr->cnt + CNT_KV + (cb >> 1)); }
          }
          __syncwarp();
          if (u == 1) {
            STAMP(35);
            if (PFT) { const char* q = (const char*)p.ssmk + chb * 4096 + lane * 128; prefetch_l2(q); prefetch_l2(q + 64 * 4096); }
          }
        }
        zero_pads(sb + OFF_CV + CV_SZ, lane);
        if (elect_one()) { mbar_arrive(sb + BAR_KU + 8); red_release(p.scr->cnt + CNT_KV + 2 + (cb >> 1)); }
        STAMP(30);
        if (lane < 24) {
          const char* r = (const char*)p.wout + (rb * 24 + lane) * (kD * 2) + (cb >> 1) * 640 + (cb & 1) * 384;
          prefetch_l2(r); prefetch_l2(r + 128); prefetch_l2(r + 256 - (cb & 1) * 384);
        }
      }
      poll_counter(p.scr->cnt + CNT_KV + 2 + (cb >> 1), kvt);
      if (elect_one()) mbar_arrive(sb + BAR_KV);
      STAMP(34);
      {
        const char* q = (const char*)p.wsp + (cb * 512 + rb * 16 + (lane >> 1)) * (kS * 2) + (lane & 1) * 128;
        uint32_t tp = clock();
#pragma unroll 1
        for (int i = LEAD / 2; i < WSP_N; i++) {
          prefetch_l2(q + i * 256);
          if (i == Z1_AT) {
            poll_counter(p.scr->cnt + CNT_Z1 + (cb >> 1), (epoch + 1) * 64);
            if (elect_one()) mbar_arrive(sb + BAR_Z1);
            STAMP(24);
          }
          pace(tp, WSP_D);
        }
      }
      const uint32_t tag = epoch + 1;
      if (HPC) {
        bar_sync(NB_Z2, 160);
        if (elect_one()) bulk_s2g(p.scr->h + (size_t)(rb * 12 + cb * 3) * A_SLOT, sb + OFF_A + 5 * A_SLOT, HPC * A_SLOT);
      }
      mbar_wait(sb + BAR_G2, 0);
      if (elect_one()) {
        bulk_s2g(p.scr->h + (size_t)(rb * 12 + cb * 3 + HPC) * A_SLOT, sb + OFF_A + (5 + HPC) * A_SLOT, (3 - HPC) * A_SLOT);
        asm volatile("cp.async.bulk.commit_group;\ncp.async.bulk.wait_group 0;" ::: "memory");
        red_release(&p.scr->hcnt[(rb >> HGRP) * 32]);
      }
      __syncwarp();
      STAMP(20);
      mbar_wait(sb + BAR_AE + 56, 0);
      STAMP(39);
      poll_counter(&p.scr->hcnt[(rb >> HGRP) * 32], tag * (4 << HGRP));
      STAMP(37);
      if (elect_one()) {
        uint32_t tp = clock();
#pragma unroll 1
        for (int it = 3; it < 12; it++) {
          if (HPACE && it > 3) { tp += HPACE; while ((int32_t)((uint32_t)clock() - tp) < 0) {} }
          bulk_g2s(sb + OFF_A + ((it + 5) % 9) * A_SLOT, p.scr->h + (size_t)(rb * 12 + g3_block(cb, it)) * A_SLOT, A_SLOT, sb + BAR_AF + 8 * ((it + 5) % 9));
        }
      }
      STAMP(21);
    } else if (warp == 13) {
      int s = 0, ph = 0;
#pragma unroll 1
      for (int it = NB; it < 20; it++) {
        mbar_wait(sb + BAR_BE + 8 * s, ph);
        if (elect_one()) { mbar_expect(sb + BAR_BF + 8 * s, B_SLOT); tma3d(sb + OFF_B + s * B_SLOT, &p.tmW, 0, (it < 10 ? it : (it + zs0) % 10) * 64, (it < 10 ? 12 : 0) + cb * 3, sb + BAR_BF + 8 * s); }
        STAMP2(32 + it);
        if (++s == NB) { s = 0; ph ^= 1; }
      }
      mbar_wait(sb + BAR_XC, 0);
#pragma unroll 1
      for (int i = 0; i < LEAD; i++) {
        mbar_wait(sb + BAR_AE + 8 * i, 0);
        if (elect_one()) { mbar_expect(sb + BAR_AF + 8 * i, A_SLOT); tma_rows(sb + OFF_A + i * A_SLOT, &p.tmWsp, i * 64, rb, sb + BAR_AF + 8 * i); }
      }
      if (ZP_AT < 0) mbar_wait(sb + BAR_ZP, 0);
      poll_counter(p.scr->zcnt + (cb >> ZSH) * 32, (epoch + 1) * (32 << ZSH));
      STAMP(22);
      int sa = LEAD, pa = 0, ia = LEAD;
#pragma unroll 1
      for (int it = 0; it < 32; it++) {
        if (it == ZP_AT) mbar_wait(sb + BAR_ZP, 0);
        if (it == 16) { mbar_wait(sb + BAR_Z1, 1); if (REFENCE & 1) acquire_fence(); }
        mbar_wait2(sb + BAR_BE + 8 * s, ph, sb + BAR_AE + 8 * sa, pa);
        if (elect_one()) {
          mbar_expect(sb + BAR_BF + 8 * s, B_SLOT);
          bulk_g2s(sb + OFF_B + s * B_SLOT, p.scr->z2 + (size_t)(cb * 32 + it) * B_SLOT, B_SLOT, sb + BAR_BF + 8 * s);
        }
#pragma unroll 1
        for (int j = (it < RAMP ? 0 : (it == 4 ? 1 + RAMP : 1)); j > 0 && ia < 32; j--, ia++) {
          if (it == 4) mbar_wait(sb + BAR_AE + 8 * sa, pa);
          if (elect_one()) { mbar_expect(sb + BAR_AF + 8 * sa, A_SLOT); tma_rows(sb + OFF_A + sa * A_SLOT, &p.tmWsp, ia * 64, rb, sb + BAR_AF + 8 * sa); }
          if (++sa == NA2) { sa = 0; pa ^= 1; }
        }
        STAMP2(52 + it);
        if (++s == NB) { s = 0; ph ^= 1; }
      }
      mbar_wait(sb + BAR_WO, 0);
      if (REFENCE & 2) acquire_fence();
#pragma unroll 1
      for (int it = 0; it < 12; it++) {
        if (it < 6) mbar_wait(sb + BAR_BE + 8 * ((0x110443 >> (4 * it)) & 7), it < 3 ? 1 : 0);
        else mbar_wait(sb + BAR_BE + 8 * s, ph);
        if (elect_one()) {
          mbar_expect(sb + BAR_BF + 8 * s, 20480);
          bulk_g2s(sb + OFF_B + (s == 5 ? 0 : s + 1) * 20480, p.scr->wo + (size_t)(cb * 12 + g3_block(cb, it)) * 20480, 20480, sb + BAR_BF + 8 * s);
        }
        STAMP2(84 + it);
        if (++s == 6) { s = 0; ph ^= 1; }
      }
    } else if (warp == 14) {
      const uint32_t tag = epoch + 1;
      mbar_wait(sb + BAR_AF + 8 * (NA - 1), 0);
#pragma unroll 1
      for (int part = 0; part < 2 - CS1BY; part++) {
        gather_colsum(p, sb, cb, part, tag, lane);
        if (part == 0) STAMP(27);
      }
      if (!CS1BY) STAMP(38);
      bar_sync(NB_Z, ZORD ? 160 : 96);
      if (elect_one()) {
        z_store(p, sb + OFF_A + zs0 * A_SLOT, rb, cb, 0);
        STAMP(7);
        red_release(p.scr->zcnt + (cb >> ZSH) * 32);
      }
      STAMP(25);
      bar_sync(NB_Z2, 96);
      if (elect_one()) {
        z_store(p, sb + OFF_A + zs0 * A_SLOT, rb, cb, 1);
        mbar_arrive(sb + BAR_ZP);
        red_release(p.scr->cnt + CNT_Z1 + (cb >> 1));
      }
      STAMP(28);
      mbar_wait(sb + BAR_AE + 72, 0);
      conv_service(p, sb, 0, chb + 64, true);
      bar_sync(NB_WO, 160);
      bar_sync(NB_CD, 64);
      if (elect_one()) { red_release(p.scr->cnt + CNT_WO + cb); red_relaxed(p.scr->cnt + CNT_Y + (cb >> 1)); }
      STAMP(49);
      poll_counter(p.scr->cnt + CNT_WO + cb, tag * 32);
      if (elect_one()) mbar_arrive(sb + BAR_WO);
      STAMP(46);
      held_service(p, sb, 0, chb + 192, rb, cb, tag, lane);
    } else {
      const uint32_t tag = epoch + 1;
      sts32(sb + OFF_BIAS + lane * 4, ldg1(p.bsp + (lane >> 3) * 512 + rb * 16 + (lane & 7) * 2));
      if (lane < 2) sts32(sb + OFF_TAG + lane * 4, lane ? 0 : tag);
      fence_async_smem();
      uint32_t t0 = 0;
      mbar_wait(sb + BAR_AF + 8 * (NA - 1), 0);
#pragma unroll 1
      while (true) {
        const uint4 u = ld_ll4(&p.scr->xstat[rb * 64 + lane]), v = ld_ll4(&p.scr->xstat[rb * 64 + 32 + lane]);
        sts64f(sb + OFF_XS + lane * 8, __uint_as_float(u.x), __uint_as_float(u.z));
        sts64f(sb + OFF_XS + 256 + lane * 8, __uint_as_float(v.x), __uint_as_float(v.z));
        if (__all_sync(0xffffffff, u.y == tag && u.w == tag && v.y == tag && v.w == tag)) break;
        spin_guard(t0);
      }
      STAMP(26);
      __syncwarp();
      if (lane == 0) mbar_arrive(sb + BAR_XS);
      if (CS1BY) { uint32_t tp = tstart; pace(tp, CS1_T); gather_colsum(p, sb, cb, 1, tag, lane); STAMP(38); }
      mbar_wait(sb + BAR_KU, 1);
      poll_counter(p.scr->cnt + CNT_KV + (cb >> 1), tag * 64);
      if (elect_one()) load_convx(p, sb + OFF_CV, sb + BAR_XF + 8, chb);
      mbar_wait(sb + BAR_KU + 8, 1);
      if (elect_one()) load_convx(p, sb + OFF_CV + CV_SZ, sb + BAR_XF, chb + 64);
      STAMP(48);
      mbar_wait(sb + BAR_AE + 72, 0);
#pragma unroll 1
      for (int i = 0; i < 2; i++) {
        conv_service(p, sb, 1, chb + i * 128, i == 0);
        if (Z1_AT < 0 && i == 0) {
          poll_counter(p.scr->cnt + CNT_Z1 + (cb >> 1), tag * 64);
          if (elect_one()) mbar_arrive(sb + BAR_Z1);
          STAMP(24);
        }
      }
      bar_arrive(NB_CD, 64);
      mbar_wait(sb + BAR_WO, 0);
      poll_counter(p.scr->cnt + CNT_Y + (cb >> 1), tag * 64);
      STAMP(47);
      if (elect_one()) mbar_arrive(sb + BAR_YT);
      held_service(p, sb, 1, chb + 256, rb, cb, tag, lane);
      if (lane == 0) *(volatile uint32_t*)&p.scr->epoch[lin] = tag;
      STAMP(23);
    }
  } else {
    if (warp == 7) STAMP(36);
    const int wg = warp >> 2, w = warp & 3, g = lane >> 2, t = lane & 3;
    Taps k;
    uint32_t xw[2][10];
    if (wg == 2) {
      asm volatile("setmaxnreg.inc.sync.aligned.u32 160;");
      const int tb = rb * 2 + (cb & 1), c0 = (cb >> 1) * 320;
      const uint32_t cv = sb + OFF_CV + CV_SZ;
      if (w == 0) zero_pads(sb + OFF_CV, lane);
      mbar_wait(sb + BAR_KV + 8, 0);
      const int t0 = tb * 32 + w * 8;
      const __nv_bfloat16* kp = p.k + (size_t)(t0 - 3) * kD + c0 + lane * 2;
      const __nv_bfloat16* vp = p.v + (size_t)t0 * kD + c0 + lane * 2;
      const __nv_bfloat16* sp = p.shift + (c0 + lane * 2) * 4;
      const uint32_t oa = cv + ((3 - w) & 1) * 1024 + lane * 32 + ((((3 - w) >> 1) ^ (lane >> 2)) & 1) * 16;
#pragma unroll 1
      for (int r = 0; r < 2; r++) {
        KvRegs n0, n1, n2;
        if (KWT && r) mbar_wait2(sb + BAR_XS, 0, sb + BAR_ST, 0);
        STAMPW(r ? 51 : 50);
        kv_load(n0, kp + r * 128, vp + r * 128, sp + r * 512, t0 > 0);
        kv_load(n1, kp + r * 128 + 64, vp + r * 128 + 64, sp + r * 512 + 256, t0 > 0);
        if (r) kv_load(n2, kp + 256, vp + 256, sp + 1024, t0 > 0);
        kv_unit(n0, oa + r * 8192);
        bar_sync(NB_WGC, 128);
        mbar_arrive_if(sb + BAR_KU + 16 * r, tid == 0);
        if (r) mbar_wait(sb + BAR_KU, 1);
        kv_unit(n1, oa + (r ? 0 : 4096));
        bar_sync(NB_WGC, 128);
        mbar_arrive_if(sb + BAR_KU + 16 * r + 8, tid == 0);
        if (r) {
          kv_unit(n2, oa + 4096);
          bar_sync(NB_WGC, 128);
          mbar_arrive_if(sb + BAR_KU + 32, tid == 0);
        } else {
          mbar_wait(sb + BAR_AF + 8 * ((cb >> 1) * 5 + 1), 0);
          mbar_wait2(sb + BAR_AF + 8 * ((cb >> 1) * 5 + 2), 0, sb + BAR_AF + 8 * ((cb >> 1) * 5 + 4), 0);
          final_load_x(xw, sb + OFF_A, cb, 1, w, lane);
          fence_async_smem();
          bar_sync(NB_WGC, 128);
          mbar_arrive_if(sb + BAR_XC, tid == 0);
        }
      }
      STAMPW(13);
      load_taps(k, p, chb, tid);
    } else {
      float d[96];
      if (wg == 0) st_ll2(&p.scr->zstat[(rb * 256 + cb * 64 + w * 16 + g + (t >> 1) * 8) * 2 + (t & 1)], 0, 0);
      else if ((tid & 7) == 0) st_ll4(&p.scr->xstat[rb * 64 + cb * 16 + (tid >> 3)], 0, 0, 0, 0);
      {
        #pragma unroll
        for (int i = 0; i < 96; i++) d[i] = 0.f;
        {
          if (__builtin_expect(wg == 1, 0)) {
            const int tid = tid_now();
            const uint32_t epoch = load_epoch(p, lin, lane);
            float s = 0.f, q = 0.f;
#pragma unroll 1
            for (int i = 0; i < 10; i++) {
              mbar_wait(sb + BAR_AF + 8 * i, 0);
              const uint4 x4 = lds128(sb + OFF_A + i * A_SLOT + cb * 2048 + tid * 16);
              const uint32_t u[4] = {x4.x, x4.y, x4.z, x4.w};
#pragma unroll
              for (int e = 0; e < 4; e++) { const float a = bf_lo(u[e]), c = bf_hi(u[e]); s += a + c; q = fmaf(a, a, q); q = fmaf(c, c, q); }
            }
#pragma unroll
            for (int o = 1; o <= 4; o <<= 1) { s += __shfl_xor_sync(0xffffffff, s, o); q += __shfl_xor_sync(0xffffffff, q, o); }
            const float m = s * (1.f / kD);
            const float r = rsqrtf(fmaxf(fmaf(-m, m, q * (1.f / kD)), 0.f) + 1e-5f);
            if ((tid & 7) == 0) st_ll4(&p.scr->xstat[rb * 64 + cb * 16 + (tid >> 3)], __float_as_uint(m), epoch + 1, __float_as_uint(r), epoch + 1);
            STAMPW(12);
            bar_sync(NB_G1, 256);
          }
          gemm_loop<192, true, 0, D1>(d, sb, 10, wg ? zs0 : 0, 0, 0, 0, wg, 2, tid_now(), [&]() { if (G1_AT == 0 && wg == 0) bar_arrive(NB_G1, 256); }, [](int) {});
          asm volatile("setmaxnreg.inc.sync.aligned.u32 160;");
          STAMPW(wg ? 14 : 1);
          if (wg == 0) ZS(0);
          mbar_wait2(sb + BAR_XS, 0, sb + BAR_ST + 8 * wg, 0);
          if (wg == 0) ZS(1);
        }
        const int t1 = tid_now();
        const uint32_t xa1 = sb + OFF_XS + (w * 16 + ((t1 & 31) >> 2)) * 8;
        const float2 s0 = lds64f(xa1), s1 = lds64f(xa1 + 64);
        uint32_t z[48];
        float st[4];
        fence_async_smem();
        fold_mean(d, sb + OFF_CS + (1 - wg) * 768, s0.x, s1.x, t1 & 3);
        if (G1_AT == 1 && wg == 0) bar_arrive(NB_G1, 256);
        WG_WAIT(0);
        acc_fence<96>(d);
        if (wg == 0) ZS(2);
        gelu_tile(d, z, st, s0.y, s1.y);
        const int tid = tid_now(), lane = tid & 31, g = lane >> 2, t = lane & 3;
        if (wg == 1) {
          uint32_t bra, brb;
          asm volatile("ld.shared.u16 %0, [%1];" : "=r"(bra) : "r"(sb + OFF_BIAS + (w * 16 + g) * 2));
          asm volatile("ld.shared.u16 %0, [%1+16];" : "=r"(brb) : "r"(sb + OFF_BIAS + (w * 16 + g) * 2));
#pragma unroll
          for (int j = 0; j < 96; j++) d[j] = bf_lo((j & 2) ? brb : bra);
          STAMPW(15);
          gemm_loop<192, true, 1, D2>(d, sb, 32, 0, 1, 20, 0, 2, 2, tid, [&]() { if (HOLD_AT < 32) mbar_arrive_if(sb + BAR_GO, tid == 0); }, [](int) {});
          if (HOLD_AT == 32) mbar_arrive_if(sb + BAR_GO, tid == 0);
          STAMPW(16);
          const int t2 = tid_now(), l2 = t2 & 31;
          const uint32_t ha = sb + OFF_A + 5 * A_SLOT + (l2 >> 4) * 1024 + (2 * w + ((l2 >> 3) & 1)) * 128 + (l2 & 7) * 16;
#pragma unroll
          for (int j = 0; j < 24; j += 2) {
#pragma unroll
            for (int e = 0; e < 4; e++) z[2 * j + e] = hmul2(z[2 * j + e], pack2(d[4 * j + 2 * e], d[4 * j + 2 * e + 1]));
            stsm4(ha + j * 1024, z[2 * j], z[2 * j + 1], z[2 * j + 2], z[2 * j + 3]);
            if (HPC && j == HPC * 8 - 2) {
              fence_async_smem();
              bar_arrive(NB_Z2, 160);
            }
          }
          fence_async_smem();
          bar_sync(NB_WGB, 128);
          mbar_arrive_if(sb + BAR_AF + 8 * (t2 == 3 ? (BAR_G2 - BAR_AF) / 8 : (t2 == 4 ? (BAR_GO - BAR_AF) / 8 : 5 + t2)), t2 < (HOLD_AT == 33 ? 5 : 4));
          STAMPW(17);
          {
            float e[80];
#pragma unroll
            for (int j = 0; j < 80; j++) e[j] = 0.f;
            gemm_loop<160, false, 2, DB>(e, sb, 12, 5, 0, 2, 0, 2, 2, tid_now(), []() {}, [](int) {});
            STAMPW(10);
            const int t3 = tid_now();
#pragma unroll
            for (int j = 0; j < 10; j++) {
              sts128(sb + OFF_A + j * 2048 + t3 * 16, pack2(e[8 * j], e[8 * j + 1]), pack2(e[8 * j + 2], e[8 * j + 3]), pack2(e[8 * j + 4], e[8 * j + 5]),
                     pack2(e[8 * j + 6], e[8 * j + 7]));
              if (j == 4) bar_arrive(NB_WO, 256);
            }
            bar_arrive(NB_Z, 256);
            STAMPW(45);
          }
          return;
        }
        ZS(3);
        const bool hi = t & 2;
        float a0 = (hi ? st[2] : st[0]) + __shfl_xor_sync(0xffffffff, hi ? st[0] : st[2], 2);
        float a1 = (hi ? st[3] : st[1]) + __shfl_xor_sync(0xffffffff, hi ? st[1] : st[3], 2);
        a0 = ((t & 1) ? a1 : a0) + __shfl_xor_sync(0xffffffff, (t & 1) ? a0 : a1, 1);
        const uint32_t tag = lds32<0>(sb + OFF_TAG);
        uint2* zs = p.scr->zstat + (rb * 256 + w * 16 + g + (t >> 1) * 8) * 2 + (t & 1);
        st_ll2(zs + cb * 128, __float_as_uint(a0), tag);
        STAMPW(2); ZS(4);
        uint2 u[4];
#pragma unroll
        for (int i = 0; i < 4; i++) u[i] = ld_ll2(zs + i * 128);
        const uint32_t keep = (cb & 2) ? 13 << 5 : 13;
        mbar_arrive_if(sb + BAR_AE + 8 * tid, tid < NA && !((keep >> tid) & 1));
        const uint32_t za = sb + OFF_A + zs0 * A_SLOT + (2 * w + ((lane >> 3) & 1)) * 3072 + (lane >> 4) * 128 + (lane & 7) * 16;
        const float ca = 0.5f * (hi ? s1.y : s0.y), inv = 1.f / 768.f;
        mbar_wait2(sb + BAR_AE + 8 * (zs0 + 2), 0, sb + BAR_XC, 0);
        ZS(6);
        uint32_t t0 = 0;
#pragma unroll 1
        while (!__all_sync(0xffffffff, u[0].y == tag && u[1].y == tag && u[2].y == tag && u[3].y == tag)) {
          spin_guard(t0);
#pragma unroll
          for (int i = 0; i < 4; i++) u[i] = ld_ll2(zs + i * 128);
        }
        STAMPW(3); ZS(7);
        a0 = ((__uint_as_float(u[0].x) + __uint_as_float(u[1].x)) + (__uint_as_float(u[2].x) + __uint_as_float(u[3].x))) * inv;
        a1 = __shfl_xor_sync(0xffffffff, a0, 1);
        const float m = (t & 1) ? a1 : a0, q = (t & 1) ? a0 : a1;
        const float r = bf_lo(pack2(ca * rsqrtf(fmaf(fmaxf(fmaf(-m, m, q), 0.f), ca * ca, 1e-5f)), 0.f));
        const uint32_t rn = pack2(r, -m * r), ro = __shfl_xor_sync(0xffffffff, rn, 2);
        const uint32_t ra2 = prmt(hi ? ro : rn, 0, 0x1010), n2a = prmt(hi ? ro : rn, 0, 0x3232), rb2 = prmt(hi ? rn : ro, 0, 0x1010), n2b = prmt(hi ? rn : ro, 0, 0x3232);
        if (ZORD && w >= 2) bar_sync(NB_Z, 160);
#pragma unroll
        for (int j = 0; j < 24; j += 2)
          stsm4(za + j * 128, hfma2(z[2 * j], ra2, n2a), hfma2(z[2 * j + 1], rb2, n2b), hfma2(z[2 * j + 2], ra2, n2a), hfma2(z[2 * j + 3], rb2, n2b));
        ZS(8);
        fence_async_smem();
        ZS(9);
        if (w < 2) bar_arrive(NB_Z, ZORD ? 160 : 96);
        else bar_arrive(NB_Z2, 96);
        final_load_x(xw, sb + OFF_A, cb, 0, w, lane);
        fence_async_smem();
        bar_sync(NB_WGA, 128);
        mbar_arrive_if(sb + BAR_AE + 8 * tid, tid < NA && ((keep >> tid) & 1));
      }
      {
        const uint32_t zero = lds32<0>(sb + OFF_TAG + 4);
#pragma unroll
        for (int i = 0; i < 20; i++) xw[i / 10][i % 10] |= zero;
      }
      load_taps(k, p, chb + 64, tid_now());
      STAMPW(4);
    }
    const int h = wg >> 1;
    {
    const int tid = tid_now(), lane = tid & 31;
    conv_worker(p, k, sb + OFF_CV + (1 - h) * CV_SZ, sb + OFF_A + 9 * A_SLOT + h * 4096, sb + BAR_XF + 8 * h, NB_WGA + h,
                chb + (h ? 0 : 64), 2 + h, sb + BAR_GO, w, lane, tid, h ? 40 : 5, rb, cb);
    {
      const int t3 = tid_now(), l3 = t3 & 31;
      const uint32_t xs_addr = sb + OFF_XS + (w * 16 + (l3 >> 2)) * 8;
      const float2 s0 = lds64f(xs_addr), s1 = lds64f(xs_addr + 64);
      const uint32_t ya = sb + y_tile(h) + ((l3 >> 4) * 8 + (l3 & 7)) * 128 + (((2 * w + ((l3 >> 3) & 1)) ^ (l3 & 7) ^ (rb & 7)) << 4);
      uint32_t sw[2][10];
      mbar_wait(sb + BAR_XF + 8 * h, h);
      final_s_early(sw, xw, ya, s0, s1);
      uint32_t ph = 1, t0 = 0, y[8];
#pragma unroll 1
      while (true) {
        mbar_wait(sb + BAR_YL + 16 * h, ph);
        if (bar_all(NB_WGA + h, 128, final_late(y, ya))) break;
        spin_guard(t0);
        ph ^= 1;
        if (t3 == 0) load_late_y(p, sb, h, rb, cb, lds32<0>(sb + OFF_TAG) & 1);
      }
#pragma unroll
      for (int e = 0; e < 8; e++) sw[e & 1][4 + (e >> 1)] = hmul2(sw[e & 1][4 + (e >> 1)], ~y[e]);
      __nv_bfloat16* o0 = p.out + (size_t)(w * 512 + rb * 16 + (l3 >> 2)) * kD + seg_col(cb, h);
      STAMPW(h ? 44 : 9);
      bar_sync(h ? NB_Z : NB_WO, 256);
      float d[40];
#pragma unroll
      for (int j = 0; j < 5; j++) {
        const uint4 v = lds128(sb + OFF_A + (h * 5 + j) * 2048 + t3 * 16);
        d[8 * j] = bf_lo(v.x); d[8 * j + 1] = bf_hi(v.x); d[8 * j + 2] = bf_lo(v.y); d[8 * j + 3] = bf_hi(v.y);
        d[8 * j + 4] = bf_lo(v.z); d[8 * j + 5] = bf_hi(v.z); d[8 * j + 6] = bf_lo(v.w); d[8 * j + 7] = bf_hi(v.w);
      }
      final_out(d, xw, sw, s0.y, s1.y, o0, h, l3 & 3);
    }
    }
  }
}

typedef CUresult (*EncodeFn)(CUtensorMap*, CUtensorMapDataType, cuuint32_t, void*, const cuuint64_t*, const cuuint64_t*, const cuuint32_t*,
                             const cuuint32_t*, CUtensorMapInterleave, CUtensorMapSwizzle, CUtensorMapL2promotion, CUtensorMapFloatOOBfill);

void encode(EncodeFn fn, CUtensorMap* m, const void* ptr, int rank, const cuuint64_t* dims, const cuuint64_t* strides, const cuuint32_t* box,
            CUtensorMapSwizzle swz = CU_TENSOR_MAP_SWIZZLE_128B) {
  const cuuint32_t es[3] = {1, 1, 1};
  fn(m, CU_TENSOR_MAP_DATA_TYPE_BFLOAT16, rank, const_cast<void*>(ptr), dims, strides, box, es, CU_TENSOR_MAP_INTERLEAVE_NONE,
     swz, CU_TENSOR_MAP_L2_PROMOTION_L2_128B, CU_TENSOR_MAP_FLOAT_OOB_FILL_NONE);
}

}

extern "C" void kernel_launch(void* const* d_in, const int* in_sizes, int n_in, void* d_out, int out_size) {
  (void)in_sizes; (void)n_in; (void)out_size;
  static EncodeFn enc = nullptr;
  static Scratch* scr = nullptr;
  static int sms = 0;
  if (!enc) {
    void* fn = nullptr;
    cudaDriverEntryPointQueryResult qr;
    cudaGetDriverEntryPoint("cuTensorMapEncodeTiled", &fn, cudaEnableDefault, &qr);
    enc = (EncodeFn)fn;
    cudaFuncSetAttribute(fused_kernel, cudaFuncAttributeMaxDynamicSharedMemorySize, SMEM_BYTES);
    cudaGetSymbolAddress((void**)&scr, g_scr);
    int dev = 0;
    cudaGetDevice(&dev);
    cudaDeviceGetAttribute(&sms, cudaDevAttrMultiProcessorCount, dev);
  }
  Params p;
  p.scr = scr;
  p.by_smid = sms == 132;
  p.k = (const __nv_bfloat16*)d_in[1];
  p.v = (const __nv_bfloat16*)d_in[2];
  p.shift = (const __nv_bfloat16*)d_in[3];
  p.ssmk = (const __nv_bfloat16*)d_in[4];
  p.ssmD = (const __nv_bfloat16*)d_in[5];
  p.wsp = (const __nv_bfloat16*)d_in[8];
  p.bsp = (const __nv_bfloat16*)d_in[9];
  p.wout = (const __nv_bfloat16*)d_in[10];
  p.out = (__nv_bfloat16*)d_out;
  for (int i = 0; i < 2; i++) {
    const cuuint64_t n = i ? kS : kD, dims[3] = {n, 512, 4}, st[2] = {n * 2, n * 1024};
    const cuuint32_t box[3] = {64, 16, 4};
    encode(enc, i ? &p.tmWsp : &p.tmX, d_in[i ? 8 : 0], 3, dims, st, box);
  }
  {
    const cuuint64_t dims[3] = {64, kD, kF / 64}, st[2] = {kF * 2, 128};
    const cuuint32_t box[3] = {64, 64, 3};
    encode(enc, &p.tmW, d_in[7], 3, dims, st, box);
  }
  {
    const cuuint64_t dims[2] = {kS, 896}, st[1] = {kS * 2};
    const cuuint32_t box[2] = {64, 16};
    encode(enc, &p.tmY, scr->y, 2, dims, st, box);
  }
  {
    const cuuint64_t dims[3] = {1024, kD / 2, 4}, st[2] = {8192, 2048};
    const cuuint32_t box[3] = {16, 32, 4};
    encode(enc, &p.tmKV, scr->kvx, 3, dims, st, box, CU_TENSOR_MAP_SWIZZLE_32B);
  }
  fused_kernel<<<132, 512, SMEM_BYTES, cudaStreamPerThread>>>(p);
}
```

```cpp
#include <cuda_runtime.h>
#include <cuda.h>
#include <cuda_bf16.h>
#include <stdint.h>

template <int N> struct WG;
template <> struct WG<16> {
  static __device__ __forceinline__ void rs(float* d, const uint32_t* a, uint64_t db) {
    asm volatile("{\n.reg .pred p;\nsetp.ne.b32 p, 1, 0;\nwgmma.mma_async.sync.aligned.m64n16k16.f32.bf16.bf16 {"
      "%0, %1, %2, %3, %4, %5, %6, %7"
      "}, {%8, %9, %10, %11}, %12, p, 1, 1, 0;\n}\n"
      :
      "+f"(d[0]), "+f"(d[1]), "+f"(d[2]), "+f"(d[3]), "+f"(d[4]), "+f"(d[5]), "+f"(d[6]), "+f"(d[7])
      : "r"(a[0]), "r"(a[1]), "r"(a[2]), "r"(a[3]), "l"(db));
  }
};
template <> struct WG<32> {
  static __device__ __forceinline__ void rs(float* d, const uint32_t* a, uint64_t db) {
    asm volatile("{\n.reg .pred p;\nsetp.ne.b32 p, 1, 0;\nwgmma.mma_async.sync.aligned.m64n32k16.f32.bf16.bf16 {"
      "%0, %1, %2, %3, %4, %5, %6, %7, %8, %9, %10, %11, %12, %13, %14, %15"
      "}, {%16, %17, %18, %19}, %20, p, 1, 1, 0;\n}\n"
      :
      "+f"(d[0]), "+f"(d[1]), "+f"(d[2]), "+f"(d[3]), "+f"(d[4]), "+f"(d[5]), "+f"(d[6]), "+f"(d[7]),
      "+f"(d[8]), "+f"(d[9]), "+f"(d[10]), "+f"(d[11]), "+f"(d[12]), "+f"(d[13]), "+f"(d[14]), "+f"(d[15])
      : "r"(a[0]), "r"(a[1]), "r"(a[2]), "r"(a[3]), "l"(db));
  }
};
template <> struct WG<48> {
  static __device__ __forceinline__ void rs(float* d, const uint32_t* a, uint64_t db) {
    asm volatile("{\n.reg .pred p;\nsetp.ne.b32 p, 1, 0;\nwgmma.mma_async.sync.aligned.m64n48k16.f32.bf16.bf16 {"
      "%0, %1, %2, %3, %4, %5, %6, %7, %8, %9, %10, %11, %12, %13, %14, %15, "
      "%16, %17, %18, %19, %20, %21, %22, %23"
      "}, {%24, %25, %26, %27}, %28, p, 1, 1, 0;\n}\n"
      :
      "+f"(d[0]), "+f"(d[1]), "+f"(d[2]), "+f"(d[3]), "+f"(d[4]), "+f"(d[5]), "+f"(d[6]), "+f"(d[7]),
      "+f"(d[8]), "+f"(d[9]), "+f"(d[10]), "+f"(d[11]), "+f"(d[12]), "+f"(d[13]), "+f"(d[14]), "+f"(d[15]),
      "+f"(d[16]), "+f"(d[17]), "+f"(d[18]), "+f"(d[19]), "+f"(d[20]), "+f"(d[21]), "+f"(d[22]), "+f"(d[23])
      : "r"(a[0]), "r"(a[1]), "r"(a[2]), "r"(a[3]), "l"(db));
  }
};
template <> struct WG<64> {
  static __device__ __forceinline__ void rs(float* d, const uint32_t* a, uint64_t db) {
    asm volatile("{\n.reg .pred p;\nsetp.ne.b32 p, 1, 0;\nwgmma.mma_async.sync.aligned.m64n64k16.f32.bf16.bf16 {"
      "%0, %1, %2, %3, %4, %5, %6, %7, %8, %9, %10, %11, %12, %13, %14, %15, "
      "%16, %17, %18, %19, %20, %21, %22, %23, %24, %25, %26, %27, %28, %29, %30, %31"
      "}, {%32, %33, %34, %35}, %36, p, 1, 1, 0;\n}\n"
      :
      "+f"(d[0]), "+f"(d[1]), "+f"(d[2]), "+f"(d[3]), "+f"(d[4]), "+f"(d[5]), "+f"(d[6]), "+f"(d[7]),
      "+f"(d[8]), "+f"(d[9]), "+f"(d[10]), "+f"(d[11]), "+f"(d[12]), "+f"(d[13]), "+f"(d[14]), "+f"(d[15]),
      "+f"(d[16]), "+f"(d[17]), "+f"(d[18]), "+f"(d[19]), "+f"(d[20]), "+f"(d[21]), "+f"(d[22]), "+f"(d[23]),
      "+f"(d[24]), "+f"(d[25]), "+f"(d[26]), "+f"(d[27]), "+f"(d[28]), "+f"(d[29]), "+f"(d[30]), "+f"(d[31])
      : "r"(a[0]), "r"(a[1]), "r"(a[2]), "r"(a[3]), "l"(db));
  }
};
template <> struct WG<80> {
  static __device__ __forceinline__ void rs(float* d, const uint32_t* a, uint64_t db) {
    asm volatile("{\n.reg .pred p;\nsetp.ne.b32 p, 1, 0;\nwgmma.mma_async.sync.aligned.m64n80k16.f32.bf16.bf16 {"
      "%0, %1, %2, %3, %4, %5, %6, %7, %8, %9, %10, %11, %12, %13, %14, %15, "
      "%16, %17, %18, %19, %20, %21, %22, %23, %24, %25, %26, %27, %28, %29, %30, %31, "
      "%32, %33, %34, %35, %36, %37, %38, %39"
      "}, {%40, %41, %42, %43}, %44, p, 1, 1, 0;\n}\n"
      :
      "+f"(d[0]), "+f"(d[1]), "+f"(d[2]), "+f"(d[3]), "+f"(d[4]), "+f"(d[5]), "+f"(d[6]), "+f"(d[7]),
      "+f"(d[8]), "+f"(d[9]), "+f"(d[10]), "+f"(d[11]), "+f"(d[12]), "+f"(d[13]), "+f"(d[14]), "+f"(d[15]),
      "+f"(d[16]), "+f"(d[17]), "+f"(d[18]), "+f"(d[19]), "+f"(d[20]), "+f"(d[21]), "+f"(d[22]), "+f"(d[23]),
      "+f"(d[24]), "+f"(d[25]), "+f"(d[26]), "+f"(d[27]), "+f"(d[28]), "+f"(d[29]), "+f"(d[30]), "+f"(d[31]),
      "+f"(d[32]), "+f"(d[33]), "+f"(d[34]), "+f"(d[35]), "+f"(d[36]), "+f"(d[37]), "+f"(d[38]), "+f"(d[39])
      : "r"(a[0]), "r"(a[1]), "r"(a[2]), "r"(a[3]), "l"(db));
  }
};
template <> struct WG<96> {
  static __device__ __forceinline__ void rs(float* d, const uint32_t* a, uint64_t db) {
    asm volatile("{\n.reg .pred p;\nsetp.ne.b32 p, 1, 0;\nwgmma.mma_async.sync.aligned.m64n96k16.f32.bf16.bf16 {"
      "%0, %1, %2, %3, %4, %5, %6, %7, %8, %9, %10, %11, %12, %13, %14, %15, "
      "%16, %17, %18, %19, %20, %21, %22, %23, %24, %25, %26, %27, %28, %29, %30, %31, "
      "%32, %33, %34, %35, %36, %37, %38, %39, %40, %41, %42, %43, %44, %45, %46, %47"
      "}, {%48, %49, %50, %51}, %52, p, 1, 1, 0;\n}\n"
      :
      "+f"(d[0]), "+f"(d[1]), "+f"(d[2]), "+f"(d[3]), "+f"(d[4]), "+f"(d[5]), "+f"(d[6]), "+f"(d[7]),
      "+f"(d[8]), "+f"(d[9]), "+f"(d[10]), "+f"(d[11]), "+f"(d[12]), "+f"(d[13]), "+f"(d[14]), "+f"(d[15]),
      "+f"(d[16]), "+f"(d[17]), "+f"(d[18]), "+f"(d[19]), "+f"(d[20]), "+f"(d[21]), "+f"(d[22]), "+f"(d[23]),
      "+f"(d[24]), "+f"(d[25]), "+f"(d[26]), "+f"(d[27]), "+f"(d[28]), "+f"(d[29]), "+f"(d[30]), "+f"(d[31]),
      "+f"(d[32]), "+f"(d[33]), "+f"(d[34]), "+f"(d[35]), "+f"(d[36]), "+f"(d[37]), "+f"(d[38]), "+f"(d[39]),
      "+f"(d[40]), "+f"(d[41]), "+f"(d[42]), "+f"(d[43]), "+f"(d[44]), "+f"(d[45]), "+f"(d[46]), "+f"(d[47])
      : "r"(a[0]), "r"(a[1]), "r"(a[2]), "r"(a[3]), "l"(db));
  }
};
template <> struct WG<112> {
  static __device__ __forceinline__ void rs(float* d, const uint32_t* a, uint64_t db) {
    asm volatile("{\n.reg .pred p;\nsetp.ne.b32 p, 1, 0;\nwgmma.mma_async.sync.aligned.m64n112k16.f32.bf16.bf16 {"
      "%0, %1, %2, %3, %4, %5, %6, %7, %8, %9, %10, %11, %12, %13, %14, %15, "
      "%16, %17, %18, %19, %20, %21, %22, %23, %24, %25, %26, %27, %28, %29, %30, %31, "
      "%32, %33, %34, %35, %36, %37, %38, %39, %40, %41, %42, %43, %44, %45, %46, %47, "
      "%48, %49, %50, %51, %52, %53, %54, %55"
      "}, {%56, %57, %58, %59}, %60, p, 1, 1, 0;\n}\n"
      :
      "+f"(d[0]), "+f"(d[1]), "+f"(d[2]), "+f"(d[3]), "+f"(d[4]), "+f"(d[5]), "+f"(d[6]), "+f"(d[7]),
      "+f"(d[8]), "+f"(d[9]), "+f"(d[10]), "+f"(d[11]), "+f"(d[12]), "+f"(d[13]), "+f"(d[14]), "+f"(d[15]),
      "+f"(d[16]), "+f"(d[17]), "+f"(d[18]), "+f"(d[19]), "+f"(d[20]), "+f"(d[21]), "+f"(d[22]), "+f"(d[23]),
      "+f"(d[24]), "+f"(d[25]), "+f"(d[26]), "+f"(d[27]), "+f"(d[28]), "+f"(d[29]), "+f"(d[30]), "+f"(d[31]),
      "+f"(d[32]), "+f"(d[33]), "+f"(d[34]), "+f"(d[35]), "+f"(d[36]), "+f"(d[37]), "+f"(d[38]), "+f"(d[39]),
      "+f"(d[40]), "+f"(d[41]), "+f"(d[42]), "+f"(d[43]), "+f"(d[44]), "+f"(d[45]), "+f"(d[46]), "+f"(d[47]),
      "+f"(d[48]), "+f"(d[49]), "+f"(d[50]), "+f"(d[51]), "+f"(d[52]), "+f"(d[53]), "+f"(d[54]), "+f"(d[55])
      : "r"(a[0]), "r"(a[1]), "r"(a[2]), "r"(a[3]), "l"(db));
  }
};
template <> struct WG<128> {
  static __device__ __forceinline__ void rs(float* d, const uint32_t* a, uint64_t db) {
    asm volatile("{\n.reg .pred p;\nsetp.ne.b32 p, 1, 0;\nwgmma.mma_async.sync.aligned.m64n128k16.f32.bf16.bf16 {"
      "%0, %1, %2, %3, %4, %5, %6, %7, %8, %9, %10, %11, %12, %13, %14, %15, "
      "%16, %17, %18, %19, %20, %21, %22, %23, %24, %25, %26, %27, %28, %29, %30, %31, "
      "%32, %33, %34, %35, %36, %37, %38, %39, %40, %41, %42, %43, %44, %45, %46, %47, "
      "%48, %49, %50, %51, %52, %53, %54, %55, %56, %57, %58, %59, %60, %61, %62, %63"
      "}, {%64, %65, %66, %67}, %68, p, 1, 1, 0;\n}\n"
      :
      "+f"(d[0]), "+f"(d[1]), "+f"(d[2]), "+f"(d[3]), "+f"(d[4]), "+f"(d[5]), "+f"(d[6]), "+f"(d[7]),
      "+f"(d[8]), "+f"(d[9]), "+f"(d[10]), "+f"(d[11]), "+f"(d[12]), "+f"(d[13]), "+f"(d[14]), "+f"(d[15]),
      "+f"(d[16]), "+f"(d[17]), "+f"(d[18]), "+f"(d[19]), "+f"(d[20]), "+f"(d[21]), "+f"(d[22]), "+f"(d[23]),
      "+f"(d[24]), "+f"(d[25]), "+f"(d[26]), "+f"(d[27]), "+f"(d[28]), "+f"(d[29]), "+f"(d[30]), "+f"(d[31]),
      "+f"(d[32]), "+f"(d[33]), "+f"(d[34]), "+f"(d[35]), "+f"(d[36]), "+f"(d[37]), "+f"(d[38]), "+f"(d[39]),
      "+f"(d[40]), "+f"(d[41]), "+f"(d[42]), "+f"(d[43]), "+f"(d[44]), "+f"(d[45]), "+f"(d[46]), "+f"(d[47]),
      "+f"(d[48]), "+f"(d[49]), "+f"(d[50]), "+f"(d[51]), "+f"(d[52]), "+f"(d[53]), "+f"(d[54]), "+f"(d[55]),
      "+f"(d[56]), "+f"(d[57]), "+f"(d[58]), "+f"(d[59]), "+f"(d[60]), "+f"(d[61]), "+f"(d[62]), "+f"(d[63])
      : "r"(a[0]), "r"(a[1]), "r"(a[2]), "r"(a[3]), "l"(db));
  }
};
template <> struct WG<160> {
  static __device__ __forceinline__ void ss(float* d, uint64_t da, uint64_t db, int sd) {
    asm volatile("{\n.reg .pred p;\nsetp.ne.b32 p, %82, 0;\nwgmma.mma_async.sync.aligned.m64n160k16.f32.bf16.bf16 {"
      "%0, %1, %2, %3, %4, %5, %6, %7, %8, %9, %10, %11, %12, %13, %14, %15, "
      "%16, %17, %18, %19, %20, %21, %22, %23, %24, %25, %26, %27, %28, %29, %30, %31, "
      "%32, %33, %34, %35, %36, %37, %38, %39, %40, %41, %42, %43, %44, %45, %46, %47, "
      "%48, %49, %50, %51, %52, %53, %54, %55, %56, %57, %58, %59, %60, %61, %62, %63, "
      "%64, %65, %66, %67, %68, %69, %70, %71, %72, %73, %74, %75, %76, %77, %78, %79"
      "}, %80, %81, p, 1, 1, 0, 1;\n}\n"
      :
      "+f"(d[0]), "+f"(d[1]), "+f"(d[2]), "+f"(d[3]), "+f"(d[4]), "+f"(d[5]), "+f"(d[6]), "+f"(d[7]),
      "+f"(d[8]), "+f"(d[9]), "+f"(d[10]), "+f"(d[11]), "+f"(d[12]), "+f"(d[13]), "+f"(d[14]), "+f"(d[15]),
      "+f"(d[16]), "+f"(d[17]), "+f"(d[18]), "+f"(d[19]), "+f"(d[20]), "+f"(d[21]), "+f"(d[22]), "+f"(d[23]),
      "+f"(d[24]), "+f"(d[25]), "+f"(d[26]), "+f"(d[27]), "+f"(d[28]), "+f"(d[29]), "+f"(d[30]), "+f"(d[31]),
      "+f"(d[32]), "+f"(d[33]), "+f"(d[34]), "+f"(d[35]), "+f"(d[36]), "+f"(d[37]), "+f"(d[38]), "+f"(d[39]),
      "+f"(d[40]), "+f"(d[41]), "+f"(d[42]), "+f"(d[43]), "+f"(d[44]), "+f"(d[45]), "+f"(d[46]), "+f"(d[47]),
      "+f"(d[48]), "+f"(d[49]), "+f"(d[50]), "+f"(d[51]), "+f"(d[52]), "+f"(d[53]), "+f"(d[54]), "+f"(d[55]),
      "+f"(d[56]), "+f"(d[57]), "+f"(d[58]), "+f"(d[59]), "+f"(d[60]), "+f"(d[61]), "+f"(d[62]), "+f"(d[63]),
      "+f"(d[64]), "+f"(d[65]), "+f"(d[66]), "+f"(d[67]), "+f"(d[68]), "+f"(d[69]), "+f"(d[70]), "+f"(d[71]),
      "+f"(d[72]), "+f"(d[73]), "+f"(d[74]), "+f"(d[75]), "+f"(d[76]), "+f"(d[77]), "+f"(d[78]), "+f"(d[79])
      : "l"(da), "l"(db), "r"(sd));
  }
};
template <> struct WG<192> {
  static __device__ __forceinline__ void ss(float* d, uint64_t da, uint64_t db, int sd) {
    asm volatile("{\n.reg .pred p;\nsetp.ne.b32 p, %98, 0;\nwgmma.mma_async.sync.aligned.m64n192k16.f32.bf16.bf16 {"
      "%0, %1, %2, %3, %4, %5, %6, %7, %8, %9, %10, %11, %12, %13, %14, %15, "
      "%16, %17, %18, %19, %20, %21, %22, %23, %24, %25, %26, %27, %28, %29, %30, %31, "
      "%32, %33, %34, %35, %36, %37, %38, %39, %40, %41, %42, %43, %44, %45, %46, %47, "
      "%48, %49, %50, %51, %52, %53, %54, %55, %56, %57, %58, %59, %60, %61, %62, %63, "
      "%64, %65, %66, %67, %68, %69, %70, %71, %72, %73, %74, %75, %76, %77, %78, %79, "
      "%80, %81, %82, %83, %84, %85, %86, %87, %88, %89, %90, %91, %92, %93, %94, %95"
      "}, %96, %97, p, 1, 1, 0, 1;\n}\n"
      :
      "+f"(d[0]), "+f"(d[1]), "+f"(d[2]), "+f"(d[3]), "+f"(d[4]), "+f"(d[5]), "+f"(d[6]), "+f"(d[7]),
      "+f"(d[8]), "+f"(d[9]), "+f"(d[10]), "+f"(d[11]), "+f"(d[12]), "+f"(d[13]), "+f"(d[14]), "+f"(d[15]),
      "+f"(d[16]), "+f"(d[17]), "+f"(d[18]), "+f"(d[19]), "+f"(d[20]), "+f"(d[21]), "+f"(d[22]), "+f"(d[23]),
      "+f"(d[24]), "+f"(d[25]), "+f"(d[26]), "+f"(d[27]), "+f"(d[28]), "+f"(d[29]), "+f"(d[30]), "+f"(d[31]),
      "+f"(d[32]), "+f"(d[33]), "+f"(d[34]), "+f"(d[35]), "+f"(d[36]), "+f"(d[37]), "+f"(d[38]), "+f"(d[39]),
      "+f"(d[40]), "+f"(d[41]), "+f"(d[42]), "+f"(d[43]), "+f"(d[44]), "+f"(d[45]), "+f"(d[46]), "+f"(d[47]),
      "+f"(d[48]), "+f"(d[49]), "+f"(d[50]), "+f"(d[51]), "+f"(d[52]), "+f"(d[53]), "+f"(d[54]), "+f"(d[55]),
      "+f"(d[56]), "+f"(d[57]), "+f"(d[58]), "+f"(d[59]), "+f"(d[60]), "+f"(d[61]), "+f"(d[62]), "+f"(d[63]),
      "+f"(d[64]), "+f"(d[65]), "+f"(d[66]), "+f"(d[67]), "+f"(d[68]), "+f"(d[69]), "+f"(d[70]), "+f"(d[71]),
      "+f"(d[72]), "+f"(d[73]), "+f"(d[74]), "+f"(d[75]), "+f"(d[76]), "+f"(d[77]), "+f"(d[78]), "+f"(d[79]),
      "+f"(d[80]), "+f"(d[81]), "+f"(d[82]), "+f"(d[83]), "+f"(d[84]), "+f"(d[85]), "+f"(d[86]), "+f"(d[87]),
      "+f"(d[88]), "+f"(d[89]), "+f"(d[90]), "+f"(d[91]), "+f"(d[92]), "+f"(d[93]), "+f"(d[94]), "+f"(d[95])
      : "l"(da), "l"(db), "r"(sd));
  }
  static __device__ __forceinline__ void rst(float* d, const uint32_t* a, uint64_t db) {
    asm volatile("{\n.reg .pred p;\nsetp.ne.b32 p, 1, 0;\nwgmma.mma_async.sync.aligned.m64n192k16.f32.bf16.bf16 {"
      "%0, %1, %2, %3, %4, %5, %6, %7, %8, %9, %10, %11, %12, %13, %14, %15, "
      "%16, %17, %18, %19, %20, %21, %22, %23, %24, %25, %26, %27, %28, %29, %30, %31, "
      "%32, %33, %34, %35, %36, %37, %38, %39, %40, %41, %42, %43, %44, %45, %46, %47, "
      "%48, %49, %50, %51, %52, %53, %54, %55, %56, %57, %58, %59, %60, %61, %62, %63, "
      "%64, %65, %66, %67, %68, %69, %70, %71, %72, %73, %74, %75, %76, %77, %78, %79, "
      "%80, %81, %82, %83, %84, %85, %86, %87, %88, %89, %90, %91, %92, %93, %94, %95"
      "}, {%96, %97, %98, %99}, %100, p, 1, 1, 1;\n}\n"
      :
      "+f"(d[0]), "+f"(d[1]), "+f"(d[2]), "+f"(d[3]), "+f"(d[4]), "+f"(d[5]), "+f"(d[6]), "+f"(d[7]),
      "+f"(d[8]), "+f"(d[9]), "+f"(d[10]), "+f"(d[11]), "+f"(d[12]), "+f"(d[13]), "+f"(d[14]), "+f"(d[15]),
      "+f"(d[16]), "+f"(d[17]), "+f"(d[18]), "+f"(d[19]), "+f"(d[20]), "+f"(d[21]), "+f"(d[22]), "+f"(d[23]),
      "+f"(d[24]), "+f"(d[25]), "+f"(d[26]), "+f"(d[27]), "+f"(d[28]), "+f"(d[29]), "+f"(d[30]), "+f"(d[31]),
      "+f"(d[32]), "+f"(d[33]), "+f"(d[34]), "+f"(d[35]), "+f"(d[36]), "+f"(d[37]), "+f"(d[38]), "+f"(d[39]),
      "+f"(d[40]), "+f"(d[41]), "+f"(d[42]), "+f"(d[43]), "+f"(d[44]), "+f"(d[45]), "+f"(d[46]), "+f"(d[47]),
      "+f"(d[48]), "+f"(d[49]), "+f"(d[50]), "+f"(d[51]), "+f"(d[52]), "+f"(d[53]), "+f"(d[54]), "+f"(d[55]),
      "+f"(d[56]), "+f"(d[57]), "+f"(d[58]), "+f"(d[59]), "+f"(d[60]), "+f"(d[61]), "+f"(d[62]), "+f"(d[63]),
      "+f"(d[64]), "+f"(d[65]), "+f"(d[66]), "+f"(d[67]), "+f"(d[68]), "+f"(d[69]), "+f"(d[70]), "+f"(d[71]),
      "+f"(d[72]), "+f"(d[73]), "+f"(d[74]), "+f"(d[75]), "+f"(d[76]), "+f"(d[77]), "+f"(d[78]), "+f"(d[79]),
      "+f"(d[80]), "+f"(d[81]), "+f"(d[82]), "+f"(d[83]), "+f"(d[84]), "+f"(d[85]), "+f"(d[86]), "+f"(d[87]),
      "+f"(d[88]), "+f"(d[89]), "+f"(d[90]), "+f"(d[91]), "+f"(d[92]), "+f"(d[93]), "+f"(d[94]), "+f"(d[95])
      : "r"(a[0]), "r"(a[1]), "r"(a[2]), "r"(a[3]), "l"(db));
  }
};

#define HPC 0
#define ZSH 1
#define ZP_AT 1
#define CS1_T 9500
#define G1_AT 0
#define HGRP 3
#define HPACE 150
#define DB 0
#define HOLD_AT 33
#define LL_AT 4
#define KV_T0 2300
#define ST_YIELD 1
#define HP0 0
#define HPD 0
#define RAMP 1
#define LEAD 2
#define WSP_N 16
#define EARLY 0
#define CPIN 1
#define CW0 0
#define PFT 1
#define WSP_D 650
#define D1 4
#define D2 4
#define NSLEEP 32

static_assert(ZP_AT <= RAMP && LEAD <= 2, "staging slots");

namespace {

constexpr int kS = 2048, kD = 640, kF = 1536;
constexpr int NA = 10, NA2 = 9, NB = 5;
constexpr int A_SLOT = 8192, B_SLOT = 24576;
constexpr int OFF_A = 0;
constexpr int OFF_B = OFF_A + NA * A_SLOT;
constexpr int XB_PL = 2112;
constexpr int CV_KE = 4224, CV_KO = CV_KE + 4160;
constexpr int CV_SZ = CV_KO + 4160;
constexpr int OFF_CV = OFF_B + NB * B_SLOT;
constexpr int OFF_CS = OFF_CV + 2 * CV_SZ;
constexpr int OFF_BIAS = OFF_CS + 1536;
constexpr int OFF_XS = OFF_BIAS + 128;
constexpr int OFF_BAR = OFF_XS + 512;
constexpr int BAR_AF = OFF_BAR, BAR_ST = BAR_AF + 8 * NA, BAR_XF = BAR_ST + 16, BAR_KV = BAR_XF + 16;
constexpr int BAR_BF = OFF_BAR + 128, BAR_G2 = BAR_BF + 8 * (NB + 1), BAR_XS = BAR_G2 + 8, BAR_KU = BAR_XS + 8, BAR_ZP = BAR_KU + 40, BAR_XC = BAR_ZP + 8, BAR_WO = BAR_XC + 8;
constexpr int BAR_AE = OFF_BAR + 256, BAR_BE = BAR_AE + 8 * NA;
constexpr int BAR_YT = BAR_KU + 24;
constexpr int BAR_Z1 = BAR_ST;
constexpr int BAR_GO = BAR_XS;
constexpr int BAR_YL = BAR_KU + 16;
constexpr int OFF_TAG = OFF_CS - 32;
constexpr int SMEM_BYTES = OFF_BAR + 384;
static_assert(SMEM_BYTES <= 232448, "smem");
constexpr int NB_WGA = 1, NB_WGC = 2, NB_G1 = 3, NB_WO = 4, NB_CD = 5, NB_Z = 6, NB_WGB = 7, NB_Z2 = 8;

constexpr int CNT_Y = 1, CNT_Z1 = 3, CNT_KV = 32, CNT_WO = 36;
struct Scratch {
  uint8_t kvx[kD * 4096];
  uint8_t z2[4 * 32 * 24576];
  uint8_t h[32 * 12 * 8192];
  uint8_t wo[4 * 12 * 20480];
  uint8_t y[896 * 4096];
  uint4 xstat[kS];
  uint2 zstat[kS * 8];
  uint2 colsum[kF];
  uint32_t zcnt[4 * 32];
  uint32_t cnt[2 * 32];
  uint32_t hcnt[32 * 32];
  uint32_t epoch[136];
};
__device__ __align__(1024) Scratch g_scr;
#define ZS(i)
#define STAMP(i)
#define STAMP2(i)
#define STAMPW(i)

struct Params {
  Scratch* scr;
  int by_smid;
  const __nv_bfloat16 *k, *v, *shift, *ssmk, *ssmD, *wsp, *bsp, *wout;
  __nv_bfloat16* out;
  CUtensorMap tmX, tmW, tmWsp, tmY, tmKV;
};

__device__ __forceinline__ uint64_t mkdesc(uint32_t addr, uint32_t lbo, uint32_t sbo, uint32_t swz) {
  return (uint64_t)((addr & 0x3FFFF) >> 4) | ((uint64_t)(lbo >> 4) << 16) | ((uint64_t)(sbo >> 4) << 32) | ((uint64_t)swz << 62);
}
#define WG_FENCE() asm volatile("wgmma.fence.sync.aligned;" ::: "memory")
#define WG_COMMIT() asm volatile("wgmma.commit_group.sync.aligned;" ::: "memory")
#define WG_WAIT(n) asm volatile("wgmma.wait_group.sync.aligned %0;" ::"n"(n) : "memory")
template <int N> __device__ __forceinline__ void acc_fence(float* d) {
#pragma unroll
  for (int i = 0; i < N; i++) asm volatile("" : "+f"(d[i])::"memory");
}
__device__ __forceinline__ void mbar_init(uint32_t bar, int cnt) { asm volatile("mbarrier.init.shared::cta.b64 [%0], %1;" ::"r"(bar), "r"(cnt) : "memory"); }
__device__ __forceinline__ void mbar_expect(uint32_t bar, uint32_t bytes) { asm volatile("mbarrier.arrive.expect_tx.shared::cta.b64 _, [%0], %1;" ::"r"(bar), "r"(bytes) : "memory"); }
__device__ __forceinline__ void mbar_arrive(uint32_t bar) { asm volatile("mbarrier.arrive.shared::cta.b64 _, [%0];" ::"r"(bar) : "memory"); }
__device__ __forceinline__ void mbar_arrive_if(uint32_t bar, bool c) {
  asm volatile("{\n.reg .pred p;\nsetp.ne.u32 p, %1, 0;\n@p mbarrier.arrive.shared::cta.b64 _, [%0];\n}\n" ::"r"(bar), "r"((uint32_t)c) : "memory");
}
__device__ __forceinline__ void mbar_expect_if(uint32_t bar, uint32_t bytes, bool c) {
  asm volatile("{\n.reg .pred p;\nsetp.ne.u32 p, %2, 0;\n@p mbarrier.arrive.expect_tx.shared::cta.b64 _, [%0], %1;\n}\n" ::"r"(bar), "r"(bytes), "r"((uint32_t)c) : "memory");
}
__device__ __forceinline__ bool mbar_try(uint32_t bar, uint32_t parity) {
  uint32_t ok;
  asm volatile("{\n.reg .pred p;\nmbarrier.try_wait.parity.shared::cta.b64 p, [%1], %2;\nselp.u32 %0, 1, 0, p;\n}\n" : "=r"(ok) : "r"(bar), "r"(parity) : "memory");
  return ok;
}
__device__ __forceinline__ bool mbar_test(uint32_t bar, uint32_t parity) {
  uint32_t ok;
  asm volatile("{\n.reg .pred p;\nmbarrier.test_wait.parity.shared::cta.b64 p, [%1], %2;\nselp.u32 %0, 1, 0, p;\n}\n" : "=r"(ok) : "r"(bar), "r"(parity) : "memory");
  return ok;
}
__device__ __forceinline__ void die() { asm volatile("st.volatile.global.u32 [%0], %1;" ::"l"(0ull), "r"(0) : "memory"); }
__device__ __forceinline__ void spin_guard(uint32_t& n) { if (++n == (1u << 22)) die(); }
__device__ __forceinline__ void mbar_wait(uint32_t bar, uint32_t parity) {
  uint32_t t0 = 0;
#pragma unroll 1
  while (!mbar_try(bar, parity)) spin_guard(t0);
}
__device__ __forceinline__ void mbar_wait2(uint32_t b0, uint32_t p0, uint32_t b1, uint32_t p1) {
  uint32_t t0 = 0;
#pragma unroll 1
  while (true) {
    const bool r0 = mbar_try(b0, p0), r1 = mbar_try(b1, p1);
    if (r0 && r1) break;
    spin_guard(t0);
  }
}
__device__ __forceinline__ int tid_now() { int v; asm volatile("mov.u32 %0, %%tid.x;" : "=r"(v)); return v & 127; }
__device__ __forceinline__ bool elect_one() {
  uint32_t p;
  asm volatile("{\n.reg .pred P;\nelect.sync _|P, 0xffffffff;\nselp.u32 %0, 1, 0, P;\n}\n" : "=r"(p));
  return p;
}
__device__ __forceinline__ void bar_sync(int id, int n) { asm volatile("bar.sync %0, %1;" ::"r"(id), "r"(n) : "memory"); }
__device__ __forceinline__ void bar_arrive(int id, int n) { asm volatile("bar.arrive %0, %1;" ::"r"(id), "r"(n) : "memory"); }
__device__ __forceinline__ void fence_async_smem() { asm volatile("fence.proxy.async.shared::cta;" ::: "memory"); }
__device__ __forceinline__ void bulk_g2s(uint32_t dst, const void* src, uint32_t bytes, uint32_t bar) {
  asm volatile("cp.async.bulk.shared::cluster.global.mbarrier::complete_tx::bytes [%0], [%1], %2, [%3];" ::"r"(dst), "l"(src), "r"(bytes), "r"(bar) : "memory");
}
__device__ __forceinline__ void bulk_s2g(void* dst, uint32_t src, uint32_t bytes) {
  asm volatile("cp.async.bulk.global.shared::cta.bulk_group [%0], [%1], %2;" ::"l"(dst), "r"(src), "r"(bytes) : "memory");
}
__device__ __forceinline__ void tma2d(uint32_t dst, const CUtensorMap* m, int c0, int c1, uint32_t bar) {
  asm volatile("cp.async.bulk.tensor.2d.shared::cluster.global.mbarrier::complete_tx::bytes [%0], [%1, {%3, %4}], [%2];" ::"r"(dst), "l"(m), "r"(bar), "r"(c0), "r"(c1) : "memory");
}
__device__ __forceinline__ void tma3d(uint32_t dst, const CUtensorMap* m, int c0, int c1, int c2, uint32_t bar) {
  asm volatile("cp.async.bulk.tensor.3d.shared::cluster.global.mbarrier::complete_tx::bytes [%0], [%1, {%3, %4, %5}], [%2];" ::"r"(dst), "l"(m), "r"(bar), "r"(c0), "r"(c1), "r"(c2) : "memory");
}
__device__ __forceinline__ void tma_rows(uint32_t dst, const CUtensorMap* m, int c0, int rb, uint32_t bar) { tma3d(dst, m, c0, rb * 16, 0, bar); }
__device__ __forceinline__ uint4 ld_ll4(const void* p) {
  uint64_t a, b;
  asm volatile("ld.relaxed.gpu.global.v2.u64 {%0,%1}, [%2];" : "=l"(a), "=l"(b) : "l"(p) : "memory");
  return make_uint4((uint32_t)a, (uint32_t)(a >> 32), (uint32_t)b, (uint32_t)(b >> 32));
}
__device__ __forceinline__ void st_ll4(void* p, uint32_t a, uint32_t b, uint32_t c, uint32_t d) {
  asm volatile("st.relaxed.gpu.global.v2.u64 [%0], {%1,%2};" ::"l"(p), "l"(a | ((uint64_t)b << 32)), "l"(c | ((uint64_t)d << 32)) : "memory");
}
__device__ __forceinline__ void st_ll2(void* p, uint32_t a, uint32_t b) { asm volatile("st.relaxed.gpu.global.u64 [%0], %1;" ::"l"(p), "l"(a | ((uint64_t)b << 32)) : "memory"); }
__device__ __forceinline__ uint2 ld_ll2(const void* p) {
  uint64_t a;
  asm volatile("ld.relaxed.gpu.global.u64 %0, [%1];" : "=l"(a) : "l"(p) : "memory");
  return make_uint2((uint32_t)a, (uint32_t)(a >> 32));
}
__device__ __forceinline__ void wgmma_colsum(float* d, uint64_t da, uint64_t db) {
  asm volatile("{\n.reg .pred p;\nsetp.ne.b32 p, 1, 0;\nwgmma.mma_async.sync.aligned.m64n8k16.f32.bf16.bf16 {%0, %1, %2, %3}, %4, %5, p, 1, 1, 1, 0;\n}\n"
               : "+f"(d[0]), "+f"(d[1]), "+f"(d[2]), "+f"(d[3]) : "l"(da), "l"(db));
}
__device__ __forceinline__ void prefetch_l2(const void* p) { asm volatile("prefetch.global.L2 [%0];" ::"l"(p)); }
__device__ __forceinline__ void pace(uint32_t& t, uint32_t dt) {
  t += dt;
  while ((int32_t)((uint32_t)clock() - t) < 0) { if (NSLEEP) __nanosleep(NSLEEP); }
}
__device__ __forceinline__ void red_relaxed(uint32_t* p) { asm volatile("red.relaxed.gpu.global.add.u32 [%0], 1;" ::"l"(p) : "memory"); }
__device__ __forceinline__ void red_release(uint32_t* p) { asm volatile("red.release.gpu.global.add.u32 [%0], 1;" ::"l"(p) : "memory"); }
__device__ __forceinline__ uint4 ldg4(const void* p) { uint4 v; asm volatile("ld.global.v4.u32 {%0,%1,%2,%3}, [%4];" : "=r"(v.x), "=r"(v.y), "=r"(v.z), "=r"(v.w) : "l"(p) : "memory"); return v; }
__device__ __forceinline__ uint32_t ldg1(const void* p) { uint32_t v; asm volatile("ld.global.u32 %0, [%1];" : "=r"(v) : "l"(p) : "memory"); return v; }
__device__ __forceinline__ void stg4_if(void* p, uint32_t a, uint32_t b, uint32_t c, uint32_t d, bool on) {
  asm volatile("{\n.reg .pred p;\nsetp.ne.u32 p, %5, 0;\n@p st.global.v4.u32 [%0], {%1,%2,%3,%4};\n}\n" ::"l"(p), "r"(a), "r"(b), "r"(c), "r"(d), "r"((uint32_t)on) : "memory");
}
template <int OFF> __device__ __forceinline__ uint32_t lds32(uint32_t a) { uint32_t v; asm volatile("ld.shared.u32 %0, [%1+%2];" : "=r"(v) : "r"(a), "n"(OFF)); return v; }
__device__ __forceinline__ uint4 lds128(uint32_t a) { uint4 v; asm volatile("ld.shared.v4.u32 {%0,%1,%2,%3}, [%4];" : "=r"(v.x), "=r"(v.y), "=r"(v.z), "=r"(v.w) : "r"(a) : "memory"); return v; }
__device__ __forceinline__ float2 lds64f(uint32_t a) { float2 v; asm volatile("ld.shared.v2.f32 {%0,%1}, [%2];" : "=f"(v.x), "=f"(v.y) : "r"(a) : "memory"); return v; }
__device__ __forceinline__ void sts64f(uint32_t a, float x, float y) { asm volatile("st.shared.v2.f32 [%0], {%1,%2};" ::"r"(a), "f"(x), "f"(y) : "memory"); }
__device__ __forceinline__ void sts32(uint32_t a, uint32_t x) { asm volatile("st.shared.u32 [%0], %1;" ::"r"(a), "r"(x) : "memory"); }
__device__ __forceinline__ void sts128(uint32_t a, uint32_t x, uint32_t y, uint32_t z, uint32_t w) { asm volatile("st.shared.v4.u32 [%0], {%1,%2,%3,%4};" ::"r"(a), "r"(x), "r"(y), "r"(z), "r"(w) : "memory"); }
__device__ __forceinline__ void stsm4(uint32_t a, uint32_t r0, uint32_t r1, uint32_t r2, uint32_t r3) {
  asm volatile("stmatrix.sync.aligned.m8n8.x4.shared.b16 [%0], {%1,%2,%3,%4};" ::"r"(a), "r"(r0), "r"(r1), "r"(r2), "r"(r3) : "memory");
}
__device__ __forceinline__ void stsm4t(uint32_t a, uint32_t r0, uint32_t r1, uint32_t r2, uint32_t r3) {
  asm volatile("stmatrix.sync.aligned.m8n8.x4.trans.shared.b16 [%0], {%1,%2,%3,%4};" ::"r"(a), "r"(r0), "r"(r1), "r"(r2), "r"(r3) : "memory");
}
__device__ __forceinline__ void ldsm4t(uint32_t* r, uint32_t a) {
  asm volatile("ldmatrix.sync.aligned.m8n8.x4.trans.shared.b16 {%0,%1,%2,%3}, [%4];" : "=r"(r[0]), "=r"(r[1]), "=r"(r[2]), "=r"(r[3]) : "r"(a) : "memory");
}
__device__ __forceinline__ uint32_t pack2(float lo, float hi) { uint32_t r; asm("cvt.rn.bf16x2.f32 %0, %1, %2;" : "=r"(r) : "f"(hi), "f"(lo)); return r; }
__device__ __forceinline__ float bf_lo(uint32_t u) { return __uint_as_float(u << 16); }
__device__ __forceinline__ float bf_hi(uint32_t u) { return __uint_as_float(u & 0xffff0000u); }
__device__ __forceinline__ float tanh_fast(float x) { float y; asm("tanh.approx.f32 %0, %1;" : "=f"(y) : "f"(x)); return y; }
__device__ __forceinline__ uint32_t hmul2(uint32_t a, uint32_t b) { uint32_t r; asm("mul.rn.bf16x2 %0, %1, %2;" : "=r"(r) : "r"(a), "r"(b)); return r; }
__device__ __forceinline__ uint32_t hfma2(uint32_t a, uint32_t b, uint32_t c) { uint32_t r; asm("fma.rn.bf16x2 %0, %1, %2, %3;" : "=r"(r) : "r"(a), "r"(b), "r"(c)); return r; }
__device__ __forceinline__ uint32_t prmt(uint32_t a, uint32_t b, uint32_t s) { return __byte_perm(a, b, s); }

__device__ __forceinline__ uint32_t ld_relaxed(const uint32_t* p) { uint32_t v; asm volatile("ld.relaxed.gpu.global.u32 %0, [%1];" : "=r"(v) : "l"(p) : "memory"); return v; }
__device__ __forceinline__ void acquire_fence() { asm volatile("fence.acquire.gpu;\nfence.proxy.async.global;" ::: "memory"); }
__device__ __forceinline__ uint32_t load_epoch(const Params& p, int idx, int lane) { return ld_relaxed(&p.scr->epoch[idx + (((lane * lane) & 3) == 2 ? 1 : 0)]); }
__device__ __forceinline__ void poll_counter(const uint32_t* cnt, uint32_t target) {
  uint32_t t0 = 0;
#pragma unroll 1
  while (!__all_sync(0xffffffff, ld_relaxed(cnt) == target)) spin_guard(t0);
  acquire_fence();
}

__device__ __forceinline__ int g3_block(int cb, int it) { return it < 3 ? cb * 3 + it : (it - 3 < cb * 3 ? it - 3 : it); }

template <int N, bool A_SWZ, int B_MODE, int DEPTH, class Hook, class Mid>
__device__ __forceinline__ void gemm_loop(float* d, uint32_t sb, int nkb, int sa, int pa, int b0, uint32_t boff, int relA, int relB, int tid, Hook hook, Mid mid) {
  constexpr uint32_t A_STEP = A_SWZ ? 2 : 128;
  constexpr uint32_t B_STEP = B_MODE == 0 ? 128 : (B_MODE == 1 ? 384 : 320);
  const uint64_t da0 = A_SWZ ? mkdesc(sb + OFF_A, 16, 1024, 1) : mkdesc(sb + OFF_A, 1024, 128, 0);
  const uint64_t db0 = B_MODE == 0 ? mkdesc(sb + OFF_B + boff, 8192, 1024, 1) : mkdesc(sb + OFF_B + boff, B_MODE == 1 ? 3072 : 2560, 128, 0);
  constexpr int MODA = B_MODE == 0 ? NA : NA2;
  constexpr int MODB = B_MODE == 2 ? 6 : NB;
  int sbk = b0 % MODB, pb = (b0 / MODB) & 1;
  auto boffs = [](int s_) { return B_MODE == 2 ? (s_ == 5 ? 0 : s_ + 1) * (20480 >> 4) : s_ * (B_SLOT >> 4); };
  uint32_t rel = 0;
  uint64_t da = da0 + sa * (A_SLOT >> 4), db = db0 + boffs(sbk);
  const bool doR = tid < 2 ? tid < relA : tid - 2 < relB;
  mbar_wait2(sb + BAR_AF + 8 * sa, pa, sb + BAR_BF + 8 * sbk, pb);
  if constexpr (DEPTH == 0) {
#pragma unroll
    for (int i = 0; i < N / 2; i++) asm volatile("" : "=f"(d[i]));
#pragma unroll 1
    for (int it = 0; it < nkb; it++) {
      WG_FENCE();
#pragma unroll
      for (int j = 0; j < 4; j++) WG<N>::ss(d, da + j * A_STEP, db + j * B_STEP, j ? 1 : it);
      WG_COMMIT();
      const uint32_t prel = rel;
      rel = sb + BAR_AE + 8 * (tid < 2 ? sa : sbk + NA);
      if (++sa == MODA) { sa = 0; pa ^= 1; }
      if (++sbk == MODB) { sbk = 0; pb ^= 1; }
      da = da0 + sa * (A_SLOT >> 4); db = db0 + boffs(sbk);
      const bool r0 = mbar_test(sb + BAR_AF + 8 * sa, pa), r1 = mbar_test(sb + BAR_BF + 8 * sbk, pb);
      WG_WAIT(1);
      mbar_arrive_if(prel, doR && prel != 0);
      if (it == 2) {
        WG_WAIT(0);
        mbar_expect_if(sb + BAR_AF + 8 * (tid == 8 ? 8 : tid), A_SLOT, tid < 9);
        mbar_arrive_if(rel, doR);
        rel = 0;
      }
      mid(it);
      if (it + 1 < nkb && !(r0 && r1)) {
        mbar_wait2(sb + BAR_AF + 8 * sa, pa, sb + BAR_BF + 8 * sbk, pb);
      }
    }
  } else
#pragma unroll 1
  for (int it = 0; it < nkb; it++) {
    WG_FENCE();
    WG<N>::ss(d, da, db, 1);
    const uint32_t prel = rel;
    rel = sb + BAR_AE + 8 * (tid < 2 ? sa : sbk + NA);
    if (++sa == MODA) { sa = 0; if (B_MODE) pa ^= 1; }
    if (++sbk == MODB) { sbk = 0; pb ^= 1; }
    if (DEPTH == 1) { WG_COMMIT(); WG_WAIT(1); }
    WG<N>::ss(d, da + A_STEP, db + B_STEP, 1);
    WG_COMMIT();
    WG_WAIT(1);
    if (EARLY == 1) mbar_arrive_if(prel, doR && it != 0);
    WG<N>::ss(d, da + 2 * A_STEP, db + 2 * B_STEP, 1);
    if (DEPTH == 1) WG_COMMIT();
    if (EARLY != 1) mbar_arrive_if(prel, doR && it != 0);
    const bool r0 = mbar_test(sb + BAR_AF + 8 * sa, pa), r1 = mbar_test(sb + BAR_BF + 8 * sbk, pb);
    const uint64_t da3 = da + 3 * A_STEP, db3 = db + 3 * B_STEP;
    da = da0 + sa * (A_SLOT >> 4); db = db0 + boffs(sbk);
    if (DEPTH == 1) WG_WAIT(1);
    WG<N>::ss(d, da3, db3, 1);
    WG_COMMIT();
    mid(it);
    if (it + 1 < nkb) {
      if (!(r0 && r1)) {
        mbar_wait2(sb + BAR_AF + 8 * sa, pa, sb + BAR_BF + 8 * sbk, pb);
      }
    }
    if (DEPTH == 2) WG_WAIT(1);
  }
  hook();
  WG_WAIT(0);
  acc_fence<N / 2>(d);
  mbar_arrive_if(rel, doR);
}

__device__ __forceinline__ void fold_mean(float* d, uint32_t cs, float ma, float mb, int t) {
  const uint32_t ha = pack2(-ma, -ma), hb = pack2(-mb, -mb);
  const float la = -ma - bf_lo(ha), lb = -mb - bf_lo(hb);
  const uint32_t a[4] = {t ? 0u : ha, t ? 0u : hb, t ? 0u : pack2(la, la), t ? 0u : pack2(lb, lb)};
  WG_FENCE();
  WG<192>::rst(d, a, mkdesc(cs, 0, 32, 0));
  WG_COMMIT();
}
__device__ __forceinline__ void gelu_tile(const float* d, uint32_t* z, float* st, float ra, float rb) {
  const float kA = 0.7978845608028654f, kB = 0.7978845608028654f * 0.044715f;
  const float c1a = kA * ra, c3a = kB * ra * ra * ra, c1b = kA * rb, c3b = kB * rb * rb * rb;
  float acc[8];
#pragma unroll
  for (int i = 0; i < 8; i++) acc[i] = 0.f;
#pragma unroll
  for (int j = 0; j < 24; j++) {
    float r[4];
#pragma unroll
    for (int e = 0; e < 4; e++) {
      const float v = d[4 * j + e];
      const float a = v * fmaf(v * v, e < 2 ? c3a : c3b, e < 2 ? c1a : c1b);
      r[e] = fmaf(v, tanh_fast(a), v);
      acc[e] += r[e];
      acc[4 + e] = fmaf(r[e], r[e], acc[4 + e]);
    }
    z[2 * j] = pack2(r[0], r[1]);
    z[2 * j + 1] = pack2(r[2], r[3]);
  }
  st[0] = acc[0] + acc[1]; st[1] = acc[4] + acc[5]; st[2] = acc[2] + acc[3]; st[3] = acc[6] + acc[7];
}

template <int Q> __device__ __forceinline__ void conv_load(uint32_t* a, uint32_t ab) {
  a[0] = lds32<512 * Q>(ab);       a[1] = lds32<512 * Q + 256>(ab);  a[2] = lds32<512 * Q + 16>(ab);   a[3] = lds32<512 * Q + 272>(ab);
  a[4] = lds32<512 * Q + 32>(ab);  a[5] = lds32<512 * Q + 288>(ab);  a[6] = lds32<512 * Q + 48>(ab);   a[7] = lds32<512 * Q + 304>(ab);
  a[8] = lds32<512 * Q + 64>(ab);  a[9] = lds32<512 * Q + 320>(ab);  a[10] = lds32<512 * Q + 80>(ab);  a[11] = lds32<512 * Q + 336>(ab);
  a[12] = lds32<512 * Q + 96>(ab); a[13] = lds32<512 * Q + 352>(ab); a[14] = lds32<512 * Q + 112>(ab); a[15] = lds32<512 * Q + 368>(ab);
}
template <int Q, int L> __device__ __forceinline__ void conv_step(float* d, uint32_t (*a)[16], uint32_t ab, uint64_t db) {
  WG_FENCE();
#pragma unroll
  for (int s = 0; s < 4; s++) WG<128 - 16 * Q>::rs(d, a[Q] + 4 * s, db + s + 16 * Q);
  WG_COMMIT();
  if (CPIN) WG_WAIT(1);
  if (L >= 0) conv_load<(L >= 0 ? L : 0)>(a[L >= 0 ? L : 0], ab);
  if (CW0 || Q == 0) WG_WAIT(0);
}

__device__ __forceinline__ int seg_col(int cb, int h) { return (cb >> 1) * 320 + (cb & 1) * 32 + h * 64; }
__device__ __forceinline__ void final_load_x(uint32_t (*xw)[10], uint32_t xt, int cb, int h, int w, int lane) {
  const int g = lane >> 2, t = lane & 3, cc = seg_col(cb, h) >> 3;
  const int c0 = cc + t, c1 = c0 + 24, c2 = cc + 16 - 6 * h + (t >> 1);
  const uint32_t r0 = xt + (w * 16 + g) * 128;
#pragma unroll
  for (int r = 0; r < 2; r++) {
    const uint4 u = lds128(r0 + r * 1024 + (c0 >> 3) * A_SLOT + (((c0 ^ g) & 7) << 4)), v = lds128(r0 + r * 1024 + (c1 >> 3) * A_SLOT + (((c1 ^ g) & 7) << 4));
    const float2 z = lds64f(r0 + r * 1024 + (c2 >> 3) * A_SLOT + (((c2 ^ g) & 7) << 4) + (t & 1) * 8);
    xw[r][0] = u.x; xw[r][1] = u.y; xw[r][2] = u.z; xw[r][3] = u.w;
    xw[r][4] = v.x; xw[r][5] = v.y; xw[r][6] = v.z; xw[r][7] = v.w;
    xw[r][8] = __float_as_uint(z.x); xw[r][9] = __float_as_uint(z.y);
  }
}
__device__ __forceinline__ void final_s_early(uint32_t (*sw)[10], const uint32_t (*xw)[10], uint32_t ya, float2 s0, float2 s1) {
  const uint32_t r2[2] = {pack2(s0.y, s0.y), pack2(s1.y, s1.y)};
  const float na = -s0.x * bf_lo(r2[0]), nb = -s1.x * bf_lo(r2[1]);
  const uint32_t n2[2] = {pack2(na, na), pack2(nb, nb)};
#pragma unroll
  for (int j = 0; j < 10; j += 2) {
    uint32_t y[4];
    if (j < 4 || j == 8) ldsm4t(y, ya + (j < 4 ? j : 4) * 1024);
#pragma unroll
    for (int e = 0; e < 4; e++) {
      const uint32_t xn = hfma2(xw[e & 1][j + (e >> 1)], r2[e & 1], n2[e & 1]);
      sw[e & 1][j + (e >> 1)] = (j < 4 || j == 8) ? hmul2(xn, y[e]) : xn;
    }
  }
}
__device__ __forceinline__ bool final_late(uint32_t* y, uint32_t ya) {
  ldsm4t(y, ya + 6144);
  ldsm4t(y + 4, ya + 8192);
  uint32_t zero = 0;
#pragma unroll
  for (int e = 0; e < 8; e++) zero |= (y[e] - 0x00010001u) & ~y[e];
  return (zero & 0x80008000u) == 0;
}
__device__ __forceinline__ bool bar_all(int id, int n, bool c) {
  uint32_t r;
  asm volatile("{\n.reg .pred p, q;\nsetp.ne.u32 p, %3, 0;\nbar.red.and.pred q, %1, %2, p;\nselp.u32 %0, 1, 0, q;\n}\n" : "=r"(r) : "r"(id), "r"(n), "r"((uint32_t)c) : "memory");
  return r;
}
__device__ __forceinline__ void final_out(const float* d, const uint32_t (*xw)[10], const uint32_t (*sw)[10], float ra, float rb, __nv_bfloat16* o0, int h, int t) {
  const float ca = 0.25f * ra, cb = 0.25f * rb;
  uint32_t o[2][10];
#pragma unroll
  for (int j = 0; j < 10; j++) {
#pragma unroll
    for (int r = 0; r < 2; r++) {
      const float h0 = d[4 * j + 2 * r] * (r ? cb : ca), h1 = d[4 * j + 2 * r + 1] * (r ? cb : ca);
      o[r][j] = hfma2(pack2(fmaf(h0, tanh_fast(h0), h0), fmaf(h1, tanh_fast(h1), h1)), sw[r][j], xw[r][j]);
      __nv_bfloat16* q = o0 + r * 8 * kD;
      if (j == 3) stg4_if(q + t * 8, o[r][0], o[r][1], o[r][2], o[r][3], true);
      if (j == 7) stg4_if(q + 192 + t * 8, o[r][4], o[r][5], o[r][6], o[r][7], true);
      if (j == 9) asm volatile("st.global.v2.u32 [%0], {%1,%2};" ::"l"(q + 128 - 48 * h + t * 4), "r"(o[r][8]), "r"(o[r][9]) : "memory");
    }
  }
}

struct Taps { uint4 r0, r1; uint32_t n0, n1, dd; };
__device__ __forceinline__ void load_taps(Taps& k, const Params& p, int ch, int tid) {
  const uint4* kp = (const uint4*)(p.ssmk + (size_t)ch * kS);
  k.r0 = ldg4(kp + tid); k.r1 = ldg4(kp + 128 + tid);
  k.n0 = ldg1(kp + tid + 1); k.n1 = tid < 127 ? ldg1(kp + 129 + tid) : 0u;
  k.dd = __bfloat16_as_ushort(p.ssmD[ch]);
}
__device__ __forceinline__ void load_convx(const Params& p, uint32_t cv, uint32_t bar, int ch) {
  mbar_expect(bar, 4096);
  bulk_g2s(cv, p.scr->kvx + (size_t)ch * 4096, 2048, bar);
  bulk_g2s(cv + XB_PL, p.scr->kvx + (size_t)ch * 4096 + 2048, 2048, bar);
}
#define CW 3
#define CSTAMP(j)
__device__ __forceinline__ void zero_pads(uint32_t cv, int lane) {
  if (lane < 8) sts128(cv + (lane >> 2) * XB_PL + 2048 + (lane & 3) * 16, 0, 0, 0, 0);
  else if (lane < 12) sts128(cv + ((lane & 2) ? CV_KO : CV_KE) + (lane & 1) * 16, 0, 0, 0, 0);
  fence_async_smem();
  __syncwarp();
}
__device__ __forceinline__ int y_row(int c, uint32_t par) {
  const int hf = c >= 320, cc = c - hf * 320, u = cc >> 6, cb = hf * 2 + ((cc >> 5) & 1);
  if (u == 2) return cb * 96 + ((cc >> 4) & 1) * 48 + 32 + (cc & 1) + ((cc >> 1) & 1) * 8 + ((cc >> 2) & 3) * 2;
  return (u < 2 ? cb * 96 + u * 48 : 384 + par * 256 + cb * 64 + (u - 3) * 32) + (cc & 1) + ((cc >> 1) & 3) * 8 + ((cc >> 3) & 3) * 2;
}
__device__ __forceinline__ void z_store(const Params& p, uint32_t src, int rb, int cb, int q) {
  uint8_t* dst = p.scr->z2 + (size_t)(cb * 32 + q * 16 + (rb >> 2)) * B_SLOT + (rb & 3) * 6144;
  bulk_s2g(dst, src + q * 12288, 6144);
  bulk_s2g(dst + 8 * B_SLOT, src + q * 12288 + 6144, 6144);
  asm volatile("cp.async.bulk.commit_group;\ncp.async.bulk.wait_group 0;" ::: "memory");
}
__device__ __forceinline__ void y_store(const Params& p, uint32_t sb, int h, int ch, uint32_t par) {
  uint8_t* dst = p.scr->y + (size_t)y_row(ch, par) * 4096;
  if (elect_one()) {
    bulk_s2g(dst, sb + OFF_A + 9 * A_SLOT + h * 4096, 4096);
    asm volatile("cp.async.bulk.commit_group;\ncp.async.bulk.wait_group 0;" ::: "memory");
  }
  __syncwarp();
}
__device__ __forceinline__ void conv_service(const Params& p, uint32_t sb, int h, int ch, bool first) {
  bar_sync(NB_WGA + 8 + h, 160);
  const bool now = !first || __all_sync(0xffffffff, mbar_test(sb + BAR_KV, 0));
  if (now && elect_one()) load_convx(p, sb + OFF_CV + (1 - h) * CV_SZ, sb + BAR_XF + 8 * h, ch + 128);
  bar_sync(NB_WGA + 8 + h, 160);
  y_store(p, sb, h, ch, 0);
  if (!now) {
    mbar_wait(sb + BAR_KV, 0);
    if (elect_one()) load_convx(p, sb + OFF_CV + (1 - h) * CV_SZ, sb + BAR_XF + 8 * h, ch + 128);
  }
}
__device__ __forceinline__ uint32_t y_tile(int h) { return OFF_CV + (1 - h) * 13312; }
__device__ __forceinline__ void load_late_y(const Params& p, uint32_t sb, int h, int rb, int cb, uint32_t par) {
  mbar_expect(sb + BAR_YL + 16 * h, 4096);
  tma2d(sb + y_tile(h) + 6144, &p.tmY, rb * 64, 384 + par * 256 + cb * 64 + h * 32, sb + BAR_YL + 16 * h);
  tma2d(sb + y_tile(h) + 8192, &p.tmY, rb * 64, 400 + par * 256 + cb * 64 + h * 32, sb + BAR_YL + 16 * h);
}
__device__ __forceinline__ void held_service(const Params& p, uint32_t sb, int h, int ch, int rb, int cb, uint32_t tag, int lane) {
#pragma unroll 1
  for (int i = 0; i < 8; i++) sts128(sb + OFF_A + 9 * A_SLOT + h * 4096 + i * 512 + lane * 16, 0, 0, 0, 0);
  fence_async_smem();
  __syncwarp();
  y_store(p, sb, h, ch, ~tag & 1);
  mbar_wait(sb + BAR_YT, 1);
  bar_sync(NB_WGA + 8 + h, 160);
  bar_sync(NB_WGA + 8 + h, 160);
  uint8_t* dst = p.scr->y + (size_t)y_row(ch, tag & 1) * 4096;
  if (elect_one()) {
    bulk_s2g(dst, sb + OFF_A + 9 * A_SLOT + h * 4096, 4096);
    asm volatile("cp.async.bulk.commit_group;" ::: "memory");
    mbar_expect(sb + BAR_XF + 8 * h, 6144);
#pragma unroll 1
    for (int i = 0; i < 3; i++) tma2d(sb + y_tile(h) + i * 2048, &p.tmY, rb * 64, cb * 96 + h * 48 + i * 16, sb + BAR_XF + 8 * h);
  }
  mbar_wait(sb + BAR_AE + 8 * (LL_AT - 1), 1);
  if (elect_one()) { load_late_y(p, sb, h, rb, cb, tag & 1); asm volatile("cp.async.bulk.wait_group 0;" ::: "memory"); }
}
__device__ __forceinline__ void conv_worker(const Params& p, Taps& k, uint32_t cv, uint32_t yb0,
                                            uint32_t xbar, int nbar, int ch0, int n, uint32_t holdbar, int w, int lane,
                                            int tid, int st0, int rb, int cb) {
  const int g = lane >> 2, t = lane & 3, w0 = w & 1, w1 = w >> 1;
  const uint32_t ab = cv + ((g & 1) ? CV_KE : CV_KO) + 32 + 2 * (64 * w0 + 8 * w1 + ((g - 15) & ~1) + 2 * t);
  const uint32_t scA = cv + (w1 ? CV_KO : CV_KE) + 32, scB = scA + 2048;
  const int dl = (t >> 1) ^ 1;
  if (n == 2) mbar_wait(xbar, 0);
  STAMPW(st0 + 3);
#pragma unroll 1
  for (int i = 0; i < n; i++) {
    if (tid == 0) {
      k.r0.x = (k.r0.x & 0xffff0000u) | (pack2(bf_lo(k.r0.x) + bf_lo(k.dd), 0.f) & 0xffffu);
      sts32(cv + CV_KO + 28, k.r0.x << 16);
    }
    sts128(cv + CV_KE + 32 + tid * 16, k.r0.x, k.r0.y, k.r0.z, k.r0.w);
    sts128(cv + CV_KO + 32 + tid * 16, prmt(k.r0.x, k.r0.y, 0x5432), prmt(k.r0.y, k.r0.z, 0x5432), prmt(k.r0.z, k.r0.w, 0x5432), prmt(k.r0.w, k.n0, 0x5432));
    sts128(cv + CV_KE + 2080 + tid * 16, k.r1.x, k.r1.y, k.r1.z, k.r1.w);
    sts128(cv + CV_KO + 2080 + tid * 16, prmt(k.r1.x, k.r1.y, 0x5432), prmt(k.r1.y, k.r1.z, 0x5432), prmt(k.r1.z, k.r1.w, 0x5432), prmt(k.r1.w, k.n1, 0x5432));
    if (i + 1 < n) load_taps(k, p, ch0 + (i + 1) * 128, tid);
    bar_sync(nbar, 128);
    CSTAMP(0);
    const uint64_t db = mkdesc(cv + (i & 0x1000), XB_PL, 128, 0);
    float d[64];
    uint32_t a[8][16];
    if (i == 0) mbar_wait(xbar, 0);
    conv_load<7>(a[7], ab); conv_load<6>(a[6], ab); conv_load<5>(a[5], ab); conv_load<4>(a[4], ab);
#pragma unroll
    for (int j = 0; j < 64; j++) d[j] = 0.f;
    mbar_wait(xbar, i & 1);
    if (i + 1 == n) mbar_wait(holdbar, 1);
    CSTAMP(1);
    conv_step<7, -1>(d, a, ab, db); conv_step<6, -1>(d, a, ab, db); conv_step<5, -1>(d, a, ab, db); conv_step<4, 3>(d, a, ab, db);
    conv_step<3, 2>(d, a, ab, db);
    conv_step<2, 1>(d, a, ab, db);
    conv_step<1, 0>(d, a, ab, db);
    conv_step<0, -1>(d, a, ab, db);
    acc_fence<64>(d);
    CSTAMP(2);
    bar_sync(nbar + 8, 160);
    float E[16][2];
#pragma unroll
    for (int j = 0; j < 15; j++) { E[j][0] = d[4 * j] + d[4 * j + 6]; E[j][1] = d[4 * j + 1] + d[4 * j + 7]; }
    E[15][0] = d[60]; E[15][1] = d[61];
    if (w0 == 0) {
#pragma unroll
      for (int j = 8; j < 16; j++) sts64f(scA + (j - 8) * 256 + lane * 8, E[j][0], E[j][1]);
    } else {
      const uint32_t a = scB - dl * 256 + (lane ^ 2) * 8;
#pragma unroll
      for (int j = 1; j < 8; j++) sts64f(a + j * 256, E[j][0], E[j][1]);
      sts64f(scB + (dl ? 7 * 256 : 0) + (lane ^ 2) * 8, dl ? E[8][0] : E[0][0], dl ? E[8][1] : E[0][1]);
    }
    bar_sync(nbar, 128);
    CSTAMP(3);
    uint32_t pk[8];
    if (w0 == 0) {
#pragma unroll
      for (int j = 0; j < 8; j++) { const float2 v = lds64f(scB + j * 256 + lane * 8); pk[j] = pack2(E[j][0] + v.x, E[j][1] + v.y); }
    } else {
      const uint32_t a0 = scA - dl * 256 + (lane ^ 2) * 8;
#pragma unroll
      for (int j = 9; j < 16; j++) { const float2 v = lds64f(a0 + (j - 8) * 256); pk[j - 8] = pack2(E[j][0] + v.x, E[j][1] + v.y); }
      const float2 v = lds64f(scA + (dl ? 7 * 256 : 0) + (lane ^ 2) * 8);
      pk[0] = pack2((dl ? 0.f : E[8][0]) + v.x, (dl ? 0.f : E[8][1]) + v.y);
    }
    CSTAMP(4);
    if (i + 1 == n) {
#pragma unroll
      for (int j = 0; j < 8; j++) pk[j] = ~pk[j];
    }
    const int c1 = (w0 ? 35 : 95) - lane, c0 = (w0 && lane < 4) ? c1 - 32 : c1 + 32;
    stsm4t(yb0 + 128 * (c0 & 31) + (((2 * (c0 >> 5) + w1) ^ (c0 & 7)) << 4), pk[0], pk[1], pk[2], pk[3]);
    stsm4t(yb0 + 128 * (c1 & 31) + (((2 * (c1 >> 5) + w1) ^ (c1 & 7)) << 4), pk[4], pk[5], pk[6], pk[7]);
    fence_async_smem();
    bar_sync(nbar + 8, 160);
    CSTAMP(5);
    STAMPW(st0 + i);
    if (n == 2 && i == 0) {
      const int u = (tid >> 3) % 5, kg = rb * 3 + (tid < 120 ? (tid >> 3) / 5 : 0), c = u < 4 ? (u >> 1) * 10 + (u & 1) * 4 : 8, o2 = u < 4 ? 2 : 10;
      const uint4* wp = (const uint4*)p.wout + (uint32_t)((kg * 8 + (tid & 7)) * (kD / 8) + (seg_col(cb, 0) >> 3) + (u < 4 ? (u >> 1) * 8 + (u & 1) * 24 : 16));
      const uint4 w0 = ldg4(wp), w1 = ldg4(wp + 1), w2 = ldg4(wp + 2), w3 = ldg4(wp + 3);
      uint8_t* dst = p.scr->wo + (uint32_t)(cb * (12 * 20480) + kg * 2560 + c * 128 + (tid & 7) * 16);
      const bool f = u < 4, on = tid < 120;
      stg4_if(dst, w0.x, f ? w1.x : w0.z, f ? w2.x : w1.x, f ? w3.x : w1.z, on);
      stg4_if(dst + 128, w0.y, f ? w1.y : w0.w, f ? w2.y : w1.y, f ? w3.y : w1.w, on);
      stg4_if(dst + o2 * 128, f ? w0.z : w2.x, f ? w1.z : w2.z, f ? w2.z : w3.x, w3.z, on);
      stg4_if(dst + o2 * 128 + 128, f ? w0.w : w2.y, f ? w1.w : w2.w, f ? w2.w : w3.y, w3.w, on);
      bar_arrive(NB_WO, 160);
    }
  }
}

struct KvRegs { uint32_t k[11], v[8]; uint4 sh; };
__device__ __forceinline__ void kv_load(KvRegs& q, const __nv_bfloat16* kp, const __nv_bfloat16* vp, const __nv_bfloat16* sp, bool halo) {
#pragma unroll
  for (int i = 0; i < 11; i++) q.k[i] = (i >= 3 || halo) ? ldg1(kp + i * kD) : 0u;
#pragma unroll
  for (int i = 0; i < 8; i++) q.v[i] = ldg1(vp + i * kD);
  q.sh = ldg4(sp);
}
__device__ __forceinline__ void kv_unit(const KvRegs& q, uint32_t oa) {
  const uint32_t w0 = prmt(q.sh.x, q.sh.z, 0x5410), w1 = prmt(q.sh.x, q.sh.z, 0x7632), w2 = prmt(q.sh.y, q.sh.w, 0x5410), w3 = prmt(q.sh.y, q.sh.w, 0x7632);
  uint32_t r[8];
#pragma unroll
  for (int i = 0; i < 8; i++) r[i] = hmul2(hfma2(q.k[i + 3], w0, hfma2(q.k[i + 2], w1, hfma2(q.k[i + 1], w2, hmul2(q.k[i], w3)))), q.v[i]);
  sts128(oa, prmt(r[7], r[6], 0x5410), prmt(r[5], r[4], 0x5410), prmt(r[3], r[2], 0x5410), prmt(r[1], r[0], 0x5410));
  sts128(oa + 2048, prmt(r[7], r[6], 0x7632), prmt(r[5], r[4], 0x7632), prmt(r[3], r[2], 0x7632), prmt(r[1], r[0], 0x7632));
}

__device__ __forceinline__ void gather_colsum(const Params& p, uint32_t sb, int cb, int part, uint32_t tag, int lane) {
  uint4 v[3];
  uint32_t t0 = 0;
#pragma unroll 1
  while (true) {
    bool ok = true;
#pragma unroll
    for (int i = 0; i < 3; i++) {
      v[i] = ld_ll4(&p.scr->colsum[(part ? 0 : 768) + cb * 192 + i * 64 + lane * 2]);
      ok = ok && v[i].y == tag && v[i].w == tag;
    }
    if (__all_sync(0xffffffff, ok)) break;
    spin_guard(t0);
  }
#pragma unroll
  for (int i = 0; i < 3; i++) {
    const uint32_t hi = pack2(__uint_as_float(v[i].x), __uint_as_float(v[i].z)), ca = sb + OFF_CS + (1 - part) * 768 + i * 256 + (lane >> 2) * 32 + (lane & 3) * 4;
    sts32(ca, hi);
    sts32(ca + 16, pack2(__uint_as_float(v[i].x) - bf_lo(hi), __uint_as_float(v[i].z) - bf_hi(hi)));
  }
  __syncwarp();
  if (lane == 0) mbar_arrive(sb + BAR_ST + 8 * part);
}

__device__ __forceinline__ void helper_cta(const Params& p, uint32_t sb, int cb, int warp, int lane) {
  constexpr int NS = 9, ONES = NS * B_SLOT, BF = ONES + 256, BE = BF + 8 * NS;
  if (warp < NS && elect_one()) {
    mbar_init(sb + BF + 8 * warp, 1); mbar_init(sb + BE + 8 * warp, 1);
    fence_async_smem();
    if (warp == 0) { mbar_expect(sb + BF, B_SLOT); tma3d(sb, &p.tmW, 0, 0, 12 + cb * 3, sb + BF); }
  }
  if (warp == 15) { sts32(sb + ONES + lane * 4, 0x3f803f80u); sts32(sb + ONES + 128 + lane * 4, 0x3f803f80u); fence_async_smem(); }
  __syncthreads();
  if (warp == 4) {
    int s = 1, ph = 1;
    uint32_t tp = clock() + HP0;
#pragma unroll 1
    for (int it = 1; it < 20; it++) {
      if (HPD && it >= 10) pace(tp, HPD);
      mbar_wait(sb + BE + 8 * s, ph);
      if (elect_one()) { mbar_expect(sb + BF + 8 * s, B_SLOT); tma3d(sb + s * B_SLOT, &p.tmW, 0, (it < 10 ? it : it - 10) * 64, (it < 10 ? 12 : 0) + cb * 3, sb + BF + 8 * s); }
      if (++s == NS) { s = 0; ph ^= 1; }
    }
  } else if (warp < 4) {
    const uint32_t tag = load_epoch(p, 128 + cb, lane) + 1;
    const uint64_t db = mkdesc(sb + ONES, 128, 128, 0);
    uint2* dst = p.scr->colsum + cb * 192 + warp * 16 + (lane >> 2);
    if ((lane & 3) == 0) {
#pragma unroll 1
      for (int j = 0; j < 12; j++) st_ll2(dst + (j < 6 ? 768 : 0) + ((j % 6) >> 1) * 64 + (j & 1) * 8, 0, 0);
    }
    int s = 0, ph = 0;
#pragma unroll 1
    for (int part = 0; part < 2; part++) {
      float d[12];
#pragma unroll
      for (int i = 0; i < 12; i++) d[i] = 0.f;
#pragma unroll 1
      for (int it = 0; it < 10; it++) {
        mbar_wait(sb + BF + 8 * s, ph);
        const uint64_t da = mkdesc(sb + s * B_SLOT, 8192, 1024, 1);
        WG_FENCE();
#pragma unroll
        for (int j = 0; j < 12; j++) wgmma_colsum(d + 4 * (j % 3), da + (j % 3) * 512 + (j / 3) * 128, db);
        WG_COMMIT();
        WG_WAIT(1);
        mbar_arrive_if(sb + BE + 8 * (s == 0 ? NS - 1 : s - 1), threadIdx.x == 0 && (it | part) != 0);
        if (++s == NS) { s = 0; ph ^= 1; }
      }
      WG_WAIT(0);
      acc_fence<12>(d);
      if ((lane & 3) == 0) {
#pragma unroll
        for (int j = 0; j < 6; j++) st_ll2(dst + (part ? 0 : 768) + (j >> 1) * 64 + (j & 1) * 8, __float_as_uint(d[2 * j]), tag);
      }
      STAMPW(1 + part);
    }
    if (threadIdx.x == 0) *(volatile uint32_t*)&p.scr->epoch[128 + cb] = tag;
  }
}

__global__ void __launch_bounds__(512, 1) fused_kernel(const __grid_constant__ Params p) {
  extern __shared__ __align__(1024) uint8_t smem[];
  const int warp = __shfl_sync(0xffffffff, (int)(threadIdx.x >> 5), 0);
  const int lane = threadIdx.x & 31, tid = threadIdx.x & 127;
  const uint32_t sb = __shfl_sync(0xffffffff, (uint32_t)__cvta_generic_to_shared(smem), 0);
  const uint32_t tstart = clock();
  if (elect_one()) {
    if (warp < 5) asm volatile("prefetch.tensormap [%0];" ::"l"(&p.tmX + warp) : "memory");
    mbar_init(sb + OFF_BAR + 8 * warp, 1); mbar_init(sb + OFF_BAR + 128 + 8 * warp, 1); mbar_init(sb + OFF_BAR + 256 + 8 * warp, 2);
    asm volatile("fence.mbarrier_init.release.cluster;" ::: "memory");
  }
  int b = blockIdx.x;
  if (p.by_smid) asm volatile("mov.u32 %0, %%smid;" : "=r"(b));
  b = __shfl_sync(0xffffffff, b, 0);
  const int tp = b >> 1, t7 = (tp - 32) / 7;
  const int lin = tp < 32 ? ((tp & 7) ? (tp & 7) * 16 : 8) + (tp >> 3) * 2 + (b & 1)
                          : (tp < 60 ? (tp - 31 - t7 * 7) * 16 + 8 + t7 * 2 + (b & 1) : (tp < 62 ? -1 : b - 124));
  const int hcb = b & 3;
  if (lin < 0) { helper_cta(p, sb, hcb, warp, lane); return; }
  const int cb = ((lin >> 4) & 1) * 2 + ((lin >> 1) & 1), rb = (lin >> 5) * 8 + ((lin >> 2) & 3) * 2 + (lin & 1);
  const int zs0 = 4 - (cb & 2);
  const int chb = (cb >> 1) * 320 + rb * 2 + (cb & 1);
  if (warp == 0 && elect_one()) {
    mbar_expect(sb + BAR_AF, A_SLOT);
    tma_rows(sb + OFF_A, &p.tmX, 0, rb, sb + BAR_AF);
    mbar_expect(sb + BAR_BF, B_SLOT);
    tma3d(sb + OFF_B, &p.tmW, 0, 0, 12 + cb * 3, sb + BAR_BF);
  }
  if (warp == 1) STAMP(31);
  if (sb & 1023) die();
  __syncthreads();

  if (warp >= 12) {
    asm volatile("setmaxnreg.dec.sync.aligned.u32 32;");
    const uint32_t epoch = load_epoch(p, lin, lane);
    if (warp == 12) {
#pragma unroll 1
      for (int i = 1; i < NA; i++) {
        if (elect_one()) {
          mbar_expect(sb + BAR_AF + 8 * i, A_SLOT);
          tma_rows(sb + OFF_A + i * A_SLOT, &p.tmX, i * 64, rb, sb + BAR_AF + 8 * i);
          if (i < NB) { mbar_expect(sb + BAR_BF + 8 * i, B_SLOT); tma3d(sb + OFF_B + i * B_SLOT, &p.tmW, 0, i * 64, 12 + cb * 3, sb + BAR_BF + 8 * i); }
        }
      }
      STAMP(32);
      uint32_t kvt;
      {
        const int tb = rb * 2 + (cb & 1);
        kvt = __shfl_sync(0xffffffff, (ld_relaxed(p.scr->cnt + CNT_KV + (cb >> 1)) & ~63u) + 64, 0);
        {
          uint32_t tp = tstart;
          pace(tp, KV_T0);
          mbar_arrive_if(sb + BAR_KV + 8, lane == 0);
        }
        if (ST_YIELD) mbar_wait2(sb + BAR_XS, 0, sb + BAR_ST, 0);
#pragma unroll 1
        for (int u = 0; u < 5; u++) {
          mbar_wait(sb + BAR_KU + 8 * u, 0);
          fence_async_smem();
          if (elect_one()) {
            asm volatile("cp.async.bulk.tensor.3d.global.shared::cta.bulk_group [%0, {%2, %3, %4}], [%1];\ncp.async.bulk.commit_group;" ::"l"(&p.tmKV),
                         "r"(sb + OFF_CV + CV_SZ + (u < 3 ? u : u - 3) * 4096), "r"((63 - tb) * 16), "r"((cb >> 1) * 160 + u * 32), "r"(0) : "memory");
            if (u == 1 || u == 4) asm volatile("cp.async.bulk.wait_group 0;" ::: "memory");
            if (u == 1) { mbar_arrive(sb + BAR_KU); red_release(p.scr->cnt + CNT_KV + (cb >> 1)); }
          }
          __syncwarp();
          if (u == 1) {
            STAMP(35);
            if (PFT) { const char* q = (const char*)p.ssmk + chb * 4096 + lane * 128; prefetch_l2(q); prefetch_l2(q + 64 * 4096); }
          }
        }
        zero_pads(sb + OFF_CV + CV_SZ, lane);
        if (elect_one()) { mbar_arrive(sb + BAR_KU + 8); red_release(p.scr->cnt + CNT_KV + 2 + (cb >> 1)); }
        STAMP(30);
        if (lane < 24) {
          const char* r = (const char*)p.wout + (rb * 24 + lane) * (kD * 2) + (cb >> 1) * 640 + (cb & 1) * 384;
          prefetch_l2(r); prefetch_l2(r + 128); prefetch_l2(r + 256 - (cb & 1) * 384);
        }
      }
      poll_counter(p.scr->cnt + CNT_KV + 2 + (cb >> 1), kvt);
      if (elect_one()) mbar_arrive(sb + BAR_KV);
      STAMP(34);
      {
        const char* q = (const char*)p.wsp + (cb * 512 + rb * 16 + (lane >> 1)) * (kS * 2) + (lane & 1) * 128;
        uint32_t tp = clock();
#pragma unroll 1
        for (int i = LEAD / 2; i < WSP_N; i++) {
          prefetch_l2(q + i * 256);
          pace(tp, WSP_D);
        }
      }
      const uint32_t tag = epoch + 1;
      if (HPC) {
        bar_sync(NB_Z2, 160);
        if (elect_one()) bulk_s2g(p.scr->h + (size_t)(rb * 12 + cb * 3) * A_SLOT, sb + OFF_A + 5 * A_SLOT, HPC * A_SLOT);
      }
      mbar_wait(sb + BAR_G2, 0);
      if (elect_one()) {
        bulk_s2g(p.scr->h + (size_t)(rb * 12 + cb * 3 + HPC) * A_SLOT, sb + OFF_A + (5 + HPC) * A_SLOT, (3 - HPC) * A_SLOT);
        asm volatile("cp.async.bulk.commit_group;\ncp.async.bulk.wait_group 0;" ::: "memory");
        red_release(&p.scr->hcnt[(rb >> HGRP) * 32]);
      }
      __syncwarp();
      STAMP(20);
      mbar_wait(sb + BAR_AE + 56, 0);
      STAMP(39);
      poll_counter(&p.scr->hcnt[(rb >> HGRP) * 32], tag * (4 << HGRP));
      STAMP(37);
      if (elect_one()) {
        uint32_t tp = clock();
#pragma unroll 1
        for (int it = 3; it < 12; it++) {
          if (HPACE && it > 3) { tp += HPACE; while ((int32_t)((uint32_t)clock() - tp) < 0) {} }
          bulk_g2s(sb + OFF_A + ((it + 5) % 9) * A_SLOT, p.scr->h + (size_t)(rb * 12 + g3_block(cb, it)) * A_SLOT, A_SLOT, sb + BAR_AF + 8 * ((it + 5) % 9));
        }
      }
      STAMP(21);
    } else if (warp == 13) {
      int s = 0, ph = 0;
#pragma unroll 1
      for (int it = NB; it < 20; it++) {
        mbar_wait(sb + BAR_BE + 8 * s, ph);
        if (elect_one()) { mbar_expect(sb + BAR_BF + 8 * s, B_SLOT); tma3d(sb + OFF_B + s * B_SLOT, &p.tmW, 0, (it < 10 ? it : (it + zs0) % 10) * 64, (it < 10 ? 12 : 0) + cb * 3, sb + BAR_BF + 8 * s); }
        STAMP2(32 + it);
        if (++s == NB) { s = 0; ph ^= 1; }
      }
      mbar_wait(sb + BAR_XC, 0);
#pragma unroll 1
      for (int i = 0; i < LEAD; i++) {
        mbar_wait(sb + BAR_AE + 8 * i, 0);
        if (elect_one()) { mbar_expect(sb + BAR_AF + 8 * i, A_SLOT); tma_rows(sb + OFF_A + i * A_SLOT, &p.tmWsp, i * 64, rb, sb + BAR_AF + 8 * i); }
      }
      poll_counter(p.scr->zcnt + (cb >> ZSH) * 32, (epoch + 1) * (32 << ZSH));
      STAMP(22);
      int sa = LEAD, pa = 0, ia = LEAD;
#pragma unroll 1
      for (int it = 0; it < 32; it++) {
        if (it == ZP_AT) mbar_wait(sb + BAR_ZP, 0);
        if (it == 16) mbar_wait(sb + BAR_Z1, 1);
        mbar_wait2(sb + BAR_BE + 8 * s, ph, sb + BAR_AE + 8 * sa, pa);
        if (elect_one()) {
          mbar_expect(sb + BAR_BF + 8 * s, B_SLOT);
          bulk_g2s(sb + OFF_B + s * B_SLOT, p.scr->z2 + (size_t)(cb * 32 + it) * B_SLOT, B_SLOT, sb + BAR_BF + 8 * s);
        }
#pragma unroll 1
        for (int j = (it < RAMP ? 0 : (it == 4 ? 1 + RAMP : 1)); j > 0 && ia < 32; j--, ia++) {
          if (it == 4) mbar_wait(sb + BAR_AE + 8 * sa, pa);
          if (elect_one()) { mbar_expect(sb + BAR_AF + 8 * sa, A_SLOT); tma_rows(sb + OFF_A + sa * A_SLOT, &p.tmWsp, ia * 64, rb, sb + BAR_AF + 8 * sa); }
          if (++sa == NA2) { sa = 0; pa ^= 1; }
        }
        STAMP2(52 + it);
        if (++s == NB) { s = 0; ph ^= 1; }
      }
      mbar_wait(sb + BAR_WO, 0);
#pragma unroll 1
      for (int it = 0; it < 12; it++) {
        if (it < 6) mbar_wait(sb + BAR_BE + 8 * ((0x110443 >> (4 * it)) & 7), it < 3 ? 1 : 0);
        else mbar_wait(sb + BAR_BE + 8 * s, ph);
        if (elect_one()) {
          mbar_expect(sb + BAR_BF + 8 * s, 20480);
          bulk_g2s(sb + OFF_B + (s == 5 ? 0 : s + 1) * 20480, p.scr->wo + (size_t)(cb * 12 + g3_block(cb, it)) * 20480, 20480, sb + BAR_BF + 8 * s);
        }
        STAMP2(84 + it);
        if (++s == 6) { s = 0; ph ^= 1; }
      }
    } else if (warp == 14) {
      const uint32_t tag = epoch + 1;
      mbar_wait(sb + BAR_AF + 8 * (NA - 1), 0);
      gather_colsum(p, sb, cb, 0, tag, lane);
      STAMP(27);
      bar_sync(NB_Z, 160);
      if (elect_one()) {
        z_store(p, sb + OFF_A + zs0 * A_SLOT, rb, cb, 0);
        STAMP(7);
        red_release(p.scr->zcnt + (cb >> ZSH) * 32);
      }
      STAMP(25);
      bar_sync(NB_Z2, 96);
      if (elect_one()) {
        z_store(p, sb + OFF_A + zs0 * A_SLOT, rb, cb, 1);
        mbar_arrive(sb + BAR_ZP);
        red_release(p.scr->cnt + CNT_Z1 + (cb >> 1));
      }
      STAMP(28);
      mbar_wait(sb + BAR_AE + 72, 0);
      conv_service(p, sb, 0, chb + 64, true);
      bar_sync(NB_WO, 160);
      bar_sync(NB_CD, 64);
      if (elect_one()) { red_release(p.scr->cnt + CNT_WO + cb); red_relaxed(p.scr->cnt + CNT_Y + (cb >> 1)); }
      STAMP(49);
      poll_counter(p.scr->cnt + CNT_WO + cb, tag * 32);
      if (elect_one()) mbar_arrive(sb + BAR_WO);
      STAMP(46);
      held_service(p, sb, 0, chb + 192, rb, cb, tag, lane);
    } else {
      const uint32_t tag = epoch + 1;
      sts32(sb + OFF_BIAS + lane * 4, ldg1(p.bsp + (lane >> 3) * 512 + rb * 16 + (lane & 7) * 2));
      if (lane < 2) sts32(sb + OFF_TAG + lane * 4, lane ? 0 : tag);
      fence_async_smem();
      uint32_t t0 = 0;
      mbar_wait(sb + BAR_AF + 8 * (NA - 1), 0);
#pragma unroll 1
      while (true) {
        const uint4 u = ld_ll4(&p.scr->xstat[rb * 64 + lane]), v = ld_ll4(&p.scr->xstat[rb * 64 + 32 + lane]);
        sts64f(sb + OFF_XS + lane * 8, __uint_as_float(u.x), __uint_as_float(u.z));
        sts64f(sb + OFF_XS + 256 + lane * 8, __uint_as_float(v.x), __uint_as_float(v.z));
        if (__all_sync(0xffffffff, u.y == tag && u.w == tag && v.y == tag && v.w == tag)) break;
        spin_guard(t0);
      }
      STAMP(26);
      __syncwarp();
      if (lane == 0) mbar_arrive(sb + BAR_XS);
      { uint32_t tp = tstart; pace(tp, CS1_T); gather_colsum(p, sb, cb, 1, tag, lane); STAMP(38); }
      mbar_wait(sb + BAR_KU, 1);
      poll_counter(p.scr->cnt + CNT_KV + (cb >> 1), tag * 64);
      if (elect_one()) load_convx(p, sb + OFF_CV, sb + BAR_XF + 8, chb);
      mbar_wait(sb + BAR_KU + 8, 1);
      if (elect_one()) load_convx(p, sb + OFF_CV + CV_SZ, sb + BAR_XF, chb + 64);
      STAMP(48);
      mbar_wait(sb + BAR_AE + 72, 0);
#pragma unroll 1
      for (int i = 0; i < 2; i++) {
        conv_service(p, sb, 1, chb + i * 128, i == 0);
        if (i == 0) {
          poll_counter(p.scr->cnt + CNT_Z1 + (cb >> 1), tag * 64);
          if (elect_one()) mbar_arrive(sb + BAR_Z1);
          STAMP(24);
        }
      }
      bar_arrive(NB_CD, 64);
      mbar_wait(sb + BAR_WO, 0);
      poll_counter(p.scr->cnt + CNT_Y + (cb >> 1), tag * 64);
      STAMP(47);
      if (elect_one()) mbar_arrive(sb + BAR_YT);
      held_service(p, sb, 1, chb + 256, rb, cb, tag, lane);
      if (lane == 0) *(volatile uint32_t*)&p.scr->epoch[lin] = tag;
      STAMP(23);
    }
  } else {
    if (warp == 7) STAMP(36);
    const int wg = warp >> 2, w = warp & 3, g = lane >> 2, t = lane & 3;
    Taps k;
    uint32_t xw[2][10];
    if (wg == 2) {
      asm volatile("setmaxnreg.inc.sync.aligned.u32 160;");
      const int tb = rb * 2 + (cb & 1), c0 = (cb >> 1) * 320;
      const uint32_t cv = sb + OFF_CV + CV_SZ;
      if (w == 0) zero_pads(sb + OFF_CV, lane);
      mbar_wait(sb + BAR_KV + 8, 0);
      const int t0 = tb * 32 + w * 8;
      const __nv_bfloat16* kp = p.k + (size_t)(t0 - 3) * kD + c0 + lane * 2;
      const __nv_bfloat16* vp = p.v + (size_t)t0 * kD + c0 + lane * 2;
      const __nv_bfloat16* sp = p.shift + (c0 + lane * 2) * 4;
      const uint32_t oa = cv + ((3 - w) & 1) * 1024 + lane * 32 + ((((3 - w) >> 1) ^ (lane >> 2)) & 1) * 16;
#pragma unroll 1
      for (int r = 0; r < 2; r++) {
        KvRegs n0, n1, n2;
        STAMPW(r ? 51 : 50);
        kv_load(n0, kp + r * 128, vp + r * 128, sp + r * 512, t0 > 0);
        kv_load(n1, kp + r * 128 + 64, vp + r * 128 + 64, sp + r * 512 + 256, t0 > 0);
        if (r) kv_load(n2, kp + 256, vp + 256, sp + 1024, t0 > 0);
        kv_unit(n0, oa + r * 8192);
        bar_sync(NB_WGC, 128);
        mbar_arrive_if(sb + BAR_KU + 16 * r, tid == 0);
        if (r) mbar_wait(sb + BAR_KU, 1);
        kv_unit(n1, oa + (r ? 0 : 4096));
        bar_sync(NB_WGC, 128);
        mbar_arrive_if(sb + BAR_KU + 16 * r + 8, tid == 0);
        if (r) {
          kv_unit(n2, oa + 4096);
          bar_sync(NB_WGC, 128);
          mbar_arrive_if(sb + BAR_KU + 32, tid == 0);
        } else {
          mbar_wait(sb + BAR_AF + 8 * ((cb >> 1) * 5 + 1), 0);
          mbar_wait2(sb + BAR_AF + 8 * ((cb >> 1) * 5 + 2), 0, sb + BAR_AF + 8 * ((cb >> 1) * 5 + 4), 0);
          final_load_x(xw, sb + OFF_A, cb, 1, w, lane);
          fence_async_smem();
          bar_sync(NB_WGC, 128);
          mbar_arrive_if(sb + BAR_XC, tid == 0);
        }
      }
      STAMPW(13);
      load_taps(k, p, chb, tid);
    } else {
      float d[96];
      if (wg == 0) st_ll2(&p.scr->zstat[(rb * 256 + cb * 64 + w * 16 + g + (t >> 1) * 8) * 2 + (t & 1)], 0, 0);
      else if ((tid & 7) == 0) st_ll4(&p.scr->xstat[rb * 64 + cb * 16 + (tid >> 3)], 0, 0, 0, 0);
      {
        #pragma unroll
        for (int i = 0; i < 96; i++) d[i] = 0.f;
        {
          if (__builtin_expect(wg == 1, 0)) {
            const int tid = tid_now();
            const uint32_t epoch = load_epoch(p, lin, lane);
            float s = 0.f, q = 0.f;
#pragma unroll 1
            for (int i = 0; i < 10; i++) {
              mbar_wait(sb + BAR_AF + 8 * i, 0);
              const uint4 x4 = lds128(sb + OFF_A + i * A_SLOT + cb * 2048 + tid * 16);
              const uint32_t u[4] = {x4.x, x4.y, x4.z, x4.w};
#pragma unroll
              for (int e = 0; e < 4; e++) { const float a = bf_lo(u[e]), c = bf_hi(u[e]); s += a + c; q = fmaf(a, a, q); q = fmaf(c, c, q); }
            }
#pragma unroll
            for (int o = 1; o <= 4; o <<= 1) { s += __shfl_xor_sync(0xffffffff, s, o); q += __shfl_xor_sync(0xffffffff, q, o); }
            const float m = s * (1.f / kD);
            const float r = rsqrtf(fmaxf(fmaf(-m, m, q * (1.f / kD)), 0.f) + 1e-5f);
            if ((tid & 7) == 0) st_ll4(&p.scr->xstat[rb * 64 + cb * 16 + (tid >> 3)], __float_as_uint(m), epoch + 1, __float_as_uint(r), epoch + 1);
            STAMPW(12);
            bar_sync(NB_G1, 256);
          }
          gemm_loop<192, true, 0, D1>(d, sb, 10, wg ? zs0 : 0, 0, 0, 0, wg, 2, tid_now(), [&]() { if (G1_AT == 0 && wg == 0) bar_arrive(NB_G1, 256); }, [](int) {});
          asm volatile("setmaxnreg.inc.sync.aligned.u32 160;");
          STAMPW(wg ? 14 : 1);
          if (wg == 0) ZS(0);
          mbar_wait2(sb + BAR_XS, 0, sb + BAR_ST + 8 * wg, 0);
          if (wg == 0) ZS(1);
        }
        const int t1 = tid_now();
        const uint32_t xa1 = sb + OFF_XS + (w * 16 + ((t1 & 31) >> 2)) * 8;
        const float2 s0 = lds64f(xa1), s1 = lds64f(xa1 + 64);
        uint32_t z[48];
        float st[4];
        fence_async_smem();
        fold_mean(d, sb + OFF_CS + (1 - wg) * 768, s0.x, s1.x, t1 & 3);
        if (G1_AT == 1 && wg == 0) bar_arrive(NB_G1, 256);
        WG_WAIT(0);
        acc_fence<96>(d);
        if (wg == 0) ZS(2);
        gelu_tile(d, z, st, s0.y, s1.y);
        const int tid = tid_now(), lane = tid & 31, g = lane >> 2, t = lane & 3;
        if (wg == 1) {
          uint32_t bra, brb;
          asm volatile("ld.shared.u16 %0, [%1];" : "=r"(bra) : "r"(sb + OFF_BIAS + (w * 16 + g) * 2));
          asm volatile("ld.shared.u16 %0, [%1+16];" : "=r"(brb) : "r"(sb + OFF_BIAS + (w * 16 + g) * 2));
#pragma unroll
          for (int j = 0; j < 96; j++) d[j] = bf_lo((j & 2) ? brb : bra);
          STAMPW(15);
          gemm_loop<192, true, 1, D2>(d, sb, 32, 0, 1, 20, 0, 2, 2, tid, [&]() { if (HOLD_AT < 32) mbar_arrive_if(sb + BAR_GO, tid == 0); }, [](int) {});
          if (HOLD_AT == 32) mbar_arrive_if(sb + BAR_GO, tid == 0);
          STAMPW(16);
          const int t2 = tid_now(), l2 = t2 & 31;
          const uint32_t ha = sb + OFF_A + 5 * A_SLOT + (l2 >> 4) * 1024 + (2 * w + ((l2 >> 3) & 1)) * 128 + (l2 & 7) * 16;
#pragma unroll
          for (int j = 0; j < 24; j += 2) {
#pragma unroll
            for (int e = 0; e < 4; e++) z[2 * j + e] = hmul2(z[2 * j + e], pack2(d[4 * j + 2 * e], d[4 * j + 2 * e + 1]));
            stsm4(ha + j * 1024, z[2 * j], z[2 * j + 1], z[2 * j + 2], z[2 * j + 3]);
            if (HPC && j == HPC * 8 - 2) {
              fence_async_smem();
              bar_arrive(NB_Z2, 160);
            }
          }
          fence_async_smem();
          bar_sync(NB_WGB, 128);
          mbar_arrive_if(sb + BAR_AF + 8 * (t2 == 3 ? (BAR_G2 - BAR_AF) / 8 : (t2 == 4 ? (BAR_GO - BAR_AF) / 8 : 5 + t2)), t2 < (HOLD_AT == 33 ? 5 : 4));
          STAMPW(17);
          {
            float e[80];
            gemm_loop<160, false, 2, DB>(e, sb, 12, 5, 0, 2, 0, 2, 2, tid_now(), []() {}, [](int) {});
            STAMPW(10);
            const int t3 = tid_now();
#pragma unroll
            for (int j = 0; j < 10; j++) {
              sts128(sb + OFF_A + j * 2048 + t3 * 16, pack2(e[8 * j], e[8 * j + 1]), pack2(e[8 * j + 2], e[8 * j + 3]), pack2(e[8 * j + 4], e[8 * j + 5]),
                     pack2(e[8 * j + 6], e[8 * j + 7]));
              if (j == 4) bar_arrive(NB_WO, 256);
            }
            bar_arrive(NB_Z, 256);
            STAMPW(45);
          }
          return;
        }
        ZS(3);
        const bool hi = t & 2;
        float a0 = (hi ? st[2] : st[0]) + __shfl_xor_sync(0xffffffff, hi ? st[0] : st[2], 2);
        float a1 = (hi ? st[3] : st[1]) + __shfl_xor_sync(0xffffffff, hi ? st[1] : st[3], 2);
        a0 = ((t & 1) ? a1 : a0) + __shfl_xor_sync(0xffffffff, (t & 1) ? a0 : a1, 1);
        const uint32_t tag = lds32<0>(sb + OFF_TAG);
        uint2* zs = p.scr->zstat + (rb * 256 + w * 16 + g + (t >> 1) * 8) * 2 + (t & 1);
        st_ll2(zs + cb * 128, __float_as_uint(a0), tag);
        STAMPW(2); ZS(4);
        uint2 u[4];
#pragma unroll
        for (int i = 0; i < 4; i++) u[i] = ld_ll2(zs + i * 128);
        const uint32_t keep = (cb & 2) ? 13 << 5 : 13;
        mbar_arrive_if(sb + BAR_AE + 8 * tid, tid < NA && !((keep >> tid) & 1));
        const uint32_t za = sb + OFF_A + zs0 * A_SLOT + (2 * w + ((lane >> 3) & 1)) * 3072 + (lane >> 4) * 128 + (lane & 7) * 16;
        const float ca = 0.5f * (hi ? s1.y : s0.y), inv = 1.f / 768.f;
        mbar_wait2(sb + BAR_AE + 8 * (zs0 + 2), 0, sb + BAR_XC, 0);
        ZS(6);
        uint32_t t0 = 0;
#pragma unroll 1
        while (!__all_sync(0xffffffff, u[0].y == tag && u[1].y == tag && u[2].y == tag && u[3].y == tag)) {
          spin_guard(t0);
#pragma unroll
          for (int i = 0; i < 4; i++) u[i] = ld_ll2(zs + i * 128);
        }
        STAMPW(3); ZS(7);
        a0 = ((__uint_as_float(u[0].x) + __uint_as_float(u[1].x)) + (__uint_as_float(u[2].x) + __uint_as_float(u[3].x))) * inv;
        a1 = __shfl_xor_sync(0xffffffff, a0, 1);
        const float m = (t & 1) ? a1 : a0, q = (t & 1) ? a0 : a1;
        const float r = bf_lo(pack2(ca * rsqrtf(fmaf(fmaxf(fmaf(-m, m, q), 0.f), ca * ca, 1e-5f)), 0.f));
        const uint32_t rn = pack2(r, -m * r), ro = __shfl_xor_sync(0xffffffff, rn, 2);
        const uint32_t ra2 = prmt(hi ? ro : rn, 0, 0x1010), n2a = prmt(hi ? ro : rn, 0, 0x3232), rb2 = prmt(hi ? rn : ro, 0, 0x1010), n2b = prmt(hi ? rn : ro, 0, 0x3232);
        if (w >= 2) bar_sync(NB_Z, 160);
#pragma unroll
        for (int j = 0; j < 24; j += 2)
          stsm4(za + j * 128, hfma2(z[2 * j], ra2, n2a), hfma2(z[2 * j + 1], rb2, n2b), hfma2(z[2 * j + 2], ra2, n2a), hfma2(z[2 * j + 3], rb2, n2b));
        ZS(8);
        fence_async_smem();
        ZS(9);
        if (w < 2) bar_arrive(NB_Z, 160);
        else bar_arrive(NB_Z2, 96);
        final_load_x(xw, sb + OFF_A, cb, 0, w, lane);
        fence_async_smem();
        bar_sync(NB_WGA, 128);
        mbar_arrive_if(sb + BAR_AE + 8 * tid, tid < NA && ((keep >> tid) & 1));
      }
      {
        const uint32_t zero = lds32<0>(sb + OFF_TAG + 4);
#pragma unroll
        for (int i = 0; i < 20; i++) xw[i / 10][i % 10] |= zero;
      }
      load_taps(k, p, chb + 64, tid_now());
      STAMPW(4);
    }
    const int h = wg >> 1;
    {
    const int tid = tid_now(), lane = tid & 31;
    conv_worker(p, k, sb + OFF_CV + (1 - h) * CV_SZ, sb + OFF_A + 9 * A_SLOT + h * 4096, sb + BAR_XF + 8 * h, NB_WGA + h,
                chb + (h ? 0 : 64), 2 + h, sb + BAR_GO, w, lane, tid, h ? 40 : 5, rb, cb);
    {
      const int t3 = tid_now(), l3 = t3 & 31;
      const uint32_t xs_addr = sb + OFF_XS + (w * 16 + (l3 >> 2)) * 8;
      const float2 s0 = lds64f(xs_addr), s1 = lds64f(xs_addr + 64);
      const uint32_t ya = sb + y_tile(h) + ((l3 >> 4) * 8 + (l3 & 7)) * 128 + (((2 * w + ((l3 >> 3) & 1)) ^ (l3 & 7) ^ (rb & 7)) << 4);
      uint32_t sw[2][10];
      mbar_wait(sb + BAR_XF + 8 * h, h);
      final_s_early(sw, xw, ya, s0, s1);
      uint32_t ph = 1, t0 = 0, y[8];
#pragma unroll 1
      while (true) {
        mbar_wait(sb + BAR_YL + 16 * h, ph);
        if (bar_all(NB_WGA + h, 128, final_late(y, ya))) break;
        spin_guard(t0);
        ph ^= 1;
        if (t3 == 0) load_late_y(p, sb, h, rb, cb, lds32<0>(sb + OFF_TAG) & 1);
      }
#pragma unroll
      for (int e = 0; e < 8; e++) sw[e & 1][4 + (e >> 1)] = hmul2(sw[e & 1][4 + (e >> 1)], ~y[e]);
      __nv_bfloat16* o0 = p.out + (size_t)(w * 512 + rb * 16 + (l3 >> 2)) * kD + seg_col(cb, h);
      STAMPW(h ? 44 : 9);
      bar_sync(h ? NB_Z : NB_WO, 256);
      float d[40];
#pragma unroll
      for (int j = 0; j < 5; j++) {
        const uint4 v = lds128(sb + OFF_A + (h * 5 + j) * 2048 + t3 * 16);
        d[8 * j] = bf_lo(v.x); d[8 * j + 1] = bf_hi(v.x); d[8 * j + 2] = bf_lo(v.y); d[8 * j + 3] = bf_hi(v.y);
        d[8 * j + 4] = bf_lo(v.z); d[8 * j + 5] = bf_hi(v.z); d[8 * j + 6] = bf_lo(v.w); d[8 * j + 7] = bf_hi(v.w);
      }
      final_out(d, xw, sw, s0.y, s1.y, o0, h, l3 & 3);
    }
    }
  }
}

typedef CUresult (*EncodeFn)(CUtensorMap*, CUtensorMapDataType, cuuint32_t, void*, const cuuint64_t*, const cuuint64_t*, const cuuint32_t*,
                             const cuuint32_t*, CUtensorMapInterleave, CUtensorMapSwizzle, CUtensorMapL2promotion, CUtensorMapFloatOOBfill);

void encode(EncodeFn fn, CUtensorMap* m, const void* ptr, int rank, const cuuint64_t* dims, const cuuint64_t* strides, const cuuint32_t* box,
            CUtensorMapSwizzle swz = CU_TENSOR_MAP_SWIZZLE_128B) {
  const cuuint32_t es[3] = {1, 1, 1};
  fn(m, CU_TENSOR_MAP_DATA_TYPE_BFLOAT16, rank, const_cast<void*>(ptr), dims, strides, box, es, CU_TENSOR_MAP_INTERLEAVE_NONE,
     swz, CU_TENSOR_MAP_L2_PROMOTION_L2_128B, CU_TENSOR_MAP_FLOAT_OOB_FILL_NONE);
}

}

extern "C" void kernel_launch(void* const* d_in, const int* in_sizes, int n_in, void* d_out, int out_size) {
  (void)in_sizes; (void)n_in; (void)out_size;
  static EncodeFn enc = nullptr;
  static Scratch* scr = nullptr;
  static int sms = 0;
  if (!enc) {
    void* fn = nullptr;
    cudaDriverEntryPointQueryResult qr;
    cudaGetDriverEntryPoint("cuTensorMapEncodeTiled", &fn, cudaEnableDefault, &qr);
    enc = (EncodeFn)fn;
    cudaFuncSetAttribute(fused_kernel, cudaFuncAttributeMaxDynamicSharedMemorySize, SMEM_BYTES);
    cudaGetSymbolAddress((void**)&scr, g_scr);
    int dev = 0;
    cudaGetDevice(&dev);
    cudaDeviceGetAttribute(&sms, cudaDevAttrMultiProcessorCount, dev);
  }
  Params p;
  p.scr = scr;
  p.by_smid = sms == 132;
  p.k = (const __nv_bfloat16*)d_in[1];
  p.v = (const __nv_bfloat16*)d_in[2];
  p.shift = (const __nv_bfloat16*)d_in[3];
  p.ssmk = (const __nv_bfloat16*)d_in[4];
  p.ssmD = (const __nv_bfloat16*)d_in[5];
  p.wsp = (const __nv_bfloat16*)d_in[8];
  p.bsp = (const __nv_bfloat16*)d_in[9];
  p.wout = (const __nv_bfloat16*)d_in[10];
  p.out = (__nv_bfloat16*)d_out;
  for (int i = 0; i < 2; i++) {
    const cuuint64_t n = i ? kS : kD, dims[3] = {n, 512, 4}, st[2] = {n * 2, n * 1024};
    const cuuint32_t box[3] = {64, 16, 4};
    encode(enc, i ? &p.tmWsp : &p.tmX, d_in[i ? 8 : 0], 3, dims, st, box);
  }
  {
    const cuuint64_t dims[3] = {64, kD, kF / 64}, st[2] = {kF * 2, 128};
    const cuuint32_t box[3] = {64, 64, 3};
    encode(enc, &p.tmW, d_in[7], 3, dims, st, box);
  }
  {
    const cuuint64_t dims[2] = {kS, 896}, st[1] = {kS * 2};
    const cuuint32_t box[2] = {64, 16};
    encode(enc, &p.tmY, scr->y, 2, dims, st, box);
  }
  {
    const cuuint64_t dims[3] = {1024, kD / 2, 4}, st[2] = {8192, 2048};
    const cuuint32_t box[3] = {16, 32, 4};
    encode(enc, &p.tmKV, scr->kvx, 3, dims, st, box, CU_TENSOR_MAP_SWIZZLE_32B);
  }
  fused_kernel<<<132, 512, SMEM_BYTES, cudaStreamPerThread>>>(p);
}
```

```cpp
#include <cuda_runtime.h>
#include <cuda.h>
#include <cuda_bf16.h>
#include <stdint.h>

template <int N> struct WG;
template <> struct WG<16> {
  static __device__ __forceinline__ void rs(float* d, const uint32_t* a, uint64_t db) {
    asm volatile("{\n.reg .pred p;\nsetp.ne.b32 p, 1, 0;\nwgmma.mma_async.sync.aligned.m64n16k16.f32.bf16.bf16 {"
      "%0, %1, %2, %3, %4, %5, %6, %7"
      "}, {%8, %9, %10, %11}, %12, p, 1, 1, 0;\n}\n"
      :
      "+f"(d[0]), "+f"(d[1]), "+f"(d[2]), "+f"(d[3]), "+f"(d[4]), "+f"(d[5]), "+f"(d[6]), "+f"(d[7])
      : "r"(a[0]), "r"(a[1]), "r"(a[2]), "r"(a[3]), "l"(db));
  }
};
template <> struct WG<32> {
  static __device__ __forceinline__ void rs(float* d, const uint32_t* a, uint64_t db) {
    asm volatile("{\n.reg .pred p;\nsetp.ne.b32 p, 1, 0;\nwgmma.mma_async.sync.aligned.m64n32k16.f32.bf16.bf16 {"
      "%0, %1, %2, %3, %4, %5, %6, %7, %8, %9, %10, %11, %12, %13, %14, %15"
      "}, {%16, %17, %18, %19}, %20, p, 1, 1, 0;\n}\n"
      :
      "+f"(d[0]), "+f"(d[1]), "+f"(d[2]), "+f"(d[3]), "+f"(d[4]), "+f"(d[5]), "+f"(d[6]), "+f"(d[7]),
      "+f"(d[8]), "+f"(d[9]), "+f"(d[10]), "+f"(d[11]), "+f"(d[12]), "+f"(d[13]), "+f"(d[14]), "+f"(d[15])
      : "r"(a[0]), "r"(a[1]), "r"(a[2]), "r"(a[3]), "l"(db));
  }
};
template <> struct WG<48> {
  static __device__ __forceinline__ void rs(float* d, const uint32_t* a, uint64_t db) {
    asm volatile("{\n.reg .pred p;\nsetp.ne.b32 p, 1, 0;\nwgmma.mma_async.sync.aligned.m64n48k16.f32.bf16.bf16 {"
      "%0, %1, %2, %3, %4, %5, %6, %7, %8, %9, %10, %11, %12, %13, %14, %15, "
      "%16, %17, %18, %19, %20, %21, %22, %23"
      "}, {%24, %25, %26, %27}, %28, p, 1, 1, 0;\n}\n"
      :
      "+f"(d[0]), "+f"(d[1]), "+f"(d[2]), "+f"(d[3]), "+f"(d[4]), "+f"(d[5]), "+f"(d[6]), "+f"(d[7]),
      "+f"(d[8]), "+f"(d[9]), "+f"(d[10]), "+f"(d[11]), "+f"(d[12]), "+f"(d[13]), "+f"(d[14]), "+f"(d[15]),
      "+f"(d[16]), "+f"(d[17]), "+f"(d[18]), "+f"(d[19]), "+f"(d[20]), "+f"(d[21]), "+f"(d[22]), "+f"(d[23])
      : "r"(a[0]), "r"(a[1]), "r"(a[2]), "r"(a[3]), "l"(db));
  }
};
template <> struct WG<64> {
  static __device__ __forceinline__ void rs(float* d, const uint32_t* a, uint64_t db) {
    asm volatile("{\n.reg .pred p;\nsetp.ne.b32 p, 1, 0;\nwgmma.mma_async.sync.aligned.m64n64k16.f32.bf16.bf16 {"
      "%0, %1, %2, %3, %4, %5, %6, %7, %8, %9, %10, %11, %12, %13, %14, %15, "
      "%16, %17, %18, %19, %20, %21, %22, %23, %24, %25, %26, %27, %28, %29, %30, %31"
      "}, {%32, %33, %34, %35}, %36, p, 1, 1, 0;\n}\n"
      :
      "+f"(d[0]), "+f"(d[1]), "+f"(d[2]), "+f"(d[3]), "+f"(d[4]), "+f"(d[5]), "+f"(d[6]), "+f"(d[7]),
      "+f"(d[8]), "+f"(d[9]), "+f"(d[10]), "+f"(d[11]), "+f"(d[12]), "+f"(d[13]), "+f"(d[14]), "+f"(d[15]),
      "+f"(d[16]), "+f"(d[17]), "+f"(d[18]), "+f"(d[19]), "+f"(d[20]), "+f"(d[21]), "+f"(d[22]), "+f"(d[23]),
      "+f"(d[24]), "+f"(d[25]), "+f"(d[26]), "+f"(d[27]), "+f"(d[28]), "+f"(d[29]), "+f"(d[30]), "+f"(d[31])
      : "r"(a[0]), "r"(a[1]), "r"(a[2]), "r"(a[3]), "l"(db));
  }
};
template <> struct WG<80> {
  static __device__ __forceinline__ void rs(float* d, const uint32_t* a, uint64_t db) {
    asm volatile("{\n.reg .pred p;\nsetp.ne.b32 p, 1, 0;\nwgmma.mma_async.sync.aligned.m64n80k16.f32.bf16.bf16 {"
      "%0, %1, %2, %3, %4, %5, %6, %7, %8, %9, %10, %11, %12, %13, %14, %15, "
      "%16, %17, %18, %19, %20, %21, %22, %23, %24, %25, %26, %27, %28, %29, %30, %31, "
      "%32, %33, %34, %35, %36, %37, %38, %39"
      "}, {%40, %41, %42, %43}, %44, p, 1, 1, 0;\n}\n"
      :
      "+f"(d[0]), "+f"(d[1]), "+f"(d[2]), "+f"(d[3]), "+f"(d[4]), "+f"(d[5]), "+f"(d[6]), "+f"(d[7]),
      "+f"(d[8]), "+f"(d[9]), "+f"(d[10]), "+f"(d[11]), "+f"(d[12]), "+f"(d[13]), "+f"(d[14]), "+f"(d[15]),
      "+f"(d[16]), "+f"(d[17]), "+f"(d[18]), "+f"(d[19]), "+f"(d[20]), "+f"(d[21]), "+f"(d[22]), "+f"(d[23]),
      "+f"(d[24]), "+f"(d[25]), "+f"(d[26]), "+f"(d[27]), "+f"(d[28]), "+f"(d[29]), "+f"(d[30]), "+f"(d[31]),
      "+f"(d[32]), "+f"(d[33]), "+f"(d[34]), "+f"(d[35]), "+f"(d[36]), "+f"(d[37]), "+f"(d[38]), "+f"(d[39])
      : "r"(a[0]), "r"(a[1]), "r"(a[2]), "r"(a[3]), "l"(db));
  }
};
template <> struct WG<96> {
  static __device__ __forceinline__ void rs(float* d, const uint32_t* a, uint64_t db) {
    asm volatile("{\n.reg .pred p;\nsetp.ne.b32 p, 1, 0;\nwgmma.mma_async.sync.aligned.m64n96k16.f32.bf16.bf16 {"
      "%0, %1, %2, %3, %4, %5, %6, %7, %8, %9, %10, %11, %12, %13, %14, %15, "
      "%16, %17, %18, %19, %20, %21, %22, %23, %24, %25, %26, %27, %28, %29, %30, %31, "
      "%32, %33, %34, %35, %36, %37, %38, %39, %40, %41, %42, %43, %44, %45, %46, %47"
      "}, {%48, %49, %50, %51}, %52, p, 1, 1, 0;\n}\n"
      :
      "+f"(d[0]), "+f"(d[1]), "+f"(d[2]), "+f"(d[3]), "+f"(d[4]), "+f"(d[5]), "+f"(d[6]), "+f"(d[7]),
      "+f"(d[8]), "+f"(d[9]), "+f"(d[10]), "+f"(d[11]), "+f"(d[12]), "+f"(d[13]), "+f"(d[14]), "+f"(d[15]),
      "+f"(d[16]), "+f"(d[17]), "+f"(d[18]), "+f"(d[19]), "+f"(d[20]), "+f"(d[21]), "+f"(d[22]), "+f"(d[23]),
      "+f"(d[24]), "+f"(d[25]), "+f"(d[26]), "+f"(d[27]), "+f"(d[28]), "+f"(d[29]), "+f"(d[30]), "+f"(d[31]),
      "+f"(d[32]), "+f"(d[33]), "+f"(d[34]), "+f"(d[35]), "+f"(d[36]), "+f"(d[37]), "+f"(d[38]), "+f"(d[39]),
      "+f"(d[40]), "+f"(d[41]), "+f"(d[42]), "+f"(d[43]), "+f"(d[44]), "+f"(d[45]), "+f"(d[46]), "+f"(d[47])
      : "r"(a[0]), "r"(a[1]), "r"(a[2]), "r"(a[3]), "l"(db));
  }
};
template <> struct WG<112> {
  static __device__ __forceinline__ void rs(float* d, const uint32_t* a, uint64_t db) {
    asm volatile("{\n.reg .pred p;\nsetp.ne.b32 p, 1, 0;\nwgmma.mma_async.sync.aligned.m64n112k16.f32.bf16.bf16 {"
      "%0, %1, %2, %3, %4, %5, %6, %7, %8, %9, %10, %11, %12, %13, %14, %15, "
      "%16, %17, %18, %19, %20, %21, %22, %23, %24, %25, %26, %27, %28, %29, %30, %31, "
      "%32, %33, %34, %35, %36, %37, %38, %39, %40, %41, %42, %43, %44, %45, %46, %47, "
      "%48, %49, %50, %51, %52, %53, %54, %55"
      "}, {%56, %57, %58, %59}, %60, p, 1, 1, 0;\n}\n"
      :
      "+f"(d[0]), "+f"(d[1]), "+f"(d[2]), "+f"(d[3]), "+f"(d[4]), "+f"(d[5]), "+f"(d[6]), "+f"(d[7]),
      "+f"(d[8]), "+f"(d[9]), "+f"(d[10]), "+f"(d[11]), "+f"(d[12]), "+f"(d[13]), "+f"(d[14]), "+f"(d[15]),
      "+f"(d[16]), "+f"(d[17]), "+f"(d[18]), "+f"(d[19]), "+f"(d[20]), "+f"(d[21]), "+f"(d[22]), "+f"(d[23]),
      "+f"(d[24]), "+f"(d[25]), "+f"(d[26]), "+f"(d[27]), "+f"(d[28]), "+f"(d[29]), "+f"(d[30]), "+f"(d[31]),
      "+f"(d[32]), "+f"(d[33]), "+f"(d[34]), "+f"(d[35]), "+f"(d[36]), "+f"(d[37]), "+f"(d[38]), "+f"(d[39]),
      "+f"(d[40]), "+f"(d[41]), "+f"(d[42]), "+f"(d[43]), "+f"(d[44]), "+f"(d[45]), "+f"(d[46]), "+f"(d[47]),
      "+f"(d[48]), "+f"(d[49]), "+f"(d[50]), "+f"(d[51]), "+f"(d[52]), "+f"(d[53]), "+f"(d[54]), "+f"(d[55])
      : "r"(a[0]), "r"(a[1]), "r"(a[2]), "r"(a[3]), "l"(db));
  }
};
template <> struct WG<128> {
  static __device__ __forceinline__ void rs(float* d, const uint32_t* a, uint64_t db) {
    asm volatile("{\n.reg .pred p;\nsetp.ne.b32 p, 1, 0;\nwgmma.mma_async.sync.aligned.m64n128k16.f32.bf16.bf16 {"
      "%0, %1, %2, %3, %4, %5, %6, %7, %8, %9, %10, %11, %12, %13, %14, %15, "
      "%16, %17, %18, %19, %20, %21, %22, %23, %24, %25, %26, %27, %28, %29, %30, %31, "
      "%32, %33, %34, %35, %36, %37, %38, %39, %40, %41, %42, %43, %44, %45, %46, %47, "
      "%48, %49, %50, %51, %52, %53, %54, %55, %56, %57, %58, %59, %60, %61, %62, %63"
      "}, {%64, %65, %66, %67}, %68, p, 1, 1, 0;\n}\n"
      :
      "+f"(d[0]), "+f"(d[1]), "+f"(d[2]), "+f"(d[3]), "+f"(d[4]), "+f"(d[5]), "+f"(d[6]), "+f"(d[7]),
      "+f"(d[8]), "+f"(d[9]), "+f"(d[10]), "+f"(d[11]), "+f"(d[12]), "+f"(d[13]), "+f"(d[14]), "+f"(d[15]),
      "+f"(d[16]), "+f"(d[17]), "+f"(d[18]), "+f"(d[19]), "+f"(d[20]), "+f"(d[21]), "+f"(d[22]), "+f"(d[23]),
      "+f"(d[24]), "+f"(d[25]), "+f"(d[26]), "+f"(d[27]), "+f"(d[28]), "+f"(d[29]), "+f"(d[30]), "+f"(d[31]),
      "+f"(d[32]), "+f"(d[33]), "+f"(d[34]), "+f"(d[35]), "+f"(d[36]), "+f"(d[37]), "+f"(d[38]), "+f"(d[39]),
      "+f"(d[40]), "+f"(d[41]), "+f"(d[42]), "+f"(d[43]), "+f"(d[44]), "+f"(d[45]), "+f"(d[46]), "+f"(d[47]),
      "+f"(d[48]), "+f"(d[49]), "+f"(d[50]), "+f"(d[51]), "+f"(d[52]), "+f"(d[53]), "+f"(d[54]), "+f"(d[55]),
      "+f"(d[56]), "+f"(d[57]), "+f"(d[58]), "+f"(d[59]), "+f"(d[60]), "+f"(d[61]), "+f"(d[62]), "+f"(d[63])
      : "r"(a[0]), "r"(a[1]), "r"(a[2]), "r"(a[3]), "l"(db));
  }
};
template <> struct WG<160> {
  static __device__ __forceinline__ void ss(float* d, uint64_t da, uint64_t db, int sd) {
    asm volatile("{\n.reg .pred p;\nsetp.ne.b32 p, %82, 0;\nwgmma.mma_async.sync.aligned.m64n160k16.f32.bf16.bf16 {"
      "%0, %1, %2, %3, %4, %5, %6, %7, %8, %9, %10, %11, %12, %13, %14, %15, "
      "%16, %17, %18, %19, %20, %21, %22, %23, %24, %25, %26, %27, %28, %29, %30, %31, "
      "%32, %33, %34, %35, %36, %37, %38, %39, %40, %41, %42, %43, %44, %45, %46, %47, "
      "%48, %49, %50, %51, %52, %53, %54, %55, %56, %57, %58, %59, %60, %61, %62, %63, "
      "%64, %65, %66, %67, %68, %69, %70, %71, %72, %73, %74, %75, %76, %77, %78, %79"
      "}, %80, %81, p, 1, 1, 0, 1;\n}\n"
      :
      "+f"(d[0]), "+f"(d[1]), "+f"(d[2]), "+f"(d[3]), "+f"(d[4]), "+f"(d[5]), "+f"(d[6]), "+f"(d[7]),
      "+f"(d[8]), "+f"(d[9]), "+f"(d[10]), "+f"(d[11]), "+f"(d[12]), "+f"(d[13]), "+f"(d[14]), "+f"(d[15]),
      "+f"(d[16]), "+f"(d[17]), "+f"(d[18]), "+f"(d[19]), "+f"(d[20]), "+f"(d[21]), "+f"(d[22]), "+f"(d[23]),
      "+f"(d[24]), "+f"(d[25]), "+f"(d[26]), "+f"(d[27]), "+f"(d[28]), "+f"(d[29]), "+f"(d[30]), "+f"(d[31]),
      "+f"(d[32]), "+f"(d[33]), "+f"(d[34]), "+f"(d[35]), "+f"(d[36]), "+f"(d[37]), "+f"(d[38]), "+f"(d[39]),
      "+f"(d[40]), "+f"(d[41]), "+f"(d[42]), "+f"(d[43]), "+f"(d[44]), "+f"(d[45]), "+f"(d[46]), "+f"(d[47]),
      "+f"(d[48]), "+f"(d[49]), "+f"(d[50]), "+f"(d[51]), "+f"(d[52]), "+f"(d[53]), "+f"(d[54]), "+f"(d[55]),
      "+f"(d[56]), "+f"(d[57]), "+f"(d[58]), "+f"(d[59]), "+f"(d[60]), "+f"(d[61]), "+f"(d[62]), "+f"(d[63]),
      "+f"(d[64]), "+f"(d[65]), "+f"(d[66]), "+f"(d[67]), "+f"(d[68]), "+f"(d[69]), "+f"(d[70]), "+f"(d[71]),
      "+f"(d[72]), "+f"(d[73]), "+f"(d[74]), "+f"(d[75]), "+f"(d[76]), "+f"(d[77]), "+f"(d[78]), "+f"(d[79])
      : "l"(da), "l"(db), "r"(sd));
  }
};
template <> struct WG<192> {
  static __device__ __forceinline__ void ss(float* d, uint64_t da, uint64_t db, int sd) {
    asm volatile("{\n.reg .pred p;\nsetp.ne.b32 p, %98, 0;\nwgmma.mma_async.sync.aligned.m64n192k16.f32.bf16.bf16 {"
      "%0, %1, %2, %3, %4, %5, %6, %7, %8, %9, %10, %11, %12, %13, %14, %15, "
      "%16, %17, %18, %19, %20, %21, %22, %23, %24, %25, %26, %27, %28, %29, %30, %31, "
      "%32, %33, %34, %35, %36, %37, %38, %39, %40, %41, %42, %43, %44, %45, %46, %47, "
      "%48, %49, %50, %51, %52, %53, %54, %55, %56, %57, %58, %59, %60, %61, %62, %63, "
      "%64, %65, %66, %67, %68, %69, %70, %71, %72, %73, %74, %75, %76, %77, %78, %79, "
      "%80, %81, %82, %83, %84, %85, %86, %87, %88, %89, %90, %91, %92, %93, %94, %95"
      "}, %96, %97, p, 1, 1, 0, 1;\n}\n"
      :
      "+f"(d[0]), "+f"(d[1]), "+f"(d[2]), "+f"(d[3]), "+f"(d[4]), "+f"(d[5]), "+f"(d[6]), "+f"(d[7]),
      "+f"(d[8]), "+f"(d[9]), "+f"(d[10]), "+f"(d[11]), "+f"(d[12]), "+f"(d[13]), "+f"(d[14]), "+f"(d[15]),
      "+f"(d[16]), "+f"(d[17]), "+f"(d[18]), "+f"(d[19]), "+f"(d[20]), "+f"(d[21]), "+f"(d[22]), "+f"(d[23]),
      "+f"(d[24]), "+f"(d[25]), "+f"(d[26]), "+f"(d[27]), "+f"(d[28]), "+f"(d[29]), "+f"(d[30]), "+f"(d[31]),
      "+f"(d[32]), "+f"(d[33]), "+f"(d[34]), "+f"(d[35]), "+f"(d[36]), "+f"(d[37]), "+f"(d[38]), "+f"(d[39]),
      "+f"(d[40]), "+f"(d[41]), "+f"(d[42]), "+f"(d[43]), "+f"(d[44]), "+f"(d[45]), "+f"(d[46]), "+f"(d[47]),
      "+f"(d[48]), "+f"(d[49]), "+f"(d[50]), "+f"(d[51]), "+f"(d[52]), "+f"(d[53]), "+f"(d[54]), "+f"(d[55]),
      "+f"(d[56]), "+f"(d[57]), "+f"(d[58]), "+f"(d[59]), "+f"(d[60]), "+f"(d[61]), "+f"(d[62]), "+f"(d[63]),
      "+f"(d[64]), "+f"(d[65]), "+f"(d[66]), "+f"(d[67]), "+f"(d[68]), "+f"(d[69]), "+f"(d[70]), "+f"(d[71]),
      "+f"(d[72]), "+f"(d[73]), "+f"(d[74]), "+f"(d[75]), "+f"(d[76]), "+f"(d[77]), "+f"(d[78]), "+f"(d[79]),
      "+f"(d[80]), "+f"(d[81]), "+f"(d[82]), "+f"(d[83]), "+f"(d[84]), "+f"(d[85]), "+f"(d[86]), "+f"(d[87]),
      "+f"(d[88]), "+f"(d[89]), "+f"(d[90]), "+f"(d[91]), "+f"(d[92]), "+f"(d[93]), "+f"(d[94]), "+f"(d[95])
      : "l"(da), "l"(db), "r"(sd));
  }
  static __device__ __forceinline__ void rst(float* d, const uint32_t* a, uint64_t db) {
    asm volatile("{\n.reg .pred p;\nsetp.ne.b32 p, 1, 0;\nwgmma.mma_async.sync.aligned.m64n192k16.f32.bf16.bf16 {"
      "%0, %1, %2, %3, %4, %5, %6, %7, %8, %9, %10, %11, %12, %13, %14, %15, "
      "%16, %17, %18, %19, %20, %21, %22, %23, %24, %25, %26, %27, %28, %29, %30, %31, "
      "%32, %33, %34, %35, %36, %37, %38, %39, %40, %41, %42, %43, %44, %45, %46, %47, "
      "%48, %49, %50, %51, %52, %53, %54, %55, %56, %57, %58, %59, %60, %61, %62, %63, "
      "%64, %65, %66, %67, %68, %69, %70, %71, %72, %73, %74, %75, %76, %77, %78, %79, "
      "%80, %81, %82, %83, %84, %85, %86, %87, %88, %89, %90, %91, %92, %93, %94, %95"
      "}, {%96, %97, %98, %99}, %100, p, 1, 1, 1;\n}\n"
      :
      "+f"(d[0]), "+f"(d[1]), "+f"(d[2]), "+f"(d[3]), "+f"(d[4]), "+f"(d[5]), "+f"(d[6]), "+f"(d[7]),
      "+f"(d[8]), "+f"(d[9]), "+f"(d[10]), "+f"(d[11]), "+f"(d[12]), "+f"(d[13]), "+f"(d[14]), "+f"(d[15]),
      "+f"(d[16]), "+f"(d[17]), "+f"(d[18]), "+f"(d[19]), "+f"(d[20]), "+f"(d[21]), "+f"(d[22]), "+f"(d[23]),
      "+f"(d[24]), "+f"(d[25]), "+f"(d[26]), "+f"(d[27]), "+f"(d[28]), "+f"(d[29]), "+f"(d[30]), "+f"(d[31]),
      "+f"(d[32]), "+f"(d[33]), "+f"(d[34]), "+f"(d[35]), "+f"(d[36]), "+f"(d[37]), "+f"(d[38]), "+f"(d[39]),
      "+f"(d[40]), "+f"(d[41]), "+f"(d[42]), "+f"(d[43]), "+f"(d[44]), "+f"(d[45]), "+f"(d[46]), "+f"(d[47]),
      "+f"(d[48]), "+f"(d[49]), "+f"(d[50]), "+f"(d[51]), "+f"(d[52]), "+f"(d[53]), "+f"(d[54]), "+f"(d[55]),
      "+f"(d[56]), "+f"(d[57]), "+f"(d[58]), "+f"(d[59]), "+f"(d[60]), "+f"(d[61]), "+f"(d[62]), "+f"(d[63]),
      "+f"(d[64]), "+f"(d[65]), "+f"(d[66]), "+f"(d[67]), "+f"(d[68]), "+f"(d[69]), "+f"(d[70]), "+f"(d[71]),
      "+f"(d[72]), "+f"(d[73]), "+f"(d[74]), "+f"(d[75]), "+f"(d[76]), "+f"(d[77]), "+f"(d[78]), "+f"(d[79]),
      "+f"(d[80]), "+f"(d[81]), "+f"(d[82]), "+f"(d[83]), "+f"(d[84]), "+f"(d[85]), "+f"(d[86]), "+f"(d[87]),
      "+f"(d[88]), "+f"(d[89]), "+f"(d[90]), "+f"(d[91]), "+f"(d[92]), "+f"(d[93]), "+f"(d[94]), "+f"(d[95])
      : "r"(a[0]), "r"(a[1]), "r"(a[2]), "r"(a[3]), "l"(db));
  }
};

#define GO1 2
#define HPC 1
#define ZSH 1
#define ZP_AT 1
#define CS1_T 9500
#define G1_AT 0
#define HGRP 3
#define HPACE 150
#define DB 0
#define HOLD_AT 33
#define LL_AT 4
#define KV_T0 2300
#define ST_YIELD 1
#define HP0 0
#define HPD 0
#define RAMP 1
#define LEAD 2
#define WSP_N 16
#define EARLY 0
#define CPIN 1
#define CW0 0
#define PFT 1
#define WSP_D 650
#define D1 4
#define D2 4
#define NSLEEP 32

static_assert(ZP_AT <= RAMP && LEAD <= 2, "staging slots");

namespace {

constexpr int kS = 2048, kD = 640, kF = 1536;
constexpr int NA = 10, NA2 = 9, NB = 5;
constexpr int A_SLOT = 8192, B_SLOT = 24576;
constexpr int OFF_A = 0;
constexpr int OFF_B = OFF_A + NA * A_SLOT;
constexpr int XB_PL = 2112;
constexpr int CV_KE = 4224, CV_KO = CV_KE + 4160;
constexpr int CV_SZ = CV_KO + 4160;
constexpr int OFF_CV = OFF_B + NB * B_SLOT;
constexpr int OFF_CS = OFF_CV + 2 * CV_SZ;
constexpr int OFF_BIAS = OFF_CS + 1536;
constexpr int OFF_XS = OFF_BIAS + 128;
constexpr int OFF_BAR = OFF_XS + 512;
constexpr int BAR_AF = OFF_BAR, BAR_ST = BAR_AF + 8 * NA, BAR_XF = BAR_ST + 16, BAR_KV = BAR_XF + 16;
constexpr int BAR_BF = OFF_BAR + 128, BAR_G2 = BAR_BF + 8 * (NB + 1), BAR_XS = BAR_G2 + 8, BAR_KU = BAR_XS + 8, BAR_ZP = BAR_KU + 40, BAR_XC = BAR_ZP + 8, BAR_WO = BAR_XC + 8;
constexpr int BAR_AE = OFF_BAR + 256, BAR_BE = BAR_AE + 8 * NA;
constexpr int BAR_YT = BAR_KU + 24;
constexpr int BAR_Z1 = BAR_ST;
constexpr int BAR_GO1 = BAR_XC;
constexpr int BAR_GO = BAR_XS;
constexpr int BAR_YL = BAR_KU + 16;
constexpr int OFF_TAG = OFF_CS - 32;
constexpr int SMEM_BYTES = OFF_BAR + 384;
static_assert(SMEM_BYTES <= 232448, "smem");
constexpr int NB_WGA = 1, NB_WGC = 2, NB_G1 = 3, NB_WO = 4, NB_CD = 5, NB_Z = 6, NB_WGB = 7, NB_Z2 = 8;

constexpr int CNT_Y = 1, CNT_Z1 = 3, CNT_KV = 32, CNT_WO = 36;
struct Scratch {
  uint8_t kvx[kD * 4096];
  uint8_t z2[4 * 32 * 24576];
  uint8_t h[32 * 12 * 8192];
  uint8_t wo[4 * 12 * 20480];
  uint8_t y[896 * 4096];
  uint4 xstat[kS];
  uint2 zstat[kS * 8];
  uint2 colsum[kF];
  uint32_t zcnt[4 * 32];
  uint32_t cnt[2 * 32];
  uint32_t hcnt[32 * 32];
  uint32_t epoch[136];
};
__device__ __align__(1024) Scratch g_scr;
#define ZS(i)
#define STAMP(i)
#define STAMP2(i)
#define STAMPW(i)

struct Params {
  Scratch* scr;
  int by_smid;
  const __nv_bfloat16 *k, *v, *shift, *ssmk, *ssmD, *wsp, *bsp, *wout;
  __nv_bfloat16* out;
  CUtensorMap tmX, tmW, tmWsp, tmY, tmKV;
};

__device__ __forceinline__ uint64_t mkdesc(uint32_t addr, uint32_t lbo, uint32_t sbo, uint32_t swz) {
  return (uint64_t)((addr & 0x3FFFF) >> 4) | ((uint64_t)(lbo >> 4) << 16) | ((uint64_t)(sbo >> 4) << 32) | ((uint64_t)swz << 62);
}
#define WG_FENCE() asm volatile("wgmma.fence.sync.aligned;" ::: "memory")
#define WG_COMMIT() asm volatile("wgmma.commit_group.sync.aligned;" ::: "memory")
#define WG_WAIT(n) asm volatile("wgmma.wait_group.sync.aligned %0;" ::"n"(n) : "memory")
template <int N> __device__ __forceinline__ void acc_fence(float* d) {
#pragma unroll
  for (int i = 0; i < N; i++) asm volatile("" : "+f"(d[i])::"memory");
}
__device__ __forceinline__ void mbar_init(uint32_t bar, int cnt) { asm volatile("mbarrier.init.shared::cta.b64 [%0], %1;" ::"r"(bar), "r"(cnt) : "memory"); }
__device__ __forceinline__ void mbar_expect(uint32_t bar, uint32_t bytes) { asm volatile("mbarrier.arrive.expect_tx.shared::cta.b64 _, [%0], %1;" ::"r"(bar), "r"(bytes) : "memory"); }
__device__ __forceinline__ void mbar_arrive(uint32_t bar) { asm volatile("mbarrier.arrive.shared::cta.b64 _, [%0];" ::"r"(bar) : "memory"); }
__device__ __forceinline__ void mbar_arrive_if(uint32_t bar, bool c) {
  asm volatile("{\n.reg .pred p;\nsetp.ne.u32 p, %1, 0;\n@p mbarrier.arrive.shared::cta.b64 _, [%0];\n}\n" ::"r"(bar), "r"((uint32_t)c) : "memory");
}
__device__ __forceinline__ void mbar_expect_if(uint32_t bar, uint32_t bytes, bool c) {
  asm volatile("{\n.reg .pred p;\nsetp.ne.u32 p, %2, 0;\n@p mbarrier.arrive.expect_tx.shared::cta.b64 _, [%0], %1;\n}\n" ::"r"(bar), "r"(bytes), "r"((uint32_t)c) : "memory");
}
__device__ __forceinline__ bool mbar_try(uint32_t bar, uint32_t parity) {
  uint32_t ok;
  asm volatile("{\n.reg .pred p;\nmbarrier.try_wait.parity.shared::cta.b64 p, [%1], %2;\nselp.u32 %0, 1, 0, p;\n}\n" : "=r"(ok) : "r"(bar), "r"(parity) : "memory");
  return ok;
}
__device__ __forceinline__ bool mbar_test(uint32_t bar, uint32_t parity) {
  uint32_t ok;
  asm volatile("{\n.reg .pred p;\nmbarrier.test_wait.parity.shared::cta.b64 p, [%1], %2;\nselp.u32 %0, 1, 0, p;\n}\n" : "=r"(ok) : "r"(bar), "r"(parity) : "memory");
  return ok;
}
__device__ __forceinline__ void die() { asm volatile("st.volatile.global.u32 [%0], %1;" ::"l"(0ull), "r"(0) : "memory"); }
__device__ __forceinline__ void spin_guard(uint32_t& n) { if (++n == (1u << 22)) die(); }
__device__ __forceinline__ void mbar_wait(uint32_t bar, uint32_t parity) {
  uint32_t t0 = 0;
#pragma unroll 1
  while (!mbar_try(bar, parity)) spin_guard(t0);
}
__device__ __forceinline__ void mbar_wait2(uint32_t b0, uint32_t p0, uint32_t b1, uint32_t p1) {
  uint32_t t0 = 0;
#pragma unroll 1
  while (true) {
    const bool r0 = mbar_try(b0, p0), r1 = mbar_try(b1, p1);
    if (r0 && r1) break;
    spin_guard(t0);
  }
}
__device__ __forceinline__ int tid_now() { int v; asm volatile("mov.u32 %0, %%tid.x;" : "=r"(v)); return v & 127; }
__device__ __forceinline__ bool elect_one() {
  uint32_t p;
  asm volatile("{\n.reg .pred P;\nelect.sync _|P, 0xffffffff;\nselp.u32 %0, 1, 0, P;\n}\n" : "=r"(p));
  return p;
}
__device__ __forceinline__ void bar_sync(int id, int n) { asm volatile("bar.sync %0, %1;" ::"r"(id), "r"(n) : "memory"); }
__device__ __forceinline__ void bar_arrive(int id, int n) { asm volatile("bar.arrive %0, %1;" ::"r"(id), "r"(n) : "memory"); }
__device__ __forceinline__ void fence_async_smem() { asm volatile("fence.proxy.async.shared::cta;" ::: "memory"); }
__device__ __forceinline__ void bulk_g2s(uint32_t dst, const void* src, uint32_t bytes, uint32_t bar) {
  asm volatile("cp.async.bulk.shared::cluster.global.mbarrier::complete_tx::bytes [%0], [%1], %2, [%3];" ::"r"(dst), "l"(src), "r"(bytes), "r"(bar) : "memory");
}
__device__ __forceinline__ void bulk_s2g(void* dst, uint32_t src, uint32_t bytes) {
  asm volatile("cp.async.bulk.global.shared::cta.bulk_group [%0], [%1], %2;" ::"l"(dst), "r"(src), "r"(bytes) : "memory");
}
__device__ __forceinline__ void tma2d(uint32_t dst, const CUtensorMap* m, int c0, int c1, uint32_t bar) {
  asm volatile("cp.async.bulk.tensor.2d.shared::cluster.global.mbarrier::complete_tx::bytes [%0], [%1, {%3, %4}], [%2];" ::"r"(dst), "l"(m), "r"(bar), "r"(c0), "r"(c1) : "memory");
}
__device__ __forceinline__ void tma3d(uint32_t dst, const CUtensorMap* m, int c0, int c1, int c2, uint32_t bar) {
  asm volatile("cp.async.bulk.tensor.3d.shared::cluster.global.mbarrier::complete_tx::bytes [%0], [%1, {%3, %4, %5}], [%2];" ::"r"(dst), "l"(m), "r"(bar), "r"(c0), "r"(c1), "r"(c2) : "memory");
}
__device__ __forceinline__ void tma_rows(uint32_t dst, const CUtensorMap* m, int c0, int rb, uint32_t bar) { tma3d(dst, m, c0, rb * 16, 0, bar); }
__device__ __forceinline__ uint4 ld_ll4(const void* p) {
  uint64_t a, b;
  asm volatile("ld.relaxed.gpu.global.v2.u64 {%0,%1}, [%2];" : "=l"(a), "=l"(b) : "l"(p) : "memory");
  return make_uint4((uint32_t)a, (uint32_t)(a >> 32), (uint32_t)b, (uint32_t)(b >> 32));
}
__device__ __forceinline__ void st_ll4(void* p, uint32_t a, uint32_t b, uint32_t c, uint32_t d) {
  asm volatile("st.relaxed.gpu.global.v2.u64 [%0], {%1,%2};" ::"l"(p), "l"(a | ((uint64_t)b << 32)), "l"(c | ((uint64_t)d << 32)) : "memory");
}
__device__ __forceinline__ void st_ll2(void* p, uint32_t a, uint32_t b) { asm volatile("st.relaxed.gpu.global.u64 [%0], %1;" ::"l"(p), "l"(a | ((uint64_t)b << 32)) : "memory"); }
__device__ __forceinline__ uint2 ld_ll2(const void* p) {
  uint64_t a;
  asm volatile("ld.relaxed.gpu.global.u64 %0, [%1];" : "=l"(a) : "l"(p) : "memory");
  return make_uint2((uint32_t)a, (uint32_t)(a >> 32));
}
__device__ __forceinline__ void wgmma_colsum(float* d, uint64_t da, uint64_t db) {
  asm volatile("{\n.reg .pred p;\nsetp.ne.b32 p, 1, 0;\nwgmma.mma_async.sync.aligned.m64n8k16.f32.bf16.bf16 {%0, %1, %2, %3}, %4, %5, p, 1, 1, 1, 0;\n}\n"
               : "+f"(d[0]), "+f"(d[1]), "+f"(d[2]), "+f"(d[3]) : "l"(da), "l"(db));
}
__device__ __forceinline__ void prefetch_l2(const void* p) { asm volatile("prefetch.global.L2 [%0];" ::"l"(p)); }
__device__ __forceinline__ void pace(uint32_t& t, uint32_t dt) {
  t += dt;
  while ((int32_t)((uint32_t)clock() - t) < 0) { if (NSLEEP) __nanosleep(NSLEEP); }
}
__device__ __forceinline__ void red_relaxed(uint32_t* p) { asm volatile("red.relaxed.gpu.global.add.u32 [%0], 1;" ::"l"(p) : "memory"); }
__device__ __forceinline__ void red_release(uint32_t* p) { asm volatile("red.release.gpu.global.add.u32 [%0], 1;" ::"l"(p) : "memory"); }
__device__ __forceinline__ uint4 ldg4(const void* p) { uint4 v; asm volatile("ld.global.v4.u32 {%0,%1,%2,%3}, [%4];" : "=r"(v.x), "=r"(v.y), "=r"(v.z), "=r"(v.w) : "l"(p) : "memory"); return v; }
__device__ __forceinline__ uint32_t ldg1(const void* p) { uint32_t v; asm volatile("ld.global.u32 %0, [%1];" : "=r"(v) : "l"(p) : "memory"); return v; }
__device__ __forceinline__ void stg4_if(void* p, uint32_t a, uint32_t b, uint32_t c, uint32_t d, bool on) {
  asm volatile("{\n.reg .pred p;\nsetp.ne.u32 p, %5, 0;\n@p st.global.v4.u32 [%0], {%1,%2,%3,%4};\n}\n" ::"l"(p), "r"(a), "r"(b), "r"(c), "r"(d), "r"((uint32_t)on) : "memory");
}
template <int OFF> __device__ __forceinline__ uint32_t lds32(uint32_t a) { uint32_t v; asm volatile("ld.shared.u32 %0, [%1+%2];" : "=r"(v) : "r"(a), "n"(OFF)); return v; }
__device__ __forceinline__ uint4 lds128(uint32_t a) { uint4 v; asm volatile("ld.shared.v4.u32 {%0,%1,%2,%3}, [%4];" : "=r"(v.x), "=r"(v.y), "=r"(v.z), "=r"(v.w) : "r"(a) : "memory"); return v; }
__device__ __forceinline__ float2 lds64f(uint32_t a) { float2 v; asm volatile("ld.shared.v2.f32 {%0,%1}, [%2];" : "=f"(v.x), "=f"(v.y) : "r"(a) : "memory"); return v; }
__device__ __forceinline__ void sts64f(uint32_t a, float x, float y) { asm volatile("st.shared.v2.f32 [%0], {%1,%2};" ::"r"(a), "f"(x), "f"(y) : "memory"); }
__device__ __forceinline__ void sts32(uint32_t a, uint32_t x) { asm volatile("st.shared.u32 [%0], %1;" ::"r"(a), "r"(x) : "memory"); }
__device__ __forceinline__ void sts128(uint32_t a, uint32_t x, uint32_t y, uint32_t z, uint32_t w) { asm volatile("st.shared.v4.u32 [%0], {%1,%2,%3,%4};" ::"r"(a), "r"(x), "r"(y), "r"(z), "r"(w) : "memory"); }
__device__ __forceinline__ void stsm4(uint32_t a, uint32_t r0, uint32_t r1, uint32_t r2, uint32_t r3) {
  asm volatile("stmatrix.sync.aligned.m8n8.x4.shared.b16 [%0], {%1,%2,%3,%4};" ::"r"(a), "r"(r0), "r"(r1), "r"(r2), "r"(r3) : "memory");
}
__device__ __forceinline__ void stsm4t(uint32_t a, uint32_t r0, uint32_t r1, uint32_t r2, uint32_t r3) {
  asm volatile("stmatrix.sync.aligned.m8n8.x4.trans.shared.b16 [%0], {%1,%2,%3,%4};" ::"r"(a), "r"(r0), "r"(r1), "r"(r2), "r"(r3) : "memory");
}
__device__ __forceinline__ void ldsm4t(uint32_t* r, uint32_t a) {
  asm volatile("ldmatrix.sync.aligned.m8n8.x4.trans.shared.b16 {%0,%1,%2,%3}, [%4];" : "=r"(r[0]), "=r"(r[1]), "=r"(r[2]), "=r"(r[3]) : "r"(a) : "memory");
}
__device__ __forceinline__ uint32_t pack2(float lo, float hi) { uint32_t r; asm("cvt.rn.bf16x2.f32 %0, %1, %2;" : "=r"(r) : "f"(hi), "f"(lo)); return r; }
__device__ __forceinline__ float bf_lo(uint32_t u) { return __uint_as_float(u << 16); }
__device__ __forceinline__ float bf_hi(uint32_t u) { return __uint_as_float(u & 0xffff0000u); }
__device__ __forceinline__ float tanh_fast(float x) { float y; asm("tanh.approx.f32 %0, %1;" : "=f"(y) : "f"(x)); return y; }
__device__ __forceinline__ uint32_t hmul2(uint32_t a, uint32_t b) { uint32_t r; asm("mul.rn.bf16x2 %0, %1, %2;" : "=r"(r) : "r"(a), "r"(b)); return r; }
__device__ __forceinline__ uint32_t hfma2(uint32_t a, uint32_t b, uint32_t c) { uint32_t r; asm("fma.rn.bf16x2 %0, %1, %2, %3;" : "=r"(r) : "r"(a), "r"(b), "r"(c)); return r; }
__device__ __forceinline__ uint32_t prmt(uint32_t a, uint32_t b, uint32_t s) { return __byte_perm(a, b, s); }

__device__ __forceinline__ uint32_t ld_relaxed(const uint32_t* p) { uint32_t v; asm volatile("ld.relaxed.gpu.global.u32 %0, [%1];" : "=r"(v) : "l"(p) : "memory"); return v; }
__device__ __forceinline__ void acquire_fence() { asm volatile("fence.acquire.gpu;\nfence.proxy.async.global;" ::: "memory"); }
__device__ __forceinline__ uint32_t load_epoch(const Params& p, int idx, int lane) { return ld_relaxed(&p.scr->epoch[idx + (((lane * lane) & 3) == 2 ? 1 : 0)]); }
__device__ __forceinline__ void poll_counter(const uint32_t* cnt, uint32_t target) {
  uint32_t t0 = 0;
#pragma unroll 1
  while (!__all_sync(0xffffffff, ld_relaxed(cnt) == target)) spin_guard(t0);
  acquire_fence();
}

__device__ __forceinline__ int g3_block(int cb, int it) { return it < 3 ? cb * 3 + it : (it - 3 < cb * 3 ? it - 3 : it); }

template <int N, bool A_SWZ, int B_MODE, int DEPTH, class Hook, class Mid>
__device__ __forceinline__ void gemm_loop(float* d, uint32_t sb, int nkb, int sa, int pa, int b0, uint32_t boff, int relA, int relB, int tid, Hook hook, Mid mid) {
  constexpr uint32_t A_STEP = A_SWZ ? 2 : 128;
  constexpr uint32_t B_STEP = B_MODE == 0 ? 128 : (B_MODE == 1 ? 384 : 320);
  const uint64_t da0 = A_SWZ ? mkdesc(sb + OFF_A, 16, 1024, 1) : mkdesc(sb + OFF_A, 1024, 128, 0);
  const uint64_t db0 = B_MODE == 0 ? mkdesc(sb + OFF_B + boff, 8192, 1024, 1) : mkdesc(sb + OFF_B + boff, B_MODE == 1 ? 3072 : 2560, 128, 0);
  constexpr int MODA = B_MODE == 0 ? NA : NA2;
  constexpr int MODB = B_MODE == 2 ? 6 : NB;
  int sbk = b0 % MODB, pb = (b0 / MODB) & 1;
  auto boffs = [](int s_) { return B_MODE == 2 ? (s_ == 5 ? 0 : s_ + 1) * (20480 >> 4) : s_ * (B_SLOT >> 4); };
  uint32_t rel = 0;
  uint64_t da = da0 + sa * (A_SLOT >> 4), db = db0 + boffs(sbk);
  const bool doR = tid < 2 ? tid < relA : tid - 2 < relB;
  mbar_wait2(sb + BAR_AF + 8 * sa, pa, sb + BAR_BF + 8 * sbk, pb);
  if constexpr (DEPTH == 0) {
#pragma unroll
    for (int i = 0; i < N / 2; i++) asm volatile("" : "=f"(d[i]));
#pragma unroll 1
    for (int it = 0; it < nkb; it++) {
      WG_FENCE();
#pragma unroll
      for (int j = 0; j < 4; j++) WG<N>::ss(d, da + j * A_STEP, db + j * B_STEP, j ? 1 : it);
      WG_COMMIT();
      const uint32_t prel = rel;
      rel = sb + BAR_AE + 8 * (tid < 2 ? sa : sbk + NA);
      if (++sa == MODA) { sa = 0; pa ^= 1; }
      if (++sbk == MODB) { sbk = 0; pb ^= 1; }
      da = da0 + sa * (A_SLOT >> 4); db = db0 + boffs(sbk);
      const bool r0 = mbar_test(sb + BAR_AF + 8 * sa, pa), r1 = mbar_test(sb + BAR_BF + 8 * sbk, pb);
      WG_WAIT(1);
      mbar_arrive_if(prel, doR && prel != 0);
      if (it == 2) {
        WG_WAIT(0);
        mbar_expect_if(sb + BAR_AF + 8 * (tid == 8 ? 8 : tid), A_SLOT, tid < 9);
        mbar_arrive_if(rel, doR);
        rel = 0;
      }
      mid(it);
      if (it + 1 < nkb && !(r0 && r1)) {
        mbar_wait2(sb + BAR_AF + 8 * sa, pa, sb + BAR_BF + 8 * sbk, pb);
      }
    }
  } else
#pragma unroll 1
  for (int it = 0; it < nkb; it++) {
    WG_FENCE();
    WG<N>::ss(d, da, db, 1);
    const uint32_t prel = rel;
    rel = sb + BAR_AE + 8 * (tid < 2 ? sa : sbk + NA);
    if (++sa == MODA) { sa = 0; if (B_MODE) pa ^= 1; }
    if (++sbk == MODB) { sbk = 0; pb ^= 1; }
    if (DEPTH == 1) { WG_COMMIT(); WG_WAIT(1); }
    WG<N>::ss(d, da + A_STEP, db + B_STEP, 1);
    WG_COMMIT();
    WG_WAIT(1);
    if (EARLY == 1) mbar_arrive_if(prel, doR && it != 0);
    WG<N>::ss(d, da + 2 * A_STEP, db + 2 * B_STEP, 1);
    if (DEPTH == 1) WG_COMMIT();
    if (EARLY != 1) mbar_arrive_if(prel, doR && it != 0);
    const bool r0 = mbar_test(sb + BAR_AF + 8 * sa, pa), r1 = mbar_test(sb + BAR_BF + 8 * sbk, pb);
    const uint64_t da3 = da + 3 * A_STEP, db3 = db + 3 * B_STEP;
    da = da0 + sa * (A_SLOT >> 4); db = db0 + boffs(sbk);
    if (DEPTH == 1) WG_WAIT(1);
    WG<N>::ss(d, da3, db3, 1);
    WG_COMMIT();
    mid(it);
    if (it + 1 < nkb) {
      if (!(r0 && r1)) {
        mbar_wait2(sb + BAR_AF + 8 * sa, pa, sb + BAR_BF + 8 * sbk, pb);
      }
    }
    if (DEPTH == 2) WG_WAIT(1);
  }
  hook();
  WG_WAIT(0);
  acc_fence<N / 2>(d);
  mbar_arrive_if(rel, doR);
}

__device__ __forceinline__ void fold_mean(float* d, uint32_t cs, float ma, float mb, int t) {
  const uint32_t ha = pack2(-ma, -ma), hb = pack2(-mb, -mb);
  const float la = -ma - bf_lo(ha), lb = -mb - bf_lo(hb);
  const uint32_t a[4] = {t ? 0u : ha, t ? 0u : hb, t ? 0u : pack2(la, la), t ? 0u : pack2(lb, lb)};
  WG_FENCE();
  WG<192>::rst(d, a, mkdesc(cs, 0, 32, 0));
  WG_COMMIT();
}
__device__ __forceinline__ void gelu_tile(const float* d, uint32_t* z, float* st, float ra, float rb) {
  const float kA = 0.7978845608028654f, kB = 0.7978845608028654f * 0.044715f;
  const float c1a = kA * ra, c3a = kB * ra * ra * ra, c1b = kA * rb, c3b = kB * rb * rb * rb;
  float acc[8];
#pragma unroll
  for (int i = 0; i < 8; i++) acc[i] = 0.f;
#pragma unroll
  for (int j = 0; j < 24; j++) {
    float r[4];
#pragma unroll
    for (int e = 0; e < 4; e++) {
      const float v = d[4 * j + e];
      const float a = v * fmaf(v * v, e < 2 ? c3a : c3b, e < 2 ? c1a : c1b);
      r[e] = fmaf(v, tanh_fast(a), v);
      acc[e] += r[e];
      acc[4 + e] = fmaf(r[e], r[e], acc[4 + e]);
    }
    z[2 * j] = pack2(r[0], r[1]);
    z[2 * j + 1] = pack2(r[2], r[3]);
  }
  st[0] = acc[0] + acc[1]; st[1] = acc[4] + acc[5]; st[2] = acc[2] + acc[3]; st[3] = acc[6] + acc[7];
}

template <int Q> __device__ __forceinline__ void conv_load(uint32_t* a, uint32_t ab) {
  a[0] = lds32<512 * Q>(ab);       a[1] = lds32<512 * Q + 256>(ab);  a[2] = lds32<512 * Q + 16>(ab);   a[3] = lds32<512 * Q + 272>(ab);
  a[4] = lds32<512 * Q + 32>(ab);  a[5] = lds32<512 * Q + 288>(ab);  a[6] = lds32<512 * Q + 48>(ab);   a[7] = lds32<512 * Q + 304>(ab);
  a[8] = lds32<512 * Q + 64>(ab);  a[9] = lds32<512 * Q + 320>(ab);  a[10] = lds32<512 * Q + 80>(ab);  a[11] = lds32<512 * Q + 336>(ab);
  a[12] = lds32<512 * Q + 96>(ab); a[13] = lds32<512 * Q + 352>(ab); a[14] = lds32<512 * Q + 112>(ab); a[15] = lds32<512 * Q + 368>(ab);
}
template <int Q, int L> __device__ __forceinline__ void conv_step(float* d, uint32_t (*a)[16], uint32_t ab, uint64_t db) {
  WG_FENCE();
#pragma unroll
  for (int s = 0; s < 4; s++) WG<128 - 16 * Q>::rs(d, a[Q] + 4 * s, db + s + 16 * Q);
  WG_COMMIT();
  if (CPIN) WG_WAIT(1);
  if (L >= 0) conv_load<(L >= 0 ? L : 0)>(a[L >= 0 ? L : 0], ab);
  if (CW0 || Q == 0) WG_WAIT(0);
}

__device__ __forceinline__ int seg_col(int cb, int h) { return (cb >> 1) * 320 + (cb & 1) * 32 + h * 64; }
__device__ __forceinline__ void final_load_x(uint32_t (*xw)[10], uint32_t xt, int cb, int h, int w, int lane) {
  const int g = lane >> 2, t = lane & 3, cc = seg_col(cb, h) >> 3;
  const int c0 = cc + t, c1 = c0 + 24, c2 = cc + 16 - 6 * h + (t >> 1);
  const uint32_t r0 = xt + (w * 16 + g) * 128;
#pragma unroll
  for (int r = 0; r < 2; r++) {
    const uint4 u = lds128(r0 + r * 1024 + (c0 >> 3) * A_SLOT + (((c0 ^ g) & 7) << 4)), v = lds128(r0 + r * 1024 + (c1 >> 3) * A_SLOT + (((c1 ^ g) & 7) << 4));
    const float2 z = lds64f(r0 + r * 1024 + (c2 >> 3) * A_SLOT + (((c2 ^ g) & 7) << 4) + (t & 1) * 8);
    xw[r][0] = u.x; xw[r][1] = u.y; xw[r][2] = u.z; xw[r][3] = u.w;
    xw[r][4] = v.x; xw[r][5] = v.y; xw[r][6] = v.z; xw[r][7] = v.w;
    xw[r][8] = __float_as_uint(z.x); xw[r][9] = __float_as_uint(z.y);
  }
}
__device__ __forceinline__ void final_s_early(uint32_t (*sw)[10], const uint32_t (*xw)[10], uint32_t ya, float2 s0, float2 s1) {
  const uint32_t r2[2] = {pack2(s0.y, s0.y), pack2(s1.y, s1.y)};
  const float na = -s0.x * bf_lo(r2[0]), nb = -s1.x * bf_lo(r2[1]);
  const uint32_t n2[2] = {pack2(na, na), pack2(nb, nb)};
#pragma unroll
  for (int j = 0; j < 10; j += 2) {
    uint32_t y[4];
    if (j < 4 || j == 8) ldsm4t(y, ya + (j < 4 ? j : 4) * 1024);
#pragma unroll
    for (int e = 0; e < 4; e++) {
      const uint32_t xn = hfma2(xw[e & 1][j + (e >> 1)], r2[e & 1], n2[e & 1]);
      sw[e & 1][j + (e >> 1)] = (j < 4 || j == 8) ? hmul2(xn, y[e]) : xn;
    }
  }
}
__device__ __forceinline__ bool final_late(uint32_t* y, uint32_t ya) {
  ldsm4t(y, ya + 6144);
  ldsm4t(y + 4, ya + 8192);
  uint32_t zero = 0;
#pragma unroll
  for (int e = 0; e < 8; e++) zero |= (y[e] - 0x00010001u) & ~y[e];
  return (zero & 0x80008000u) == 0;
}
__device__ __forceinline__ bool bar_all(int id, int n, bool c) {
  uint32_t r;
  asm volatile("{\n.reg .pred p, q;\nsetp.ne.u32 p, %3, 0;\nbar.red.and.pred q, %1, %2, p;\nselp.u32 %0, 1, 0, q;\n}\n" : "=r"(r) : "r"(id), "r"(n), "r"((uint32_t)c) : "memory");
  return r;
}
__device__ __forceinline__ void final_out(const float* d, const uint32_t (*xw)[10], const uint32_t (*sw)[10], float ra, float rb, __nv_bfloat16* o0, int h, int t) {
  const float ca = 0.25f * ra, cb = 0.25f * rb;
  uint32_t o[2][10];
#pragma unroll
  for (int j = 0; j < 10; j++) {
#pragma unroll
    for (int r = 0; r < 2; r++) {
      const float h0 = d[4 * j + 2 * r] * (r ? cb : ca), h1 = d[4 * j + 2 * r + 1] * (r ? cb : ca);
      o[r][j] = hfma2(pack2(fmaf(h0, tanh_fast(h0), h0), fmaf(h1, tanh_fast(h1), h1)), sw[r][j], xw[r][j]);
      __nv_bfloat16* q = o0 + r * 8 * kD;
      if (j == 3) stg4_if(q + t * 8, o[r][0], o[r][1], o[r][2], o[r][3], true);
      if (j == 7) stg4_if(q + 192 + t * 8, o[r][4], o[r][5], o[r][6], o[r][7], true);
      if (j == 9) asm volatile("st.global.v2.u32 [%0], {%1,%2};" ::"l"(q + 128 - 48 * h + t * 4), "r"(o[r][8]), "r"(o[r][9]) : "memory");
    }
  }
}

struct Taps { uint4 r0, r1; uint32_t n0, n1, dd; };
__device__ __forceinline__ void load_taps(Taps& k, const Params& p, int ch, int tid) {
  const uint4* kp = (const uint4*)(p.ssmk + (size_t)ch * kS);
  k.r0 = ldg4(kp + tid); k.r1 = ldg4(kp + 128 + tid);
  k.n0 = ldg1(kp + tid + 1); k.n1 = tid < 127 ? ldg1(kp + 129 + tid) : 0u;
  k.dd = __bfloat16_as_ushort(p.ssmD[ch]);
}
__device__ __forceinline__ void load_convx(const Params& p, uint32_t cv, uint32_t bar, int ch) {
  mbar_expect(bar, 4096);
  bulk_g2s(cv, p.scr->kvx + (size_t)ch * 4096, 2048, bar);
  bulk_g2s(cv + XB_PL, p.scr->kvx + (size_t)ch * 4096 + 2048, 2048, bar);
}
#define CW 3
#define CSTAMP(j)
__device__ __forceinline__ void zero_pads(uint32_t cv, int lane) {
  if (lane < 8) sts128(cv + (lane >> 2) * XB_PL + 2048 + (lane & 3) * 16, 0, 0, 0, 0);
  else if (lane < 12) sts128(cv + ((lane & 2) ? CV_KO : CV_KE) + (lane & 1) * 16, 0, 0, 0, 0);
  fence_async_smem();
  __syncwarp();
}
__device__ __forceinline__ int y_row(int c, uint32_t par) {
  const int hf = c >= 320, cc = c - hf * 320, u = cc >> 6, cb = hf * 2 + ((cc >> 5) & 1);
  if (u == 2) return cb * 96 + ((cc >> 4) & 1) * 48 + 32 + (cc & 1) + ((cc >> 1) & 1) * 8 + ((cc >> 2) & 3) * 2;
  return (u < 2 ? cb * 96 + u * 48 : 384 + par * 256 + cb * 64 + (u - 3) * 32) + (cc & 1) + ((cc >> 1) & 3) * 8 + ((cc >> 3) & 3) * 2;
}
__device__ __forceinline__ void z_store(const Params& p, uint32_t src, int rb, int cb, int q) {
  uint8_t* dst = p.scr->z2 + (size_t)(cb * 32 + q * 16 + (rb >> 2)) * B_SLOT + (rb & 3) * 6144;
  bulk_s2g(dst, src + q * 12288, 6144);
  bulk_s2g(dst + 8 * B_SLOT, src + q * 12288 + 6144, 6144);
  asm volatile("cp.async.bulk.commit_group;\ncp.async.bulk.wait_group 0;" ::: "memory");
}
__device__ __forceinline__ void y_store(const Params& p, uint32_t sb, int h, int ch, uint32_t par) {
  uint8_t* dst = p.scr->y + (size_t)y_row(ch, par) * 4096;
  if (elect_one()) {
    bulk_s2g(dst, sb + OFF_A + 9 * A_SLOT + h * 4096, 4096);
    asm volatile("cp.async.bulk.commit_group;\ncp.async.bulk.wait_group 0;" ::: "memory");
  }
  __syncwarp();
}
__device__ __forceinline__ void conv_service(const Params& p, uint32_t sb, int h, int ch, bool first) {
  bar_sync(NB_WGA + 8 + h, 160);
  const bool now = !first || __all_sync(0xffffffff, mbar_test(sb + BAR_KV, 0));
  if (now && elect_one()) load_convx(p, sb + OFF_CV + (1 - h) * CV_SZ, sb + BAR_XF + 8 * h, ch + 128);
  bar_sync(NB_WGA + 8 + h, 160);
  y_store(p, sb, h, ch, 0);
  if (!now) {
    mbar_wait(sb + BAR_KV, 0);
    if (elect_one()) load_convx(p, sb + OFF_CV + (1 - h) * CV_SZ, sb + BAR_XF + 8 * h, ch + 128);
  }
}
__device__ __forceinline__ uint32_t y_tile(int h) { return OFF_CV + (1 - h) * 13312; }
__device__ __forceinline__ void load_late_y(const Params& p, uint32_t sb, int h, int rb, int cb, uint32_t par) {
  mbar_expect(sb + BAR_YL + 16 * h, 4096);
  tma2d(sb + y_tile(h) + 6144, &p.tmY, rb * 64, 384 + par * 256 + cb * 64 + h * 32, sb + BAR_YL + 16 * h);
  tma2d(sb + y_tile(h) + 8192, &p.tmY, rb * 64, 400 + par * 256 + cb * 64 + h * 32, sb + BAR_YL + 16 * h);
}
__device__ __forceinline__ void held_service(const Params& p, uint32_t sb, int h, int ch, int rb, int cb, uint32_t tag, int lane) {
#pragma unroll 1
  for (int i = 0; i < 8; i++) sts128(sb + OFF_A + 9 * A_SLOT + h * 4096 + i * 512 + lane * 16, 0, 0, 0, 0);
  fence_async_smem();
  __syncwarp();
  y_store(p, sb, h, ch, ~tag & 1);
  mbar_wait(sb + BAR_YT, 1);
  uint8_t* dst = p.scr->y + (size_t)y_row(ch, tag & 1) * 4096;
  asm volatile("" : "+l"(dst));
  bar_sync(NB_WGA + 8 + h, 160);
  bar_sync(NB_WGA + 8 + h, 160);
  if (elect_one()) {
    bulk_s2g(dst, sb + OFF_A + 9 * A_SLOT + h * 4096, 4096);
    asm volatile("cp.async.bulk.commit_group;" ::: "memory");
    mbar_expect(sb + BAR_XF + 8 * h, 6144);
#pragma unroll 1
    for (int i = 0; i < 3; i++) tma2d(sb + y_tile(h) + i * 2048, &p.tmY, rb * 64, cb * 96 + h * 48 + i * 16, sb + BAR_XF + 8 * h);
  }
  mbar_wait(sb + BAR_AE + 8 * (LL_AT - 1), 1);
  if (elect_one()) { load_late_y(p, sb, h, rb, cb, tag & 1); asm volatile("cp.async.bulk.wait_group 0;" ::: "memory"); }
}
__device__ __forceinline__ void conv_worker(const Params& p, Taps& k, uint32_t cv, uint32_t yb0,
                                            uint32_t xbar, int nbar, int ch0, int n, uint32_t holdbar, int w, int lane,
                                            int tid, int st0, int rb, int cb) {
  const int g = lane >> 2, t = lane & 3, w0 = w & 1, w1 = w >> 1;
  const uint32_t ab = cv + ((g & 1) ? CV_KE : CV_KO) + 32 + 2 * (64 * w0 + 8 * w1 + ((g - 15) & ~1) + 2 * t);
  const uint32_t scA = cv + (w1 ? CV_KO : CV_KE) + 32, scB = scA + 2048;
  const int dl = (t >> 1) ^ 1;
  if (n == 2) mbar_wait(xbar, 0);
  STAMPW(st0 + 3);
#pragma unroll 1
  for (int i = 0; i < n; i++) {
    if (tid == 0) {
      k.r0.x = (k.r0.x & 0xffff0000u) | (pack2(bf_lo(k.r0.x) + bf_lo(k.dd), 0.f) & 0xffffu);
      sts32(cv + CV_KO + 28, k.r0.x << 16);
    }
    sts128(cv + CV_KE + 32 + tid * 16, k.r0.x, k.r0.y, k.r0.z, k.r0.w);
    sts128(cv + CV_KO + 32 + tid * 16, prmt(k.r0.x, k.r0.y, 0x5432), prmt(k.r0.y, k.r0.z, 0x5432), prmt(k.r0.z, k.r0.w, 0x5432), prmt(k.r0.w, k.n0, 0x5432));
    sts128(cv + CV_KE + 2080 + tid * 16, k.r1.x, k.r1.y, k.r1.z, k.r1.w);
    sts128(cv + CV_KO + 2080 + tid * 16, prmt(k.r1.x, k.r1.y, 0x5432), prmt(k.r1.y, k.r1.z, 0x5432), prmt(k.r1.z, k.r1.w, 0x5432), prmt(k.r1.w, k.n1, 0x5432));
    if (i + 1 < n) load_taps(k, p, ch0 + (i + 1) * 128, tid);
    bar_sync(nbar, 128);
    CSTAMP(0);
    const uint64_t db = mkdesc(cv + (i & 0x1000), XB_PL, 128, 0);
    float d[64];
    uint32_t a[8][16];
    if (i == 0) mbar_wait(xbar, 0);
    conv_load<7>(a[7], ab); conv_load<6>(a[6], ab); conv_load<5>(a[5], ab); conv_load<4>(a[4], ab);
#pragma unroll
    for (int j = 0; j < 64; j++) d[j] = 0.f;
    mbar_wait(xbar, i & 1);
    if (i + 1 == n) mbar_wait(GO1 ? holdbar + (BAR_GO1 - BAR_GO) : holdbar, 1);
    CSTAMP(1);
    conv_step<7, -1>(d, a, ab, db); conv_step<6, -1>(d, a, ab, db); conv_step<5, -1>(d, a, ab, db); conv_step<4, -1>(d, a, ab, db);
    if (GO1 && i + 1 == n) mbar_wait(holdbar, 1);
    conv_load<3>(a[3], ab);
    conv_step<3, 2>(d, a, ab, db);
    conv_step<2, 1>(d, a, ab, db);
    conv_step<1, 0>(d, a, ab, db);
    conv_step<0, -1>(d, a, ab, db);
    acc_fence<64>(d);
    CSTAMP(2);
    bar_sync(nbar + 8, 160);
    float E[16][2];
#pragma unroll
    for (int j = 0; j < 15; j++) { E[j][0] = d[4 * j] + d[4 * j + 6]; E[j][1] = d[4 * j + 1] + d[4 * j + 7]; }
    E[15][0] = d[60]; E[15][1] = d[61];
    if (w0 == 0) {
#pragma unroll
      for (int j = 8; j < 16; j++) sts64f(scA + (j - 8) * 256 + lane * 8, E[j][0], E[j][1]);
    } else {
      const uint32_t a = scB - dl * 256 + (lane ^ 2) * 8;
#pragma unroll
      for (int j = 1; j < 8; j++) sts64f(a + j * 256, E[j][0], E[j][1]);
      sts64f(scB + (dl ? 7 * 256 : 0) + (lane ^ 2) * 8, dl ? E[8][0] : E[0][0], dl ? E[8][1] : E[0][1]);
    }
    bar_sync(nbar, 128);
    CSTAMP(3);
    uint32_t pk[8];
    if (w0 == 0) {
#pragma unroll
      for (int j = 0; j < 8; j++) { const float2 v = lds64f(scB + j * 256 + lane * 8); pk[j] = pack2(E[j][0] + v.x, E[j][1] + v.y); }
    } else {
      const uint32_t a0 = scA - dl * 256 + (lane ^ 2) * 8;
#pragma unroll
      for (int j = 9; j < 16; j++) { const float2 v = lds64f(a0 + (j - 8) * 256); pk[j - 8] = pack2(E[j][0] + v.x, E[j][1] + v.y); }
      const float2 v = lds64f(scA + (dl ? 7 * 256 : 0) + (lane ^ 2) * 8);
      pk[0] = pack2((dl ? 0.f : E[8][0]) + v.x, (dl ? 0.f : E[8][1]) + v.y);
    }
    CSTAMP(4);
    if (i + 1 == n) {
#pragma unroll
      for (int j = 0; j < 8; j++) pk[j] = ~pk[j];
    }
    const int c1 = (w0 ? 35 : 95) - lane, c0 = (w0 && lane < 4) ? c1 - 32 : c1 + 32;
    stsm4t(yb0 + 128 * (c0 & 31) + (((2 * (c0 >> 5) + w1) ^ (c0 & 7)) << 4), pk[0], pk[1], pk[2], pk[3]);
    stsm4t(yb0 + 128 * (c1 & 31) + (((2 * (c1 >> 5) + w1) ^ (c1 & 7)) << 4), pk[4], pk[5], pk[6], pk[7]);
    fence_async_smem();
    bar_sync(nbar + 8, 160);
    CSTAMP(5);
    STAMPW(st0 + i);
    if (n == 2 && i == 0) {
      const int u = (tid >> 3) % 5, kg = rb * 3 + (tid < 120 ? (tid >> 3) / 5 : 0), c = u < 4 ? (u >> 1) * 10 + (u & 1) * 4 : 8, o2 = u < 4 ? 2 : 10;
      const uint4* wp = (const uint4*)p.wout + (uint32_t)((kg * 8 + (tid & 7)) * (kD / 8) + (seg_col(cb, 0) >> 3) + (u < 4 ? (u >> 1) * 8 + (u & 1) * 24 : 16));
      const uint4 w0 = ldg4(wp), w1 = ldg4(wp + 1), w2 = ldg4(wp + 2), w3 = ldg4(wp + 3);
      uint8_t* dst = p.scr->wo + (uint32_t)(cb * (12 * 20480) + kg * 2560 + c * 128 + (tid & 7) * 16);
      const bool f = u < 4, on = tid < 120;
      stg4_if(dst, w0.x, f ? w1.x : w0.z, f ? w2.x : w1.x, f ? w3.x : w1.z, on);
      stg4_if(dst + 128, w0.y, f ? w1.y : w0.w, f ? w2.y : w1.y, f ? w3.y : w1.w, on);
      stg4_if(dst + o2 * 128, f ? w0.z : w2.x, f ? w1.z : w2.z, f ? w2.z : w3.x, w3.z, on);
      stg4_if(dst + o2 * 128 + 128, f ? w0.w : w2.y, f ? w1.w : w2.w, f ? w2.w : w3.y, w3.w, on);
      bar_arrive(NB_WO, 160);
    }
  }
}

struct KvRegs { uint32_t k[11], v[8]; uint4 sh; };
__device__ __forceinline__ void kv_load(KvRegs& q, const __nv_bfloat16* kp, const __nv_bfloat16* vp, const __nv_bfloat16* sp, bool halo) {
#pragma unroll
  for (int i = 0; i < 11; i++) q.k[i] = (i >= 3 || halo) ? ldg1(kp + i * kD) : 0u;
#pragma unroll
  for (int i = 0; i < 8; i++) q.v[i] = ldg1(vp + i * kD);
  q.sh = ldg4(sp);
}
__device__ __forceinline__ void kv_unit(const KvRegs& q, uint32_t oa) {
  const uint32_t w0 = prmt(q.sh.x, q.sh.z, 0x5410), w1 = prmt(q.sh.x, q.sh.z, 0x7632), w2 = prmt(q.sh.y, q.sh.w, 0x5410), w3 = prmt(q.sh.y, q.sh.w, 0x7632);
  uint32_t r[8];
#pragma unroll
  for (int i = 0; i < 8; i++) r[i] = hmul2(hfma2(q.k[i + 3], w0, hfma2(q.k[i + 2], w1, hfma2(q.k[i + 1], w2, hmul2(q.k[i], w3)))), q.v[i]);
  sts128(oa, prmt(r[7], r[6], 0x5410), prmt(r[5], r[4], 0x5410), prmt(r[3], r[2], 0x5410), prmt(r[1], r[0], 0x5410));
  sts128(oa + 2048, prmt(r[7], r[6], 0x7632), prmt(r[5], r[4], 0x7632), prmt(r[3], r[2], 0x7632), prmt(r[1], r[0], 0x7632));
}

__device__ __forceinline__ void gather_colsum(const Params& p, uint32_t sb, int cb, int part, uint32_t tag, int lane) {
  uint4 v[3];
  uint32_t t0 = 0;
#pragma unroll 1
  while (true) {
    bool ok = true;
#pragma unroll
    for (int i = 0; i < 3; i++) {
      v[i] = ld_ll4(&p.scr->colsum[(part ? 0 : 768) + cb * 192 + i * 64 + lane * 2]);
      ok = ok && v[i].y == tag && v[i].w == tag;
    }
    if (__all_sync(0xffffffff, ok)) break;
    spin_guard(t0);
  }
#pragma unroll
  for (int i = 0; i < 3; i++) {
    const uint32_t hi = pack2(__uint_as_float(v[i].x), __uint_as_float(v[i].z)), ca = sb + OFF_CS + (1 - part) * 768 + i * 256 + (lane >> 2) * 32 + (lane & 3) * 4;
    sts32(ca, hi);
    sts32(ca + 16, pack2(__uint_as_float(v[i].x) - bf_lo(hi), __uint_as_float(v[i].z) - bf_hi(hi)));
  }
  __syncwarp();
  if (lane == 0) mbar_arrive(sb + BAR_ST + 8 * part);
}

__device__ __forceinline__ void helper_cta(const Params& p, uint32_t sb, int cb, int warp, int lane) {
  constexpr int NS = 9, ONES = NS * B_SLOT, BF = ONES + 256, BE = BF + 8 * NS;
  if (warp < NS && elect_one()) {
    mbar_init(sb + BF + 8 * warp, 1); mbar_init(sb + BE + 8 * warp, 1);
    fence_async_smem();
    if (warp == 0) { mbar_expect(sb + BF, B_SLOT); tma3d(sb, &p.tmW, 0, 0, 12 + cb * 3, sb + BF); }
  }
  if (warp == 15) { sts32(sb + ONES + lane * 4, 0x3f803f80u); sts32(sb + ONES + 128 + lane * 4, 0x3f803f80u); fence_async_smem(); }
  __syncthreads();
  if (warp == 4) {
    int s = 1, ph = 1;
    uint32_t tp = clock() + HP0;
#pragma unroll 1
    for (int it = 1; it < 20; it++) {
      if (HPD && it >= 10) pace(tp, HPD);
      mbar_wait(sb + BE + 8 * s, ph);
      if (elect_one()) { mbar_expect(sb + BF + 8 * s, B_SLOT); tma3d(sb + s * B_SLOT, &p.tmW, 0, (it < 10 ? it : it - 10) * 64, (it < 10 ? 12 : 0) + cb * 3, sb + BF + 8 * s); }
      if (++s == NS) { s = 0; ph ^= 1; }
    }
  } else if (warp < 4) {
    const uint32_t tag = load_epoch(p, 128 + cb, lane) + 1;
    const uint64_t db = mkdesc(sb + ONES, 128, 128, 0);
    uint2* dst = p.scr->colsum + cb * 192 + warp * 16 + (lane >> 2);
    if ((lane & 3) == 0) {
#pragma unroll 1
      for (int j = 0; j < 12; j++) st_ll2(dst + (j < 6 ? 768 : 0) + ((j % 6) >> 1) * 64 + (j & 1) * 8, 0, 0);
    }
    int s = 0, ph = 0;
#pragma unroll 1
    for (int part = 0; part < 2; part++) {
      float d[12];
#pragma unroll
      for (int i = 0; i < 12; i++) d[i] = 0.f;
#pragma unroll 1
      for (int it = 0; it < 10; it++) {
        mbar_wait(sb + BF + 8 * s, ph);
        const uint64_t da = mkdesc(sb + s * B_SLOT, 8192, 1024, 1);
        WG_FENCE();
#pragma unroll
        for (int j = 0; j < 12; j++) wgmma_colsum(d + 4 * (j % 3), da + (j % 3) * 512 + (j / 3) * 128, db);
        WG_COMMIT();
        WG_WAIT(1);
        mbar_arrive_if(sb + BE + 8 * (s == 0 ? NS - 1 : s - 1), threadIdx.x == 0 && (it | part) != 0);
        if (++s == NS) { s = 0; ph ^= 1; }
      }
      WG_WAIT(0);
      acc_fence<12>(d);
      if ((lane & 3) == 0) {
#pragma unroll
        for (int j = 0; j < 6; j++) st_ll2(dst + (part ? 0 : 768) + (j >> 1) * 64 + (j & 1) * 8, __float_as_uint(d[2 * j]), tag);
      }
      STAMPW(1 + part);
    }
    if (threadIdx.x == 0) *(volatile uint32_t*)&p.scr->epoch[128 + cb] = tag;
  }
}

__global__ void __launch_bounds__(512, 1) fused_kernel(const __grid_constant__ Params p) {
  extern __shared__ __align__(1024) uint8_t smem[];
  const int warp = __shfl_sync(0xffffffff, (int)(threadIdx.x >> 5), 0);
  const int lane = threadIdx.x & 31, tid = threadIdx.x & 127;
  const uint32_t sb = __shfl_sync(0xffffffff, (uint32_t)__cvta_generic_to_shared(smem), 0);
  const uint32_t tstart = clock();
  if (elect_one()) {
    if (warp < 5) asm volatile("prefetch.tensormap [%0];" ::"l"(&p.tmX + warp) : "memory");
    mbar_init(sb + OFF_BAR + 8 * warp, 1); mbar_init(sb + OFF_BAR + 128 + 8 * warp, 1); mbar_init(sb + OFF_BAR + 256 + 8 * warp, 2);
    asm volatile("fence.mbarrier_init.release.cluster;" ::: "memory");
  }
  int b = blockIdx.x;
  if (p.by_smid) asm volatile("mov.u32 %0, %%smid;" : "=r"(b));
  b = __shfl_sync(0xffffffff, b, 0);
  const int tp = b >> 1, t7 = (tp - 32) / 7;
  const int lin = tp < 32 ? ((tp & 7) ? (tp & 7) * 16 : 8) + (tp >> 3) * 2 + (b & 1)
                          : (tp < 60 ? (tp - 31 - t7 * 7) * 16 + 8 + t7 * 2 + (b & 1) : (tp < 62 ? -1 : b - 124));
  const int hcb = b & 3;
  if (lin < 0) { helper_cta(p, sb, hcb, warp, lane); return; }
  const int cb = ((lin >> 4) & 1) * 2 + ((lin >> 1) & 1), rb = (lin >> 5) * 8 + ((lin >> 2) & 3) * 2 + (lin & 1);
  const int zs0 = 4 - (cb & 2);
  const int chb = (cb >> 1) * 320 + rb * 2 + (cb & 1);
  if (warp == 0 && elect_one()) {
    mbar_expect(sb + BAR_AF, A_SLOT);
    tma_rows(sb + OFF_A, &p.tmX, 0, rb, sb + BAR_AF);
    mbar_expect(sb + BAR_BF, B_SLOT);
    tma3d(sb + OFF_B, &p.tmW, 0, 0, 12 + cb * 3, sb + BAR_BF);
  }
  if (warp == 1) STAMP(31);
  if (sb & 1023) die();
  __syncthreads();

  if (warp >= 12) {
    asm volatile("setmaxnreg.dec.sync.aligned.u32 32;");
    const uint32_t epoch = load_epoch(p, lin, lane);
    if (warp == 12) {
#pragma unroll 1
      for (int i = 1; i < NA; i++) {
        if (elect_one()) {
          mbar_expect(sb + BAR_AF + 8 * i, A_SLOT);
          tma_rows(sb + OFF_A + i * A_SLOT, &p.tmX, i * 64, rb, sb + BAR_AF + 8 * i);
          if (i < NB) { mbar_expect(sb + BAR_BF + 8 * i, B_SLOT); tma3d(sb + OFF_B + i * B_SLOT, &p.tmW, 0, i * 64, 12 + cb * 3, sb + BAR_BF + 8 * i); }
        }
      }
      STAMP(32);
      uint32_t kvt;
      {
        const int tb = rb * 2 + (cb & 1);
        kvt = __shfl_sync(0xffffffff, (ld_relaxed(p.scr->cnt + CNT_KV + (cb >> 1)) & ~63u) + 64, 0);
        {
          uint32_t tp = tstart;
          pace(tp, KV_T0);
          mbar_arrive_if(sb + BAR_KV + 8, lane == 0);
        }
        if (ST_YIELD) mbar_wait2(sb + BAR_XS, 0, sb + BAR_ST, 0);
#pragma unroll 1
        for (int u = 0; u < 5; u++) {
          mbar_wait(sb + BAR_KU + 8 * u, 0);
          fence_async_smem();
          if (elect_one()) {
            asm volatile("cp.async.bulk.tensor.3d.global.shared::cta.bulk_group [%0, {%2, %3, %4}], [%1];\ncp.async.bulk.commit_group;" ::"l"(&p.tmKV),
                         "r"(sb + OFF_CV + CV_SZ + (u < 3 ? u : u - 3) * 4096), "r"((63 - tb) * 16), "r"((cb >> 1) * 160 + u * 32), "r"(0) : "memory");
            if (u == 1 || u == 4) asm volatile("cp.async.bulk.wait_group 0;" ::: "memory");
            if (u == 1) { mbar_arrive(sb + BAR_KU); red_release(p.scr->cnt + CNT_KV + (cb >> 1)); }
          }
          __syncwarp();
          if (u == 1) {
            STAMP(35);
            if (PFT) { const char* q = (const char*)p.ssmk + chb * 4096 + lane * 128; prefetch_l2(q); prefetch_l2(q + 64 * 4096); }
          }
        }
        zero_pads(sb + OFF_CV + CV_SZ, lane);
        if (elect_one()) { mbar_arrive(sb + BAR_KU + 8); red_release(p.scr->cnt + CNT_KV + 2 + (cb >> 1)); }
        STAMP(30);
        if (lane < 24) {
          const char* r = (const char*)p.wout + (rb * 24 + lane) * (kD * 2) + (cb >> 1) * 640 + (cb & 1) * 384;
          prefetch_l2(r); prefetch_l2(r + 128); prefetch_l2(r + 256 - (cb & 1) * 384);
        }
      }
      poll_counter(p.scr->cnt + CNT_KV + 2 + (cb >> 1), kvt);
      if (elect_one()) mbar_arrive(sb + BAR_KV);
      STAMP(34);
      {
        const char* q = (const char*)p.wsp + (cb * 512 + rb * 16 + (lane >> 1)) * (kS * 2) + (lane & 1) * 128;
        uint32_t tp = clock();
#pragma unroll 1
        for (int i = LEAD / 2; i < WSP_N; i++) {
          prefetch_l2(q + i * 256);
          pace(tp, WSP_D);
        }
      }
      const uint32_t tag = epoch + 1;
      if (HPC) {
        bar_sync(NB_Z2, 160);
        if (elect_one()) bulk_s2g(p.scr->h + (size_t)(rb * 12 + cb * 3) * A_SLOT, sb + OFF_A + 5 * A_SLOT, HPC * A_SLOT);
      }
      mbar_wait(sb + BAR_G2, 0);
      if (elect_one()) {
        bulk_s2g(p.scr->h + (size_t)(rb * 12 + cb * 3 + HPC) * A_SLOT, sb + OFF_A + (5 + HPC) * A_SLOT, (3 - HPC) * A_SLOT);
        asm volatile("cp.async.bulk.commit_group;\ncp.async.bulk.wait_group 0;" ::: "memory");
        red_release(&p.scr->hcnt[(rb >> HGRP) * 32]);
      }
      __syncwarp();
      STAMP(20);
      mbar_wait(sb + BAR_AE + 56, 0);
      STAMP(39);
      poll_counter(&p.scr->hcnt[(rb >> HGRP) * 32], tag * (4 << HGRP));
      STAMP(37);
      if (elect_one()) {
        uint32_t tp = clock();
#pragma unroll 1
        for (int it = 3; it < 12; it++) {
          if (HPACE && it > 3) { tp += HPACE; while ((int32_t)((uint32_t)clock() - tp) < 0) {} }
          bulk_g2s(sb + OFF_A + ((it + 5) % 9) * A_SLOT, p.scr->h + (size_t)(rb * 12 + g3_block(cb, it)) * A_SLOT, A_SLOT, sb + BAR_AF + 8 * ((it + 5) % 9));
        }
      }
      STAMP(21);
    } else if (warp == 13) {
      int s = 0, ph = 0;
#pragma unroll 1
      for (int it = NB; it < 20; it++) {
        mbar_wait(sb + BAR_BE + 8 * s, ph);
        if (elect_one()) { mbar_expect(sb + BAR_BF + 8 * s, B_SLOT); tma3d(sb + OFF_B + s * B_SLOT, &p.tmW, 0, (it < 10 ? it : (it + zs0) % 10) * 64, (it < 10 ? 12 : 0) + cb * 3, sb + BAR_BF + 8 * s); }
        STAMP2(32 + it);
        if (++s == NB) { s = 0; ph ^= 1; }
      }
      mbar_wait(sb + BAR_XC, 0);
#pragma unroll 1
      for (int i = 0; i < LEAD; i++) {
        mbar_wait(sb + BAR_AE + 8 * i, 0);
        if (elect_one()) { mbar_expect(sb + BAR_AF + 8 * i, A_SLOT); tma_rows(sb + OFF_A + i * A_SLOT, &p.tmWsp, i * 64, rb, sb + BAR_AF + 8 * i); }
      }
      poll_counter(p.scr->zcnt + (cb >> ZSH) * 32, (epoch + 1) * (32 << ZSH));
      STAMP(22);
      int sa = LEAD, pa = 0, ia = LEAD;
#pragma unroll 1
      for (int it = 0; it < 32; it++) {
        if (it == ZP_AT) mbar_wait(sb + BAR_ZP, 0);
        if (it == 16) mbar_wait(sb + BAR_Z1, 1);
        mbar_wait2(sb + BAR_BE + 8 * s, ph, sb + BAR_AE + 8 * sa, pa);
        if (elect_one()) {
          mbar_expect(sb + BAR_BF + 8 * s, B_SLOT);
          bulk_g2s(sb + OFF_B + s * B_SLOT, p.scr->z2 + (size_t)(cb * 32 + it) * B_SLOT, B_SLOT, sb + BAR_BF + 8 * s);
        }
#pragma unroll 1
        for (int j = (it < RAMP ? 0 : (it == 4 ? 1 + RAMP : 1)); j > 0 && ia < 32; j--, ia++) {
          if (it == 4) mbar_wait(sb + BAR_AE + 8 * sa, pa);
          if (elect_one()) { mbar_expect(sb + BAR_AF + 8 * sa, A_SLOT); tma_rows(sb + OFF_A + sa * A_SLOT, &p.tmWsp, ia * 64, rb, sb + BAR_AF + 8 * sa); }
          if (++sa == NA2) { sa = 0; pa ^= 1; }
        }
        STAMP2(52 + it);
        if (++s == NB) { s = 0; ph ^= 1; }
      }
      mbar_wait(sb + BAR_WO, 0);
#pragma unroll 1
      for (int it = 0; it < 12; it++) {
        if (it < 6) mbar_wait(sb + BAR_BE + 8 * ((0x110443 >> (4 * it)) & 7), it < 3 ? 1 : 0);
        else mbar_wait(sb + BAR_BE + 8 * s, ph);
        if (elect_one()) {
          mbar_expect(sb + BAR_BF + 8 * s, 20480);
          bulk_g2s(sb + OFF_B + (s == 5 ? 0 : s + 1) * 20480, p.scr->wo + (size_t)(cb * 12 + g3_block(cb, it)) * 20480, 20480, sb + BAR_BF + 8 * s);
        }
        STAMP2(84 + it);
        if (++s == 6) { s = 0; ph ^= 1; }
      }
    } else if (warp == 14) {
      const uint32_t tag = epoch + 1;
      mbar_wait(sb + BAR_AF + 8 * (NA - 1), 0);
      gather_colsum(p, sb, cb, 0, tag, lane);
      STAMP(27);
      bar_sync(NB_Z, 160);
      if (elect_one()) {
        z_store(p, sb + OFF_A + zs0 * A_SLOT, rb, cb, 0);
        STAMP(7);
        red_release(p.scr->zcnt + (cb >> ZSH) * 32);
      }
      STAMP(25);
      bar_sync(NB_Z2, 96);
      if (elect_one()) {
        z_store(p, sb + OFF_A + zs0 * A_SLOT, rb, cb, 1);
        mbar_arrive(sb + BAR_ZP);
        red_release(p.scr->cnt + CNT_Z1 + (cb >> 1));
      }
      STAMP(28);
      mbar_wait(sb + BAR_AE + 72, 0);
      conv_service(p, sb, 0, chb + 64, true);
      bar_sync(NB_WO, 160);
      bar_sync(NB_CD, 64);
      if (elect_one()) { red_release(p.scr->cnt + CNT_WO + cb); red_relaxed(p.scr->cnt + CNT_Y + (cb >> 1)); }
      STAMP(49);
      poll_counter(p.scr->cnt + CNT_WO + cb, tag * 32);
      if (elect_one()) mbar_arrive(sb + BAR_WO);
      STAMP(46);
      held_service(p, sb, 0, chb + 192, rb, cb, tag, lane);
    } else {
      const uint32_t tag = epoch + 1;
      sts32(sb + OFF_BIAS + lane * 4, ldg1(p.bsp + (lane >> 3) * 512 + rb * 16 + (lane & 7) * 2));
      if (lane < 2) sts32(sb + OFF_TAG + lane * 4, lane ? 0 : tag);
      fence_async_smem();
      uint32_t t0 = 0;
      mbar_wait(sb + BAR_AF + 8 * (NA - 1), 0);
#pragma unroll 1
      while (true) {
        const uint4 u = ld_ll4(&p.scr->xstat[rb * 64 + lane]), v = ld_ll4(&p.scr->xstat[rb * 64 + 32 + lane]);
        sts64f(sb + OFF_XS + lane * 8, __uint_as_float(u.x), __uint_as_float(u.z));
        sts64f(sb + OFF_XS + 256 + lane * 8, __uint_as_float(v.x), __uint_as_float(v.z));
        if (__all_sync(0xffffffff, u.y == tag && u.w == tag && v.y == tag && v.w == tag)) break;
        spin_guard(t0);
      }
      STAMP(26);
      __syncwarp();
      if (lane == 0) mbar_arrive(sb + BAR_XS);
      { uint32_t tp = tstart; pace(tp, CS1_T); gather_colsum(p, sb, cb, 1, tag, lane); STAMP(38); }
      mbar_wait(sb + BAR_KU, 1);
      poll_counter(p.scr->cnt + CNT_KV + (cb >> 1), tag * 64);
      if (elect_one()) load_convx(p, sb + OFF_CV, sb + BAR_XF + 8, chb);
      mbar_wait(sb + BAR_KU + 8, 1);
      if (elect_one()) load_convx(p, sb + OFF_CV + CV_SZ, sb + BAR_XF, chb + 64);
      STAMP(48);
      mbar_wait(sb + BAR_AE + 72, 0);
#pragma unroll 1
      for (int i = 0; i < 2; i++) {
        conv_service(p, sb, 1, chb + i * 128, i == 0);
        if (i == 0) {
          poll_counter(p.scr->cnt + CNT_Z1 + (cb >> 1), tag * 64);
          if (elect_one()) mbar_arrive(sb + BAR_Z1);
          STAMP(24);
        }
      }
      bar_arrive(NB_CD, 64);
      mbar_wait(sb + BAR_WO, 0);
      poll_counter(p.scr->cnt + CNT_Y + (cb >> 1), tag * 64);
      STAMP(47);
      if (elect_one()) mbar_arrive(sb + BAR_YT);
      held_service(p, sb, 1, chb + 256, rb, cb, tag, lane);
      if (lane == 0) *(volatile uint32_t*)&p.scr->epoch[lin] = tag;
      STAMP(23);
    }
  } else {
    if (warp == 7) STAMP(36);
    const int wg = warp >> 2, w = warp & 3, g = lane >> 2, t = lane & 3;
    Taps k;
    uint32_t xw[2][10];
    if (wg == 2) {
      asm volatile("setmaxnreg.inc.sync.aligned.u32 160;");
      const int tb = rb * 2 + (cb & 1), c0 = (cb >> 1) * 320;
      const uint32_t cv = sb + OFF_CV + CV_SZ;
      if (w == 0) zero_pads(sb + OFF_CV, lane);
      mbar_wait(sb + BAR_KV + 8, 0);
      const int t0 = tb * 32 + w * 8;
      const __nv_bfloat16* kp = p.k + (size_t)(t0 - 3) * kD + c0 + lane * 2;
      const __nv_bfloat16* vp = p.v + (size_t)t0 * kD + c0 + lane * 2;
      const __nv_bfloat16* sp = p.shift + (c0 + lane * 2) * 4;
      const uint32_t oa = cv + ((3 - w) & 1) * 1024 + lane * 32 + ((((3 - w) >> 1) ^ (lane >> 2)) & 1) * 16;
#pragma unroll 1
      for (int r = 0; r < 2; r++) {
        KvRegs n0, n1, n2;
        STAMPW(r ? 51 : 50);
        kv_load(n0, kp + r * 128, vp + r * 128, sp + r * 512, t0 > 0);
        kv_load(n1, kp + r * 128 + 64, vp + r * 128 + 64, sp + r * 512 + 256, t0 > 0);
        if (r) kv_load(n2, kp + 256, vp + 256, sp + 1024, t0 > 0);
        kv_unit(n0, oa + r * 8192);
        bar_sync(NB_WGC, 128);
        mbar_arrive_if(sb + BAR_KU + 16 * r, tid == 0);
        if (r) mbar_wait(sb + BAR_KU, 1);
        kv_unit(n1, oa + (r ? 0 : 4096));
        bar_sync(NB_WGC, 128);
        mbar_arrive_if(sb + BAR_KU + 16 * r + 8, tid == 0);
        if (r) {
          kv_unit(n2, oa + 4096);
          bar_sync(NB_WGC, 128);
          mbar_arrive_if(sb + BAR_KU + 32, tid == 0);
        } else {
          mbar_wait(sb + BAR_AF + 8 * ((cb >> 1) * 5 + 1), 0);
          mbar_wait2(sb + BAR_AF + 8 * ((cb >> 1) * 5 + 2), 0, sb + BAR_AF + 8 * ((cb >> 1) * 5 + 4), 0);
          final_load_x(xw, sb + OFF_A, cb, 1, w, lane);
          fence_async_smem();
          bar_sync(NB_WGC, 128);
          mbar_arrive_if(sb + BAR_XC, tid == 0);
        }
      }
      STAMPW(13);
      load_taps(k, p, chb, tid);
    } else {
      float d[96];
      if (wg == 0) st_ll2(&p.scr->zstat[(rb * 256 + cb * 64 + w * 16 + g + (t >> 1) * 8) * 2 + (t & 1)], 0, 0);
      else if ((tid & 7) == 0) st_ll4(&p.scr->xstat[rb * 64 + cb * 16 + (tid >> 3)], 0, 0, 0, 0);
      {
        #pragma unroll
        for (int i = 0; i < 96; i++) d[i] = 0.f;
        {
          if (__builtin_expect(wg == 1, 0)) {
            const int tid = tid_now();
            const uint32_t epoch = load_epoch(p, lin, lane);
            float s = 0.f, q = 0.f;
#pragma unroll 1
            for (int i = 0; i < 10; i++) {
              mbar_wait(sb + BAR_AF + 8 * i, 0);
              const uint4 x4 = lds128(sb + OFF_A + i * A_SLOT + cb * 2048 + tid * 16);
              const uint32_t u[4] = {x4.x, x4.y, x4.z, x4.w};
#pragma unroll
              for (int e = 0; e < 4; e++) { const float a = bf_lo(u[e]), c = bf_hi(u[e]); s += a + c; q = fmaf(a, a, q); q = fmaf(c, c, q); }
            }
#pragma unroll
            for (int o = 1; o <= 4; o <<= 1) { s += __shfl_xor_sync(0xffffffff, s, o); q += __shfl_xor_sync(0xffffffff, q, o); }
            const float m = s * (1.f / kD);
            const float r = rsqrtf(fmaxf(fmaf(-m, m, q * (1.f / kD)), 0.f) + 1e-5f);
            if ((tid & 7) == 0) st_ll4(&p.scr->xstat[rb * 64 + cb * 16 + (tid >> 3)], __float_as_uint(m), epoch + 1, __float_as_uint(r), epoch + 1);
            STAMPW(12);
            bar_sync(NB_G1, 256);
          }
          gemm_loop<192, true, 0, D1>(d, sb, 10, wg ? zs0 : 0, 0, 0, 0, wg, 2, tid_now(), [&]() { if (G1_AT == 0 && wg == 0) bar_arrive(NB_G1, 256); }, [](int) {});
          asm volatile("setmaxnreg.inc.sync.aligned.u32 160;");
          STAMPW(wg ? 14 : 1);
          if (wg == 0) ZS(0);
          mbar_wait2(sb + BAR_XS, 0, sb + BAR_ST + 8 * wg, 0);
          if (wg == 0) ZS(1);
        }
        const int t1 = tid_now();
        const uint32_t xa1 = sb + OFF_XS + (w * 16 + ((t1 & 31) >> 2)) * 8;
        const float2 s0 = lds64f(xa1), s1 = lds64f(xa1 + 64);
        uint32_t z[48];
        float st[4];
        fence_async_smem();
        fold_mean(d, sb + OFF_CS + (1 - wg) * 768, s0.x, s1.x, t1 & 3);
        if (G1_AT == 1 && wg == 0) bar_arrive(NB_G1, 256);
        WG_WAIT(0);
        acc_fence<96>(d);
        if (wg == 0) ZS(2);
        gelu_tile(d, z, st, s0.y, s1.y);
        const int tid = tid_now(), lane = tid & 31, g = lane >> 2, t = lane & 3;
        if (wg == 1) {
          uint32_t bra, brb;
          asm volatile("ld.shared.u16 %0, [%1];" : "=r"(bra) : "r"(sb + OFF_BIAS + (w * 16 + g) * 2));
          asm volatile("ld.shared.u16 %0, [%1+16];" : "=r"(brb) : "r"(sb + OFF_BIAS + (w * 16 + g) * 2));
#pragma unroll
          for (int j = 0; j < 96; j++) d[j] = bf_lo((j & 2) ? brb : bra);
          STAMPW(15);
          gemm_loop<192, true, 1, D2>(d, sb, 32, 0, 1, 20, 0, 2, 2, tid, [&]() { if (HOLD_AT < 32) mbar_arrive_if(sb + BAR_GO, tid == 0); if (GO1 == 1) mbar_arrive_if(sb + BAR_GO1, tid == 0); }, [](int) {});
          if (GO1 == 2) mbar_arrive_if(sb + BAR_GO1, tid == 0);
          if (HOLD_AT == 32) mbar_arrive_if(sb + BAR_GO, tid == 0);
          STAMPW(16);
          const int t2 = tid_now(), l2 = t2 & 31;
          const uint32_t ha = sb + OFF_A + 5 * A_SLOT + (l2 >> 4) * 1024 + (2 * w + ((l2 >> 3) & 1)) * 128 + (l2 & 7) * 16;
#pragma unroll
          for (int j = 0; j < 24; j += 2) {
#pragma unroll
            for (int e = 0; e < 4; e++) z[2 * j + e] = hmul2(z[2 * j + e], pack2(d[4 * j + 2 * e], d[4 * j + 2 * e + 1]));
            stsm4(ha + j * 1024, z[2 * j], z[2 * j + 1], z[2 * j + 2], z[2 * j + 3]);
            if (HPC && j == HPC * 8 - 2) {
              fence_async_smem();
              bar_arrive(NB_Z2, 160);
            }
          }
          fence_async_smem();
          bar_sync(NB_WGB, 128);
          mbar_arrive_if(sb + BAR_AF + 8 * (t2 == 3 ? (BAR_G2 - BAR_AF) / 8 : (t2 == 4 ? (BAR_GO - BAR_AF) / 8 : 5 + t2)), t2 < (HOLD_AT == 33 ? 5 : 4));
          STAMPW(17);
          {
            float e[80];
            gemm_loop<160, false, 2, DB>(e, sb, 12, 5, 0, 2, 0, 2, 2, tid_now(), []() {}, [](int) {});
            STAMPW(10);
            const int t3 = tid_now();
#pragma unroll
            for (int j = 0; j < 10; j++) {
              sts128(sb + OFF_A + j * 2048 + t3 * 16, pack2(e[8 * j], e[8 * j + 1]), pack2(e[8 * j + 2], e[8 * j + 3]), pack2(e[8 * j + 4], e[8 * j + 5]),
                     pack2(e[8 * j + 6], e[8 * j + 7]));
              if (j == 4) bar_arrive(NB_WO, 256);
            }
            bar_arrive(NB_Z, 256);
            STAMPW(45);
          }
          return;
        }
        ZS(3);
        const bool hi = t & 2;
        float a0 = (hi ? st[2] : st[0]) + __shfl_xor_sync(0xffffffff, hi ? st[0] : st[2], 2);
        float a1 = (hi ? st[3] : st[1]) + __shfl_xor_sync(0xffffffff, hi ? st[1] : st[3], 2);
        a0 = ((t & 1) ? a1 : a0) + __shfl_xor_sync(0xffffffff, (t & 1) ? a0 : a1, 1);
        const uint32_t tag = lds32<0>(sb + OFF_TAG);
        uint2* zs = p.scr->zstat + (rb * 256 + w * 16 + g + (t >> 1) * 8) * 2 + (t & 1);
        st_ll2(zs + cb * 128, __float_as_uint(a0), tag);
        STAMPW(2); ZS(4);
        uint2 u[4];
#pragma unroll
        for (int i = 0; i < 4; i++) u[i] = ld_ll2(zs + i * 128);
        const uint32_t keep = (cb & 2) ? 13 << 5 : 13;
        mbar_arrive_if(sb + BAR_AE + 8 * tid, tid < NA && !((keep >> tid) & 1));
        const uint32_t za = sb + OFF_A + zs0 * A_SLOT + (2 * w + ((lane >> 3) & 1)) * 3072 + (lane >> 4) * 128 + (lane & 7) * 16;
        const float ca = 0.5f * (hi ? s1.y : s0.y), inv = 1.f / 768.f;
        mbar_wait2(sb + BAR_AE + 8 * (zs0 + 2), 0, sb + BAR_XC, 0);
        ZS(6);
        uint32_t t0 = 0;
#pragma unroll 1
        while (!__all_sync(0xffffffff, u[0].y == tag && u[1].y == tag && u[2].y == tag && u[3].y == tag)) {
          spin_guard(t0);
#pragma unroll
          for (int i = 0; i < 4; i++) u[i] = ld_ll2(zs + i * 128);
        }
        STAMPW(3); ZS(7);
        a0 = ((__uint_as_float(u[0].x) + __uint_as_float(u[1].x)) + (__uint_as_float(u[2].x) + __uint_as_float(u[3].x))) * inv;
        a1 = __shfl_xor_sync(0xffffffff, a0, 1);
        const float m = (t & 1) ? a1 : a0, q = (t & 1) ? a0 : a1;
        const float r = bf_lo(pack2(ca * rsqrtf(fmaf(fmaxf(fmaf(-m, m, q), 0.f), ca * ca, 1e-5f)), 0.f));
        const uint32_t rn = pack2(r, -m * r), ro = __shfl_xor_sync(0xffffffff, rn, 2);
        const uint32_t ra2 = prmt(hi ? ro : rn, 0, 0x1010), n2a = prmt(hi ? ro : rn, 0, 0x3232), rb2 = prmt(hi ? rn : ro, 0, 0x1010), n2b = prmt(hi ? rn : ro, 0, 0x3232);
        if (w >= 2) bar_sync(NB_Z, 160);
#pragma unroll
        for (int j = 0; j < 24; j += 2)
          stsm4(za + j * 128, hfma2(z[2 * j], ra2, n2a), hfma2(z[2 * j + 1], rb2, n2b), hfma2(z[2 * j + 2], ra2, n2a), hfma2(z[2 * j + 3], rb2, n2b));
        ZS(8);
        fence_async_smem();
        ZS(9);
        if (w < 2) bar_arrive(NB_Z, 160);
        else bar_arrive(NB_Z2, 96);
        final_load_x(xw, sb + OFF_A, cb, 0, w, lane);
        fence_async_smem();
        bar_sync(NB_WGA, 128);
        mbar_arrive_if(sb + BAR_AE + 8 * tid, tid < NA && ((keep >> tid) & 1));
      }
      {
        const uint32_t zero = lds32<0>(sb + OFF_TAG + 4);
#pragma unroll
        for (int i = 0; i < 20; i++) xw[i / 10][i % 10] |= zero;
      }
      load_taps(k, p, chb + 64, tid_now());
      STAMPW(4);
    }
    const int h = wg >> 1;
    {
    const int tid = tid_now(), lane = tid & 31;
    conv_worker(p, k, sb + OFF_CV + (1 - h) * CV_SZ, sb + OFF_A + 9 * A_SLOT + h * 4096, sb + BAR_XF + 8 * h, NB_WGA + h,
                chb + (h ? 0 : 64), 2 + h, sb + BAR_GO, w, lane, tid, h ? 40 : 5, rb, cb);
    {
      const int t3 = tid_now(), l3 = t3 & 31;
      const uint32_t xs_addr = sb + OFF_XS + (w * 16 + (l3 >> 2)) * 8;
      const float2 s0 = lds64f(xs_addr), s1 = lds64f(xs_addr + 64);
      const uint32_t ya = sb + y_tile(h) + ((l3 >> 4) * 8 + (l3 & 7)) * 128 + (((2 * w + ((l3 >> 3) & 1)) ^ (l3 & 7) ^ (rb & 7)) << 4);
      uint32_t sw[2][10];
      mbar_wait(sb + BAR_XF + 8 * h, h);
      final_s_early(sw, xw, ya, s0, s1);
      uint32_t ph = 1, t0 = 0, y[8];
#pragma unroll 1
      while (true) {
        mbar_wait(sb + BAR_YL + 16 * h, ph);
        if (bar_all(NB_WGA + h, 128, final_late(y, ya))) break;
        spin_guard(t0);
        ph ^= 1;
        if (t3 == 0) load_late_y(p, sb, h, rb, cb, lds32<0>(sb + OFF_TAG) & 1);
      }
#pragma unroll
      for (int e = 0; e < 8; e++) sw[e & 1][4 + (e >> 1)] = hmul2(sw[e & 1][4 + (e >> 1)], ~y[e]);
      __nv_bfloat16* o0 = p.out + (size_t)(w * 512 + rb * 16 + (l3 >> 2)) * kD + seg_col(cb, h);
      STAMPW(h ? 44 : 9);
      bar_sync(h ? NB_Z : NB_WO, 256);
      float d[40];
#pragma unroll
      for (int j = 0; j < 5; j++) {
        const uint4 v = lds128(sb + OFF_A + (h * 5 + j) * 2048 + t3 * 16);
        d[8 * j] = bf_lo(v.x); d[8 * j + 1] = bf_hi(v.x); d[8 * j + 2] = bf_lo(v.y); d[8 * j + 3] = bf_hi(v.y);
        d[8 * j + 4] = bf_lo(v.z); d[8 * j + 5] = bf_hi(v.z); d[8 * j + 6] = bf_lo(v.w); d[8 * j + 7] = bf_hi(v.w);
      }
      final_out(d, xw, sw, s0.y, s1.y, o0, h, l3 & 3);
    }
    }
  }
}

typedef CUresult (*EncodeFn)(CUtensorMap*, CUtensorMapDataType, cuuint32_t, void*, const cuuint64_t*, const cuuint64_t*, const cuuint32_t*,
                             const cuuint32_t*, CUtensorMapInterleave, CUtensorMapSwizzle, CUtensorMapL2promotion, CUtensorMapFloatOOBfill);

void encode(EncodeFn fn, CUtensorMap* m, const void* ptr, int rank, const cuuint64_t* dims, const cuuint64_t* strides, const cuuint32_t* box,
            CUtensorMapSwizzle swz = CU_TENSOR_MAP_SWIZZLE_128B) {
  const cuuint32_t es[3] = {1, 1, 1};
  fn(m, CU_TENSOR_MAP_DATA_TYPE_BFLOAT16, rank, const_cast<void*>(ptr), dims, strides, box, es, CU_TENSOR_MAP_INTERLEAVE_NONE,
     swz, CU_TENSOR_MAP_L2_PROMOTION_L2_128B, CU_TENSOR_MAP_FLOAT_OOB_FILL_NONE);
}

}

extern "C" void kernel_launch(void* const* d_in, const int* in_sizes, int n_in, void* d_out, int out_size) {
  (void)in_sizes; (void)n_in; (void)out_size;
  static EncodeFn enc = nullptr;
  static Scratch* scr = nullptr;
  static int sms = 0;
  if (!enc) {
    void* fn = nullptr;
    cudaDriverEntryPointQueryResult qr;
    cudaGetDriverEntryPoint("cuTensorMapEncodeTiled", &fn, cudaEnableDefault, &qr);
    enc = (EncodeFn)fn;
    cudaFuncSetAttribute(fused_kernel, cudaFuncAttributeMaxDynamicSharedMemorySize, SMEM_BYTES);
    cudaGetSymbolAddress((void**)&scr, g_scr);
    int dev = 0;
    cudaGetDevice(&dev);
    cudaDeviceGetAttribute(&sms, cudaDevAttrMultiProcessorCount, dev);
  }
  Params p;
  p.scr = scr;
  p.by_smid = sms == 132;
  p.k = (const __nv_bfloat16*)d_in[1];
  p.v = (const __nv_bfloat16*)d_in[2];
  p.shift = (const __nv_bfloat16*)d_in[3];
  p.ssmk = (const __nv_bfloat16*)d_in[4];
  p.ssmD = (const __nv_bfloat16*)d_in[5];
  p.wsp = (const __nv_bfloat16*)d_in[8];
  p.bsp = (const __nv_bfloat16*)d_in[9];
  p.wout = (const __nv_bfloat16*)d_in[10];
  p.out = (__nv_bfloat16*)d_out;
  for (int i = 0; i < 2; i++) {
    const cuuint64_t n = i ? kS : kD, dims[3] = {n, 512, 4}, st[2] = {n * 2, n * 1024};
    const cuuint32_t box[3] = {64, 16, 4};
    encode(enc, i ? &p.tmWsp : &p.tmX, d_in[i ? 8 : 0], 3, dims, st, box);
  }
  {
    const cuuint64_t dims[3] = {64, kD, kF / 64}, st[2] = {kF * 2, 128};
    const cuuint32_t box[3] = {64, 64, 3};
    encode(enc, &p.tmW, d_in[7], 3, dims, st, box);
  }
  {
    const cuuint64_t dims[2] = {kS, 896}, st[1] = {kS * 2};
    const cuuint32_t box[2] = {64, 16};
    encode(enc, &p.tmY, scr->y, 2, dims, st, box);
  }
  {
    const cuuint64_t dims[3] = {1024, kD / 2, 4}, st[2] = {8192, 2048};
    const cuuint32_t box[3] = {16, 32, 4};
    encode(enc, &p.tmKV, scr->kvx, 3, dims, st, box, CU_TENSOR_MAP_SWIZZLE_32B);
  }
  fused_kernel<<<132, 512, SMEM_BYTES, cudaStreamPerThread>>>(p);
}
```

```cpp
#include <cuda_runtime.h>
#include <cuda.h>
#include <cuda_bf16.h>
#include <stdint.h>

template <int N> struct WG;
template <> struct WG<16> {
  static __device__ __forceinline__ void rs(float* d, const uint32_t* a, uint64_t db) {
    asm volatile("{\n.reg .pred p;\nsetp.ne.b32 p, 1, 0;\nwgmma.mma_async.sync.aligned.m64n16k16.f32.bf16.bf16 {"
      "%0, %1, %2, %3, %4, %5, %6, %7"
      "}, {%8, %9, %10, %11}, %12, p, 1, 1, 0;\n}\n"
      :
      "+f"(d[0]), "+f"(d[1]), "+f"(d[2]), "+f"(d[3]), "+f"(d[4]), "+f"(d[5]), "+f"(d[6]), "+f"(d[7])
      : "r"(a[0]), "r"(a[1]), "r"(a[2]), "r"(a[3]), "l"(db));
  }
};
template <> struct WG<32> {
  static __device__ __forceinline__ void rs(float* d, const uint32_t* a, uint64_t db) {
    asm volatile("{\n.reg .pred p;\nsetp.ne.b32 p, 1, 0;\nwgmma.mma_async.sync.aligned.m64n32k16.f32.bf16.bf16 {"
      "%0, %1, %2, %3, %4, %5, %6, %7, %8, %9, %10, %11, %12, %13, %14, %15"
      "}, {%16, %17, %18, %19}, %20, p, 1, 1, 0;\n}\n"
      :
      "+f"(d[0]), "+f"(d[1]), "+f"(d[2]), "+f"(d[3]), "+f"(d[4]), "+f"(d[5]), "+f"(d[6]), "+f"(d[7]),
      "+f"(d[8]), "+f"(d[9]), "+f"(d[10]), "+f"(d[11]), "+f"(d[12]), "+f"(d[13]), "+f"(d[14]), "+f"(d[15])
      : "r"(a[0]), "r"(a[1]), "r"(a[2]), "r"(a[3]), "l"(db));
  }
};
template <> struct WG<48> {
  static __device__ __forceinline__ void rs(float* d, const uint32_t* a, uint64_t db) {
    asm volatile("{\n.reg .pred p;\nsetp.ne.b32 p, 1, 0;\nwgmma.mma_async.sync.aligned.m64n48k16.f32.bf16.bf16 {"
      "%0, %1, %2, %3, %4, %5, %6, %7, %8, %9, %10, %11, %12, %13, %14, %15, "
      "%16, %17, %18, %19, %20, %21, %22, %23"
      "}, {%24, %25, %26, %27}, %28, p, 1, 1, 0;\n}\n"
      :
      "+f"(d[0]), "+f"(d[1]), "+f"(d[2]), "+f"(d[3]), "+f"(d[4]), "+f"(d[5]), "+f"(d[6]), "+f"(d[7]),
      "+f"(d[8]), "+f"(d[9]), "+f"(d[10]), "+f"(d[11]), "+f"(d[12]), "+f"(d[13]), "+f"(d[14]), "+f"(d[15]),
      "+f"(d[16]), "+f"(d[17]), "+f"(d[18]), "+f"(d[19]), "+f"(d[20]), "+f"(d[21]), "+f"(d[22]), "+f"(d[23])
      : "r"(a[0]), "r"(a[1]), "r"(a[2]), "r"(a[3]), "l"(db));
  }
};
template <> struct WG<64> {
  static __device__ __forceinline__ void rs(float* d, const uint32_t* a, uint64_t db) {
    asm volatile("{\n.reg .pred p;\nsetp.ne.b32 p, 1, 0;\nwgmma.mma_async.sync.aligned.m64n64k16.f32.bf16.bf16 {"
      "%0, %1, %2, %3, %4, %5, %6, %7, %8, %9, %10, %11, %12, %13, %14, %15, "
      "%16, %17, %18, %19, %20, %21, %22, %23, %24, %25, %26, %27, %28, %29, %30, %31"
      "}, {%32, %33, %34, %35}, %36, p, 1, 1, 0;\n}\n"
      :
      "+f"(d[0]), "+f"(d[1]), "+f"(d[2]), "+f"(d[3]), "+f"(d[4]), "+f"(d[5]), "+f"(d[6]), "+f"(d[7]),
      "+f"(d[8]), "+f"(d[9]), "+f"(d[10]), "+f"(d[11]), "+f"(d[12]), "+f"(d[13]), "+f"(d[14]), "+f"(d[15]),
      "+f"(d[16]), "+f"(d[17]), "+f"(d[18]), "+f"(d[19]), "+f"(d[20]), "+f"(d[21]), "+f"(d[22]), "+f"(d[23]),
      "+f"(d[24]), "+f"(d[25]), "+f"(d[26]), "+f"(d[27]), "+f"(d[28]), "+f"(d[29]), "+f"(d[30]), "+f"(d[31])
      : "r"(a[0]), "r"(a[1]), "r"(a[2]), "r"(a[3]), "l"(db));
  }
};
template <> struct WG<80> {
  static __device__ __forceinline__ void rs(float* d, const uint32_t* a, uint64_t db) {
    asm volatile("{\n.reg .pred p;\nsetp.ne.b32 p, 1, 0;\nwgmma.mma_async.sync.aligned.m64n80k16.f32.bf16.bf16 {"
      "%0, %1, %2, %3, %4, %5, %6, %7, %8, %9, %10, %11, %12, %13, %14, %15, "
      "%16, %17, %18, %19, %20, %21, %22, %23, %24, %25, %26, %27, %28, %29, %30, %31, "
      "%32, %33, %34, %35, %36, %37, %38, %39"
      "}, {%40, %41, %42, %43}, %44, p, 1, 1, 0;\n}\n"
      :
      "+f"(d[0]), "+f"(d[1]), "+f"(d[2]), "+f"(d[3]), "+f"(d[4]), "+f"(d[5]), "+f"(d[6]), "+f"(d[7]),
      "+f"(d[8]), "+f"(d[9]), "+f"(d[10]), "+f"(d[11]), "+f"(d[12]), "+f"(d[13]), "+f"(d[14]), "+f"(d[15]),
      "+f"(d[16]), "+f"(d[17]), "+f"(d[18]), "+f"(d[19]), "+f"(d[20]), "+f"(d[21]), "+f"(d[22]), "+f"(d[23]),
      "+f"(d[24]), "+f"(d[25]), "+f"(d[26]), "+f"(d[27]), "+f"(d[28]), "+f"(d[29]), "+f"(d[30]), "+f"(d[31]),
      "+f"(d[32]), "+f"(d[33]), "+f"(d[34]), "+f"(d[35]), "+f"(d[36]), "+f"(d[37]), "+f"(d[38]), "+f"(d[39])
      : "r"(a[0]), "r"(a[1]), "r"(a[2]), "r"(a[3]), "l"(db));
  }
};
template <> struct WG<96> {
  static __device__ __forceinline__ void rs(float* d, const uint32_t* a, uint64_t db) {
    asm volatile("{\n.reg .pred p;\nsetp.ne.b32 p, 1, 0;\nwgmma.mma_async.sync.aligned.m64n96k16.f32.bf16.bf16 {"
      "%0, %1, %2, %3, %4, %5, %6, %7, %8, %9, %10, %11, %12, %13, %14, %15, "
      "%16, %17, %18, %19, %20, %21, %22, %23, %24, %25, %26, %27, %28, %29, %30, %31, "
      "%32, %33, %34, %35, %36, %37, %38, %39, %40, %41, %42, %43, %44, %45, %46, %47"
      "}, {%48, %49, %50, %51}, %52, p, 1, 1, 0;\n}\n"
      :
      "+f"(d[0]), "+f"(d[1]), "+f"(d[2]), "+f"(d[3]), "+f"(d[4]), "+f"(d[5]), "+f"(d[6]), "+f"(d[7]),
      "+f"(d[8]), "+f"(d[9]), "+f"(d[10]), "+f"(d[11]), "+f"(d[12]), "+f"(d[13]), "+f"(d[14]), "+f"(d[15]),
      "+f"(d[16]), "+f"(d[17]), "+f"(d[18]), "+f"(d[19]), "+f"(d[20]), "+f"(d[21]), "+f"(d[22]), "+f"(d[23]),
      "+f"(d[24]), "+f"(d[25]), "+f"(d[26]), "+f"(d[27]), "+f"(d[28]), "+f"(d[29]), "+f"(d[30]), "+f"(d[31]),
      "+f"(d[32]), "+f"(d[33]), "+f"(d[34]), "+f"(d[35]), "+f"(d[36]), "+f"(d[37]), "+f"(d[38]), "+f"(d[39]),
      "+f"(d[40]), "+f"(d[41]), "+f"(d[42]), "+f"(d[43]), "+f"(d[44]), "+f"(d[45]), "+f"(d[46]), "+f"(d[47])
      : "r"(a[0]), "r"(a[1]), "r"(a[2]), "r"(a[3]), "l"(db));
  }
};
template <> struct WG<112> {
  static __device__ __forceinline__ void rs(float* d, const uint32_t* a, uint64_t db) {
    asm volatile("{\n.reg .pred p;\nsetp.ne.b32 p, 1, 0;\nwgmma.mma_async.sync.aligned.m64n112k16.f32.bf16.bf16 {"
      "%0, %1, %2, %3, %4, %5, %6, %7, %8, %9, %10, %11, %12, %13, %14, %15, "
      "%16, %17, %18, %19, %20, %21, %22, %23, %24, %25, %26, %27, %28, %29, %30, %31, "
      "%32, %33, %34, %35, %36, %37, %38, %39, %40, %41, %42, %43, %44, %45, %46, %47, "
      "%48, %49, %50, %51, %52, %53, %54, %55"
      "}, {%56, %57, %58, %59}, %60, p, 1, 1, 0;\n}\n"
      :
      "+f"(d[0]), "+f"(d[1]), "+f"(d[2]), "+f"(d[3]), "+f"(d[4]), "+f"(d[5]), "+f"(d[6]), "+f"(d[7]),
      "+f"(d[8]), "+f"(d[9]), "+f"(d[10]), "+f"(d[11]), "+f"(d[12]), "+f"(d[13]), "+f"(d[14]), "+f"(d[15]),
      "+f"(d[16]), "+f"(d[17]), "+f"(d[18]), "+f"(d[19]), "+f"(d[20]), "+f"(d[21]), "+f"(d[22]), "+f"(d[23]),
      "+f"(d[24]), "+f"(d[25]), "+f"(d[26]), "+f"(d[27]), "+f"(d[28]), "+f"(d[29]), "+f"(d[30]), "+f"(d[31]),
      "+f"(d[32]), "+f"(d[33]), "+f"(d[34]), "+f"(d[35]), "+f"(d[36]), "+f"(d[37]), "+f"(d[38]), "+f"(d[39]),
      "+f"(d[40]), "+f"(d[41]), "+f"(d[42]), "+f"(d[43]), "+f"(d[44]), "+f"(d[45]), "+f"(d[46]), "+f"(d[47]),
      "+f"(d[48]), "+f"(d[49]), "+f"(d[50]), "+f"(d[51]), "+f"(d[52]), "+f"(d[53]), "+f"(d[54]), "+f"(d[55])
      : "r"(a[0]), "r"(a[1]), "r"(a[2]), "r"(a[3]), "l"(db));
  }
};
template <> struct WG<128> {
  static __device__ __forceinline__ void rs(float* d, const uint32_t* a, uint64_t db) {
    asm volatile("{\n.reg .pred p;\nsetp.ne.b32 p, 1, 0;\nwgmma.mma_async.sync.aligned.m64n128k16.f32.bf16.bf16 {"
      "%0, %1, %2, %3, %4, %5, %6, %7, %8, %9, %10, %11, %12, %13, %14, %15, "
      "%16, %17, %18, %19, %20, %21, %22, %23, %24, %25, %26, %27, %28, %29, %30, %31, "
      "%32, %33, %34, %35, %36, %37, %38, %39, %40, %41, %42, %43, %44, %45, %46, %47, "
      "%48, %49, %50, %51, %52, %53, %54, %55, %56, %57, %58, %59, %60, %61, %62, %63"
      "}, {%64, %65, %66, %67}, %68, p, 1, 1, 0;\n}\n"
      :
      "+f"(d[0]), "+f"(d[1]), "+f"(d[2]), "+f"(d[3]), "+f"(d[4]), "+f"(d[5]), "+f"(d[6]), "+f"(d[7]),
      "+f"(d[8]), "+f"(d[9]), "+f"(d[10]), "+f"(d[11]), "+f"(d[12]), "+f"(d[13]), "+f"(d[14]), "+f"(d[15]),
      "+f"(d[16]), "+f"(d[17]), "+f"(d[18]), "+f"(d[19]), "+f"(d[20]), "+f"(d[21]), "+f"(d[22]), "+f"(d[23]),
      "+f"(d[24]), "+f"(d[25]), "+f"(d[26]), "+f"(d[27]), "+f"(d[28]), "+f"(d[29]), "+f"(d[30]), "+f"(d[31]),
      "+f"(d[32]), "+f"(d[33]), "+f"(d[34]), "+f"(d[35]), "+f"(d[36]), "+f"(d[37]), "+f"(d[38]), "+f"(d[39]),
      "+f"(d[40]), "+f"(d[41]), "+f"(d[42]), "+f"(d[43]), "+f"(d[44]), "+f"(d[45]), "+f"(d[46]), "+f"(d[47]),
      "+f"(d[48]), "+f"(d[49]), "+f"(d[50]), "+f"(d[51]), "+f"(d[52]), "+f"(d[53]), "+f"(d[54]), "+f"(d[55]),
      "+f"(d[56]), "+f"(d[57]), "+f"(d[58]), "+f"(d[59]), "+f"(d[60]), "+f"(d[61]), "+f"(d[62]), "+f"(d[63])
      : "r"(a[0]), "r"(a[1]), "r"(a[2]), "r"(a[3]), "l"(db));
  }
};
template <> struct WG<160> {
  static __device__ __forceinline__ void ss(float* d, uint64_t da, uint64_t db, int sd) {
    asm volatile("{\n.reg .pred p;\nsetp.ne.b32 p, %82, 0;\nwgmma.mma_async.sync.aligned.m64n160k16.f32.bf16.bf16 {"
      "%0, %1, %2, %3, %4, %5, %6, %7, %8, %9, %10, %11, %12, %13, %14, %15, "
      "%16, %17, %18, %19, %20, %21, %22, %23, %24, %25, %26, %27, %28, %29, %30, %31, "
      "%32, %33, %34, %35, %36, %37, %38, %39, %40, %41, %42, %43, %44, %45, %46, %47, "
      "%48, %49, %50, %51, %52, %53, %54, %55, %56, %57, %58, %59, %60, %61, %62, %63, "
      "%64, %65, %66, %67, %68, %69, %70, %71, %72, %73, %74, %75, %76, %77, %78, %79"
      "}, %80, %81, p, 1, 1, 0, 1;\n}\n"
      :
      "+f"(d[0]), "+f"(d[1]), "+f"(d[2]), "+f"(d[3]), "+f"(d[4]), "+f"(d[5]), "+f"(d[6]), "+f"(d[7]),
      "+f"(d[8]), "+f"(d[9]), "+f"(d[10]), "+f"(d[11]), "+f"(d[12]), "+f"(d[13]), "+f"(d[14]), "+f"(d[15]),
      "+f"(d[16]), "+f"(d[17]), "+f"(d[18]), "+f"(d[19]), "+f"(d[20]), "+f"(d[21]), "+f"(d[22]), "+f"(d[23]),
      "+f"(d[24]), "+f"(d[25]), "+f"(d[26]), "+f"(d[27]), "+f"(d[28]), "+f"(d[29]), "+f"(d[30]), "+f"(d[31]),
      "+f"(d[32]), "+f"(d[33]), "+f"(d[34]), "+f"(d[35]), "+f"(d[36]), "+f"(d[37]), "+f"(d[38]), "+f"(d[39]),
      "+f"(d[40]), "+f"(d[41]), "+f"(d[42]), "+f"(d[43]), "+f"(d[44]), "+f"(d[45]), "+f"(d[46]), "+f"(d[47]),
      "+f"(d[48]), "+f"(d[49]), "+f"(d[50]), "+f"(d[51]), "+f"(d[52]), "+f"(d[53]), "+f"(d[54]), "+f"(d[55]),
      "+f"(d[56]), "+f"(d[57]), "+f"(d[58]), "+f"(d[59]), "+f"(d[60]), "+f"(d[61]), "+f"(d[62]), "+f"(d[63]),
      "+f"(d[64]), "+f"(d[65]), "+f"(d[66]), "+f"(d[67]), "+f"(d[68]), "+f"(d[69]), "+f"(d[70]), "+f"(d[71]),
      "+f"(d[72]), "+f"(d[73]), "+f"(d[74]), "+f"(d[75]), "+f"(d[76]), "+f"(d[77]), "+f"(d[78]), "+f"(d[79])
      : "l"(da), "l"(db), "r"(sd));
  }
};
template <> struct WG<192> {
  static __device__ __forceinline__ void ss(float* d, uint64_t da, uint64_t db, int sd) {
    asm volatile("{\n.reg .pred p;\nsetp.ne.b32 p, %98, 0;\nwgmma.mma_async.sync.aligned.m64n192k16.f32.bf16.bf16 {"
      "%0, %1, %2, %3, %4, %5, %6, %7, %8, %9, %10, %11, %12, %13, %14, %15, "
      "%16, %17, %18, %19, %20, %21, %22, %23, %24, %25, %26, %27, %28, %29, %30, %31, "
      "%32, %33, %34, %35, %36, %37, %38, %39, %40, %41, %42, %43, %44, %45, %46, %47, "
      "%48, %49, %50, %51, %52, %53, %54, %55, %56, %57, %58, %59, %60, %61, %62, %63, "
      "%64, %65, %66, %67, %68, %69, %70, %71, %72, %73, %74, %75, %76, %77, %78, %79, "
      "%80, %81, %82, %83, %84, %85, %86, %87, %88, %89, %90, %91, %92, %93, %94, %95"
      "}, %96, %97, p, 1, 1, 0, 1;\n}\n"
      :
      "+f"(d[0]), "+f"(d[1]), "+f"(d[2]), "+f"(d[3]), "+f"(d[4]), "+f"(d[5]), "+f"(d[6]), "+f"(d[7]),
      "+f"(d[8]), "+f"(d[9]), "+f"(d[10]), "+f"(d[11]), "+f"(d[12]), "+f"(d[13]), "+f"(d[14]), "+f"(d[15]),
      "+f"(d[16]), "+f"(d[17]), "+f"(d[18]), "+f"(d[19]), "+f"(d[20]), "+f"(d[21]), "+f"(d[22]), "+f"(d[23]),
      "+f"(d[24]), "+f"(d[25]), "+f"(d[26]), "+f"(d[27]), "+f"(d[28]), "+f"(d[29]), "+f"(d[30]), "+f"(d[31]),
      "+f"(d[32]), "+f"(d[33]), "+f"(d[34]), "+f"(d[35]), "+f"(d[36]), "+f"(d[37]), "+f"(d[38]), "+f"(d[39]),
      "+f"(d[40]), "+f"(d[41]), "+f"(d[42]), "+f"(d[43]), "+f"(d[44]), "+f"(d[45]), "+f"(d[46]), "+f"(d[47]),
      "+f"(d[48]), "+f"(d[49]), "+f"(d[50]), "+f"(d[51]), "+f"(d[52]), "+f"(d[53]), "+f"(d[54]), "+f"(d[55]),
      "+f"(d[56]), "+f"(d[57]), "+f"(d[58]), "+f"(d[59]), "+f"(d[60]), "+f"(d[61]), "+f"(d[62]), "+f"(d[63]),
      "+f"(d[64]), "+f"(d[65]), "+f"(d[66]), "+f"(d[67]), "+f"(d[68]), "+f"(d[69]), "+f"(d[70]), "+f"(d[71]),
      "+f"(d[72]), "+f"(d[73]), "+f"(d[74]), "+f"(d[75]), "+f"(d[76]), "+f"(d[77]), "+f"(d[78]), "+f"(d[79]),
      "+f"(d[80]), "+f"(d[81]), "+f"(d[82]), "+f"(d[83]), "+f"(d[84]), "+f"(d[85]), "+f"(d[86]), "+f"(d[87]),
      "+f"(d[88]), "+f"(d[89]), "+f"(d[90]), "+f"(d[91]), "+f"(d[92]), "+f"(d[93]), "+f"(d[94]), "+f"(d[95])
      : "l"(da), "l"(db), "r"(sd));
  }
  static __device__ __forceinline__ void rst(float* d, const uint32_t* a, uint64_t db) {
    asm volatile("{\n.reg .pred p;\nsetp.ne.b32 p, 1, 0;\nwgmma.mma_async.sync.aligned.m64n192k16.f32.bf16.bf16 {"
      "%0, %1, %2, %3, %4, %5, %6, %7, %8, %9, %10, %11, %12, %13, %14, %15, "
      "%16, %17, %18, %19, %20, %21, %22, %23, %24, %25, %26, %27, %28, %29, %30, %31, "
      "%32, %33, %34, %35, %36, %37, %38, %39, %40, %41, %42, %43, %44, %45, %46, %47, "
      "%48, %49, %50, %51, %52, %53, %54, %55, %56, %57, %58, %59, %60, %61, %62, %63, "
      "%64, %65, %66, %67, %68, %69, %70, %71, %72, %73, %74, %75, %76, %77, %78, %79, "
      "%80, %81, %82, %83, %84, %85, %86, %87, %88, %89, %90, %91, %92, %93, %94, %95"
      "}, {%96, %97, %98, %99}, %100, p, 1, 1, 1;\n}\n"
      :
      "+f"(d[0]), "+f"(d[1]), "+f"(d[2]), "+f"(d[3]), "+f"(d[4]), "+f"(d[5]), "+f"(d[6]), "+f"(d[7]),
      "+f"(d[8]), "+f"(d[9]), "+f"(d[10]), "+f"(d[11]), "+f"(d[12]), "+f"(d[13]), "+f"(d[14]), "+f"(d[15]),
      "+f"(d[16]), "+f"(d[17]), "+f"(d[18]), "+f"(d[19]), "+f"(d[20]), "+f"(d[21]), "+f"(d[22]), "+f"(d[23]),
      "+f"(d[24]), "+f"(d[25]), "+f"(d[26]), "+f"(d[27]), "+f"(d[28]), "+f"(d[29]), "+f"(d[30]), "+f"(d[31]),
      "+f"(d[32]), "+f"(d[33]), "+f"(d[34]), "+f"(d[35]), "+f"(d[36]), "+f"(d[37]), "+f"(d[38]), "+f"(d[39]),
      "+f"(d[40]), "+f"(d[41]), "+f"(d[42]), "+f"(d[43]), "+f"(d[44]), "+f"(d[45]), "+f"(d[46]), "+f"(d[47]),
      "+f"(d[48]), "+f"(d[49]), "+f"(d[50]), "+f"(d[51]), "+f"(d[52]), "+f"(d[53]), "+f"(d[54]), "+f"(d[55]),
      "+f"(d[56]), "+f"(d[57]), "+f"(d[58]), "+f"(d[59]), "+f"(d[60]), "+f"(d[61]), "+f"(d[62]), "+f"(d[63]),
      "+f"(d[64]), "+f"(d[65]), "+f"(d[66]), "+f"(d[67]), "+f"(d[68]), "+f"(d[69]), "+f"(d[70]), "+f"(d[71]),
      "+f"(d[72]), "+f"(d[73]), "+f"(d[74]), "+f"(d[75]), "+f"(d[76]), "+f"(d[77]), "+f"(d[78]), "+f"(d[79]),
      "+f"(d[80]), "+f"(d[81]), "+f"(d[82]), "+f"(d[83]), "+f"(d[84]), "+f"(d[85]), "+f"(d[86]), "+f"(d[87]),
      "+f"(d[88]), "+f"(d[89]), "+f"(d[90]), "+f"(d[91]), "+f"(d[92]), "+f"(d[93]), "+f"(d[94]), "+f"(d[95])
      : "r"(a[0]), "r"(a[1]), "r"(a[2]), "r"(a[3]), "l"(db));
  }
};

#define GO1 2
#define HPC 1
#define ZSH 1
#define ZP_AT 1
#define CS1_T 9500
#define G1_AT 0
#define HGRP 3
#define HPACE 150
#define DB 0
#define HOLD_AT 33
#define LL_AT 4
#define KV_T0 2300
#define ST_YIELD 1
#define HP0 0
#define HPD 0
#define RAMP 1
#define LEAD 2
#define WSP_N 16
#define EARLY 0
#define CPIN 1
#define CW0 0
#define PFT 1
#define WSP_D 650
#define D1 4
#define D2 4
#define NSLEEP 32

static_assert(ZP_AT <= RAMP && LEAD <= 2, "staging slots");

namespace {

constexpr int kS = 2048, kD = 640, kF = 1536;
constexpr int NA = 10, NA2 = 9, NB = 5;
constexpr int A_SLOT = 8192, B_SLOT = 24576;
constexpr int OFF_A = 0;
constexpr int OFF_B = OFF_A + NA * A_SLOT;
constexpr int XB_PL = 2112;
constexpr int CV_KE = 4224, CV_KO = CV_KE + 4160;
constexpr int CV_SZ = CV_KO + 4160;
constexpr int OFF_CV = OFF_B + NB * B_SLOT;
constexpr int OFF_CS = OFF_CV + 2 * CV_SZ;
constexpr int OFF_BIAS = OFF_CS + 1536;
constexpr int OFF_XS = OFF_BIAS + 128;
constexpr int OFF_BAR = OFF_XS + 512;
constexpr int BAR_AF = OFF_BAR, BAR_ST = BAR_AF + 8 * NA, BAR_XF = BAR_ST + 16, BAR_KV = BAR_XF + 16;
constexpr int BAR_BF = OFF_BAR + 128, BAR_G2 = BAR_BF + 8 * (NB + 1), BAR_XS = BAR_G2 + 8, BAR_KU = BAR_XS + 8, BAR_ZP = BAR_KU + 40, BAR_XC = BAR_ZP + 8, BAR_WO = BAR_XC + 8;
constexpr int BAR_AE = OFF_BAR + 256, BAR_BE = BAR_AE + 8 * NA;
constexpr int BAR_YT = BAR_KU + 24;
constexpr int BAR_Z1 = BAR_ST;
constexpr int BAR_GO1 = BAR_XC;
constexpr int BAR_GO = BAR_XS;
constexpr int BAR_YL = BAR_KU + 16;
constexpr int OFF_TAG = OFF_CS - 32;
constexpr int SMEM_BYTES = OFF_BAR + 384;
static_assert(SMEM_BYTES <= 232448, "smem");
constexpr int NB_WGA = 1, NB_WGC = 2, NB_G1 = 3, NB_WO = 4, NB_CD = 5, NB_Z = 6, NB_WGB = 7, NB_Z2 = 8;

constexpr int CSP = 32, EPS = 8;
constexpr int CNT_Y = 0, CNT_Z1 = 2, CNT_KV = 4, CNT_WO = 8;
struct Scratch {
  uint8_t kvx[kD * 4096];
  uint8_t z2[4 * 32 * 24576];
  uint8_t h[32 * 12 * 8192];
  uint8_t wo[4 * 12 * 20480];
  uint8_t y[896 * 4096];
  uint4 xstat[kS];
  uint2 zstat[kS * 8];
  uint2 colsum[kF];
  uint32_t zcnt[4 * 32];
  uint32_t cnt[12 * 32];
  uint32_t hcnt[32 * 32];
  uint32_t epoch[136 * EPS];
};
__device__ __align__(1024) Scratch g_scr;
#define ZS(i)
#define STAMP(i)
#define STAMP2(i)
#define STAMPW(i)

struct Params {
  Scratch* scr;
  int by_smid;
  const __nv_bfloat16 *k, *v, *shift, *ssmk, *ssmD, *wsp, *bsp, *wout;
  __nv_bfloat16* out;
  CUtensorMap tmX, tmW, tmWsp, tmY, tmKV;
};

__device__ __forceinline__ uint64_t mkdesc(uint32_t addr, uint32_t lbo, uint32_t sbo, uint32_t swz) {
  return (uint64_t)((addr & 0x3FFFF) >> 4) | ((uint64_t)(lbo >> 4) << 16) | ((uint64_t)(sbo >> 4) << 32) | ((uint64_t)swz << 62);
}
#define WG_FENCE() asm volatile("wgmma.fence.sync.aligned;" ::: "memory")
#define WG_COMMIT() asm volatile("wgmma.commit_group.sync.aligned;" ::: "memory")
#define WG_WAIT(n) asm volatile("wgmma.wait_group.sync.aligned %0;" ::"n"(n) : "memory")
template <int N> __device__ __forceinline__ void acc_fence(float* d) {
#pragma unroll
  for (int i = 0; i < N; i++) asm volatile("" : "+f"(d[i])::"memory");
}
__device__ __forceinline__ void mbar_init(uint32_t bar, int cnt) { asm volatile("mbarrier.init.shared::cta.b64 [%0], %1;" ::"r"(bar), "r"(cnt) : "memory"); }
__device__ __forceinline__ void mbar_expect(uint32_t bar, uint32_t bytes) { asm volatile("mbarrier.arrive.expect_tx.shared::cta.b64 _, [%0], %1;" ::"r"(bar), "r"(bytes) : "memory"); }
__device__ __forceinline__ void mbar_arrive(uint32_t bar) { asm volatile("mbarrier.arrive.shared::cta.b64 _, [%0];" ::"r"(bar) : "memory"); }
__device__ __forceinline__ void mbar_arrive_if(uint32_t bar, bool c) {
  asm volatile("{\n.reg .pred p;\nsetp.ne.u32 p, %1, 0;\n@p mbarrier.arrive.shared::cta.b64 _, [%0];\n}\n" ::"r"(bar), "r"((uint32_t)c) : "memory");
}
__device__ __forceinline__ void mbar_expect_if(uint32_t bar, uint32_t bytes, bool c) {
  asm volatile("{\n.reg .pred p;\nsetp.ne.u32 p, %2, 0;\n@p mbarrier.arrive.expect_tx.shared::cta.b64 _, [%0], %1;\n}\n" ::"r"(bar), "r"(bytes), "r"((uint32_t)c) : "memory");
}
__device__ __forceinline__ bool mbar_try(uint32_t bar, uint32_t parity) {
  uint32_t ok;
  asm volatile("{\n.reg .pred p;\nmbarrier.try_wait.parity.shared::cta.b64 p, [%1], %2;\nselp.u32 %0, 1, 0, p;\n}\n" : "=r"(ok) : "r"(bar), "r"(parity) : "memory");
  return ok;
}
__device__ __forceinline__ bool mbar_test(uint32_t bar, uint32_t parity) {
  uint32_t ok;
  asm volatile("{\n.reg .pred p;\nmbarrier.test_wait.parity.shared::cta.b64 p, [%1], %2;\nselp.u32 %0, 1, 0, p;\n}\n" : "=r"(ok) : "r"(bar), "r"(parity) : "memory");
  return ok;
}
__device__ __forceinline__ void die() { asm volatile("st.volatile.global.u32 [%0], %1;" ::"l"(0ull), "r"(0) : "memory"); }
__device__ __forceinline__ void spin_guard(uint32_t& n) { if (++n == (1u << 22)) die(); }
__device__ __forceinline__ void mbar_wait(uint32_t bar, uint32_t parity) {
  uint32_t t0 = 0;
#pragma unroll 1
  while (!mbar_try(bar, parity)) spin_guard(t0);
}
__device__ __forceinline__ void mbar_wait2(uint32_t b0, uint32_t p0, uint32_t b1, uint32_t p1) {
  uint32_t t0 = 0;
#pragma unroll 1
  while (true) {
    const bool r0 = mbar_try(b0, p0), r1 = mbar_try(b1, p1);
    if (r0 && r1) break;
    spin_guard(t0);
  }
}
__device__ __forceinline__ int tid_now() { int v; asm volatile("mov.u32 %0, %%tid.x;" : "=r"(v)); return v & 127; }
__device__ __forceinline__ bool elect_one() {
  uint32_t p;
  asm volatile("{\n.reg .pred P;\nelect.sync _|P, 0xffffffff;\nselp.u32 %0, 1, 0, P;\n}\n" : "=r"(p));
  return p;
}
__device__ __forceinline__ void bar_sync(int id, int n) { asm volatile("bar.sync %0, %1;" ::"r"(id), "r"(n) : "memory"); }
__device__ __forceinline__ void bar_arrive(int id, int n) { asm volatile("bar.arrive %0, %1;" ::"r"(id), "r"(n) : "memory"); }
__device__ __forceinline__ void fence_async_smem() { asm volatile("fence.proxy.async.shared::cta;" ::: "memory"); }
__device__ __forceinline__ void bulk_g2s(uint32_t dst, const void* src, uint32_t bytes, uint32_t bar) {
  asm volatile("cp.async.bulk.shared::cluster.global.mbarrier::complete_tx::bytes [%0], [%1], %2, [%3];" ::"r"(dst), "l"(src), "r"(bytes), "r"(bar) : "memory");
}
__device__ __forceinline__ void bulk_s2g(void* dst, uint32_t src, uint32_t bytes) {
  asm volatile("cp.async.bulk.global.shared::cta.bulk_group [%0], [%1], %2;" ::"l"(dst), "r"(src), "r"(bytes) : "memory");
}
__device__ __forceinline__ void tma2d(uint32_t dst, const CUtensorMap* m, int c0, int c1, uint32_t bar) {
  asm volatile("cp.async.bulk.tensor.2d.shared::cluster.global.mbarrier::complete_tx::bytes [%0], [%1, {%3, %4}], [%2];" ::"r"(dst), "l"(m), "r"(bar), "r"(c0), "r"(c1) : "memory");
}
__device__ __forceinline__ void tma3d(uint32_t dst, const CUtensorMap* m, int c0, int c1, int c2, uint32_t bar) {
  asm volatile("cp.async.bulk.tensor.3d.shared::cluster.global.mbarrier::complete_tx::bytes [%0], [%1, {%3, %4, %5}], [%2];" ::"r"(dst), "l"(m), "r"(bar), "r"(c0), "r"(c1), "r"(c2) : "memory");
}
__device__ __forceinline__ void tma_rows(uint32_t dst, const CUtensorMap* m, int c0, int rb, uint32_t bar) { tma3d(dst, m, c0, rb * 16, 0, bar); }
__device__ __forceinline__ uint4 ld_ll4(const void* p) {
  uint64_t a, b;
  asm volatile("ld.relaxed.gpu.global.v2.u64 {%0,%1}, [%2];" : "=l"(a), "=l"(b) : "l"(p) : "memory");
  return make_uint4((uint32_t)a, (uint32_t)(a >> 32), (uint32_t)b, (uint32_t)(b >> 32));
}
__device__ __forceinline__ void st_ll4(void* p, uint32_t a, uint32_t b, uint32_t c, uint32_t d) {
  asm volatile("st.relaxed.gpu.global.v2.u64 [%0], {%1,%2};" ::"l"(p), "l"(a | ((uint64_t)b << 32)), "l"(c | ((uint64_t)d << 32)) : "memory");
}
__device__ __forceinline__ void st_ll2(void* p, uint32_t a, uint32_t b) { asm volatile("st.relaxed.gpu.global.u64 [%0], %1;" ::"l"(p), "l"(a | ((uint64_t)b << 32)) : "memory"); }
__device__ __forceinline__ uint2 ld_ll2(const void* p) {
  uint64_t a;
  asm volatile("ld.relaxed.gpu.global.u64 %0, [%1];" : "=l"(a) : "l"(p) : "memory");
  return make_uint2((uint32_t)a, (uint32_t)(a >> 32));
}
__device__ __forceinline__ void wgmma_colsum(float* d, uint64_t da, uint64_t db) {
  asm volatile("{\n.reg .pred p;\nsetp.ne.b32 p, 1, 0;\nwgmma.mma_async.sync.aligned.m64n8k16.f32.bf16.bf16 {%0, %1, %2, %3}, %4, %5, p, 1, 1, 1, 0;\n}\n"
               : "+f"(d[0]), "+f"(d[1]), "+f"(d[2]), "+f"(d[3]) : "l"(da), "l"(db));
}
__device__ __forceinline__ void prefetch_l2(const void* p) { asm volatile("prefetch.global.L2 [%0];" ::"l"(p)); }
__device__ __forceinline__ void pace(uint32_t& t, uint32_t dt) {
  t += dt;
  while ((int32_t)((uint32_t)clock() - t) < 0) { if (NSLEEP) __nanosleep(NSLEEP); }
}
__device__ __forceinline__ void red_relaxed(uint32_t* p) { asm volatile("red.relaxed.gpu.global.add.u32 [%0], 1;" ::"l"(p) : "memory"); }
__device__ __forceinline__ void red_release(uint32_t* p) { asm volatile("red.release.gpu.global.add.u32 [%0], 1;" ::"l"(p) : "memory"); }
__device__ __forceinline__ uint4 ldg4(const void* p) { uint4 v; asm volatile("ld.global.v4.u32 {%0,%1,%2,%3}, [%4];" : "=r"(v.x), "=r"(v.y), "=r"(v.z), "=r"(v.w) : "l"(p) : "memory"); return v; }
__device__ __forceinline__ uint32_t ldg1(const void* p) { uint32_t v; asm volatile("ld.global.u32 %0, [%1];" : "=r"(v) : "l"(p) : "memory"); return v; }
__device__ __forceinline__ void stg4_if(void* p, uint32_t a, uint32_t b, uint32_t c, uint32_t d, bool on) {
  asm volatile("{\n.reg .pred p;\nsetp.ne.u32 p, %5, 0;\n@p st.global.v4.u32 [%0], {%1,%2,%3,%4};\n}\n" ::"l"(p), "r"(a), "r"(b), "r"(c), "r"(d), "r"((uint32_t)on) : "memory");
}
template <int OFF> __device__ __forceinline__ uint32_t lds32(uint32_t a) { uint32_t v; asm volatile("ld.shared.u32 %0, [%1+%2];" : "=r"(v) : "r"(a), "n"(OFF)); return v; }
__device__ __forceinline__ uint4 lds128(uint32_t a) { uint4 v; asm volatile("ld.shared.v4.u32 {%0,%1,%2,%3}, [%4];" : "=r"(v.x), "=r"(v.y), "=r"(v.z), "=r"(v.w) : "r"(a) : "memory"); return v; }
__device__ __forceinline__ float2 lds64f(uint32_t a) { float2 v; asm volatile("ld.shared.v2.f32 {%0,%1}, [%2];" : "=f"(v.x), "=f"(v.y) : "r"(a) : "memory"); return v; }
__device__ __forceinline__ void sts64f(uint32_t a, float x, float y) { asm volatile("st.shared.v2.f32 [%0], {%1,%2};" ::"r"(a), "f"(x), "f"(y) : "memory"); }
__device__ __forceinline__ void sts32(uint32_t a, uint32_t x) { asm volatile("st.shared.u32 [%0], %1;" ::"r"(a), "r"(x) : "memory"); }
__device__ __forceinline__ void sts128(uint32_t a, uint32_t x, uint32_t y, uint32_t z, uint32_t w) { asm volatile("st.shared.v4.u32 [%0], {%1,%2,%3,%4};" ::"r"(a), "r"(x), "r"(y), "r"(z), "r"(w) : "memory"); }
__device__ __forceinline__ void stsm4(uint32_t a, uint32_t r0, uint32_t r1, uint32_t r2, uint32_t r3) {
  asm volatile("stmatrix.sync.aligned.m8n8.x4.shared.b16 [%0], {%1,%2,%3,%4};" ::"r"(a), "r"(r0), "r"(r1), "r"(r2), "r"(r3) : "memory");
}
__device__ __forceinline__ void stsm4t(uint32_t a, uint32_t r0, uint32_t r1, uint32_t r2, uint32_t r3) {
  asm volatile("stmatrix.sync.aligned.m8n8.x4.trans.shared.b16 [%0], {%1,%2,%3,%4};" ::"r"(a), "r"(r0), "r"(r1), "r"(r2), "r"(r3) : "memory");
}
__device__ __forceinline__ void ldsm4t(uint32_t* r, uint32_t a) {
  asm volatile("ldmatrix.sync.aligned.m8n8.x4.trans.shared.b16 {%0,%1,%2,%3}, [%4];" : "=r"(r[0]), "=r"(r[1]), "=r"(r[2]), "=r"(r[3]) : "r"(a) : "memory");
}
__device__ __forceinline__ uint32_t pack2(float lo, float hi) { uint32_t r; asm("cvt.rn.bf16x2.f32 %0, %1, %2;" : "=r"(r) : "f"(hi), "f"(lo)); return r; }
__device__ __forceinline__ float bf_lo(uint32_t u) { return __uint_as_float(u << 16); }
__device__ __forceinline__ float bf_hi(uint32_t u) { return __uint_as_float(u & 0xffff0000u); }
__device__ __forceinline__ float tanh_fast(float x) { float y; asm("tanh.approx.f32 %0, %1;" : "=f"(y) : "f"(x)); return y; }
__device__ __forceinline__ uint32_t hmul2(uint32_t a, uint32_t b) { uint32_t r; asm("mul.rn.bf16x2 %0, %1, %2;" : "=r"(r) : "r"(a), "r"(b)); return r; }
__device__ __forceinline__ uint32_t hfma2(uint32_t a, uint32_t b, uint32_t c) { uint32_t r; asm("fma.rn.bf16x2 %0, %1, %2, %3;" : "=r"(r) : "r"(a), "r"(b), "r"(c)); return r; }
__device__ __forceinline__ uint32_t prmt(uint32_t a, uint32_t b, uint32_t s) { return __byte_perm(a, b, s); }

__device__ __forceinline__ void st_relaxed(uint32_t* p, uint32_t v) { asm volatile("st.relaxed.gpu.global.u32 [%0], %1;" ::"l"(p), "r"(v) : "memory"); }
__device__ __forceinline__ uint32_t ld_relaxed(const uint32_t* p) { uint32_t v; asm volatile("ld.relaxed.gpu.global.u32 %0, [%1];" : "=r"(v) : "l"(p) : "memory"); return v; }
__device__ __forceinline__ void acquire_fence() { asm volatile("fence.acquire.gpu;\nfence.proxy.async.global;" ::: "memory"); }
__device__ __forceinline__ uint32_t load_epoch(const Params& p, int idx, int lane) { return ld_relaxed(&p.scr->epoch[idx * EPS + (((lane * lane) & 3) == 2 ? 1 : 0)]); }
__device__ __forceinline__ void poll_counter(const uint32_t* cnt, uint32_t target) {
  uint32_t t0 = 0;
#pragma unroll 1
  while (!__all_sync(0xffffffff, ld_relaxed(cnt) == target)) spin_guard(t0);
  acquire_fence();
}

__device__ __forceinline__ int g3_block(int cb, int it) { return it < 3 ? cb * 3 + it : (it - 3 < cb * 3 ? it - 3 : it); }

template <int N, bool A_SWZ, int B_MODE, int DEPTH, class Hook, class Mid>
__device__ __forceinline__ void gemm_loop(float* d, uint32_t sb, int nkb, int sa, int pa, int b0, uint32_t boff, int relA, int relB, int tid, Hook hook, Mid mid) {
  constexpr uint32_t A_STEP = A_SWZ ? 2 : 128;
  constexpr uint32_t B_STEP = B_MODE == 0 ? 128 : (B_MODE == 1 ? 384 : 320);
  const uint64_t da0 = A_SWZ ? mkdesc(sb + OFF_A, 16, 1024, 1) : mkdesc(sb + OFF_A, 1024, 128, 0);
  const uint64_t db0 = B_MODE == 0 ? mkdesc(sb + OFF_B + boff, 8192, 1024, 1) : mkdesc(sb + OFF_B + boff, B_MODE == 1 ? 3072 : 2560, 128, 0);
  constexpr int MODA = B_MODE == 0 ? NA : NA2;
  constexpr int MODB = B_MODE == 2 ? 6 : NB;
  int sbk = b0 % MODB, pb = (b0 / MODB) & 1;
  auto boffs = [](int s_) { return B_MODE == 2 ? (s_ == 5 ? 0 : s_ + 1) * (20480 >> 4) : s_ * (B_SLOT >> 4); };
  uint32_t rel = 0;
  uint64_t da = da0 + sa * (A_SLOT >> 4), db = db0 + boffs(sbk);
  const bool doR = tid < 2 ? tid < relA : tid - 2 < relB;
  mbar_wait2(sb + BAR_AF + 8 * sa, pa, sb + BAR_BF + 8 * sbk, pb);
  if constexpr (DEPTH == 0) {
#pragma unroll
    for (int i = 0; i < N / 2; i++) asm volatile("" : "=f"(d[i]));
#pragma unroll 1
    for (int it = 0; it < nkb; it++) {
      WG_FENCE();
#pragma unroll
      for (int j = 0; j < 4; j++) WG<N>::ss(d, da + j * A_STEP, db + j * B_STEP, j ? 1 : it);
      WG_COMMIT();
      const uint32_t prel = rel;
      rel = sb + BAR_AE + 8 * (tid < 2 ? sa : sbk + NA);
      if (++sa == MODA) { sa = 0; pa ^= 1; }
      if (++sbk == MODB) { sbk = 0; pb ^= 1; }
      da = da0 + sa * (A_SLOT >> 4); db = db0 + boffs(sbk);
      const bool r0 = mbar_test(sb + BAR_AF + 8 * sa, pa), r1 = mbar_test(sb + BAR_BF + 8 * sbk, pb);
      WG_WAIT(1);
      mbar_arrive_if(prel, doR && prel != 0);
      if (it == 2) {
        WG_WAIT(0);
        mbar_expect_if(sb + BAR_AF + 8 * (tid == 8 ? 8 : tid), A_SLOT, tid < 9);
        mbar_arrive_if(rel, doR);
        rel = 0;
      }
      mid(it);
      if (it + 1 < nkb && !(r0 && r1)) {
        mbar_wait2(sb + BAR_AF + 8 * sa, pa, sb + BAR_BF + 8 * sbk, pb);
      }
    }
  } else
#pragma unroll 1
  for (int it = 0; it < nkb; it++) {
    WG_FENCE();
    WG<N>::ss(d, da, db, 1);
    const uint32_t prel = rel;
    rel = sb + BAR_AE + 8 * (tid < 2 ? sa : sbk + NA);
    if (++sa == MODA) { sa = 0; if (B_MODE) pa ^= 1; }
    if (++sbk == MODB) { sbk = 0; pb ^= 1; }
    if (DEPTH == 1) { WG_COMMIT(); WG_WAIT(1); }
    WG<N>::ss(d, da + A_STEP, db + B_STEP, 1);
    WG_COMMIT();
    WG_WAIT(1);
    if (EARLY == 1) mbar_arrive_if(prel, doR && it != 0);
    WG<N>::ss(d, da + 2 * A_STEP, db + 2 * B_STEP, 1);
    if (DEPTH == 1) WG_COMMIT();
    if (EARLY != 1) mbar_arrive_if(prel, doR && it != 0);
    const bool r0 = mbar_test(sb + BAR_AF + 8 * sa, pa), r1 = mbar_test(sb + BAR_BF + 8 * sbk, pb);
    const uint64_t da3 = da + 3 * A_STEP, db3 = db + 3 * B_STEP;
    da = da0 + sa * (A_SLOT >> 4); db = db0 + boffs(sbk);
    if (DEPTH == 1) WG_WAIT(1);
    WG<N>::ss(d, da3, db3, 1);
    WG_COMMIT();
    mid(it);
    if (it + 1 < nkb) {
      if (!(r0 && r1)) {
        mbar_wait2(sb + BAR_AF + 8 * sa, pa, sb + BAR_BF + 8 * sbk, pb);
      }
    }
    if (DEPTH == 2) WG_WAIT(1);
  }
  hook();
  WG_WAIT(0);
  acc_fence<N / 2>(d);
  mbar_arrive_if(rel, doR);
}

__device__ __forceinline__ void fold_mean(float* d, uint32_t cs, float ma, float mb, int t) {
  const uint32_t ha = pack2(-ma, -ma), hb = pack2(-mb, -mb);
  const float la = -ma - bf_lo(ha), lb = -mb - bf_lo(hb);
  const uint32_t a[4] = {t ? 0u : ha, t ? 0u : hb, t ? 0u : pack2(la, la), t ? 0u : pack2(lb, lb)};
  WG_FENCE();
  WG<192>::rst(d, a, mkdesc(cs, 0, 32, 0));
  WG_COMMIT();
}
__device__ __forceinline__ void gelu_tile(const float* d, uint32_t* z, float* st, float ra, float rb) {
  const float kA = 0.7978845608028654f, kB = 0.7978845608028654f * 0.044715f;
  const float c1a = kA * ra, c3a = kB * ra * ra * ra, c1b = kA * rb, c3b = kB * rb * rb * rb;
  float acc[8];
#pragma unroll
  for (int i = 0; i < 8; i++) acc[i] = 0.f;
#pragma unroll
  for (int j = 0; j < 24; j++) {
    float r[4];
#pragma unroll
    for (int e = 0; e < 4; e++) {
      const float v = d[4 * j + e];
      const float a = v * fmaf(v * v, e < 2 ? c3a : c3b, e < 2 ? c1a : c1b);
      r[e] = fmaf(v, tanh_fast(a), v);
      acc[e] += r[e];
      acc[4 + e] = fmaf(r[e], r[e], acc[4 + e]);
    }
    z[2 * j] = pack2(r[0], r[1]);
    z[2 * j + 1] = pack2(r[2], r[3]);
  }
  st[0] = acc[0] + acc[1]; st[1] = acc[4] + acc[5]; st[2] = acc[2] + acc[3]; st[3] = acc[6] + acc[7];
}

template <int Q> __device__ __forceinline__ void conv_load(uint32_t* a, uint32_t ab) {
  a[0] = lds32<512 * Q>(ab);       a[1] = lds32<512 * Q + 256>(ab);  a[2] = lds32<512 * Q + 16>(ab);   a[3] = lds32<512 * Q + 272>(ab);
  a[4] = lds32<512 * Q + 32>(ab);  a[5] = lds32<512 * Q + 288>(ab);  a[6] = lds32<512 * Q + 48>(ab);   a[7] = lds32<512 * Q + 304>(ab);
  a[8] = lds32<512 * Q + 64>(ab);  a[9] = lds32<512 * Q + 320>(ab);  a[10] = lds32<512 * Q + 80>(ab);  a[11] = lds32<512 * Q + 336>(ab);
  a[12] = lds32<512 * Q + 96>(ab); a[13] = lds32<512 * Q + 352>(ab); a[14] = lds32<512 * Q + 112>(ab); a[15] = lds32<512 * Q + 368>(ab);
}
template <int Q, int L> __device__ __forceinline__ void conv_step(float* d, uint32_t (*a)[16], uint32_t ab, uint64_t db) {
  WG_FENCE();
#pragma unroll
  for (int s = 0; s < 4; s++) WG<128 - 16 * Q>::rs(d, a[Q] + 4 * s, db + s + 16 * Q);
  WG_COMMIT();
  if (CPIN) WG_WAIT(1);
  if (L >= 0) conv_load<(L >= 0 ? L : 0)>(a[L >= 0 ? L : 0], ab);
  if (CW0 || Q == 0) WG_WAIT(0);
}

__device__ __forceinline__ int seg_col(int cb, int h) { return (cb >> 1) * 320 + (cb & 1) * 32 + h * 64; }
__device__ __forceinline__ void final_load_x(uint32_t (*xw)[10], uint32_t xt, int cb, int h, int w, int lane) {
  const int g = lane >> 2, t = lane & 3, cc = seg_col(cb, h) >> 3;
  const int c0 = cc + t, c1 = c0 + 24, c2 = cc + 16 - 6 * h + (t >> 1);
  const uint32_t r0 = xt + (w * 16 + g) * 128;
#pragma unroll
  for (int r = 0; r < 2; r++) {
    const uint4 u = lds128(r0 + r * 1024 + (c0 >> 3) * A_SLOT + (((c0 ^ g) & 7) << 4)), v = lds128(r0 + r * 1024 + (c1 >> 3) * A_SLOT + (((c1 ^ g) & 7) << 4));
    const float2 z = lds64f(r0 + r * 1024 + (c2 >> 3) * A_SLOT + (((c2 ^ g) & 7) << 4) + (t & 1) * 8);
    xw[r][0] = u.x; xw[r][1] = u.y; xw[r][2] = u.z; xw[r][3] = u.w;
    xw[r][4] = v.x; xw[r][5] = v.y; xw[r][6] = v.z; xw[r][7] = v.w;
    xw[r][8] = __float_as_uint(z.x); xw[r][9] = __float_as_uint(z.y);
  }
}
__device__ __forceinline__ void final_s_early(uint32_t (*sw)[10], const uint32_t (*xw)[10], uint32_t ya, float2 s0, float2 s1) {
  const uint32_t r2[2] = {pack2(s0.y, s0.y), pack2(s1.y, s1.y)};
  const float na = -s0.x * bf_lo(r2[0]), nb = -s1.x * bf_lo(r2[1]);
  const uint32_t n2[2] = {pack2(na, na), pack2(nb, nb)};
#pragma unroll
  for (int j = 0; j < 10; j += 2) {
    uint32_t y[4];
    if (j < 4 || j == 8) ldsm4t(y, ya + (j < 4 ? j : 4) * 1024);
#pragma unroll
    for (int e = 0; e < 4; e++) {
      const uint32_t xn = hfma2(xw[e & 1][j + (e >> 1)], r2[e & 1], n2[e & 1]);
      sw[e & 1][j + (e >> 1)] = (j < 4 || j == 8) ? hmul2(xn, y[e]) : xn;
    }
  }
}
__device__ __forceinline__ bool final_late(uint32_t* y, uint32_t ya) {
  ldsm4t(y, ya + 6144);
  ldsm4t(y + 4, ya + 8192);
  uint32_t zero = 0;
#pragma unroll
  for (int e = 0; e < 8; e++) zero |= (y[e] - 0x00010001u) & ~y[e];
  return (zero & 0x80008000u) == 0;
}
__device__ __forceinline__ bool bar_all(int id, int n, bool c) {
  uint32_t r;
  asm volatile("{\n.reg .pred p, q;\nsetp.ne.u32 p, %3, 0;\nbar.red.and.pred q, %1, %2, p;\nselp.u32 %0, 1, 0, q;\n}\n" : "=r"(r) : "r"(id), "r"(n), "r"((uint32_t)c) : "memory");
  return r;
}
__device__ __forceinline__ void final_out(const float* d, const uint32_t (*xw)[10], const uint32_t (*sw)[10], float ra, float rb, __nv_bfloat16* o0, int h, int t) {
  const float ca = 0.25f * ra, cb = 0.25f * rb;
  uint32_t o[2][10];
#pragma unroll
  for (int j = 0; j < 10; j++) {
#pragma unroll
    for (int r = 0; r < 2; r++) {
      const float h0 = d[4 * j + 2 * r] * (r ? cb : ca), h1 = d[4 * j + 2 * r + 1] * (r ? cb : ca);
      o[r][j] = hfma2(pack2(fmaf(h0, tanh_fast(h0), h0), fmaf(h1, tanh_fast(h1), h1)), sw[r][j], xw[r][j]);
      __nv_bfloat16* q = o0 + r * 8 * kD;
      if (j == 3) stg4_if(q + t * 8, o[r][0], o[r][1], o[r][2], o[r][3], true);
      if (j == 7) stg4_if(q + 192 + t * 8, o[r][4], o[r][5], o[r][6], o[r][7], true);
      if (j == 9) asm volatile("st.global.v2.u32 [%0], {%1,%2};" ::"l"(q + 128 - 48 * h + t * 4), "r"(o[r][8]), "r"(o[r][9]) : "memory");
    }
  }
}

struct Taps { uint4 r0, r1; uint32_t n0, n1, dd; };
__device__ __forceinline__ void load_taps(Taps& k, const Params& p, int ch, int tid) {
  const uint4* kp = (const uint4*)(p.ssmk + (size_t)ch * kS);
  k.r0 = ldg4(kp + tid); k.r1 = ldg4(kp + 128 + tid);
  k.n0 = ldg1(kp + tid + 1); k.n1 = tid < 127 ? ldg1(kp + 129 + tid) : 0u;
  k.dd = __bfloat16_as_ushort(p.ssmD[ch]);
}
__device__ __forceinline__ void load_convx(const Params& p, uint32_t cv, uint32_t bar, int ch) {
  mbar_expect(bar, 4096);
  bulk_g2s(cv, p.scr->kvx + (size_t)ch * 4096, 2048, bar);
  bulk_g2s(cv + XB_PL, p.scr->kvx + (size_t)ch * 4096 + 2048, 2048, bar);
}
#define CW 3
#define CSTAMP(j)
__device__ __forceinline__ void zero_pads(uint32_t cv, int lane) {
  if (lane < 8) sts128(cv + (lane >> 2) * XB_PL + 2048 + (lane & 3) * 16, 0, 0, 0, 0);
  else if (lane < 12) sts128(cv + ((lane & 2) ? CV_KO : CV_KE) + (lane & 1) * 16, 0, 0, 0, 0);
  fence_async_smem();
  __syncwarp();
}
__device__ __forceinline__ int y_row(int c, uint32_t par) {
  const int hf = c >= 320, cc = c - hf * 320, u = cc >> 6, cb = hf * 2 + ((cc >> 5) & 1);
  if (u == 2) return cb * 96 + ((cc >> 4) & 1) * 48 + 32 + (cc & 1) + ((cc >> 1) & 1) * 8 + ((cc >> 2) & 3) * 2;
  return (u < 2 ? cb * 96 + u * 48 : 384 + par * 256 + cb * 64 + (u - 3) * 32) + (cc & 1) + ((cc >> 1) & 3) * 8 + ((cc >> 3) & 3) * 2;
}
__device__ __forceinline__ void z_store(const Params& p, uint32_t src, int rb, int cb, int q) {
  uint8_t* dst = p.scr->z2 + (size_t)(cb * 32 + q * 16 + (rb >> 2)) * B_SLOT + (rb & 3) * 6144;
  bulk_s2g(dst, src + q * 12288, 6144);
  bulk_s2g(dst + 8 * B_SLOT, src + q * 12288 + 6144, 6144);
  asm volatile("cp.async.bulk.commit_group;\ncp.async.bulk.wait_group 0;" ::: "memory");
}
__device__ __forceinline__ void y_store(const Params& p, uint32_t sb, int h, int ch, uint32_t par) {
  uint8_t* dst = p.scr->y + (size_t)y_row(ch, par) * 4096;
  if (elect_one()) {
    bulk_s2g(dst, sb + OFF_A + 9 * A_SLOT + h * 4096, 4096);
    asm volatile("cp.async.bulk.commit_group;\ncp.async.bulk.wait_group 0;" ::: "memory");
  }
  __syncwarp();
}
__device__ __forceinline__ void conv_service(const Params& p, uint32_t sb, int h, int ch, bool first) {
  bar_sync(NB_WGA + 8 + h, 160);
  const bool now = !first || __all_sync(0xffffffff, mbar_test(sb + BAR_KV, 0));
  if (now && elect_one()) load_convx(p, sb + OFF_CV + (1 - h) * CV_SZ, sb + BAR_XF + 8 * h, ch + 128);
  bar_sync(NB_WGA + 8 + h, 160);
  y_store(p, sb, h, ch, 0);
  if (!now) {
    mbar_wait(sb + BAR_KV, 0);
    if (elect_one()) load_convx(p, sb + OFF_CV + (1 - h) * CV_SZ, sb + BAR_XF + 8 * h, ch + 128);
  }
}
__device__ __forceinline__ uint32_t y_tile(int h) { return OFF_CV + (1 - h) * 13312; }
__device__ __forceinline__ void load_late_y(const Params& p, uint32_t sb, int h, int rb, int cb, uint32_t par) {
  mbar_expect(sb + BAR_YL + 16 * h, 4096);
  tma2d(sb + y_tile(h) + 6144, &p.tmY, rb * 64, 384 + par * 256 + cb * 64 + h * 32, sb + BAR_YL + 16 * h);
  tma2d(sb + y_tile(h) + 8192, &p.tmY, rb * 64, 400 + par * 256 + cb * 64 + h * 32, sb + BAR_YL + 16 * h);
}
__device__ __forceinline__ void held_service(const Params& p, uint32_t sb, int h, int ch, int rb, int cb, uint32_t tag, int lane) {
#pragma unroll 1
  for (int i = 0; i < 8; i++) sts128(sb + OFF_A + 9 * A_SLOT + h * 4096 + i * 512 + lane * 16, 0, 0, 0, 0);
  fence_async_smem();
  __syncwarp();
  y_store(p, sb, h, ch, ~tag & 1);
  mbar_wait(sb + BAR_YT, 1);
  uint8_t* dst = p.scr->y + (size_t)y_row(ch, tag & 1) * 4096;
  asm volatile("" : "+l"(dst));
  bar_sync(NB_WGA + 8 + h, 160);
  bar_sync(NB_WGA + 8 + h, 160);
  if (elect_one()) {
    bulk_s2g(dst, sb + OFF_A + 9 * A_SLOT + h * 4096, 4096);
    asm volatile("cp.async.bulk.commit_group;" ::: "memory");
    mbar_expect(sb + BAR_XF + 8 * h, 6144);
#pragma unroll 1
    for (int i = 0; i < 3; i++) tma2d(sb + y_tile(h) + i * 2048, &p.tmY, rb * 64, cb * 96 + h * 48 + i * 16, sb + BAR_XF + 8 * h);
  }
  mbar_wait(sb + BAR_AE + 8 * (LL_AT - 1), 1);
  if (elect_one()) { load_late_y(p, sb, h, rb, cb, tag & 1); asm volatile("cp.async.bulk.wait_group 0;" ::: "memory"); }
}
__device__ __forceinline__ void conv_worker(const Params& p, Taps& k, uint32_t cv, uint32_t yb0,
                                            uint32_t xbar, int nbar, int ch0, int n, uint32_t holdbar, int w, int lane,
                                            int tid, int st0, int rb, int cb) {
  const int g = lane >> 2, t = lane & 3, w0 = w & 1, w1 = w >> 1;
  const uint32_t ab = cv + ((g & 1) ? CV_KE : CV_KO) + 32 + 2 * (64 * w0 + 8 * w1 + ((g - 15) & ~1) + 2 * t);
  const uint32_t scA = cv + (w1 ? CV_KO : CV_KE) + 32, scB = scA + 2048;
  const int dl = (t >> 1) ^ 1;
  if (n == 2) mbar_wait(xbar, 0);
  STAMPW(st0 + 3);
#pragma unroll 1
  for (int i = 0; i < n; i++) {
    if (tid == 0) {
      k.r0.x = (k.r0.x & 0xffff0000u) | (pack2(bf_lo(k.r0.x) + bf_lo(k.dd), 0.f) & 0xffffu);
      sts32(cv + CV_KO + 28, k.r0.x << 16);
    }
    sts128(cv + CV_KE + 32 + tid * 16, k.r0.x, k.r0.y, k.r0.z, k.r0.w);
    sts128(cv + CV_KO + 32 + tid * 16, prmt(k.r0.x, k.r0.y, 0x5432), prmt(k.r0.y, k.r0.z, 0x5432), prmt(k.r0.z, k.r0.w, 0x5432), prmt(k.r0.w, k.n0, 0x5432));
    sts128(cv + CV_KE + 2080 + tid * 16, k.r1.x, k.r1.y, k.r1.z, k.r1.w);
    sts128(cv + CV_KO + 2080 + tid * 16, prmt(k.r1.x, k.r1.y, 0x5432), prmt(k.r1.y, k.r1.z, 0x5432), prmt(k.r1.z, k.r1.w, 0x5432), prmt(k.r1.w, k.n1, 0x5432));
    if (i + 1 < n) load_taps(k, p, ch0 + (i + 1) * 128, tid);
    bar_sync(nbar, 128);
    CSTAMP(0);
    const uint64_t db = mkdesc(cv + (i & 0x1000), XB_PL, 128, 0);
    float d[64];
    uint32_t a[8][16];
    if (i == 0) mbar_wait(xbar, 0);
    conv_load<7>(a[7], ab); conv_load<6>(a[6], ab); conv_load<5>(a[5], ab); conv_load<4>(a[4], ab);
#pragma unroll
    for (int j = 0; j < 64; j++) d[j] = 0.f;
    mbar_wait(xbar, i & 1);
    if (i + 1 == n) mbar_wait(GO1 ? holdbar + (BAR_GO1 - BAR_GO) : holdbar, 1);
    CSTAMP(1);
    conv_step<7, -1>(d, a, ab, db); conv_step<6, -1>(d, a, ab, db); conv_step<5, -1>(d, a, ab, db); conv_step<4, -1>(d, a, ab, db);
    if (GO1 && i + 1 == n) mbar_wait(holdbar, 1);
    conv_load<3>(a[3], ab);
    conv_step<3, 2>(d, a, ab, db);
    conv_step<2, 1>(d, a, ab, db);
    conv_step<1, 0>(d, a, ab, db);
    conv_step<0, -1>(d, a, ab, db);
    acc_fence<64>(d);
    CSTAMP(2);
    bar_sync(nbar + 8, 160);
    float E[16][2];
#pragma unroll
    for (int j = 0; j < 15; j++) { E[j][0] = d[4 * j] + d[4 * j + 6]; E[j][1] = d[4 * j + 1] + d[4 * j + 7]; }
    E[15][0] = d[60]; E[15][1] = d[61];
    if (w0 == 0) {
#pragma unroll
      for (int j = 8; j < 16; j++) sts64f(scA + (j - 8) * 256 + lane * 8, E[j][0], E[j][1]);
    } else {
      const uint32_t a = scB - dl * 256 + (lane ^ 2) * 8;
#pragma unroll
      for (int j = 1; j < 8; j++) sts64f(a + j * 256, E[j][0], E[j][1]);
      sts64f(scB + (dl ? 7 * 256 : 0) + (lane ^ 2) * 8, dl ? E[8][0] : E[0][0], dl ? E[8][1] : E[0][1]);
    }
    bar_sync(nbar, 128);
    CSTAMP(3);
    uint32_t pk[8];
    if (w0 == 0) {
#pragma unroll
      for (int j = 0; j < 8; j++) { const float2 v = lds64f(scB + j * 256 + lane * 8); pk[j] = pack2(E[j][0] + v.x, E[j][1] + v.y); }
    } else {
      const uint32_t a0 = scA - dl * 256 + (lane ^ 2) * 8;
#pragma unroll
      for (int j = 9; j < 16; j++) { const float2 v = lds64f(a0 + (j - 8) * 256); pk[j - 8] = pack2(E[j][0] + v.x, E[j][1] + v.y); }
      const float2 v = lds64f(scA + (dl ? 7 * 256 : 0) + (lane ^ 2) * 8);
      pk[0] = pack2((dl ? 0.f : E[8][0]) + v.x, (dl ? 0.f : E[8][1]) + v.y);
    }
    CSTAMP(4);
    if (i + 1 == n) {
#pragma unroll
      for (int j = 0; j < 8; j++) pk[j] = ~pk[j];
    }
    const int c1 = (w0 ? 35 : 95) - lane, c0 = (w0 && lane < 4) ? c1 - 32 : c1 + 32;
    stsm4t(yb0 + 128 * (c0 & 31) + (((2 * (c0 >> 5) + w1) ^ (c0 & 7)) << 4), pk[0], pk[1], pk[2], pk[3]);
    stsm4t(yb0 + 128 * (c1 & 31) + (((2 * (c1 >> 5) + w1) ^ (c1 & 7)) << 4), pk[4], pk[5], pk[6], pk[7]);
    fence_async_smem();
    bar_sync(nbar + 8, 160);
    CSTAMP(5);
    STAMPW(st0 + i);
    if (n == 2 && i == 0) {
      const int u = (tid >> 3) % 5, kg = rb * 3 + (tid < 120 ? (tid >> 3) / 5 : 0), c = u < 4 ? (u >> 1) * 10 + (u & 1) * 4 : 8, o2 = u < 4 ? 2 : 10;
      const uint4* wp = (const uint4*)p.wout + (uint32_t)((kg * 8 + (tid & 7)) * (kD / 8) + (seg_col(cb, 0) >> 3) + (u < 4 ? (u >> 1) * 8 + (u & 1) * 24 : 16));
      const uint4 w0 = ldg4(wp), w1 = ldg4(wp + 1), w2 = ldg4(wp + 2), w3 = ldg4(wp + 3);
      uint8_t* dst = p.scr->wo + (uint32_t)(cb * (12 * 20480) + kg * 2560 + c * 128 + (tid & 7) * 16);
      const bool f = u < 4, on = tid < 120;
      stg4_if(dst, w0.x, f ? w1.x : w0.z, f ? w2.x : w1.x, f ? w3.x : w1.z, on);
      stg4_if(dst + 128, w0.y, f ? w1.y : w0.w, f ? w2.y : w1.y, f ? w3.y : w1.w, on);
      stg4_if(dst + o2 * 128, f ? w0.z : w2.x, f ? w1.z : w2.z, f ? w2.z : w3.x, w3.z, on);
      stg4_if(dst + o2 * 128 + 128, f ? w0.w : w2.y, f ? w1.w : w2.w, f ? w2.w : w3.y, w3.w, on);
      bar_arrive(NB_WO, 160);
    }
  }
}

struct KvRegs { uint32_t k[11], v[8]; uint4 sh; };
__device__ __forceinline__ void kv_load(KvRegs& q, const __nv_bfloat16* kp, const __nv_bfloat16* vp, const __nv_bfloat16* sp, bool halo) {
#pragma unroll
  for (int i = 0; i < 11; i++) q.k[i] = (i >= 3 || halo) ? ldg1(kp + i * kD) : 0u;
#pragma unroll
  for (int i = 0; i < 8; i++) q.v[i] = ldg1(vp + i * kD);
  q.sh = ldg4(sp);
}
__device__ __forceinline__ void kv_unit(const KvRegs& q, uint32_t oa) {
  const uint32_t w0 = prmt(q.sh.x, q.sh.z, 0x5410), w1 = prmt(q.sh.x, q.sh.z, 0x7632), w2 = prmt(q.sh.y, q.sh.w, 0x5410), w3 = prmt(q.sh.y, q.sh.w, 0x7632);
  uint32_t r[8];
#pragma unroll
  for (int i = 0; i < 8; i++) r[i] = hmul2(hfma2(q.k[i + 3], w0, hfma2(q.k[i + 2], w1, hfma2(q.k[i + 1], w2, hmul2(q.k[i], w3)))), q.v[i]);
  sts128(oa, prmt(r[7], r[6], 0x5410), prmt(r[5], r[4], 0x5410), prmt(r[3], r[2], 0x5410), prmt(r[1], r[0], 0x5410));
  sts128(oa + 2048, prmt(r[7], r[6], 0x7632), prmt(r[5], r[4], 0x7632), prmt(r[3], r[2], 0x7632), prmt(r[1], r[0], 0x7632));
}

__device__ __forceinline__ void gather_colsum(const Params& p, uint32_t sb, int cb, int part, uint32_t tag, int lane) {
  uint4 v[3];
  uint32_t t0 = 0;
#pragma unroll 1
  while (true) {
    bool ok = true;
#pragma unroll
    for (int i = 0; i < 3; i++) {
      v[i] = ld_ll4(&p.scr->colsum[(part ? 0 : 768) + cb * 192 + i * 64 + lane * 2]);
      ok = ok && v[i].y == tag && v[i].w == tag;
    }
    if (__all_sync(0xffffffff, ok)) break;
    spin_guard(t0);
  }
#pragma unroll
  for (int i = 0; i < 3; i++) {
    const uint32_t hi = pack2(__uint_as_float(v[i].x), __uint_as_float(v[i].z)), ca = sb + OFF_CS + (1 - part) * 768 + i * 256 + (lane >> 2) * 32 + (lane & 3) * 4;
    sts32(ca, hi);
    sts32(ca + 16, pack2(__uint_as_float(v[i].x) - bf_lo(hi), __uint_as_float(v[i].z) - bf_hi(hi)));
  }
  __syncwarp();
  if (lane == 0) mbar_arrive(sb + BAR_ST + 8 * part);
}

__device__ __forceinline__ void helper_cta(const Params& p, uint32_t sb, int cb, int warp, int lane) {
  constexpr int NS = 9, ONES = NS * B_SLOT, BF = ONES + 256, BE = BF + 8 * NS;
  if (warp < NS && elect_one()) {
    mbar_init(sb + BF + 8 * warp, 1); mbar_init(sb + BE + 8 * warp, 1);
    fence_async_smem();
    if (warp == 0) { mbar_expect(sb + BF, B_SLOT); tma3d(sb, &p.tmW, 0, 0, 12 + cb * 3, sb + BF); }
  }
  if (warp == 15) { sts32(sb + ONES + lane * 4, 0x3f803f80u); sts32(sb + ONES + 128 + lane * 4, 0x3f803f80u); fence_async_smem(); }
  __syncthreads();
  if (warp == 4) {
    int s = 1, ph = 1;
    uint32_t tp = clock() + HP0;
#pragma unroll 1
    for (int it = 1; it < 20; it++) {
      if (HPD && it >= 10) pace(tp, HPD);
      mbar_wait(sb + BE + 8 * s, ph);
      if (elect_one()) { mbar_expect(sb + BF + 8 * s, B_SLOT); tma3d(sb + s * B_SLOT, &p.tmW, 0, (it < 10 ? it : it - 10) * 64, (it < 10 ? 12 : 0) + cb * 3, sb + BF + 8 * s); }
      if (++s == NS) { s = 0; ph ^= 1; }
    }
  } else if (warp < 4) {
    const uint32_t tag = load_epoch(p, 128 + cb, lane) + 1;
    const uint64_t db = mkdesc(sb + ONES, 128, 128, 0);
    uint2* dst = p.scr->colsum + cb * 192 + warp * 16 + (lane >> 2);
    if ((lane & 3) == 0) {
#pragma unroll 1
      for (int j = 0; j < 12; j++) st_ll2(dst + (j < 6 ? 768 : 0) + ((j % 6) >> 1) * 64 + (j & 1) * 8, 0, 0);
    }
    int s = 0, ph = 0;
#pragma unroll 1
    for (int part = 0; part < 2; part++) {
      float d[12];
#pragma unroll
      for (int i = 0; i < 12; i++) d[i] = 0.f;
#pragma unroll 1
      for (int it = 0; it < 10; it++) {
        mbar_wait(sb + BF + 8 * s, ph);
        const uint64_t da = mkdesc(sb + s * B_SLOT, 8192, 1024, 1);
        WG_FENCE();
#pragma unroll
        for (int j = 0; j < 12; j++) wgmma_colsum(d + 4 * (j % 3), da + (j % 3) * 512 + (j / 3) * 128, db);
        WG_COMMIT();
        WG_WAIT(1);
        mbar_arrive_if(sb + BE + 8 * (s == 0 ? NS - 1 : s - 1), threadIdx.x == 0 && (it | part) != 0);
        if (++s == NS) { s = 0; ph ^= 1; }
      }
      WG_WAIT(0);
      acc_fence<12>(d);
      if ((lane & 3) == 0) {
#pragma unroll
        for (int j = 0; j < 6; j++) st_ll2(dst + (part ? 0 : 768) + (j >> 1) * 64 + (j & 1) * 8, __float_as_uint(d[2 * j]), tag);
      }
      STAMPW(1 + part);
    }
    if (threadIdx.x == 0) st_relaxed(&p.scr->epoch[(128 + cb) * EPS], tag);
  }
}

__global__ void __launch_bounds__(512, 1) fused_kernel(const __grid_constant__ Params p) {
  extern __shared__ __align__(1024) uint8_t smem[];
  const int warp = __shfl_sync(0xffffffff, (int)(threadIdx.x >> 5), 0);
  const int lane = threadIdx.x & 31, tid = threadIdx.x & 127;
  const uint32_t sb = __shfl_sync(0xffffffff, (uint32_t)__cvta_generic_to_shared(smem), 0);
  const uint32_t tstart = clock();
  if (elect_one()) {
    if (warp < 5) asm volatile("prefetch.tensormap [%0];" ::"l"(&p.tmX + warp) : "memory");
    mbar_init(sb + OFF_BAR + 8 * warp, 1); mbar_init(sb + OFF_BAR + 128 + 8 * warp, 1); mbar_init(sb + OFF_BAR + 256 + 8 * warp, 2);
    asm volatile("fence.mbarrier_init.release.cluster;" ::: "memory");
  }
  int b = blockIdx.x;
  if (p.by_smid) asm volatile("mov.u32 %0, %%smid;" : "=r"(b));
  b = __shfl_sync(0xffffffff, b, 0);
  const int tp = b >> 1, t7 = (tp - 32) / 7;
  const int lin = tp < 32 ? ((tp & 7) ? (tp & 7) * 16 : 8) + (tp >> 3) * 2 + (b & 1)
                          : (tp < 60 ? (tp - 31 - t7 * 7) * 16 + 8 + t7 * 2 + (b & 1) : (tp < 62 ? -1 : b - 124));
  const int hcb = b & 3;
  if (lin < 0) { helper_cta(p, sb, hcb, warp, lane); return; }
  const int cb = ((lin >> 4) & 1) * 2 + ((lin >> 1) & 1), rb = (lin >> 5) * 8 + ((lin >> 2) & 3) * 2 + (lin & 1);
  const int zs0 = 4 - (cb & 2);
  const int chb = (cb >> 1) * 320 + rb * 2 + (cb & 1);
  if (warp == 0 && elect_one()) {
    mbar_expect(sb + BAR_AF, A_SLOT);
    tma_rows(sb + OFF_A, &p.tmX, 0, rb, sb + BAR_AF);
    mbar_expect(sb + BAR_BF, B_SLOT);
    tma3d(sb + OFF_B, &p.tmW, 0, 0, 12 + cb * 3, sb + BAR_BF);
  }
  if (warp == 1) STAMP(31);
  if (sb & 1023) die();
  __syncthreads();

  if (warp >= 12) {
    asm volatile("setmaxnreg.dec.sync.aligned.u32 32;");
    uint32_t bias2 = 0;
    if (warp == 15) bias2 = ldg1(p.bsp + (lane >> 3) * 512 + rb * 16 + (lane & 7) * 2);
    const uint32_t epoch = load_epoch(p, lin, lane);
    if (warp == 12) {
#pragma unroll 1
      for (int i = 1; i < NA; i++) {
        if (elect_one()) {
          mbar_expect(sb + BAR_AF + 8 * i, A_SLOT);
          tma_rows(sb + OFF_A + i * A_SLOT, &p.tmX, i * 64, rb, sb + BAR_AF + 8 * i);
          if (i < NB) { mbar_expect(sb + BAR_BF + 8 * i, B_SLOT); tma3d(sb + OFF_B + i * B_SLOT, &p.tmW, 0, i * 64, 12 + cb * 3, sb + BAR_BF + 8 * i); }
        }
      }
      STAMP(32);
      uint32_t kvt;
      {
        const int tb = rb * 2 + (cb & 1);
        kvt = __shfl_sync(0xffffffff, (ld_relaxed(p.scr->cnt + (CNT_KV + (cb >> 1)) * CSP) & ~63u) + 64, 0);
        {
          uint32_t tp = tstart;
          pace(tp, KV_T0);
          mbar_arrive_if(sb + BAR_KV + 8, lane == 0);
        }
        if (ST_YIELD) mbar_wait2(sb + BAR_XS, 0, sb + BAR_ST, 0);
#pragma unroll 1
        for (int u = 0; u < 5; u++) {
          mbar_wait(sb + BAR_KU + 8 * u, 0);
          fence_async_smem();
          if (elect_one()) {
            asm volatile("cp.async.bulk.tensor.3d.global.shared::cta.bulk_group [%0, {%2, %3, %4}], [%1];\ncp.async.bulk.commit_group;" ::"l"(&p.tmKV),
                         "r"(sb + OFF_CV + CV_SZ + (u < 3 ? u : u - 3) * 4096), "r"((63 - tb) * 16), "r"((cb >> 1) * 160 + u * 32), "r"(0) : "memory");
            if (u == 1 || u == 4) asm volatile("cp.async.bulk.wait_group 0;" ::: "memory");
            if (u == 1) { mbar_arrive(sb + BAR_KU); red_release(p.scr->cnt + (CNT_KV + (cb >> 1)) * CSP); }
          }
          __syncwarp();
          if (u == 1) {
            STAMP(35);
            if (PFT) { const char* q = (const char*)p.ssmk + chb * 4096 + lane * 128; prefetch_l2(q); prefetch_l2(q + 64 * 4096); }
          }
        }
        zero_pads(sb + OFF_CV + CV_SZ, lane);
        if (elect_one()) { mbar_arrive(sb + BAR_KU + 8); red_release(p.scr->cnt + (CNT_KV + 2 + (cb >> 1)) * CSP); }
        STAMP(30);
        if (lane < 24) {
          const char* r = (const char*)p.wout + (rb * 24 + lane) * (kD * 2) + (cb >> 1) * 640 + (cb & 1) * 384;
          prefetch_l2(r); prefetch_l2(r + 128); prefetch_l2(r + 256 - (cb & 1) * 384);
        }
      }
      poll_counter(p.scr->cnt + (CNT_KV + 2 + (cb >> 1)) * CSP, kvt);
      if (elect_one()) mbar_arrive(sb + BAR_KV);
      STAMP(34);
      {
        const char* q = (const char*)p.wsp + (cb * 512 + rb * 16 + (lane >> 1)) * (kS * 2) + (lane & 1) * 128;
        uint32_t tp = clock();
#pragma unroll 1
        for (int i = LEAD / 2; i < WSP_N; i++) {
          prefetch_l2(q + i * 256);
          pace(tp, WSP_D);
        }
      }
      const uint32_t tag = epoch + 1;
      if (HPC) {
        bar_sync(NB_Z2, 160);
        if (elect_one()) bulk_s2g(p.scr->h + (size_t)(rb * 12 + cb * 3) * A_SLOT, sb + OFF_A + 5 * A_SLOT, HPC * A_SLOT);
      }
      mbar_wait(sb + BAR_G2, 0);
      if (elect_one()) {
        bulk_s2g(p.scr->h + (size_t)(rb * 12 + cb * 3 + HPC) * A_SLOT, sb + OFF_A + (5 + HPC) * A_SLOT, (3 - HPC) * A_SLOT);
        asm volatile("cp.async.bulk.commit_group;\ncp.async.bulk.wait_group 0;" ::: "memory");
        red_release(&p.scr->hcnt[(rb >> HGRP) * 32]);
      }
      __syncwarp();
      STAMP(20);
      mbar_wait(sb + BAR_AE + 56, 0);
      STAMP(39);
      poll_counter(&p.scr->hcnt[(rb >> HGRP) * 32], tag * (4 << HGRP));
      STAMP(37);
      if (elect_one()) {
        uint32_t tp = clock();
#pragma unroll 1
        for (int it = 3; it < 12; it++) {
          if (HPACE && it > 3) { tp += HPACE; while ((int32_t)((uint32_t)clock() - tp) < 0) {} }
          bulk_g2s(sb + OFF_A + ((it + 5) % 9) * A_SLOT, p.scr->h + (size_t)(rb * 12 + g3_block(cb, it)) * A_SLOT, A_SLOT, sb + BAR_AF + 8 * ((it + 5) % 9));
        }
      }
      STAMP(21);
    } else if (warp == 13) {
      int s = 0, ph = 0;
#pragma unroll 1
      for (int it = NB; it < 20; it++) {
        mbar_wait(sb + BAR_BE + 8 * s, ph);
        if (elect_one()) { mbar_expect(sb + BAR_BF + 8 * s, B_SLOT); tma3d(sb + OFF_B + s * B_SLOT, &p.tmW, 0, (it < 10 ? it : (it + zs0) % 10) * 64, (it < 10 ? 12 : 0) + cb * 3, sb + BAR_BF + 8 * s); }
        STAMP2(32 + it);
        if (++s == NB) { s = 0; ph ^= 1; }
      }
      mbar_wait(sb + BAR_XC, 0);
#pragma unroll 1
      for (int i = 0; i < LEAD; i++) {
        mbar_wait(sb + BAR_AE + 8 * i, 0);
        if (elect_one()) { mbar_expect(sb + BAR_AF + 8 * i, A_SLOT); tma_rows(sb + OFF_A + i * A_SLOT, &p.tmWsp, i * 64, rb, sb + BAR_AF + 8 * i); }
      }
      poll_counter(p.scr->zcnt + (cb >> ZSH) * 32, (epoch + 1) * (32 << ZSH));
      STAMP(22);
      int sa = LEAD, pa = 0, ia = LEAD;
#pragma unroll 1
      for (int it = 0; it < 32; it++) {
        if (it == ZP_AT) mbar_wait(sb + BAR_ZP, 0);
        if (it == 16) mbar_wait(sb + BAR_Z1, 1);
        mbar_wait2(sb + BAR_BE + 8 * s, ph, sb + BAR_AE + 8 * sa, pa);
        if (elect_one()) {
          mbar_expect(sb + BAR_BF + 8 * s, B_SLOT);
          bulk_g2s(sb + OFF_B + s * B_SLOT, p.scr->z2 + (size_t)(cb * 32 + it) * B_SLOT, B_SLOT, sb + BAR_BF + 8 * s);
        }
#pragma unroll 1
        for (int j = (it < RAMP ? 0 : (it == 4 ? 1 + RAMP : 1)); j > 0 && ia < 32; j--, ia++) {
          if (it == 4) mbar_wait(sb + BAR_AE + 8 * sa, pa);
          if (elect_one()) { mbar_expect(sb + BAR_AF + 8 * sa, A_SLOT); tma_rows(sb + OFF_A + sa * A_SLOT, &p.tmWsp, ia * 64, rb, sb + BAR_AF + 8 * sa); }
          if (++sa == NA2) { sa = 0; pa ^= 1; }
        }
        STAMP2(52 + it);
        if (++s == NB) { s = 0; ph ^= 1; }
      }
      mbar_wait(sb + BAR_WO, 0);
#pragma unroll 1
      for (int it = 0; it < 12; it++) {
        if (it < 6) mbar_wait(sb + BAR_BE + 8 * ((0x110443 >> (4 * it)) & 7), it < 3 ? 1 : 0);
        else mbar_wait(sb + BAR_BE + 8 * s, ph);
        if (elect_one()) {
          mbar_expect(sb + BAR_BF + 8 * s, 20480);
          bulk_g2s(sb + OFF_B + (s == 5 ? 0 : s + 1) * 20480, p.scr->wo + (size_t)(cb * 12 + g3_block(cb, it)) * 20480, 20480, sb + BAR_BF + 8 * s);
        }
        STAMP2(84 + it);
        if (++s == 6) { s = 0; ph ^= 1; }
      }
    } else if (warp == 14) {
      const uint32_t tag = epoch + 1;
      mbar_wait(sb + BAR_AF + 8 * (NA - 1), 0);
      gather_colsum(p, sb, cb, 0, tag, lane);
      STAMP(27);
      bar_sync(NB_Z, 160);
      if (elect_one()) {
        z_store(p, sb + OFF_A + zs0 * A_SLOT, rb, cb, 0);
        STAMP(7);
        red_release(p.scr->zcnt + (cb >> ZSH) * 32);
      }
      STAMP(25);
      bar_sync(NB_Z2, 96);
      if (elect_one()) {
        z_store(p, sb + OFF_A + zs0 * A_SLOT, rb, cb, 1);
        mbar_arrive(sb + BAR_ZP);
        red_release(p.scr->cnt + (CNT_Z1 + (cb >> 1)) * CSP);
      }
      STAMP(28);
      mbar_wait(sb + BAR_AE + 72, 0);
      conv_service(p, sb, 0, chb + 64, true);
      bar_sync(NB_WO, 160);
      bar_sync(NB_CD, 64);
      if (elect_one()) { red_release(p.scr->cnt + (CNT_WO + cb) * CSP); red_relaxed(p.scr->cnt + (CNT_Y + (cb >> 1)) * CSP); }
      STAMP(49);
      poll_counter(p.scr->cnt + (CNT_WO + cb) * CSP, tag * 32);
      if (elect_one()) mbar_arrive(sb + BAR_WO);
      STAMP(46);
      held_service(p, sb, 0, chb + 192, rb, cb, tag, lane);
    } else {
      const uint32_t tag = epoch + 1;
      sts32(sb + OFF_BIAS + lane * 4, bias2);
      if (lane < 2) sts32(sb + OFF_TAG + lane * 4, lane ? 0 : tag);
      fence_async_smem();
      uint32_t t0 = 0;
      mbar_wait(sb + BAR_AF + 8 * (NA - 1), 0);
#pragma unroll 1
      while (true) {
        const uint4 u = ld_ll4(&p.scr->xstat[rb * 64 + lane]), v = ld_ll4(&p.scr->xstat[rb * 64 + 32 + lane]);
        sts64f(sb + OFF_XS + lane * 8, __uint_as_float(u.x), __uint_as_float(u.z));
        sts64f(sb + OFF_XS + 256 + lane * 8, __uint_as_float(v.x), __uint_as_float(v.z));
        if (__all_sync(0xffffffff, u.y == tag && u.w == tag && v.y == tag && v.w == tag)) break;
        spin_guard(t0);
      }
      STAMP(26);
      __syncwarp();
      if (lane == 0) mbar_arrive(sb + BAR_XS);
      { uint32_t tp = tstart; pace(tp, CS1_T); gather_colsum(p, sb, cb, 1, tag, lane); STAMP(38); }
      mbar_wait(sb + BAR_KU, 1);
      poll_counter(p.scr->cnt + (CNT_KV + (cb >> 1)) * CSP, tag * 64);
      if (elect_one()) load_convx(p, sb + OFF_CV, sb + BAR_XF + 8, chb);
      mbar_wait(sb + BAR_KU + 8, 1);
      if (elect_one()) load_convx(p, sb + OFF_CV + CV_SZ, sb + BAR_XF, chb + 64);
      STAMP(48);
      mbar_wait(sb + BAR_AE + 72, 0);
#pragma unroll 1
      for (int i = 0; i < 2; i++) {
        conv_service(p, sb, 1, chb + i * 128, i == 0);
        if (i == 0) {
          poll_counter(p.scr->cnt + (CNT_Z1 + (cb >> 1)) * CSP, tag * 64);
          if (elect_one()) mbar_arrive(sb + BAR_Z1);
          STAMP(24);
        }
      }
      bar_arrive(NB_CD, 64);
      mbar_wait(sb + BAR_WO, 0);
      poll_counter(p.scr->cnt + (CNT_Y + (cb >> 1)) * CSP, tag * 64);
      STAMP(47);
      if (elect_one()) mbar_arrive(sb + BAR_YT);
      held_service(p, sb, 1, chb + 256, rb, cb, tag, lane);
      if (lane == 0) st_relaxed(&p.scr->epoch[lin * EPS], tag);
      STAMP(23);
    }
  } else {
    if (warp == 7) STAMP(36);
    const int wg = warp >> 2, w = warp & 3, g = lane >> 2, t = lane & 3;
    Taps k;
    uint32_t xw[2][10];
    if (wg == 2) {
      asm volatile("setmaxnreg.inc.sync.aligned.u32 160;");
      const int tb = rb * 2 + (cb & 1), c0 = (cb >> 1) * 320;
      const uint32_t cv = sb + OFF_CV + CV_SZ;
      if (w == 0) zero_pads(sb + OFF_CV, lane);
      mbar_wait(sb + BAR_KV + 8, 0);
      const int t0 = tb * 32 + w * 8;
      const __nv_bfloat16* kp = p.k + (size_t)(t0 - 3) * kD + c0 + lane * 2;
      const __nv_bfloat16* vp = p.v + (size_t)t0 * kD + c0 + lane * 2;
      const __nv_bfloat16* sp = p.shift + (c0 + lane * 2) * 4;
      const uint32_t oa = cv + ((3 - w) & 1) * 1024 + lane * 32 + ((((3 - w) >> 1) ^ (lane >> 2)) & 1) * 16;
#pragma unroll 1
      for (int r = 0; r < 2; r++) {
        KvRegs n0, n1, n2;
        STAMPW(r ? 51 : 50);
        kv_load(n0, kp + r * 128, vp + r * 128, sp + r * 512, t0 > 0);
        kv_load(n1, kp + r * 128 + 64, vp + r * 128 + 64, sp + r * 512 + 256, t0 > 0);
        if (r) kv_load(n2, kp + 256, vp + 256, sp + 1024, t0 > 0);
        kv_unit(n0, oa + r * 8192);
        bar_sync(NB_WGC, 128);
        mbar_arrive_if(sb + BAR_KU + 16 * r, tid == 0);
        if (r) mbar_wait(sb + BAR_KU, 1);
        kv_unit(n1, oa + (r ? 0 : 4096));
        bar_sync(NB_WGC, 128);
        mbar_arrive_if(sb + BAR_KU + 16 * r + 8, tid == 0);
        if (r) {
          kv_unit(n2, oa + 4096);
          bar_sync(NB_WGC, 128);
          mbar_arrive_if(sb + BAR_KU + 32, tid == 0);
        } else {
          mbar_wait(sb + BAR_AF + 8 * ((cb >> 1) * 5 + 1), 0);
          mbar_wait2(sb + BAR_AF + 8 * ((cb >> 1) * 5 + 2), 0, sb + BAR_AF + 8 * ((cb >> 1) * 5 + 4), 0);
          final_load_x(xw, sb + OFF_A, cb, 1, w, lane);
          fence_async_smem();
          bar_sync(NB_WGC, 128);
          mbar_arrive_if(sb + BAR_XC, tid == 0);
        }
      }
      STAMPW(13);
      load_taps(k, p, chb, tid);
    } else {
      float d[96];
      if (wg == 0) st_ll2(&p.scr->zstat[(rb * 256 + cb * 64 + w * 16 + g + (t >> 1) * 8) * 2 + (t & 1)], 0, 0);
      else if ((tid & 7) == 0) st_ll4(&p.scr->xstat[rb * 64 + cb * 16 + (tid >> 3)], 0, 0, 0, 0);
      {
        #pragma unroll
        for (int i = 0; i < 96; i++) d[i] = 0.f;
        {
          if (__builtin_expect(wg == 1, 0)) {
            const int tid = tid_now();
            const uint32_t epoch = load_epoch(p, lin, lane);
            float s = 0.f, q = 0.f;
#pragma unroll 1
            for (int i = 0; i < 10; i++) {
              mbar_wait(sb + BAR_AF + 8 * i, 0);
              const uint4 x4 = lds128(sb + OFF_A + i * A_SLOT + cb * 2048 + tid * 16);
              const uint32_t u[4] = {x4.x, x4.y, x4.z, x4.w};
#pragma unroll
              for (int e = 0; e < 4; e++) { const float a = bf_lo(u[e]), c = bf_hi(u[e]); s += a + c; q = fmaf(a, a, q); q = fmaf(c, c, q); }
            }
#pragma unroll
            for (int o = 1; o <= 4; o <<= 1) { s += __shfl_xor_sync(0xffffffff, s, o); q += __shfl_xor_sync(0xffffffff, q, o); }
            const float m = s * (1.f / kD);
            const float r = rsqrtf(fmaxf(fmaf(-m, m, q * (1.f / kD)), 0.f) + 1e-5f);
            if ((tid & 7) == 0) st_ll4(&p.scr->xstat[rb * 64 + cb * 16 + (tid >> 3)], __float_as_uint(m), epoch + 1, __float_as_uint(r), epoch + 1);
            STAMPW(12);
            bar_sync(NB_G1, 256);
          }
          gemm_loop<192, true, 0, D1>(d, sb, 10, wg ? zs0 : 0, 0, 0, 0, wg, 2, tid_now(), [&]() { if (G1_AT == 0 && wg == 0) bar_arrive(NB_G1, 256); }, [](int) {});
          asm volatile("setmaxnreg.inc.sync.aligned.u32 160;");
          STAMPW(wg ? 14 : 1);
          if (wg == 0) ZS(0);
          mbar_wait2(sb + BAR_XS, 0, sb + BAR_ST + 8 * wg, 0);
          if (wg == 0) ZS(1);
        }
        const int t1 = tid_now();
        const uint32_t xa1 = sb + OFF_XS + (w * 16 + ((t1 & 31) >> 2)) * 8;
        const float2 s0 = lds64f(xa1), s1 = lds64f(xa1 + 64);
        uint32_t z[48];
        float st[4];
        fence_async_smem();
        fold_mean(d, sb + OFF_CS + (1 - wg) * 768, s0.x, s1.x, t1 & 3);
        if (G1_AT == 1 && wg == 0) bar_arrive(NB_G1, 256);
        WG_WAIT(0);
        acc_fence<96>(d);
        if (wg == 0) ZS(2);
        gelu_tile(d, z, st, s0.y, s1.y);
        const int tid = tid_now(), lane = tid & 31, g = lane >> 2, t = lane & 3;
        if (wg == 1) {
          uint32_t bra, brb;
          asm volatile("ld.shared.u16 %0, [%1];" : "=r"(bra) : "r"(sb + OFF_BIAS + (w * 16 + g) * 2));
          asm volatile("ld.shared.u16 %0, [%1+16];" : "=r"(brb) : "r"(sb + OFF_BIAS + (w * 16 + g) * 2));
#pragma unroll
          for (int j = 0; j < 96; j++) d[j] = bf_lo((j & 2) ? brb : bra);
          STAMPW(15);
          gemm_loop<192, true, 1, D2>(d, sb, 32, 0, 1, 20, 0, 2, 2, tid, [&]() { if (HOLD_AT < 32) mbar_arrive_if(sb + BAR_GO, tid == 0); if (GO1 == 1) mbar_arrive_if(sb + BAR_GO1, tid == 0); }, [](int) {});
          if (GO1 == 2) mbar_arrive_if(sb + BAR_GO1, tid == 0);
          if (HOLD_AT == 32) mbar_arrive_if(sb + BAR_GO, tid == 0);
          STAMPW(16);
          const int t2 = tid_now(), l2 = t2 & 31;
          const uint32_t ha = sb + OFF_A + 5 * A_SLOT + (l2 >> 4) * 1024 + (2 * w + ((l2 >> 3) & 1)) * 128 + (l2 & 7) * 16;
#pragma unroll
          for (int j = 0; j < 24; j += 2) {
#pragma unroll
            for (int e = 0; e < 4; e++) z[2 * j + e] = hmul2(z[2 * j + e], pack2(d[4 * j + 2 * e], d[4 * j + 2 * e + 1]));
            stsm4(ha + j * 1024, z[2 * j], z[2 * j + 1], z[2 * j + 2], z[2 * j + 3]);
            if (HPC && j == HPC * 8 - 2) {
              fence_async_smem();
              bar_arrive(NB_Z2, 160);
            }
          }
          fence_async_smem();
          bar_sync(NB_WGB, 128);
          mbar_arrive_if(sb + BAR_AF + 8 * (t2 == 3 ? (BAR_G2 - BAR_AF) / 8 : (t2 == 4 ? (BAR_GO - BAR_AF) / 8 : 5 + t2)), t2 < (HOLD_AT == 33 ? 5 : 4));
          STAMPW(17);
          {
            float e[80];
            gemm_loop<160, false, 2, DB>(e, sb, 12, 5, 0, 2, 0, 2, 2, tid_now(), []() {}, [](int) {});
            STAMPW(10);
            const int t3 = tid_now();
#pragma unroll
            for (int j = 0; j < 10; j++) {
              sts128(sb + OFF_A + j * 2048 + t3 * 16, pack2(e[8 * j], e[8 * j + 1]), pack2(e[8 * j + 2], e[8 * j + 3]), pack2(e[8 * j + 4], e[8 * j + 5]),
                     pack2(e[8 * j + 6], e[8 * j + 7]));
              if (j == 4) bar_arrive(NB_WO, 256);
            }
            bar_arrive(NB_Z, 256);
            STAMPW(45);
          }
          return;
        }
        ZS(3);
        const bool hi = t & 2;
        float a0 = (hi ? st[2] : st[0]) + __shfl_xor_sync(0xffffffff, hi ? st[0] : st[2], 2);
        float a1 = (hi ? st[3] : st[1]) + __shfl_xor_sync(0xffffffff, hi ? st[1] : st[3], 2);
        a0 = ((t & 1) ? a1 : a0) + __shfl_xor_sync(0xffffffff, (t & 1) ? a0 : a1, 1);
        const uint32_t tag = lds32<0>(sb + OFF_TAG);
        uint2* zs = p.scr->zstat + (rb * 256 + w * 16 + g + (t >> 1) * 8) * 2 + (t & 1);
        st_ll2(zs + cb * 128, __float_as_uint(a0), tag);
        STAMPW(2); ZS(4);
        uint2 u[4];
#pragma unroll
        for (int i = 0; i < 4; i++) u[i] = ld_ll2(zs + i * 128);
        const uint32_t keep = (cb & 2) ? 13 << 5 : 13;
        mbar_arrive_if(sb + BAR_AE + 8 * tid, tid < NA && !((keep >> tid) & 1));
        const uint32_t za = sb + OFF_A + zs0 * A_SLOT + (2 * w + ((lane >> 3) & 1)) * 3072 + (lane >> 4) * 128 + (lane & 7) * 16;
        const float ca = 0.5f * (hi ? s1.y : s0.y), inv = 1.f / 768.f;
        mbar_wait2(sb + BAR_AE + 8 * (zs0 + 2), 0, sb + BAR_XC, 0);
        ZS(6);
        uint32_t t0 = 0;
#pragma unroll 1
        while (!__all_sync(0xffffffff, u[0].y == tag && u[1].y == tag && u[2].y == tag && u[3].y == tag)) {
          spin_guard(t0);
#pragma unroll
          for (int i = 0; i < 4; i++) u[i] = ld_ll2(zs + i * 128);
        }
        STAMPW(3); ZS(7);
        a0 = ((__uint_as_float(u[0].x) + __uint_as_float(u[1].x)) + (__uint_as_float(u[2].x) + __uint_as_float(u[3].x))) * inv;
        a1 = __shfl_xor_sync(0xffffffff, a0, 1);
        const float m = (t & 1) ? a1 : a0, q = (t & 1) ? a0 : a1;
        const float r = bf_lo(pack2(ca * rsqrtf(fmaf(fmaxf(fmaf(-m, m, q), 0.f), ca * ca, 1e-5f)), 0.f));
        const uint32_t rn = pack2(r, -m * r), ro = __shfl_xor_sync(0xffffffff, rn, 2);
        const uint32_t ra2 = prmt(hi ? ro : rn, 0, 0x1010), n2a = prmt(hi ? ro : rn, 0, 0x3232), rb2 = prmt(hi ? rn : ro, 0, 0x1010), n2b = prmt(hi ? rn : ro, 0, 0x3232);
        if (w >= 2) bar_sync(NB_Z, 160);
#pragma unroll
        for (int j = 0; j < 24; j += 2)
          stsm4(za + j * 128, hfma2(z[2 * j], ra2, n2a), hfma2(z[2 * j + 1], rb2, n2b), hfma2(z[2 * j + 2], ra2, n2a), hfma2(z[2 * j + 3], rb2, n2b));
        ZS(8);
        fence_async_smem();
        ZS(9);
        if (w < 2) bar_arrive(NB_Z, 160);
        else bar_arrive(NB_Z2, 96);
        final_load_x(xw, sb + OFF_A, cb, 0, w, lane);
        fence_async_smem();
        bar_sync(NB_WGA, 128);
        mbar_arrive_if(sb + BAR_AE + 8 * tid, tid < NA && ((keep >> tid) & 1));
      }
      {
        const uint32_t zero = lds32<0>(sb + OFF_TAG + 4);
#pragma unroll
        for (int i = 0; i < 20; i++) xw[i / 10][i % 10] |= zero;
      }
      load_taps(k, p, chb + 64, tid_now());
      STAMPW(4);
    }
    const int h = wg >> 1;
    {
    const int tid = tid_now(), lane = tid & 31;
    conv_worker(p, k, sb + OFF_CV + (1 - h) * CV_SZ, sb + OFF_A + 9 * A_SLOT + h * 4096, sb + BAR_XF + 8 * h, NB_WGA + h,
                chb + (h ? 0 : 64), 2 + h, sb + BAR_GO, w, lane, tid, h ? 40 : 5, rb, cb);
    {
      const int t3 = tid_now(), l3 = t3 & 31;
      const uint32_t xs_addr = sb + OFF_XS + (w * 16 + (l3 >> 2)) * 8;
      const float2 s0 = lds64f(xs_addr), s1 = lds64f(xs_addr + 64);
      const uint32_t ya = sb + y_tile(h) + ((l3 >> 4) * 8 + (l3 & 7)) * 128 + (((2 * w + ((l3 >> 3) & 1)) ^ (l3 & 7) ^ (rb & 7)) << 4);
      uint32_t sw[2][10];
      mbar_wait(sb + BAR_XF + 8 * h, h);
      final_s_early(sw, xw, ya, s0, s1);
      uint32_t ph = 1, t0 = 0, y[8];
#pragma unroll 1
      while (true) {
        mbar_wait(sb + BAR_YL + 16 * h, ph);
        if (bar_all(NB_WGA + h, 128, final_late(y, ya))) break;
        spin_guard(t0);
        ph ^= 1;
        if (t3 == 0) load_late_y(p, sb, h, rb, cb, lds32<0>(sb + OFF_TAG) & 1);
      }
#pragma unroll
      for (int e = 0; e < 8; e++) sw[e & 1][4 + (e >> 1)] = hmul2(sw[e & 1][4 + (e >> 1)], ~y[e]);
      __nv_bfloat16* o0 = p.out + (size_t)(w * 512 + rb * 16 + (l3 >> 2)) * kD + seg_col(cb, h);
      STAMPW(h ? 44 : 9);
      bar_sync(h ? NB_Z : NB_WO, 256);
      float d[40];
#pragma unroll
      for (int j = 0; j < 5; j++) {
        const uint4 v = lds128(sb + OFF_A + (h * 5 + j) * 2048 + t3 * 16);
        d[8 * j] = bf_lo(v.x); d[8 * j + 1] = bf_hi(v.x); d[8 * j + 2] = bf_lo(v.y); d[8 * j + 3] = bf_hi(v.y);
        d[8 * j + 4] = bf_lo(v.z); d[8 * j + 5] = bf_hi(v.z); d[8 * j + 6] = bf_lo(v.w); d[8 * j + 7] = bf_hi(v.w);
      }
      final_out(d, xw, sw, s0.y, s1.y, o0, h, l3 & 3);
    }
    }
  }
}

typedef CUresult (*EncodeFn)(CUtensorMap*, CUtensorMapDataType, cuuint32_t, void*, const cuuint64_t*, const cuuint64_t*, const cuuint32_t*,
                             const cuuint32_t*, CUtensorMapInterleave, CUtensorMapSwizzle, CUtensorMapL2promotion, CUtensorMapFloatOOBfill);

void encode(EncodeFn fn, CUtensorMap* m, const void* ptr, int rank, const cuuint64_t* dims, const cuuint64_t* strides, const cuuint32_t* box,
            CUtensorMapSwizzle swz = CU_TENSOR_MAP_SWIZZLE_128B) {
  const cuuint32_t es[3] = {1, 1, 1};
  fn(m, CU_TENSOR_MAP_DATA_TYPE_BFLOAT16, rank, const_cast<void*>(ptr), dims, strides, box, es, CU_TENSOR_MAP_INTERLEAVE_NONE,
     swz, CU_TENSOR_MAP_L2_PROMOTION_L2_128B, CU_TENSOR_MAP_FLOAT_OOB_FILL_NONE);
}

}

extern "C" void kernel_launch(void* const* d_in, const int* in_sizes, int n_in, void* d_out, int out_size) {
  (void)in_sizes; (void)n_in; (void)out_size;
  static EncodeFn enc = nullptr;
  static Scratch* scr = nullptr;
  static int sms = 0;
  if (!enc) {
    void* fn = nullptr;
    cudaDriverEntryPointQueryResult qr;
    cudaGetDriverEntryPoint("cuTensorMapEncodeTiled", &fn, cudaEnableDefault, &qr);
    enc = (EncodeFn)fn;
    cudaFuncSetAttribute(fused_kernel, cudaFuncAttributeMaxDynamicSharedMemorySize, SMEM_BYTES);
    cudaGetSymbolAddress((void**)&scr, g_scr);
    int dev = 0;
    cudaGetDevice(&dev);
    cudaDeviceGetAttribute(&sms, cudaDevAttrMultiProcessorCount, dev);
  }
  Params p;
  p.scr = scr;
  p.by_smid = sms == 132;
  p.k = (const __nv_bfloat16*)d_in[1];
  p.v = (const __nv_bfloat16*)d_in[2];
  p.shift = (const __nv_bfloat16*)d_in[3];
  p.ssmk = (const __nv_bfloat16*)d_in[4];
  p.ssmD = (const __nv_bfloat16*)d_in[5];
  p.wsp = (const __nv_bfloat16*)d_in[8];
  p.bsp = (const __nv_bfloat16*)d_in[9];
  p.wout = (const __nv_bfloat16*)d_in[10];
  p.out = (__nv_bfloat16*)d_out;
  for (int i = 0; i < 2; i++) {
    const cuuint64_t n = i ? kS : kD, dims[3] = {n, 512, 4}, st[2] = {n * 2, n * 1024};
    const cuuint32_t box[3] = {64, 16, 4};
    encode(enc, i ? &p.tmWsp : &p.tmX, d_in[i ? 8 : 0], 3, dims, st, box);
  }
  {
    const cuuint64_t dims[3] = {64, kD, kF / 64}, st[2] = {kF * 2, 128};
    const cuuint32_t box[3] = {64, 64, 3};
    encode(enc, &p.tmW, d_in[7], 3, dims, st, box);
  }
  {
    const cuuint64_t dims[2] = {kS, 896}, st[1] = {kS * 2};
    const cuuint32_t box[2] = {64, 16};
    encode(enc, &p.tmY, scr->y, 2, dims, st, box);
  }
  {
    const cuuint64_t dims[3] = {1024, kD / 2, 4}, st[2] = {8192, 2048};
    const cuuint32_t box[3] = {16, 32, 4};
    encode(enc, &p.tmKV, scr->kvx, 3, dims, st, box, CU_TENSOR_MAP_SWIZZLE_32B);
  }
  fused_kernel<<<132, 512, SMEM_BYTES, cudaStreamPerThread>>>(p);
}
```

```cpp
#include <cuda_runtime.h>
#include <cuda.h>
#include <cuda_bf16.h>
#include <stdint.h>

template <int N> struct WG;
template <> struct WG<16> {
  static __device__ __forceinline__ void rs(float* d, const uint32_t* a, uint64_t db) {
    asm volatile("{\n.reg .pred p;\nsetp.ne.b32 p, 1, 0;\nwgmma.mma_async.sync.aligned.m64n16k16.f32.bf16.bf16 {"
      "%0, %1, %2, %3, %4, %5, %6, %7"
      "}, {%8, %9, %10, %11}, %12, p, 1, 1, 0;\n}\n"
      :
      "+f"(d[0]), "+f"(d[1]), "+f"(d[2]), "+f"(d[3]), "+f"(d[4]), "+f"(d[5]), "+f"(d[6]), "+f"(d[7])
      : "r"(a[0]), "r"(a[1]), "r"(a[2]), "r"(a[3]), "l"(db));
  }
};
template <> struct WG<32> {
  static __device__ __forceinline__ void rs(float* d, const uint32_t* a, uint64_t db) {
    asm volatile("{\n.reg .pred p;\nsetp.ne.b32 p, 1, 0;\nwgmma.mma_async.sync.aligned.m64n32k16.f32.bf16.bf16 {"
      "%0, %1, %2, %3, %4, %5, %6, %7, %8, %9, %10, %11, %12, %13, %14, %15"
      "}, {%16, %17, %18, %19}, %20, p, 1, 1, 0;\n}\n"
      :
      "+f"(d[0]), "+f"(d[1]), "+f"(d[2]), "+f"(d[3]), "+f"(d[4]), "+f"(d[5]), "+f"(d[6]), "+f"(d[7]),
      "+f"(d[8]), "+f"(d[9]), "+f"(d[10]), "+f"(d[11]), "+f"(d[12]), "+f"(d[13]), "+f"(d[14]), "+f"(d[15])
      : "r"(a[0]), "r"(a[1]), "r"(a[2]), "r"(a[3]), "l"(db));
  }
};
template <> struct WG<48> {
  static __device__ __forceinline__ void rs(float* d, const uint32_t* a, uint64_t db) {
    asm volatile("{\n.reg .pred p;\nsetp.ne.b32 p, 1, 0;\nwgmma.mma_async.sync.aligned.m64n48k16.f32.bf16.bf16 {"
      "%0, %1, %2, %3, %4, %5, %6, %7, %8, %9, %10, %11, %12, %13, %14, %15, "
      "%16, %17, %18, %19, %20, %21, %22, %23"
      "}, {%24, %25, %26, %27}, %28, p, 1, 1, 0;\n}\n"
      :
      "+f"(d[0]), "+f"(d[1]), "+f"(d[2]), "+f"(d[3]), "+f"(d[4]), "+f"(d[5]), "+f"(d[6]), "+f"(d[7]),
      "+f"(d[8]), "+f"(d[9]), "+f"(d[10]), "+f"(d[11]), "+f"(d[12]), "+f"(d[13]), "+f"(d[14]), "+f"(d[15]),
      "+f"(d[16]), "+f"(d[17]), "+f"(d[18]), "+f"(d[19]), "+f"(d[20]), "+f"(d[21]), "+f"(d[22]), "+f"(d[23])
      : "r"(a[0]), "r"(a[1]), "r"(a[2]), "r"(a[3]), "l"(db));
  }
};
template <> struct WG<64> {
  static __device__ __forceinline__ void rs(float* d, const uint32_t* a, uint64_t db) {
    asm volatile("{\n.reg .pred p;\nsetp.ne.b32 p, 1, 0;\nwgmma.mma_async.sync.aligned.m64n64k16.f32.bf16.bf16 {"
      "%0, %1, %2, %3, %4, %5, %6, %7, %8, %9, %10, %11, %12, %13, %14, %15, "
      "%16, %17, %18, %19, %20, %21, %22, %23, %24, %25, %26, %27, %28, %29, %30, %31"
      "}, {%32, %33, %34, %35}, %36, p, 1, 1, 0;\n}\n"
      :
      "+f"(d[0]), "+f"(d[1]), "+f"(d[2]), "+f"(d[3]), "+f"(d[4]), "+f"(d[5]), "+f"(d[6]), "+f"(d[7]),
      "+f"(d[8]), "+f"(d[9]), "+f"(d[10]), "+f"(d[11]), "+f"(d[12]), "+f"(d[13]), "+f"(d[14]), "+f"(d[15]),
      "+f"(d[16]), "+f"(d[17]), "+f"(d[18]), "+f"(d[19]), "+f"(d[20]), "+f"(d[21]), "+f"(d[22]), "+f"(d[23]),
      "+f"(d[24]), "+f"(d[25]), "+f"(d[26]), "+f"(d[27]), "+f"(d[28]), "+f"(d[29]), "+f"(d[30]), "+f"(d[31])
      : "r"(a[0]), "r"(a[1]), "r"(a[2]), "r"(a[3]), "l"(db));
  }
};
template <> struct WG<80> {
  static __device__ __forceinline__ void rs(float* d, const uint32_t* a, uint64_t db) {
    asm volatile("{\n.reg .pred p;\nsetp.ne.b32 p, 1, 0;\nwgmma.mma_async.sync.aligned.m64n80k16.f32.bf16.bf16 {"
      "%0, %1, %2, %3, %4, %5, %6, %7, %8, %9, %10, %11, %12, %13, %14, %15, "
      "%16, %17, %18, %19, %20, %21, %22, %23, %24, %25, %26, %27, %28, %29, %30, %31, "
      "%32, %33, %34, %35, %36, %37, %38, %39"
      "}, {%40, %41, %42, %43}, %44, p, 1, 1, 0;\n}\n"
      :
      "+f"(d[0]), "+f"(d[1]), "+f"(d[2]), "+f"(d[3]), "+f"(d[4]), "+f"(d[5]), "+f"(d[6]), "+f"(d[7]),
      "+f"(d[8]), "+f"(d[9]), "+f"(d[10]), "+f"(d[11]), "+f"(d[12]), "+f"(d[13]), "+f"(d[14]), "+f"(d[15]),
      "+f"(d[16]), "+f"(d[17]), "+f"(d[18]), "+f"(d[19]), "+f"(d[20]), "+f"(d[21]), "+f"(d[22]), "+f"(d[23]),
      "+f"(d[24]), "+f"(d[25]), "+f"(d[26]), "+f"(d[27]), "+f"(d[28]), "+f"(d[29]), "+f"(d[30]), "+f"(d[31]),
      "+f"(d[32]), "+f"(d[33]), "+f"(d[34]), "+f"(d[35]), "+f"(d[36]), "+f"(d[37]), "+f"(d[38]), "+f"(d[39])
      : "r"(a[0]), "r"(a[1]), "r"(a[2]), "r"(a[3]), "l"(db));
  }
};
template <> struct WG<96> {
  static __device__ __forceinline__ void rs(float* d, const uint32_t* a, uint64_t db) {
    asm volatile("{\n.reg .pred p;\nsetp.ne.b32 p, 1, 0;\nwgmma.mma_async.sync.aligned.m64n96k16.f32.bf16.bf16 {"
      "%0, %1, %2, %3, %4, %5, %6, %7, %8, %9, %10, %11, %12, %13, %14, %15, "
      "%16, %17, %18, %19, %20, %21, %22, %23, %24, %25, %26, %27, %28, %29, %30, %31, "
      "%32, %33, %34, %35, %36, %37, %38, %39, %40, %41, %42, %43, %44, %45, %46, %47"
      "}, {%48, %49, %50, %51}, %52, p, 1, 1, 0;\n}\n"
      :
      "+f"(d[0]), "+f"(d[1]), "+f"(d[2]), "+f"(d[3]), "+f"(d[4]), "+f"(d[5]), "+f"(d[6]), "+f"(d[7]),
      "+f"(d[8]), "+f"(d[9]), "+f"(d[10]), "+f"(d[11]), "+f"(d[12]), "+f"(d[13]), "+f"(d[14]), "+f"(d[15]),
      "+f"(d[16]), "+f"(d[17]), "+f"(d[18]), "+f"(d[19]), "+f"(d[20]), "+f"(d[21]), "+f"(d[22]), "+f"(d[23]),
      "+f"(d[24]), "+f"(d[25]), "+f"(d[26]), "+f"(d[27]), "+f"(d[28]), "+f"(d[29]), "+f"(d[30]), "+f"(d[31]),
      "+f"(d[32]), "+f"(d[33]), "+f"(d[34]), "+f"(d[35]), "+f"(d[36]), "+f"(d[37]), "+f"(d[38]), "+f"(d[39]),
      "+f"(d[40]), "+f"(d[41]), "+f"(d[42]), "+f"(d[43]), "+f"(d[44]), "+f"(d[45]), "+f"(d[46]), "+f"(d[47])
      : "r"(a[0]), "r"(a[1]), "r"(a[2]), "r"(a[3]), "l"(db));
  }
};
template <> struct WG<112> {
  static __device__ __forceinline__ void rs(float* d, const uint32_t* a, uint64_t db) {
    asm volatile("{\n.reg .pred p;\nsetp.ne.b32 p, 1, 0;\nwgmma.mma_async.sync.aligned.m64n112k16.f32.bf16.bf16 {"
      "%0, %1, %2, %3, %4, %5, %6, %7, %8, %9, %10, %11, %12, %13, %14, %15, "
      "%16, %17, %18, %19, %20, %21, %22, %23, %24, %25, %26, %27, %28, %29, %30, %31, "
      "%32, %33, %34, %35, %36, %37, %38, %39, %40, %41, %42, %43, %44, %45, %46, %47, "
      "%48, %49, %50, %51, %52, %53, %54, %55"
      "}, {%56, %57, %58, %59}, %60, p, 1, 1, 0;\n}\n"
      :
      "+f"(d[0]), "+f"(d[1]), "+f"(d[2]), "+f"(d[3]), "+f"(d[4]), "+f"(d[5]), "+f"(d[6]), "+f"(d[7]),
      "+f"(d[8]), "+f"(d[9]), "+f"(d[10]), "+f"(d[11]), "+f"(d[12]), "+f"(d[13]), "+f"(d[14]), "+f"(d[15]),
      "+f"(d[16]), "+f"(d[17]), "+f"(d[18]), "+f"(d[19]), "+f"(d[20]), "+f"(d[21]), "+f"(d[22]), "+f"(d[23]),
      "+f"(d[24]), "+f"(d[25]), "+f"(d[26]), "+f"(d[27]), "+f"(d[28]), "+f"(d[29]), "+f"(d[30]), "+f"(d[31]),
      "+f"(d[32]), "+f"(d[33]), "+f"(d[34]), "+f"(d[35]), "+f"(d[36]), "+f"(d[37]), "+f"(d[38]), "+f"(d[39]),
      "+f"(d[40]), "+f"(d[41]), "+f"(d[42]), "+f"(d[43]), "+f"(d[44]), "+f"(d[45]), "+f"(d[46]), "+f"(d[47]),
      "+f"(d[48]), "+f"(d[49]), "+f"(d[50]), "+f"(d[51]), "+f"(d[52]), "+f"(d[53]), "+f"(d[54]), "+f"(d[55])
      : "r"(a[0]), "r"(a[1]), "r"(a[2]), "r"(a[3]), "l"(db));
  }
};
template <> struct WG<128> {
  static __device__ __forceinline__ void rs(float* d, const uint32_t* a, uint64_t db) {
    asm volatile("{\n.reg .pred p;\nsetp.ne.b32 p, 1, 0;\nwgmma.mma_async.sync.aligned.m64n128k16.f32.bf16.bf16 {"
      "%0, %1, %2, %3, %4, %5, %6, %7, %8, %9, %10, %11, %12, %13, %14, %15, "
      "%16, %17, %18, %19, %20, %21, %22, %23, %24, %25, %26, %27, %28, %29, %30, %31, "
      "%32, %33, %34, %35, %36, %37, %38, %39, %40, %41, %42, %43, %44, %45, %46, %47, "
      "%48, %49, %50, %51, %52, %53, %54, %55, %56, %57, %58, %59, %60, %61, %62, %63"
      "}, {%64, %65, %66, %67}, %68, p, 1, 1, 0;\n}\n"
      :
      "+f"(d[0]), "+f"(d[1]), "+f"(d[2]), "+f"(d[3]), "+f"(d[4]), "+f"(d[5]), "+f"(d[6]), "+f"(d[7]),
      "+f"(d[8]), "+f"(d[9]), "+f"(d[10]), "+f"(d[11]), "+f"(d[12]), "+f"(d[13]), "+f"(d[14]), "+f"(d[15]),
      "+f"(d[16]), "+f"(d[17]), "+f"(d[18]), "+f"(d[19]), "+f"(d[20]), "+f"(d[21]), "+f"(d[22]), "+f"(d[23]),
      "+f"(d[24]), "+f"(d[25]), "+f"(d[26]), "+f"(d[27]), "+f"(d[28]), "+f"(d[29]), "+f"(d[30]), "+f"(d[31]),
      "+f"(d[32]), "+f"(d[33]), "+f"(d[34]), "+f"(d[35]), "+f"(d[36]), "+f"(d[37]), "+f"(d[38]), "+f"(d[39]),
      "+f"(d[40]), "+f"(d[41]), "+f"(d[42]), "+f"(d[43]), "+f"(d[44]), "+f"(d[45]), "+f"(d[46]), "+f"(d[47]),
      "+f"(d[48]), "+f"(d[49]), "+f"(d[50]), "+f"(d[51]), "+f"(d[52]), "+f"(d[53]), "+f"(d[54]), "+f"(d[55]),
      "+f"(d[56]), "+f"(d[57]), "+f"(d[58]), "+f"(d[59]), "+f"(d[60]), "+f"(d[61]), "+f"(d[62]), "+f"(d[63])
      : "r"(a[0]), "r"(a[1]), "r"(a[2]), "r"(a[3]), "l"(db));
  }
};
template <> struct WG<160> {
  static __device__ __forceinline__ void ss(float* d, uint64_t da, uint64_t db, int sd) {
    asm volatile("{\n.reg .pred p;\nsetp.ne.b32 p, %82, 0;\nwgmma.mma_async.sync.aligned.m64n160k16.f32.bf16.bf16 {"
      "%0, %1, %2, %3, %4, %5, %6, %7, %8, %9, %10, %11, %12, %13, %14, %15, "
      "%16, %17, %18, %19, %20, %21, %22, %23, %24, %25, %26, %27, %28, %29, %30, %31, "
      "%32, %33, %34, %35, %36, %37, %38, %39, %40, %41, %42, %43, %44, %45, %46, %47, "
      "%48, %49, %50, %51, %52, %53, %54, %55, %56, %57, %58, %59, %60, %61, %62, %63, "
      "%64, %65, %66, %67, %68, %69, %70, %71, %72, %73, %74, %75, %76, %77, %78, %79"
      "}, %80, %81, p, 1, 1, 0, 1;\n}\n"
      :
      "+f"(d[0]), "+f"(d[1]), "+f"(d[2]), "+f"(d[3]), "+f"(d[4]), "+f"(d[5]), "+f"(d[6]), "+f"(d[7]),
      "+f"(d[8]), "+f"(d[9]), "+f"(d[10]), "+f"(d[11]), "+f"(d[12]), "+f"(d[13]), "+f"(d[14]), "+f"(d[15]),
      "+f"(d[16]), "+f"(d[17]), "+f"(d[18]), "+f"(d[19]), "+f"(d[20]), "+f"(d[21]), "+f"(d[22]), "+f"(d[23]),
      "+f"(d[24]), "+f"(d[25]), "+f"(d[26]), "+f"(d[27]), "+f"(d[28]), "+f"(d[29]), "+f"(d[30]), "+f"(d[31]),
      "+f"(d[32]), "+f"(d[33]), "+f"(d[34]), "+f"(d[35]), "+f"(d[36]), "+f"(d[37]), "+f"(d[38]), "+f"(d[39]),
      "+f"(d[40]), "+f"(d[41]), "+f"(d[42]), "+f"(d[43]), "+f"(d[44]), "+f"(d[45]), "+f"(d[46]), "+f"(d[47]),
      "+f"(d[48]), "+f"(d[49]), "+f"(d[50]), "+f"(d[51]), "+f"(d[52]), "+f"(d[53]), "+f"(d[54]), "+f"(d[55]),
      "+f"(d[56]), "+f"(d[57]), "+f"(d[58]), "+f"(d[59]), "+f"(d[60]), "+f"(d[61]), "+f"(d[62]), "+f"(d[63]),
      "+f"(d[64]), "+f"(d[65]), "+f"(d[66]), "+f"(d[67]), "+f"(d[68]), "+f"(d[69]), "+f"(d[70]), "+f"(d[71]),
      "+f"(d[72]), "+f"(d[73]), "+f"(d[74]), "+f"(d[75]), "+f"(d[76]), "+f"(d[77]), "+f"(d[78]), "+f"(d[79])
      : "l"(da), "l"(db), "r"(sd));
  }
};
template <> struct WG<192> {
  static __device__ __forceinline__ void ss(float* d, uint64_t da, uint64_t db, int sd) {
    asm volatile("{\n.reg .pred p;\nsetp.ne.b32 p, %98, 0;\nwgmma.mma_async.sync.aligned.m64n192k16.f32.bf16.bf16 {"
      "%0, %1, %2, %3, %4, %5, %6, %7, %8, %9, %10, %11, %12, %13, %14, %15, "
      "%16, %17, %18, %19, %20, %21, %22, %23, %24, %25, %26, %27, %28, %29, %30, %31, "
      "%32, %33, %34, %35, %36, %37, %38, %39, %40, %41, %42, %43, %44, %45, %46, %47, "
      "%48, %49, %50, %51, %52, %53, %54, %55, %56, %57, %58, %59, %60, %61, %62, %63, "
      "%64, %65, %66, %67, %68, %69, %70, %71, %72, %73, %74, %75, %76, %77, %78, %79, "
      "%80, %81, %82, %83, %84, %85, %86, %87, %88, %89, %90, %91, %92, %93, %94, %95"
      "}, %96, %97, p, 1, 1, 0, 1;\n}\n"
      :
      "+f"(d[0]), "+f"(d[1]), "+f"(d[2]), "+f"(d[3]), "+f"(d[4]), "+f"(d[5]), "+f"(d[6]), "+f"(d[7]),
      "+f"(d[8]), "+f"(d[9]), "+f"(d[10]), "+f"(d[11]), "+f"(d[12]), "+f"(d[13]), "+f"(d[14]), "+f"(d[15]),
      "+f"(d[16]), "+f"(d[17]), "+f"(d[18]), "+f"(d[19]), "+f"(d[20]), "+f"(d[21]), "+f"(d[22]), "+f"(d[23]),
      "+f"(d[24]), "+f"(d[25]), "+f"(d[26]), "+f"(d[27]), "+f"(d[28]), "+f"(d[29]), "+f"(d[30]), "+f"(d[31]),
      "+f"(d[32]), "+f"(d[33]), "+f"(d[34]), "+f"(d[35]), "+f"(d[36]), "+f"(d[37]), "+f"(d[38]), "+f"(d[39]),
      "+f"(d[40]), "+f"(d[41]), "+f"(d[42]), "+f"(d[43]), "+f"(d[44]), "+f"(d[45]), "+f"(d[46]), "+f"(d[47]),
      "+f"(d[48]), "+f"(d[49]), "+f"(d[50]), "+f"(d[51]), "+f"(d[52]), "+f"(d[53]), "+f"(d[54]), "+f"(d[55]),
      "+f"(d[56]), "+f"(d[57]), "+f"(d[58]), "+f"(d[59]), "+f"(d[60]), "+f"(d[61]), "+f"(d[62]), "+f"(d[63]),
      "+f"(d[64]), "+f"(d[65]), "+f"(d[66]), "+f"(d[67]), "+f"(d[68]), "+f"(d[69]), "+f"(d[70]), "+f"(d[71]),
      "+f"(d[72]), "+f"(d[73]), "+f"(d[74]), "+f"(d[75]), "+f"(d[76]), "+f"(d[77]), "+f"(d[78]), "+f"(d[79]),
      "+f"(d[80]), "+f"(d[81]), "+f"(d[82]), "+f"(d[83]), "+f"(d[84]), "+f"(d[85]), "+f"(d[86]), "+f"(d[87]),
      "+f"(d[88]), "+f"(d[89]), "+f"(d[90]), "+f"(d[91]), "+f"(d[92]), "+f"(d[93]), "+f"(d[94]), "+f"(d[95])
      : "l"(da), "l"(db), "r"(sd));
  }
  static __device__ __forceinline__ void rst(float* d, const uint32_t* a, uint64_t db) {
    asm volatile("{\n.reg .pred p;\nsetp.ne.b32 p, 1, 0;\nwgmma.mma_async.sync.aligned.m64n192k16.f32.bf16.bf16 {"
      "%0, %1, %2, %3, %4, %5, %6, %7, %8, %9, %10, %11, %12, %13, %14, %15, "
      "%16, %17, %18, %19, %20, %21, %22, %23, %24, %25, %26, %27, %28, %29, %30, %31, "
      "%32, %33, %34, %35, %36, %37, %38, %39, %40, %41, %42, %43, %44, %45, %46, %47, "
      "%48, %49, %50, %51, %52, %53, %54, %55, %56, %57, %58, %59, %60, %61, %62, %63, "
      "%64, %65, %66, %67, %68, %69, %70, %71, %72, %73, %74, %75, %76, %77, %78, %79, "
      "%80, %81, %82, %83, %84, %85, %86, %87, %88, %89, %90, %91, %92, %93, %94, %95"
      "}, {%96, %97, %98, %99}, %100, p, 1, 1, 1;\n}\n"
      :
      "+f"(d[0]), "+f"(d[1]), "+f"(d[2]), "+f"(d[3]), "+f"(d[4]), "+f"(d[5]), "+f"(d[6]), "+f"(d[7]),
      "+f"(d[8]), "+f"(d[9]), "+f"(d[10]), "+f"(d[11]), "+f"(d[12]), "+f"(d[13]), "+f"(d[14]), "+f"(d[15]),
      "+f"(d[16]), "+f"(d[17]), "+f"(d[18]), "+f"(d[19]), "+f"(d[20]), "+f"(d[21]), "+f"(d[22]), "+f"(d[23]),
      "+f"(d[24]), "+f"(d[25]), "+f"(d[26]), "+f"(d[27]), "+f"(d[28]), "+f"(d[29]), "+f"(d[30]), "+f"(d[31]),
      "+f"(d[32]), "+f"(d[33]), "+f"(d[34]), "+f"(d[35]), "+f"(d[36]), "+f"(d[37]), "+f"(d[38]), "+f"(d[39]),
      "+f"(d[40]), "+f"(d[41]), "+f"(d[42]), "+f"(d[43]), "+f"(d[44]), "+f"(d[45]), "+f"(d[46]), "+f"(d[47]),
      "+f"(d[48]), "+f"(d[49]), "+f"(d[50]), "+f"(d[51]), "+f"(d[52]), "+f"(d[53]), "+f"(d[54]), "+f"(d[55]),
      "+f"(d[56]), "+f"(d[57]), "+f"(d[58]), "+f"(d[59]), "+f"(d[60]), "+f"(d[61]), "+f"(d[62]), "+f"(d[63]),
      "+f"(d[64]), "+f"(d[65]), "+f"(d[66]), "+f"(d[67]), "+f"(d[68]), "+f"(d[69]), "+f"(d[70]), "+f"(d[71]),
      "+f"(d[72]), "+f"(d[73]), "+f"(d[74]), "+f"(d[75]), "+f"(d[76]), "+f"(d[77]), "+f"(d[78]), "+f"(d[79]),
      "+f"(d[80]), "+f"(d[81]), "+f"(d[82]), "+f"(d[83]), "+f"(d[84]), "+f"(d[85]), "+f"(d[86]), "+f"(d[87]),
      "+f"(d[88]), "+f"(d[89]), "+f"(d[90]), "+f"(d[91]), "+f"(d[92]), "+f"(d[93]), "+f"(d[94]), "+f"(d[95])
      : "r"(a[0]), "r"(a[1]), "r"(a[2]), "r"(a[3]), "l"(db));
  }
};

#define ZPACE 0
#define GO1 2
#define ZSH 1
#define CS1_T 9500
#define G1_AT 0
#define HGRP 3
#define HPACE 150
#define DB 0
#define HOLD_AT 33
#define LL_AT 4
#define KV_T0 2300
#define ST_YIELD 1
#define HP0 0
#define HPD 0
#define LEAD 2
#define WSP_N 16
#define EARLY 0
#define CPIN 1
#define CW0 0
#define PFT 1
#define WSP_D 650
#define D1 4
#define D2 4
#define NSLEEP 32

static_assert(LEAD == 2, "staging slots");

namespace {

constexpr int kS = 2048, kD = 640, kF = 1536;
constexpr int NA = 10, NA2 = 9, NB = 5;
constexpr int A_SLOT = 8192, B_SLOT = 24576;
constexpr int OFF_A = 0;
constexpr int OFF_B = OFF_A + NA * A_SLOT;
constexpr int XB_PL = 2112;
constexpr int CV_KE = 4224, CV_KO = CV_KE + 4160;
constexpr int CV_SZ = CV_KO + 4160;
constexpr int OFF_CV = OFF_B + NB * B_SLOT;
constexpr int OFF_CS = OFF_CV + 2 * CV_SZ;
constexpr int OFF_BIAS = OFF_CS + 1536;
constexpr int OFF_XS = OFF_BIAS + 128;
constexpr int OFF_BAR = OFF_XS + 512;
constexpr int BAR_AF = OFF_BAR, BAR_ST = BAR_AF + 8 * NA, BAR_XF = BAR_ST + 16, BAR_KV = BAR_XF + 16;
constexpr int BAR_BF = OFF_BAR + 128, BAR_G2 = BAR_BF + 8 * (NB + 1), BAR_XS = BAR_G2 + 8, BAR_KU = BAR_XS + 8, BAR_ZP = BAR_KU + 40, BAR_XC = BAR_ZP + 8, BAR_WO = BAR_XC + 8;
constexpr int BAR_AE = OFF_BAR + 256, BAR_BE = BAR_AE + 8 * NA;
constexpr int BAR_YT = BAR_KU + 24;
constexpr int BAR_Z1 = BAR_ST;
constexpr int BAR_GO1 = BAR_XC;
constexpr int BAR_GO = BAR_XS;
constexpr int BAR_YL = BAR_KU + 16;
constexpr int OFF_TAG = OFF_CS - 32;
constexpr int SMEM_BYTES = OFF_BAR + 384;
static_assert(SMEM_BYTES <= 232448, "smem");
constexpr int NB_WGA = 1, NB_WGC = 2, NB_G1 = 3, NB_WO = 4, NB_CD = 5, NB_Z = 6, NB_WGB = 7, NB_Z2 = 8;

constexpr int CSP = 32, EPS = 8;
constexpr int CNT_Y = 0, CNT_Z1 = 2, CNT_KV = 4, CNT_WO = 8;
struct Scratch {
  uint8_t kvx[kD * 4096];
  uint8_t z2[4 * 32 * 24576];
  uint8_t h[32 * 12 * 8192];
  uint8_t wo[4 * 12 * 20480];
  uint8_t y[896 * 4096];
  uint4 xstat[kS];
  uint2 zstat[kS * 8];
  uint2 colsum[kF];
  uint32_t zcnt[4 * 32];
  uint32_t cnt[12 * 32];
  uint32_t hcnt[32 * 32];
  uint32_t epoch[136 * EPS];
};
__device__ __align__(1024) Scratch g_scr;
#define ZS(i)
#define STAMP(i)
#define STAMP2(i)
#define STAMPW(i)

struct Params {
  Scratch* scr;
  int by_smid;
  const __nv_bfloat16 *k, *v, *shift, *ssmk, *ssmD, *wsp, *bsp, *wout;
  __nv_bfloat16* out;
  CUtensorMap tmX, tmW, tmWsp, tmY, tmKV;
};

__device__ __forceinline__ uint64_t mkdesc(uint32_t addr, uint32_t lbo, uint32_t sbo, uint32_t swz) {
  return (uint64_t)((addr & 0x3FFFF) >> 4) | ((uint64_t)(lbo >> 4) << 16) | ((uint64_t)(sbo >> 4) << 32) | ((uint64_t)swz << 62);
}
#define WG_FENCE() asm volatile("wgmma.fence.sync.aligned;" ::: "memory")
#define WG_COMMIT() asm volatile("wgmma.commit_group.sync.aligned;" ::: "memory")
#define WG_WAIT(n) asm volatile("wgmma.wait_group.sync.aligned %0;" ::"n"(n) : "memory")
template <int N> __device__ __forceinline__ void acc_fence(float* d) {
#pragma unroll
  for (int i = 0; i < N; i++) asm volatile("" : "+f"(d[i])::"memory");
}
__device__ __forceinline__ void mbar_init(uint32_t bar, int cnt) { asm volatile("mbarrier.init.shared::cta.b64 [%0], %1;" ::"r"(bar), "r"(cnt) : "memory"); }
__device__ __forceinline__ void mbar_expect(uint32_t bar, uint32_t bytes) { asm volatile("mbarrier.arrive.expect_tx.shared::cta.b64 _, [%0], %1;" ::"r"(bar), "r"(bytes) : "memory"); }
__device__ __forceinline__ void mbar_arrive(uint32_t bar) { asm volatile("mbarrier.arrive.shared::cta.b64 _, [%0];" ::"r"(bar) : "memory"); }
__device__ __forceinline__ void mbar_arrive_if(uint32_t bar, bool c) {
  asm volatile("{\n.reg .pred p;\nsetp.ne.u32 p, %1, 0;\n@p mbarrier.arrive.shared::cta.b64 _, [%0];\n}\n" ::"r"(bar), "r"((uint32_t)c) : "memory");
}
__device__ __forceinline__ void mbar_expect_if(uint32_t bar, uint32_t bytes, bool c) {
  asm volatile("{\n.reg .pred p;\nsetp.ne.u32 p, %2, 0;\n@p mbarrier.arrive.expect_tx.shared::cta.b64 _, [%0], %1;\n}\n" ::"r"(bar), "r"(bytes), "r"((uint32_t)c) : "memory");
}
__device__ __forceinline__ bool mbar_try(uint32_t bar, uint32_t parity) {
  uint32_t ok;
  asm volatile("{\n.reg .pred p;\nmbarrier.try_wait.parity.shared::cta.b64 p, [%1], %2;\nselp.u32 %0, 1, 0, p;\n}\n" : "=r"(ok) : "r"(bar), "r"(parity) : "memory");
  return ok;
}
__device__ __forceinline__ bool mbar_test(uint32_t bar, uint32_t parity) {
  uint32_t ok;
  asm volatile("{\n.reg .pred p;\nmbarrier.test_wait.parity.shared::cta.b64 p, [%1], %2;\nselp.u32 %0, 1, 0, p;\n}\n" : "=r"(ok) : "r"(bar), "r"(parity) : "memory");
  return ok;
}
__device__ __forceinline__ void die() { asm volatile("st.volatile.global.u32 [%0], %1;" ::"l"(0ull), "r"(0) : "memory"); }
__device__ __forceinline__ void spin_guard(uint32_t& n) { if (++n == (1u << 22)) die(); }
__device__ __forceinline__ void mbar_wait(uint32_t bar, uint32_t parity) {
  uint32_t t0 = 0;
#pragma unroll 1
  while (!mbar_try(bar, parity)) spin_guard(t0);
}
__device__ __forceinline__ void mbar_wait2(uint32_t b0, uint32_t p0, uint32_t b1, uint32_t p1) {
  uint32_t t0 = 0;
#pragma unroll 1
  while (true) {
    const bool r0 = mbar_try(b0, p0), r1 = mbar_try(b1, p1);
    if (r0 && r1) break;
    spin_guard(t0);
  }
}
__device__ __forceinline__ int tid_now() { int v; asm volatile("mov.u32 %0, %%tid.x;" : "=r"(v)); return v & 127; }
__device__ __forceinline__ bool elect_one() {
  uint32_t p;
  asm volatile("{\n.reg .pred P;\nelect.sync _|P, 0xffffffff;\nselp.u32 %0, 1, 0, P;\n}\n" : "=r"(p));
  return p;
}
__device__ __forceinline__ void bar_sync(int id, int n) { asm volatile("bar.sync %0, %1;" ::"r"(id), "r"(n) : "memory"); }
__device__ __forceinline__ void bar_arrive(int id, int n) { asm volatile("bar.arrive %0, %1;" ::"r"(id), "r"(n) : "memory"); }
__device__ __forceinline__ void fence_async_smem() { asm volatile("fence.proxy.async.shared::cta;" ::: "memory"); }
__device__ __forceinline__ void bulk_g2s(uint32_t dst, const void* src, uint32_t bytes, uint32_t bar) {
  asm volatile("cp.async.bulk.shared::cluster.global.mbarrier::complete_tx::bytes [%0], [%1], %2, [%3];" ::"r"(dst), "l"(src), "r"(bytes), "r"(bar) : "memory");
}
__device__ __forceinline__ void bulk_s2g(void* dst, uint32_t src, uint32_t bytes) {
  asm volatile("cp.async.bulk.global.shared::cta.bulk_group [%0], [%1], %2;" ::"l"(dst), "r"(src), "r"(bytes) : "memory");
}
__device__ __forceinline__ void tma2d(uint32_t dst, const CUtensorMap* m, int c0, int c1, uint32_t bar) {
  asm volatile("cp.async.bulk.tensor.2d.shared::cluster.global.mbarrier::complete_tx::bytes [%0], [%1, {%3, %4}], [%2];" ::"r"(dst), "l"(m), "r"(bar), "r"(c0), "r"(c1) : "memory");
}
__device__ __forceinline__ void tma3d(uint32_t dst, const CUtensorMap* m, int c0, int c1, int c2, uint32_t bar) {
  asm volatile("cp.async.bulk.tensor.3d.shared::cluster.global.mbarrier::complete_tx::bytes [%0], [%1, {%3, %4, %5}], [%2];" ::"r"(dst), "l"(m), "r"(bar), "r"(c0), "r"(c1), "r"(c2) : "memory");
}
__device__ __forceinline__ void tma_rows(uint32_t dst, const CUtensorMap* m, int c0, int rb, uint32_t bar) { tma3d(dst, m, c0, rb * 16, 0, bar); }
__device__ __forceinline__ uint4 ld_ll4(const void* p) {
  uint64_t a, b;
  asm volatile("ld.relaxed.gpu.global.v2.u64 {%0,%1}, [%2];" : "=l"(a), "=l"(b) : "l"(p) : "memory");
  return make_uint4((uint32_t)a, (uint32_t)(a >> 32), (uint32_t)b, (uint32_t)(b >> 32));
}
__device__ __forceinline__ void st_ll4(void* p, uint32_t a, uint32_t b, uint32_t c, uint32_t d) {
  asm volatile("st.relaxed.gpu.global.v2.u64 [%0], {%1,%2};" ::"l"(p), "l"(a | ((uint64_t)b << 32)), "l"(c | ((uint64_t)d << 32)) : "memory");
}
__device__ __forceinline__ void st_ll2(void* p, uint32_t a, uint32_t b) { asm volatile("st.relaxed.gpu.global.u64 [%0], %1;" ::"l"(p), "l"(a | ((uint64_t)b << 32)) : "memory"); }
__device__ __forceinline__ uint2 ld_ll2(const void* p) {
  uint64_t a;
  asm volatile("ld.relaxed.gpu.global.u64 %0, [%1];" : "=l"(a) : "l"(p) : "memory");
  return make_uint2((uint32_t)a, (uint32_t)(a >> 32));
}
__device__ __forceinline__ void wgmma_colsum(float* d, uint64_t da, uint64_t db) {
  asm volatile("{\n.reg .pred p;\nsetp.ne.b32 p, 1, 0;\nwgmma.mma_async.sync.aligned.m64n8k16.f32.bf16.bf16 {%0, %1, %2, %3}, %4, %5, p, 1, 1, 1, 0;\n}\n"
               : "+f"(d[0]), "+f"(d[1]), "+f"(d[2]), "+f"(d[3]) : "l"(da), "l"(db));
}
__device__ __forceinline__ void prefetch_l2(const void* p) { asm volatile("prefetch.global.L2 [%0];" ::"l"(p)); }
__device__ __forceinline__ void pace(uint32_t& t, uint32_t dt) {
  t += dt;
  while ((int32_t)((uint32_t)clock() - t) < 0) { if (NSLEEP) __nanosleep(NSLEEP); }
}
__device__ __forceinline__ void red_relaxed(uint32_t* p) { asm volatile("red.relaxed.gpu.global.add.u32 [%0], 1;" ::"l"(p) : "memory"); }
__device__ __forceinline__ void red_release(uint32_t* p) { asm volatile("red.release.gpu.global.add.u32 [%0], 1;" ::"l"(p) : "memory"); }
__device__ __forceinline__ uint4 ldg4(const void* p) { uint4 v; asm volatile("ld.global.v4.u32 {%0,%1,%2,%3}, [%4];" : "=r"(v.x), "=r"(v.y), "=r"(v.z), "=r"(v.w) : "l"(p) : "memory"); return v; }
__device__ __forceinline__ uint32_t ldg1(const void* p) { uint32_t v; asm volatile("ld.global.u32 %0, [%1];" : "=r"(v) : "l"(p) : "memory"); return v; }
__device__ __forceinline__ void stg4_if(void* p, uint32_t a, uint32_t b, uint32_t c, uint32_t d, bool on) {
  asm volatile("{\n.reg .pred p;\nsetp.ne.u32 p, %5, 0;\n@p st.global.v4.u32 [%0], {%1,%2,%3,%4};\n}\n" ::"l"(p), "r"(a), "r"(b), "r"(c), "r"(d), "r"((uint32_t)on) : "memory");
}
template <int OFF> __device__ __forceinline__ uint32_t lds32(uint32_t a) { uint32_t v; asm volatile("ld.shared.u32 %0, [%1+%2];" : "=r"(v) : "r"(a), "n"(OFF)); return v; }
__device__ __forceinline__ uint4 lds128(uint32_t a) { uint4 v; asm volatile("ld.shared.v4.u32 {%0,%1,%2,%3}, [%4];" : "=r"(v.x), "=r"(v.y), "=r"(v.z), "=r"(v.w) : "r"(a) : "memory"); return v; }
__device__ __forceinline__ float2 lds64f(uint32_t a) { float2 v; asm volatile("ld.shared.v2.f32 {%0,%1}, [%2];" : "=f"(v.x), "=f"(v.y) : "r"(a) : "memory"); return v; }
__device__ __forceinline__ void sts64f(uint32_t a, float x, float y) { asm volatile("st.shared.v2.f32 [%0], {%1,%2};" ::"r"(a), "f"(x), "f"(y) : "memory"); }
__device__ __forceinline__ void sts32(uint32_t a, uint32_t x) { asm volatile("st.shared.u32 [%0], %1;" ::"r"(a), "r"(x) : "memory"); }
__device__ __forceinline__ void sts128(uint32_t a, uint32_t x, uint32_t y, uint32_t z, uint32_t w) { asm volatile("st.shared.v4.u32 [%0], {%1,%2,%3,%4};" ::"r"(a), "r"(x), "r"(y), "r"(z), "r"(w) : "memory"); }
__device__ __forceinline__ void stsm4(uint32_t a, uint32_t r0, uint32_t r1, uint32_t r2, uint32_t r3) {
  asm volatile("stmatrix.sync.aligned.m8n8.x4.shared.b16 [%0], {%1,%2,%3,%4};" ::"r"(a), "r"(r0), "r"(r1), "r"(r2), "r"(r3) : "memory");
}
__device__ __forceinline__ void stsm4t(uint32_t a, uint32_t r0, uint32_t r1, uint32_t r2, uint32_t r3) {
  asm volatile("stmatrix.sync.aligned.m8n8.x4.trans.shared.b16 [%0], {%1,%2,%3,%4};" ::"r"(a), "r"(r0), "r"(r1), "r"(r2), "r"(r3) : "memory");
}
__device__ __forceinline__ void ldsm4t(uint32_t* r, uint32_t a) {
  asm volatile("ldmatrix.sync.aligned.m8n8.x4.trans.shared.b16 {%0,%1,%2,%3}, [%4];" : "=r"(r[0]), "=r"(r[1]), "=r"(r[2]), "=r"(r[3]) : "r"(a) : "memory");
}
__device__ __forceinline__ uint32_t pack2(float lo, float hi) { uint32_t r; asm("cvt.rn.bf16x2.f32 %0, %1, %2;" : "=r"(r) : "f"(hi), "f"(lo)); return r; }
__device__ __forceinline__ float bf_lo(uint32_t u) { return __uint_as_float(u << 16); }
__device__ __forceinline__ float bf_hi(uint32_t u) { return __uint_as_float(u & 0xffff0000u); }
__device__ __forceinline__ float tanh_fast(float x) { float y; asm("tanh.approx.f32 %0, %1;" : "=f"(y) : "f"(x)); return y; }
__device__ __forceinline__ uint32_t hmul2(uint32_t a, uint32_t b) { uint32_t r; asm("mul.rn.bf16x2 %0, %1, %2;" : "=r"(r) : "r"(a), "r"(b)); return r; }
__device__ __forceinline__ uint32_t hfma2(uint32_t a, uint32_t b, uint32_t c) { uint32_t r; asm("fma.rn.bf16x2 %0, %1, %2, %3;" : "=r"(r) : "r"(a), "r"(b), "r"(c)); return r; }
__device__ __forceinline__ uint32_t prmt(uint32_t a, uint32_t b, uint32_t s) { return __byte_perm(a, b, s); }

__device__ __forceinline__ void st_relaxed(uint32_t* p, uint32_t v) { asm volatile("st.relaxed.gpu.global.u32 [%0], %1;" ::"l"(p), "r"(v) : "memory"); }
__device__ __forceinline__ uint32_t ld_relaxed(const uint32_t* p) { uint32_t v; asm volatile("ld.relaxed.gpu.global.u32 %0, [%1];" : "=r"(v) : "l"(p) : "memory"); return v; }
__device__ __forceinline__ void acquire_fence() { asm volatile("fence.acquire.gpu;\nfence.proxy.async.global;" ::: "memory"); }
__device__ __forceinline__ uint32_t load_epoch(const Params& p, int idx, int lane) { return ld_relaxed(&p.scr->epoch[idx * EPS + (((lane * lane) & 3) == 2 ? 1 : 0)]); }
__device__ __forceinline__ void poll_counter(const uint32_t* cnt, uint32_t target) {
  uint32_t t0 = 0;
#pragma unroll 1
  while (!__all_sync(0xffffffff, ld_relaxed(cnt) == target)) spin_guard(t0);
  acquire_fence();
}

__device__ __forceinline__ void poll_one(const uint32_t* cnt, uint32_t target) {
  uint32_t t0 = 0;
#pragma unroll 1
  while (ld_relaxed(cnt) != target) spin_guard(t0);
  acquire_fence();
}
__device__ __forceinline__ uint32_t anchor(uint32_t v) { return __shfl_sync(0xffffffff, v, 0); }
__device__ __forceinline__ int g3_block(int cb, int it) { return it < 3 ? cb * 3 + it : (it - 3 < cb * 3 ? it - 3 : it); }

template <int N, bool A_SWZ, int B_MODE, int DEPTH, class Hook, class Mid>
__device__ __forceinline__ void gemm_loop(float* d, uint32_t sb, int nkb, int sa, int pa, int b0, uint32_t boff, int relA, int relB, int tid, Hook hook, Mid mid) {
  constexpr uint32_t A_STEP = A_SWZ ? 2 : 128;
  constexpr uint32_t B_STEP = B_MODE == 0 ? 128 : (B_MODE == 1 ? 384 : 320);
  const uint64_t da0 = A_SWZ ? mkdesc(sb + OFF_A, 16, 1024, 1) : mkdesc(sb + OFF_A, 1024, 128, 0);
  const uint64_t db0 = B_MODE == 0 ? mkdesc(sb + OFF_B + boff, 8192, 1024, 1) : mkdesc(sb + OFF_B + boff, B_MODE == 1 ? 3072 : 2560, 128, 0);
  constexpr int MODA = B_MODE == 0 ? NA : NA2;
  constexpr int MODB = B_MODE == 2 ? 6 : NB;
  int sbk = b0 % MODB, pb = (b0 / MODB) & 1;
  auto boffs = [](int s_) { return B_MODE == 2 ? (s_ == 5 ? 0 : s_ + 1) * (20480 >> 4) : s_ * (B_SLOT >> 4); };
  uint32_t rel = 0;
  uint64_t da = da0 + sa * (A_SLOT >> 4), db = db0 + boffs(sbk);
  const bool doR = tid < 2 ? tid < relA : tid - 2 < relB;
  mbar_wait2(sb + BAR_AF + 8 * sa, pa, sb + BAR_BF + 8 * sbk, pb);
  if constexpr (DEPTH == 0) {
#pragma unroll
    for (int i = 0; i < N / 2; i++) asm volatile("" : "=f"(d[i]));
#pragma unroll 1
    for (int it = 0; it < nkb; it++) {
      WG_FENCE();
#pragma unroll
      for (int j = 0; j < 4; j++) WG<N>::ss(d, da + j * A_STEP, db + j * B_STEP, j ? 1 : it);
      WG_COMMIT();
      const uint32_t prel = rel;
      rel = sb + BAR_AE + 8 * (tid < 2 ? sa : sbk + NA);
      if (++sa == MODA) { sa = 0; pa ^= 1; }
      if (++sbk == MODB) { sbk = 0; pb ^= 1; }
      da = da0 + sa * (A_SLOT >> 4); db = db0 + boffs(sbk);
      const bool r0 = mbar_test(sb + BAR_AF + 8 * sa, pa), r1 = mbar_test(sb + BAR_BF + 8 * sbk, pb);
      WG_WAIT(1);
      mbar_arrive_if(prel, doR && prel != 0);
      if (it == 2) {
        WG_WAIT(0);
        mbar_expect_if(sb + BAR_AF + 8 * (tid == 8 ? 8 : tid), A_SLOT, tid < 9);
        mbar_arrive_if(rel, doR);
        rel = 0;
      }
      mid(it);
      if (it + 1 < nkb && !(r0 && r1)) {
        mbar_wait2(sb + BAR_AF + 8 * sa, pa, sb + BAR_BF + 8 * sbk, pb);
      }
    }
  } else
#pragma unroll 1
  for (int it = 0; it < nkb; it++) {
    WG_FENCE();
    WG<N>::ss(d, da, db, 1);
    const uint32_t prel = rel;
    rel = sb + BAR_AE + 8 * (tid < 2 ? sa : sbk + NA);
    if (++sa == MODA) { sa = 0; if (B_MODE) pa ^= 1; }
    if (++sbk == MODB) { sbk = 0; pb ^= 1; }
    if (DEPTH == 1) { WG_COMMIT(); WG_WAIT(1); }
    WG<N>::ss(d, da + A_STEP, db + B_STEP, 1);
    WG_COMMIT();
    WG_WAIT(1);
    if (EARLY == 1) mbar_arrive_if(prel, doR && it != 0);
    WG<N>::ss(d, da + 2 * A_STEP, db + 2 * B_STEP, 1);
    if (DEPTH == 1) WG_COMMIT();
    if (EARLY != 1) mbar_arrive_if(prel, doR && it != 0);
    const bool r0 = mbar_test(sb + BAR_AF + 8 * sa, pa), r1 = mbar_test(sb + BAR_BF + 8 * sbk, pb);
    const uint64_t da3 = da + 3 * A_STEP, db3 = db + 3 * B_STEP;
    da = da0 + sa * (A_SLOT >> 4); db = db0 + boffs(sbk);
    if (DEPTH == 1) WG_WAIT(1);
    WG<N>::ss(d, da3, db3, 1);
    WG_COMMIT();
    mid(it);
    if (it + 1 < nkb) {
      if (!(r0 && r1)) {
        mbar_wait2(sb + BAR_AF + 8 * sa, pa, sb + BAR_BF + 8 * sbk, pb);
      }
    }
    if (DEPTH == 2) WG_WAIT(1);
  }
  hook();
  WG_WAIT(0);
  acc_fence<N / 2>(d);
  mbar_arrive_if(rel, doR);
}

__device__ __forceinline__ void fold_mean(float* d, uint32_t cs, float ma, float mb, int t) {
  const uint32_t ha = pack2(-ma, -ma), hb = pack2(-mb, -mb);
  const float la = -ma - bf_lo(ha), lb = -mb - bf_lo(hb);
  const uint32_t a[4] = {t ? 0u : ha, t ? 0u : hb, t ? 0u : pack2(la, la), t ? 0u : pack2(lb, lb)};
  WG_FENCE();
  WG<192>::rst(d, a, mkdesc(cs, 0, 32, 0));
  WG_COMMIT();
}
__device__ __forceinline__ void gelu_tile(const float* d, uint32_t* z, float* st, float ra, float rb) {
  const float kA = 0.7978845608028654f, kB = 0.7978845608028654f * 0.044715f;
  const float c1a = kA * ra, c3a = kB * ra * ra * ra, c1b = kA * rb, c3b = kB * rb * rb * rb;
  float acc[8];
#pragma unroll
  for (int i = 0; i < 8; i++) acc[i] = 0.f;
#pragma unroll
  for (int j = 0; j < 24; j++) {
    float r[4];
#pragma unroll
    for (int e = 0; e < 4; e++) {
      const float v = d[4 * j + e];
      const float a = v * fmaf(v * v, e < 2 ? c3a : c3b, e < 2 ? c1a : c1b);
      r[e] = fmaf(v, tanh_fast(a), v);
      acc[e] += r[e];
      acc[4 + e] = fmaf(r[e], r[e], acc[4 + e]);
    }
    z[2 * j] = pack2(r[0], r[1]);
    z[2 * j + 1] = pack2(r[2], r[3]);
  }
  st[0] = acc[0] + acc[1]; st[1] = acc[4] + acc[5]; st[2] = acc[2] + acc[3]; st[3] = acc[6] + acc[7];
}

template <int Q> __device__ __forceinline__ void conv_load(uint32_t* a, uint32_t ab) {
  a[0] = lds32<512 * Q>(ab);       a[1] = lds32<512 * Q + 256>(ab);  a[2] = lds32<512 * Q + 16>(ab);   a[3] = lds32<512 * Q + 272>(ab);
  a[4] = lds32<512 * Q + 32>(ab);  a[5] = lds32<512 * Q + 288>(ab);  a[6] = lds32<512 * Q + 48>(ab);   a[7] = lds32<512 * Q + 304>(ab);
  a[8] = lds32<512 * Q + 64>(ab);  a[9] = lds32<512 * Q + 320>(ab);  a[10] = lds32<512 * Q + 80>(ab);  a[11] = lds32<512 * Q + 336>(ab);
  a[12] = lds32<512 * Q + 96>(ab); a[13] = lds32<512 * Q + 352>(ab); a[14] = lds32<512 * Q + 112>(ab); a[15] = lds32<512 * Q + 368>(ab);
}
template <int Q, int L> __device__ __forceinline__ void conv_step(float* d, uint32_t (*a)[16], uint32_t ab, uint64_t db) {
  WG_FENCE();
#pragma unroll
  for (int s = 0; s < 4; s++) WG<128 - 16 * Q>::rs(d, a[Q] + 4 * s, db + s + 16 * Q);
  WG_COMMIT();
  if (CPIN) WG_WAIT(1);
  if (L >= 0) conv_load<(L >= 0 ? L : 0)>(a[L >= 0 ? L : 0], ab);
  if (CW0 || Q == 0) WG_WAIT(0);
}

__device__ __forceinline__ int seg_col(int cb, int h) { return (cb >> 1) * 320 + (cb & 1) * 32 + h * 64; }
__device__ __forceinline__ void final_load_x(uint32_t (*xw)[10], uint32_t xt, int cb, int h, int w, int lane) {
  const int g = lane >> 2, t = lane & 3, cc = seg_col(cb, h) >> 3;
  const int c0 = cc + t, c1 = c0 + 24, c2 = cc + 16 - 6 * h + (t >> 1);
  const uint32_t r0 = xt + (w * 16 + g) * 128;
#pragma unroll
  for (int r = 0; r < 2; r++) {
    const uint4 u = lds128(r0 + r * 1024 + (c0 >> 3) * A_SLOT + (((c0 ^ g) & 7) << 4)), v = lds128(r0 + r * 1024 + (c1 >> 3) * A_SLOT + (((c1 ^ g) & 7) << 4));
    const float2 z = lds64f(r0 + r * 1024 + (c2 >> 3) * A_SLOT + (((c2 ^ g) & 7) << 4) + (t & 1) * 8);
    xw[r][0] = u.x; xw[r][1] = u.y; xw[r][2] = u.z; xw[r][3] = u.w;
    xw[r][4] = v.x; xw[r][5] = v.y; xw[r][6] = v.z; xw[r][7] = v.w;
    xw[r][8] = __float_as_uint(z.x); xw[r][9] = __float_as_uint(z.y);
  }
}
__device__ __forceinline__ void final_s_early(uint32_t (*sw)[10], const uint32_t (*xw)[10], uint32_t ya, float2 s0, float2 s1) {
  const uint32_t r2[2] = {pack2(s0.y, s0.y), pack2(s1.y, s1.y)};
  const float na = -s0.x * bf_lo(r2[0]), nb = -s1.x * bf_lo(r2[1]);
  const uint32_t n2[2] = {pack2(na, na), pack2(nb, nb)};
#pragma unroll
  for (int j = 0; j < 10; j += 2) {
    uint32_t y[4];
    if (j < 4 || j == 8) ldsm4t(y, ya + (j < 4 ? j : 4) * 1024);
#pragma unroll
    for (int e = 0; e < 4; e++) {
      const uint32_t xn = hfma2(xw[e & 1][j + (e >> 1)], r2[e & 1], n2[e & 1]);
      sw[e & 1][j + (e >> 1)] = (j < 4 || j == 8) ? hmul2(xn, y[e]) : xn;
    }
  }
}
__device__ __forceinline__ bool final_late(uint32_t* y, uint32_t ya) {
  ldsm4t(y, ya + 6144);
  ldsm4t(y + 4, ya + 8192);
  uint32_t zero = 0;
#pragma unroll
  for (int e = 0; e < 8; e++) zero |= (y[e] - 0x00010001u) & ~y[e];
  return (zero & 0x80008000u) == 0;
}
__device__ __forceinline__ bool bar_all(int id, int n, bool c) {
  uint32_t r;
  asm volatile("{\n.reg .pred p, q;\nsetp.ne.u32 p, %3, 0;\nbar.red.and.pred q, %1, %2, p;\nselp.u32 %0, 1, 0, q;\n}\n" : "=r"(r) : "r"(id), "r"(n), "r"((uint32_t)c) : "memory");
  return r;
}
__device__ __forceinline__ void final_out(const float* d, const uint32_t (*xw)[10], const uint32_t (*sw)[10], float ra, float rb, __nv_bfloat16* o0, int h, int t) {
  const float ca = 0.25f * ra, cb = 0.25f * rb;
  uint32_t o[2][10];
#pragma unroll
  for (int j = 0; j < 10; j++) {
#pragma unroll
    for (int r = 0; r < 2; r++) {
      const float h0 = d[4 * j + 2 * r] * (r ? cb : ca), h1 = d[4 * j + 2 * r + 1] * (r ? cb : ca);
      o[r][j] = hfma2(pack2(fmaf(h0, tanh_fast(h0), h0), fmaf(h1, tanh_fast(h1), h1)), sw[r][j], xw[r][j]);
      __nv_bfloat16* q = o0 + r * 8 * kD;
      if (j == 3) stg4_if(q + t * 8, o[r][0], o[r][1], o[r][2], o[r][3], true);
      if (j == 7) stg4_if(q + 192 + t * 8, o[r][4], o[r][5], o[r][6], o[r][7], true);
      if (j == 9) asm volatile("st.global.v2.u32 [%0], {%1,%2};" ::"l"(q + 128 - 48 * h + t * 4), "r"(o[r][8]), "r"(o[r][9]) : "memory");
    }
  }
}

struct Taps { uint4 r0, r1; uint32_t n0, n1, dd; };
__device__ __forceinline__ void load_taps(Taps& k, const Params& p, int ch, int tid) {
  const uint4* kp = (const uint4*)(p.ssmk + (size_t)ch * kS);
  k.r0 = ldg4(kp + tid); k.r1 = ldg4(kp + 128 + tid);
  k.n0 = ldg1(kp + tid + 1); k.n1 = tid < 127 ? ldg1(kp + 129 + tid) : 0u;
  k.dd = __bfloat16_as_ushort(p.ssmD[ch]);
}
__device__ __forceinline__ void load_convx(const Params& p, uint32_t cv, uint32_t bar, int ch) {
  mbar_expect(bar, 4096);
  bulk_g2s(cv, p.scr->kvx + (size_t)ch * 4096, 2048, bar);
  bulk_g2s(cv + XB_PL, p.scr->kvx + (size_t)ch * 4096 + 2048, 2048, bar);
}
#define CW 3
#define CSTAMP(j)
__device__ __forceinline__ void zero_pads(uint32_t cv, int lane) {
  if (lane < 8) sts128(cv + (lane >> 2) * XB_PL + 2048 + (lane & 3) * 16, 0, 0, 0, 0);
  else if (lane < 12) sts128(cv + ((lane & 2) ? CV_KO : CV_KE) + (lane & 1) * 16, 0, 0, 0, 0);
  fence_async_smem();
  __syncwarp();
}
__device__ __forceinline__ int y_row(int c, uint32_t par) {
  const int hf = c >= 320, cc = c - hf * 320, u = cc >> 6, cb = hf * 2 + ((cc >> 5) & 1);
  if (u == 2) return cb * 96 + ((cc >> 4) & 1) * 48 + 32 + (cc & 1) + ((cc >> 1) & 1) * 8 + ((cc >> 2) & 3) * 2;
  return (u < 2 ? cb * 96 + u * 48 : 384 + par * 256 + cb * 64 + (u - 3) * 32) + (cc & 1) + ((cc >> 1) & 3) * 8 + ((cc >> 3) & 3) * 2;
}
__device__ __forceinline__ void z_store(uint8_t* dst, uint32_t src, int q) {
  dst += q * 16 * B_SLOT;
  bulk_s2g(dst, src + q * 12288, 6144);
  bulk_s2g(dst + 8 * B_SLOT, src + q * 12288 + 6144, 6144);
  asm volatile("cp.async.bulk.commit_group;\ncp.async.bulk.wait_group 0;" ::: "memory");
}
__device__ __forceinline__ void y_store(const Params& p, uint32_t sb, int h, int ch, uint32_t par) {
  uint8_t* dst = p.scr->y + (size_t)y_row(ch, par) * 4096;
  if (elect_one()) {
    bulk_s2g(dst, sb + OFF_A + 9 * A_SLOT + h * 4096, 4096);
    asm volatile("cp.async.bulk.commit_group;\ncp.async.bulk.wait_group 0;" ::: "memory");
  }
  __syncwarp();
}
__device__ __forceinline__ void conv_service(const Params& p, uint32_t sb, int h, int ch, bool first) {
  bar_sync(NB_WGA + 8 + h, 160);
  const bool now = !first || __all_sync(0xffffffff, mbar_test(sb + BAR_KV, 0));
  if (now && elect_one()) load_convx(p, sb + OFF_CV + (1 - h) * CV_SZ, sb + BAR_XF + 8 * h, ch + 128);
  bar_sync(NB_WGA + 8 + h, 160);
  y_store(p, sb, h, ch, 0);
  if (!now) {
    mbar_wait(sb + BAR_KV, 0);
    if (elect_one()) load_convx(p, sb + OFF_CV + (1 - h) * CV_SZ, sb + BAR_XF + 8 * h, ch + 128);
  }
}
__device__ __forceinline__ uint32_t y_tile(int h) { return OFF_CV + (1 - h) * 13312; }
__device__ __forceinline__ void load_late_y(const Params& p, uint32_t sb, int h, int rb, int cb, uint32_t par) {
  mbar_expect(sb + BAR_YL + 16 * h, 4096);
  tma2d(sb + y_tile(h) + 6144, &p.tmY, rb * 64, 384 + par * 256 + cb * 64 + h * 32, sb + BAR_YL + 16 * h);
  tma2d(sb + y_tile(h) + 8192, &p.tmY, rb * 64, 400 + par * 256 + cb * 64 + h * 32, sb + BAR_YL + 16 * h);
}
__device__ __forceinline__ void held_service(const Params& p, uint32_t sb, int h, int ch, int rb, int cb, uint32_t tag, int lane) {
#pragma unroll 1
  for (int i = 0; i < 8; i++) sts128(sb + OFF_A + 9 * A_SLOT + h * 4096 + i * 512 + lane * 16, 0, 0, 0, 0);
  fence_async_smem();
  __syncwarp();
  y_store(p, sb, h, ch, ~tag & 1);
  mbar_wait(sb + BAR_YT, 1);
  uint8_t* dst = p.scr->y + (size_t)y_row(ch, tag & 1) * 4096;
  asm volatile("" : "+l"(dst));
  bar_sync(NB_WGA + 8 + h, 160);
  bar_sync(NB_WGA + 8 + h, 160);
  if (elect_one()) {
    bulk_s2g(dst, sb + OFF_A + 9 * A_SLOT + h * 4096, 4096);
    asm volatile("cp.async.bulk.commit_group;" ::: "memory");
    mbar_expect(sb + BAR_XF + 8 * h, 6144);
#pragma unroll 1
    for (int i = 0; i < 3; i++) tma2d(sb + y_tile(h) + i * 2048, &p.tmY, rb * 64, cb * 96 + h * 48 + i * 16, sb + BAR_XF + 8 * h);
  }
  mbar_wait(sb + BAR_AE + 8 * (LL_AT - 1), 1);
  if (elect_one()) { load_late_y(p, sb, h, rb, cb, tag & 1); asm volatile("cp.async.bulk.wait_group 0;" ::: "memory"); }
}
__device__ __forceinline__ void conv_worker(const Params& p, Taps& k, uint32_t cv, uint32_t yb0,
                                            uint32_t xbar, int nbar, int ch0, int n, uint32_t holdbar, int w, int lane,
                                            int tid, int st0, int rb, int cb) {
  const int g = lane >> 2, t = lane & 3, w0 = w & 1, w1 = w >> 1;
  const uint32_t ab = cv + ((g & 1) ? CV_KE : CV_KO) + 32 + 2 * (64 * w0 + 8 * w1 + ((g - 15) & ~1) + 2 * t);
  const uint32_t scA = cv + (w1 ? CV_KO : CV_KE) + 32, scB = scA + 2048;
  const int dl = (t >> 1) ^ 1;
  if (n == 2) mbar_wait(xbar, 0);
  STAMPW(st0 + 3);
#pragma unroll 1
  for (int i = 0; i < n; i++) {
    if (tid == 0) {
      k.r0.x = (k.r0.x & 0xffff0000u) | (pack2(bf_lo(k.r0.x) + bf_lo(k.dd), 0.f) & 0xffffu);
      sts32(cv + CV_KO + 28, k.r0.x << 16);
    }
    sts128(cv + CV_KE + 32 + tid * 16, k.r0.x, k.r0.y, k.r0.z, k.r0.w);
    sts128(cv + CV_KO + 32 + tid * 16, prmt(k.r0.x, k.r0.y, 0x5432), prmt(k.r0.y, k.r0.z, 0x5432), prmt(k.r0.z, k.r0.w, 0x5432), prmt(k.r0.w, k.n0, 0x5432));
    sts128(cv + CV_KE + 2080 + tid * 16, k.r1.x, k.r1.y, k.r1.z, k.r1.w);
    sts128(cv + CV_KO + 2080 + tid * 16, prmt(k.r1.x, k.r1.y, 0x5432), prmt(k.r1.y, k.r1.z, 0x5432), prmt(k.r1.z, k.r1.w, 0x5432), prmt(k.r1.w, k.n1, 0x5432));
    if (i + 1 < n) load_taps(k, p, ch0 + (i + 1) * 128, tid);
    bar_sync(nbar, 128);
    CSTAMP(0);
    const uint64_t db = mkdesc(cv + (i & 0x1000), XB_PL, 128, 0);
    float d[64];
    uint32_t a[8][16];
    if (i == 0) mbar_wait(xbar, 0);
    conv_load<7>(a[7], ab); conv_load<6>(a[6], ab); conv_load<5>(a[5], ab); conv_load<4>(a[4], ab);
#pragma unroll
    for (int j = 0; j < 64; j++) d[j] = 0.f;
    mbar_wait(xbar, i & 1);
    if (i + 1 == n) mbar_wait(GO1 ? holdbar + (BAR_GO1 - BAR_GO) : holdbar, 1);
    CSTAMP(1);
    conv_step<7, -1>(d, a, ab, db); conv_step<6, -1>(d, a, ab, db); conv_step<5, -1>(d, a, ab, db); conv_step<4, -1>(d, a, ab, db);
    if (GO1 && i + 1 == n) mbar_wait(holdbar, 1);
    conv_load<3>(a[3], ab);
    conv_step<3, 2>(d, a, ab, db);
    conv_step<2, 1>(d, a, ab, db);
    conv_step<1, 0>(d, a, ab, db);
    conv_step<0, -1>(d, a, ab, db);
    acc_fence<64>(d);
    CSTAMP(2);
    bar_sync(nbar + 8, 160);
    float E[16][2];
#pragma unroll
    for (int j = 0; j < 15; j++) { E[j][0] = d[4 * j] + d[4 * j + 6]; E[j][1] = d[4 * j + 1] + d[4 * j + 7]; }
    E[15][0] = d[60]; E[15][1] = d[61];
    if (w0 == 0) {
#pragma unroll
      for (int j = 8; j < 16; j++) sts64f(scA + (j - 8) * 256 + lane * 8, E[j][0], E[j][1]);
    } else {
      const uint32_t a = scB - dl * 256 + (lane ^ 2) * 8;
#pragma unroll
      for (int j = 1; j < 8; j++) sts64f(a + j * 256, E[j][0], E[j][1]);
      sts64f(scB + (dl ? 7 * 256 : 0) + (lane ^ 2) * 8, dl ? E[8][0] : E[0][0], dl ? E[8][1] : E[0][1]);
    }
    bar_sync(nbar, 128);
    CSTAMP(3);
    uint32_t pk[8];
    if (w0 == 0) {
#pragma unroll
      for (int j = 0; j < 8; j++) { const float2 v = lds64f(scB + j * 256 + lane * 8); pk[j] = pack2(E[j][0] + v.x, E[j][1] + v.y); }
    } else {
      const uint32_t a0 = scA - dl * 256 + (lane ^ 2) * 8;
#pragma unroll
      for (int j = 9; j < 16; j++) { const float2 v = lds64f(a0 + (j - 8) * 256); pk[j - 8] = pack2(E[j][0] + v.x, E[j][1] + v.y); }
      const float2 v = lds64f(scA + (dl ? 7 * 256 : 0) + (lane ^ 2) * 8);
      pk[0] = pack2((dl ? 0.f : E[8][0]) + v.x, (dl ? 0.f : E[8][1]) + v.y);
    }
    CSTAMP(4);
    if (i + 1 == n) {
#pragma unroll
      for (int j = 0; j < 8; j++) pk[j] = ~pk[j];
    }
    const int c1 = (w0 ? 35 : 95) - lane, c0 = (w0 && lane < 4) ? c1 - 32 : c1 + 32;
    stsm4t(yb0 + 128 * (c0 & 31) + (((2 * (c0 >> 5) + w1) ^ (c0 & 7)) << 4), pk[0], pk[1], pk[2], pk[3]);
    stsm4t(yb0 + 128 * (c1 & 31) + (((2 * (c1 >> 5) + w1) ^ (c1 & 7)) << 4), pk[4], pk[5], pk[6], pk[7]);
    fence_async_smem();
    bar_sync(nbar + 8, 160);
    CSTAMP(5);
    STAMPW(st0 + i);
    if (n == 2 && i == 0) {
      const int u = (tid >> 3) % 5, kg = rb * 3 + (tid < 120 ? (tid >> 3) / 5 : 0), c = u < 4 ? (u >> 1) * 10 + (u & 1) * 4 : 8, o2 = u < 4 ? 2 : 10;
      const uint4* wp = (const uint4*)p.wout + (uint32_t)((kg * 8 + (tid & 7)) * (kD / 8) + (seg_col(cb, 0) >> 3) + (u < 4 ? (u >> 1) * 8 + (u & 1) * 24 : 16));
      const uint4 w0 = ldg4(wp), w1 = ldg4(wp + 1), w2 = ldg4(wp + 2), w3 = ldg4(wp + 3);
      uint8_t* dst = p.scr->wo + (uint32_t)(cb * (12 * 20480) + kg * 2560 + c * 128 + (tid & 7) * 16);
      const bool f = u < 4, on = tid < 120;
      stg4_if(dst, w0.x, f ? w1.x : w0.z, f ? w2.x : w1.x, f ? w3.x : w1.z, on);
      stg4_if(dst + 128, w0.y, f ? w1.y : w0.w, f ? w2.y : w1.y, f ? w3.y : w1.w, on);
      stg4_if(dst + o2 * 128, f ? w0.z : w2.x, f ? w1.z : w2.z, f ? w2.z : w3.x, w3.z, on);
      stg4_if(dst + o2 * 128 + 128, f ? w0.w : w2.y, f ? w1.w : w2.w, f ? w2.w : w3.y, w3.w, on);
      bar_arrive(NB_WO, 160);
    }
  }
}

struct KvRegs { uint32_t k[11], v[8]; uint4 sh; };
__device__ __forceinline__ void kv_load(KvRegs& q, const __nv_bfloat16* kp, const __nv_bfloat16* vp, const __nv_bfloat16* sp, bool halo) {
#pragma unroll
  for (int i = 0; i < 11; i++) q.k[i] = (i >= 3 || halo) ? ldg1(kp + i * kD) : 0u;
#pragma unroll
  for (int i = 0; i < 8; i++) q.v[i] = ldg1(vp + i * kD);
  q.sh = ldg4(sp);
}
__device__ __forceinline__ void kv_unit(const KvRegs& q, uint32_t oa) {
  const uint32_t w0 = prmt(q.sh.x, q.sh.z, 0x5410), w1 = prmt(q.sh.x, q.sh.z, 0x7632), w2 = prmt(q.sh.y, q.sh.w, 0x5410), w3 = prmt(q.sh.y, q.sh.w, 0x7632);
  uint32_t r[8];
#pragma unroll
  for (int i = 0; i < 8; i++) r[i] = hmul2(hfma2(q.k[i + 3], w0, hfma2(q.k[i + 2], w1, hfma2(q.k[i + 1], w2, hmul2(q.k[i], w3)))), q.v[i]);
  sts128(oa, prmt(r[7], r[6], 0x5410), prmt(r[5], r[4], 0x5410), prmt(r[3], r[2], 0x5410), prmt(r[1], r[0], 0x5410));
  sts128(oa + 2048, prmt(r[7], r[6], 0x7632), prmt(r[5], r[4], 0x7632), prmt(r[3], r[2], 0x7632), prmt(r[1], r[0], 0x7632));
}

__device__ __forceinline__ void gather_colsum(const Params& p, uint32_t sb, int cb, int part, uint32_t tag, int lane) {
  uint4 v[3];
  uint32_t t0 = 0;
#pragma unroll 1
  while (true) {
    bool ok = true;
#pragma unroll
    for (int i = 0; i < 3; i++) {
      v[i] = ld_ll4(&p.scr->colsum[(part ? 0 : 768) + cb * 192 + i * 64 + lane * 2]);
      ok = ok && v[i].y == tag && v[i].w == tag;
    }
    if (__all_sync(0xffffffff, ok)) break;
    spin_guard(t0);
  }
#pragma unroll
  for (int i = 0; i < 3; i++) {
    const uint32_t hi = pack2(__uint_as_float(v[i].x), __uint_as_float(v[i].z)), ca = sb + OFF_CS + (1 - part) * 768 + i * 256 + (lane >> 2) * 32 + (lane & 3) * 4;
    sts32(ca, hi);
    sts32(ca + 16, pack2(__uint_as_float(v[i].x) - bf_lo(hi), __uint_as_float(v[i].z) - bf_hi(hi)));
  }
  __syncwarp();
  if (lane == 0) mbar_arrive(sb + BAR_ST + 8 * part);
}

__device__ __forceinline__ void helper_cta(const Params& p, uint32_t sb, int cb, int warp, int lane) {
  constexpr int NS = 9, ONES = NS * B_SLOT, BF = ONES + 256, BE = BF + 8 * NS;
  if (warp < NS && elect_one()) {
    mbar_init(sb + BF + 8 * warp, 1); mbar_init(sb + BE + 8 * warp, 1);
    fence_async_smem();
    if (warp == 0) { mbar_expect(sb + BF, B_SLOT); tma3d(sb, &p.tmW, 0, 0, 12 + cb * 3, sb + BF); }
  }
  if (warp == 15) { sts32(sb + ONES + lane * 4, 0x3f803f80u); sts32(sb + ONES + 128 + lane * 4, 0x3f803f80u); fence_async_smem(); }
  __syncthreads();
  if (warp == 4) {
    int s = 1, ph = 1;
    uint32_t tp = clock() + HP0;
#pragma unroll 1
    for (int it = 1; it < 20; it++) {
      if (HPD && it >= 10) pace(tp, HPD);
      mbar_wait(sb + BE + 8 * s, ph);
      if (elect_one()) { mbar_expect(sb + BF + 8 * s, B_SLOT); tma3d(sb + s * B_SLOT, &p.tmW, 0, (it < 10 ? it : it - 10) * 64, (it < 10 ? 12 : 0) + cb * 3, sb + BF + 8 * s); }
      if (++s == NS) { s = 0; ph ^= 1; }
    }
  } else if (warp < 4) {
    const uint32_t tag = load_epoch(p, 128 + cb, lane) + 1;
    const uint64_t db = mkdesc(sb + ONES, 128, 128, 0);
    uint2* dst = p.scr->colsum + cb * 192 + warp * 16 + (lane >> 2);
    if ((lane & 3) == 0) {
#pragma unroll 1
      for (int j = 0; j < 12; j++) st_ll2(dst + (j < 6 ? 768 : 0) + ((j % 6) >> 1) * 64 + (j & 1) * 8, 0, 0);
    }
    int s = 0, ph = 0;
#pragma unroll 1
    for (int part = 0; part < 2; part++) {
      float d[12];
#pragma unroll
      for (int i = 0; i < 12; i++) d[i] = 0.f;
#pragma unroll 1
      for (int it = 0; it < 10; it++) {
        mbar_wait(sb + BF + 8 * s, ph);
        const uint64_t da = mkdesc(sb + s * B_SLOT, 8192, 1024, 1);
        WG_FENCE();
#pragma unroll
        for (int j = 0; j < 12; j++) wgmma_colsum(d + 4 * (j % 3), da + (j % 3) * 512 + (j / 3) * 128, db);
        WG_COMMIT();
        WG_WAIT(1);
        mbar_arrive_if(sb + BE + 8 * (s == 0 ? NS - 1 : s - 1), threadIdx.x == 0 && (it | part) != 0);
        if (++s == NS) { s = 0; ph ^= 1; }
      }
      WG_WAIT(0);
      acc_fence<12>(d);
      if ((lane & 3) == 0) {
#pragma unroll
        for (int j = 0; j < 6; j++) st_ll2(dst + (part ? 0 : 768) + (j >> 1) * 64 + (j & 1) * 8, __float_as_uint(d[2 * j]), tag);
      }
      STAMPW(1 + part);
    }
    if (threadIdx.x == 0) st_relaxed(&p.scr->epoch[(128 + cb) * EPS], tag);
  }
}

__global__ void __launch_bounds__(512, 1) fused_kernel(const __grid_constant__ Params p) {
  extern __shared__ __align__(1024) uint8_t smem[];
  const int warp = __shfl_sync(0xffffffff, (int)(threadIdx.x >> 5), 0);
  const int lane = threadIdx.x & 31, tid = threadIdx.x & 127;
  const uint32_t sb = __shfl_sync(0xffffffff, (uint32_t)__cvta_generic_to_shared(smem), 0);
  const uint32_t tstart = clock();
  if (elect_one()) {
    if (warp < 5) asm volatile("prefetch.tensormap [%0];" ::"l"(&p.tmX + warp) : "memory");
    mbar_init(sb + OFF_BAR + 8 * warp, 1); mbar_init(sb + OFF_BAR + 128 + 8 * warp, 1); mbar_init(sb + OFF_BAR + 256 + 8 * warp, 2);
    asm volatile("fence.mbarrier_init.release.cluster;" ::: "memory");
  }
  int b = blockIdx.x;
  if (p.by_smid) asm volatile("mov.u32 %0, %%smid;" : "=r"(b));
  b = __shfl_sync(0xffffffff, b, 0);
  const int tp = b >> 1, t7 = (tp - 32) / 7;
  const int lin = tp < 32 ? ((tp & 7) ? (tp & 7) * 16 : 8) + (tp >> 3) * 2 + (b & 1)
                          : (tp < 60 ? (tp - 31 - t7 * 7) * 16 + 8 + t7 * 2 + (b & 1) : (tp < 62 ? -1 : b - 124));
  const int hcb = b & 3;
  if (lin < 0) { helper_cta(p, sb, hcb, warp, lane); return; }
  const int cb = ((lin >> 4) & 1) * 2 + ((lin >> 1) & 1), rb = (lin >> 5) * 8 + ((lin >> 2) & 3) * 2 + (lin & 1);
  const int zs0 = 4 - (cb & 2);
  const int chb = (cb >> 1) * 320 + rb * 2 + (cb & 1);
  if (warp == 0 && elect_one()) {
    mbar_expect(sb + BAR_AF, A_SLOT);
    tma_rows(sb + OFF_A, &p.tmX, 0, rb, sb + BAR_AF);
    mbar_expect(sb + BAR_BF, B_SLOT);
    tma3d(sb + OFF_B, &p.tmW, 0, 0, 12 + cb * 3, sb + BAR_BF);
  }
  if (warp == 1) STAMP(31);
  if (sb & 1023) die();
  __syncthreads();

  if (warp >= 12) {
    asm volatile("setmaxnreg.dec.sync.aligned.u32 32;");
    uint32_t bias2 = 0;
    if (warp == 15) bias2 = ldg1(p.bsp + (lane >> 3) * 512 + rb * 16 + (lane & 7) * 2);
    const uint32_t epoch = load_epoch(p, lin, lane);
    if (warp == 12) {
#pragma unroll 1
      for (int i = 1; i < NA; i++) {
        if (elect_one()) {
          mbar_expect(sb + BAR_AF + 8 * i, A_SLOT);
          tma_rows(sb + OFF_A + i * A_SLOT, &p.tmX, i * 64, rb, sb + BAR_AF + 8 * i);
          if (i < NB) { mbar_expect(sb + BAR_BF + 8 * i, B_SLOT); tma3d(sb + OFF_B + i * B_SLOT, &p.tmW, 0, i * 64, 12 + cb * 3, sb + BAR_BF + 8 * i); }
        }
      }
      STAMP(32);
      uint32_t kvt;
      {
        const int tb = rb * 2 + (cb & 1);
        kvt = __shfl_sync(0xffffffff, (ld_relaxed(p.scr->cnt + (CNT_KV + (cb >> 1)) * CSP) & ~63u) + 64, 0);
        {
          uint32_t tp = tstart;
          pace(tp, KV_T0);
          mbar_arrive_if(sb + BAR_KV + 8, lane == 0);
        }
        if (ST_YIELD) mbar_wait2(sb + BAR_XS, 0, sb + BAR_ST, 0);
#pragma unroll 1
        for (int u = 0; u < 5; u++) {
          mbar_wait(sb + BAR_KU + 8 * u, 0);
          fence_async_smem();
          if (elect_one()) {
            asm volatile("cp.async.bulk.tensor.3d.global.shared::cta.bulk_group [%0, {%2, %3, %4}], [%1];\ncp.async.bulk.commit_group;" ::"l"(&p.tmKV),
                         "r"(sb + OFF_CV + CV_SZ + (u < 3 ? u : u - 3) * 4096), "r"((63 - tb) * 16), "r"((cb >> 1) * 160 + u * 32), "r"(0) : "memory");
            if (u == 1 || u == 4) asm volatile("cp.async.bulk.wait_group 0;" ::: "memory");
            if (u == 1) { mbar_arrive(sb + BAR_KU); red_release(p.scr->cnt + (CNT_KV + (cb >> 1)) * CSP); }
          }
          __syncwarp();
          if (u == 1) {
            STAMP(35);
            if (PFT) { const char* q = (const char*)p.ssmk + chb * 4096 + lane * 128; prefetch_l2(q); prefetch_l2(q + 64 * 4096); }
          }
        }
        zero_pads(sb + OFF_CV + CV_SZ, lane);
        if (elect_one()) { mbar_arrive(sb + BAR_KU + 8); red_release(p.scr->cnt + (CNT_KV + 2 + (cb >> 1)) * CSP); }
        STAMP(30);
        if (lane < 24) {
          const char* r = (const char*)p.wout + (rb * 24 + lane) * (kD * 2) + (cb >> 1) * 640 + (cb & 1) * 384;
          prefetch_l2(r); prefetch_l2(r + 128); prefetch_l2(r + 256 - (cb & 1) * 384);
        }
      }
      poll_counter(p.scr->cnt + (CNT_KV + 2 + (cb >> 1)) * CSP, kvt);
      if (elect_one()) mbar_arrive(sb + BAR_KV);
      STAMP(34);
      {
        const char* q = (const char*)p.wsp + (cb * 512 + rb * 16 + (lane >> 1)) * (kS * 2) + (lane & 1) * 128;
        uint32_t tp = clock();
#pragma unroll 1
        for (int i = LEAD / 2; i < WSP_N; i++) {
          prefetch_l2(q + i * 256);
          pace(tp, WSP_D);
        }
      }
      const uint32_t tag = epoch + 1;
      uint8_t* hrow = p.scr->h + anchor(rb * 12 * A_SLOT);
      uint8_t* hown = hrow + anchor(cb * 3 * A_SLOT);
      bar_sync(NB_Z2, 160);
      if (elect_one()) bulk_s2g(hown, sb + OFF_A + 5 * A_SLOT, A_SLOT);
      mbar_wait(sb + BAR_G2, 0);
      if (elect_one()) {
        bulk_s2g(hown + A_SLOT, sb + OFF_A + 6 * A_SLOT, 2 * A_SLOT);
        asm volatile("cp.async.bulk.commit_group;\ncp.async.bulk.wait_group 0;" ::: "memory");
        red_release(&p.scr->hcnt[(rb >> HGRP) * 32]);
      }
      __syncwarp();
      STAMP(20);
      mbar_wait(sb + BAR_AE + 56, 0);
      STAMP(39);
      const uint8_t* hsrc = cb ? hrow : hrow + 3 * A_SLOT;
      if (elect_one()) {
        poll_one(&p.scr->hcnt[(rb >> HGRP) * 32], tag * (4 << HGRP));
        bulk_g2s(sb + OFF_A + 8 * A_SLOT, hsrc, A_SLOT, sb + BAR_AF + 64);
        STAMP(37);
        uint32_t tp = clock();
#pragma unroll 1
        for (int i = 0; i < 8; i++) {
          hsrc += A_SLOT;
          if (hsrc == hown) hsrc += 3 * A_SLOT;
          tp += HPACE;
          while ((int32_t)((uint32_t)clock() - tp) < 0) {}
          bulk_g2s(sb + OFF_A + i * A_SLOT, hsrc, A_SLOT, sb + BAR_AF + 8 * i);
        }
      }
      STAMP(21);
    } else if (warp == 13) {
      int s = 0, ph = 0;
#pragma unroll 1
      for (int it = NB; it < 20; it++) {
        mbar_wait(sb + BAR_BE + 8 * s, ph);
        if (elect_one()) { mbar_expect(sb + BAR_BF + 8 * s, B_SLOT); tma3d(sb + OFF_B + s * B_SLOT, &p.tmW, 0, (it < 10 ? it : (it + zs0) % 10) * 64, (it < 10 ? 12 : 0) + cb * 3, sb + BAR_BF + 8 * s); }
        STAMP2(32 + it);
        if (++s == NB) { s = 0; ph ^= 1; }
      }
      mbar_wait(sb + BAR_XC, 0);
#pragma unroll 1
      for (int i = 0; i < LEAD; i++) {
        mbar_wait(sb + BAR_AE + 8 * i, 0);
        if (elect_one()) { mbar_expect(sb + BAR_AF + 8 * i, A_SLOT); tma_rows(sb + OFF_A + i * A_SLOT, &p.tmWsp, i * 64, rb, sb + BAR_AF + 8 * i); }
      }
#pragma unroll 1
      for (int i = 0; i < NB; i++) mbar_wait2(sb + BAR_BE + 8 * i, 1, sb + BAR_AE + 8 * (LEAD + i), 0);
      mbar_expect_if(sb + (lane < NB ? BAR_BF + 8 * lane : BAR_AF + 8 * (LEAD + lane - NB)), lane < NB ? B_SLOT : A_SLOT, lane < 2 * NB);
      const uint8_t* zt = p.scr->z2 + anchor(cb * 32 * B_SLOT);
      if (elect_one()) {
        poll_one(p.scr->zcnt + (cb >> ZSH) * 32, (epoch + 1) * (32 << ZSH));
        bulk_g2s(sb + OFF_B, zt, B_SLOT, sb + BAR_BF);
        uint32_t tp = clock();
#pragma unroll 1
        for (int it = 1; it < NB + LEAD; it++) {
          if (ZPACE) { tp += ZPACE; while ((int32_t)((uint32_t)clock() - tp) < 0) {} }
          if (it == LEAD) mbar_wait(sb + BAR_ZP, 0);
          if (it >= LEAD) tma_rows(sb + OFF_A + it * A_SLOT, &p.tmWsp, it * 64, rb, sb + BAR_AF + 8 * it);
          if (it < NB) bulk_g2s(sb + OFF_B + it * B_SLOT, zt + it * B_SLOT, B_SLOT, sb + BAR_BF + 8 * it);
        }
      }
      __syncwarp();
      STAMP(22);
      int sa = NB + LEAD, pa = 0;
      ph = 0;
#pragma unroll 1
      for (int it = NB; it < 32; it++) {
        if (it == 16) mbar_wait(sb + BAR_Z1, 1);
        mbar_wait2(sb + BAR_BE + 8 * s, ph, sb + BAR_AE + 8 * sa, pa);
        if (elect_one()) {
          mbar_expect(sb + BAR_BF + 8 * s, B_SLOT);
          bulk_g2s(sb + OFF_B + s * B_SLOT, zt + it * B_SLOT, B_SLOT, sb + BAR_BF + 8 * s);
          if (it + LEAD < 32) { mbar_expect(sb + BAR_AF + 8 * sa, A_SLOT); tma_rows(sb + OFF_A + sa * A_SLOT, &p.tmWsp, (it + LEAD) * 64, rb, sb + BAR_AF + 8 * sa); }
        }
        if (it + LEAD < 31 && ++sa == NA2) { sa = 0; pa ^= 1; }
        STAMP2(52 + it);
        if (++s == NB) { s = 0; ph ^= 1; }
      }
      mbar_wait(sb + BAR_WO, 0);
#pragma unroll 1
      for (int it = 0; it < 12; it++) {
        if (it < 6) mbar_wait(sb + BAR_BE + 8 * ((0x110443 >> (4 * it)) & 7), it < 3 ? 1 : 0);
        else mbar_wait(sb + BAR_BE + 8 * s, ph);
        if (elect_one()) {
          mbar_expect(sb + BAR_BF + 8 * s, 20480);
          bulk_g2s(sb + OFF_B + (s == 5 ? 0 : s + 1) * 20480, p.scr->wo + (size_t)(cb * 12 + g3_block(cb, it)) * 20480, 20480, sb + BAR_BF + 8 * s);
        }
        STAMP2(84 + it);
        if (++s == 6) { s = 0; ph ^= 1; }
      }
    } else if (warp == 14) {
      const uint32_t tag = epoch + 1;
      mbar_wait(sb + BAR_AF + 8 * (NA - 1), 0);
      gather_colsum(p, sb, cb, 0, tag, lane);
      STAMP(27);
      uint8_t* zd = p.scr->z2 + anchor((cb * 32 + (rb >> 2)) * B_SLOT + (rb & 3) * 6144);
      const uint32_t zsrc = anchor(sb + OFF_A + zs0 * A_SLOT);
      bar_sync(NB_Z, 160);
      if (elect_one()) {
        z_store(zd, zsrc, 0);
        STAMP(7);
        red_release(p.scr->zcnt + (cb >> ZSH) * 32);
      }
      STAMP(25);
      bar_sync(NB_Z2, 96);
      if (elect_one()) {
        z_store(zd, zsrc, 1);
        mbar_arrive(sb + BAR_ZP);
        red_release(p.scr->cnt + (CNT_Z1 + (cb >> 1)) * CSP);
      }
      STAMP(28);
      mbar_wait(sb + BAR_AE + 72, 0);
      conv_service(p, sb, 0, chb + 64, true);
      bar_sync(NB_WO, 160);
      bar_sync(NB_CD, 64);
      if (elect_one()) { red_release(p.scr->cnt + (CNT_WO + cb) * CSP); red_relaxed(p.scr->cnt + (CNT_Y + (cb >> 1)) * CSP); }
      STAMP(49);
      poll_counter(p.scr->cnt + (CNT_WO + cb) * CSP, tag * 32);
      if (elect_one()) mbar_arrive(sb + BAR_WO);
      STAMP(46);
      held_service(p, sb, 0, chb + 192, rb, cb, tag, lane);
    } else {
      const uint32_t tag = epoch + 1;
      sts32(sb + OFF_BIAS + lane * 4, bias2);
      if (lane < 2) sts32(sb + OFF_TAG + lane * 4, lane ? 0 : tag);
      fence_async_smem();
      uint32_t t0 = 0;
      mbar_wait(sb + BAR_AF + 8 * (NA - 1), 0);
#pragma unroll 1
      while (true) {
        const uint4 u = ld_ll4(&p.scr->xstat[rb * 64 + lane]), v = ld_ll4(&p.scr->xstat[rb * 64 + 32 + lane]);
        sts64f(sb + OFF_XS + lane * 8, __uint_as_float(u.x), __uint_as_float(u.z));
        sts64f(sb + OFF_XS + 256 + lane * 8, __uint_as_float(v.x), __uint_as_float(v.z));
        if (__all_sync(0xffffffff, u.y == tag && u.w == tag && v.y == tag && v.w == tag)) break;
        spin_guard(t0);
      }
      STAMP(26);
      __syncwarp();
      if (lane == 0) mbar_arrive(sb + BAR_XS);
      { uint32_t tp = tstart; pace(tp, CS1_T); gather_colsum(p, sb, cb, 1, tag, lane); STAMP(38); }
      mbar_wait(sb + BAR_KU, 1);
      poll_counter(p.scr->cnt + (CNT_KV + (cb >> 1)) * CSP, tag * 64);
      if (elect_one()) load_convx(p, sb + OFF_CV, sb + BAR_XF + 8, chb);
      mbar_wait(sb + BAR_KU + 8, 1);
      if (elect_one()) load_convx(p, sb + OFF_CV + CV_SZ, sb + BAR_XF, chb + 64);
      STAMP(48);
      mbar_wait(sb + BAR_AE + 72, 0);
#pragma unroll 1
      for (int i = 0; i < 2; i++) {
        conv_service(p, sb, 1, chb + i * 128, i == 0);
        if (i == 0) {
          poll_counter(p.scr->cnt + (CNT_Z1 + (cb >> 1)) * CSP, tag * 64);
          if (elect_one()) mbar_arrive(sb + BAR_Z1);
          STAMP(24);
        }
      }
      bar_arrive(NB_CD, 64);
      mbar_wait(sb + BAR_WO, 0);
      poll_counter(p.scr->cnt + (CNT_Y + (cb >> 1)) * CSP, tag * 64);
      STAMP(47);
      if (elect_one()) mbar_arrive(sb + BAR_YT);
      held_service(p, sb, 1, chb + 256, rb, cb, tag, lane);
      if (lane == 0) st_relaxed(&p.scr->epoch[lin * EPS], tag);
      STAMP(23);
    }
  } else {
    if (warp == 7) STAMP(36);
    const int wg = warp >> 2, w = warp & 3, g = lane >> 2, t = lane & 3;
    Taps k;
    uint32_t xw[2][10];
    if (wg == 2) {
      asm volatile("setmaxnreg.inc.sync.aligned.u32 160;");
      const int tb = rb * 2 + (cb & 1), c0 = (cb >> 1) * 320;
      const uint32_t cv = sb + OFF_CV + CV_SZ;
      if (w == 0) zero_pads(sb + OFF_CV, lane);
      mbar_wait(sb + BAR_KV + 8, 0);
      const int t0 = tb * 32 + w * 8;
      const __nv_bfloat16* kp = p.k + (size_t)(t0 - 3) * kD + c0 + lane * 2;
      const __nv_bfloat16* vp = p.v + (size_t)t0 * kD + c0 + lane * 2;
      const __nv_bfloat16* sp = p.shift + (c0 + lane * 2) * 4;
      const uint32_t oa = cv + ((3 - w) & 1) * 1024 + lane * 32 + ((((3 - w) >> 1) ^ (lane >> 2)) & 1) * 16;
#pragma unroll 1
      for (int r = 0; r < 2; r++) {
        KvRegs n0, n1, n2;
        STAMPW(r ? 51 : 50);
        kv_load(n0, kp + r * 128, vp + r * 128, sp + r * 512, t0 > 0);
        kv_load(n1, kp + r * 128 + 64, vp + r * 128 + 64, sp + r * 512 + 256, t0 > 0);
        if (r) kv_load(n2, kp + 256, vp + 256, sp + 1024, t0 > 0);
        kv_unit(n0, oa + r * 8192);
        bar_sync(NB_WGC, 128);
        mbar_arrive_if(sb + BAR_KU + 16 * r, tid == 0);
        if (r) mbar_wait(sb + BAR_KU, 1);
        kv_unit(n1, oa + (r ? 0 : 4096));
        bar_sync(NB_WGC, 128);
        mbar_arrive_if(sb + BAR_KU + 16 * r + 8, tid == 0);
        if (r) {
          kv_unit(n2, oa + 4096);
          bar_sync(NB_WGC, 128);
          mbar_arrive_if(sb + BAR_KU + 32, tid == 0);
        } else {
          mbar_wait(sb + BAR_AF + 8 * ((cb >> 1) * 5 + 1), 0);
          mbar_wait2(sb + BAR_AF + 8 * ((cb >> 1) * 5 + 2), 0, sb + BAR_AF + 8 * ((cb >> 1) * 5 + 4), 0);
          final_load_x(xw, sb + OFF_A, cb, 1, w, lane);
          fence_async_smem();
          bar_sync(NB_WGC, 128);
          mbar_arrive_if(sb + BAR_XC, tid == 0);
        }
      }
      STAMPW(13);
      load_taps(k, p, chb, tid);
    } else {
      float d[96];
      if (wg == 0) st_ll2(&p.scr->zstat[(rb * 256 + cb * 64 + w * 16 + g + (t >> 1) * 8) * 2 + (t & 1)], 0, 0);
      else if ((tid & 7) == 0) st_ll4(&p.scr->xstat[rb * 64 + cb * 16 + (tid >> 3)], 0, 0, 0, 0);
      {
        #pragma unroll
        for (int i = 0; i < 96; i++) d[i] = 0.f;
        {
          if (__builtin_expect(wg == 1, 0)) {
            const int tid = tid_now();
            const uint32_t epoch = load_epoch(p, lin, lane);
            float s = 0.f, q = 0.f;
#pragma unroll 1
            for (int i = 0; i < 10; i++) {
              mbar_wait(sb + BAR_AF + 8 * i, 0);
              const uint4 x4 = lds128(sb + OFF_A + i * A_SLOT + cb * 2048 + tid * 16);
              const uint32_t u[4] = {x4.x, x4.y, x4.z, x4.w};
#pragma unroll
              for (int e = 0; e < 4; e++) { const float a = bf_lo(u[e]), c = bf_hi(u[e]); s += a + c; q = fmaf(a, a, q); q = fmaf(c, c, q); }
            }
#pragma unroll
            for (int o = 1; o <= 4; o <<= 1) { s += __shfl_xor_sync(0xffffffff, s, o); q += __shfl_xor_sync(0xffffffff, q, o); }
            const float m = s * (1.f / kD);
            const float r = rsqrtf(fmaxf(fmaf(-m, m, q * (1.f / kD)), 0.f) + 1e-5f);
            if ((tid & 7) == 0) st_ll4(&p.scr->xstat[rb * 64 + cb * 16 + (tid >> 3)], __float_as_uint(m), epoch + 1, __float_as_uint(r), epoch + 1);
            STAMPW(12);
            bar_sync(NB_G1, 256);
          }
          gemm_loop<192, true, 0, D1>(d, sb, 10, wg ? zs0 : 0, 0, 0, 0, wg, 2, tid_now(), [&]() { if (G1_AT == 0 && wg == 0) bar_arrive(NB_G1, 256); }, [](int) {});
          asm volatile("setmaxnreg.inc.sync.aligned.u32 160;");
          STAMPW(wg ? 14 : 1);
          if (wg == 0) ZS(0);
          mbar_wait2(sb + BAR_XS, 0, sb + BAR_ST + 8 * wg, 0);
          if (wg == 0) ZS(1);
        }
        const int t1 = tid_now();
        const uint32_t xa1 = sb + OFF_XS + (w * 16 + ((t1 & 31) >> 2)) * 8;
        const float2 s0 = lds64f(xa1), s1 = lds64f(xa1 + 64);
        uint32_t z[48];
        float st[4];
        fence_async_smem();
        fold_mean(d, sb + OFF_CS + (1 - wg) * 768, s0.x, s1.x, t1 & 3);
        if (G1_AT == 1 && wg == 0) bar_arrive(NB_G1, 256);
        WG_WAIT(0);
        acc_fence<96>(d);
        if (wg == 0) ZS(2);
        gelu_tile(d, z, st, s0.y, s1.y);
        const int tid = tid_now(), lane = tid & 31, g = lane >> 2, t = lane & 3;
        if (wg == 1) {
          uint32_t bra, brb;
          asm volatile("ld.shared.u16 %0, [%1];" : "=r"(bra) : "r"(sb + OFF_BIAS + (w * 16 + g) * 2));
          asm volatile("ld.shared.u16 %0, [%1+16];" : "=r"(brb) : "r"(sb + OFF_BIAS + (w * 16 + g) * 2));
#pragma unroll
          for (int j = 0; j < 96; j++) d[j] = bf_lo((j & 2) ? brb : bra);
          STAMPW(15);
          gemm_loop<192, true, 1, D2>(d, sb, 32, 0, 1, 20, 0, 2, 2, tid, [&]() { if (HOLD_AT < 32) mbar_arrive_if(sb + BAR_GO, tid == 0); if (GO1 == 1) mbar_arrive_if(sb + BAR_GO1, tid == 0); }, [](int) {});
          if (GO1 == 2) mbar_arrive_if(sb + BAR_GO1, tid == 0);
          if (HOLD_AT == 32) mbar_arrive_if(sb + BAR_GO, tid == 0);
          STAMPW(16);
          const int t2 = tid_now(), l2 = t2 & 31;
          const uint32_t ha = sb + OFF_A + 5 * A_SLOT + (l2 >> 4) * 1024 + (2 * w + ((l2 >> 3) & 1)) * 128 + (l2 & 7) * 16;
#pragma unroll
          for (int j = 0; j < 24; j += 2) {
#pragma unroll
            for (int e = 0; e < 4; e++) z[2 * j + e] = hmul2(z[2 * j + e], pack2(d[4 * j + 2 * e], d[4 * j + 2 * e + 1]));
            stsm4(ha + j * 1024, z[2 * j], z[2 * j + 1], z[2 * j + 2], z[2 * j + 3]);
            if (j == 6) {
              fence_async_smem();
              bar_arrive(NB_Z2, 160);
            }
          }
          fence_async_smem();
          bar_sync(NB_WGB, 128);
          mbar_arrive_if(sb + BAR_AF + 8 * (t2 == 3 ? (BAR_G2 - BAR_AF) / 8 : (t2 == 4 ? (BAR_GO - BAR_AF) / 8 : 5 + t2)), t2 < (HOLD_AT == 33 ? 5 : 4));
          STAMPW(17);
          {
            float e[80];
            gemm_loop<160, false, 2, DB>(e, sb, 12, 5, 0, 2, 0, 2, 2, tid_now(), []() {}, [](int) {});
            STAMPW(10);
            const int t3 = tid_now();
#pragma unroll
            for (int j = 0; j < 10; j++) {
              sts128(sb + OFF_A + j * 2048 + t3 * 16, pack2(e[8 * j], e[8 * j + 1]), pack2(e[8 * j + 2], e[8 * j + 3]), pack2(e[8 * j + 4], e[8 * j + 5]),
                     pack2(e[8 * j + 6], e[8 * j + 7]));
              if (j == 4) bar_arrive(NB_WO, 256);
            }
            bar_arrive(NB_Z, 256);
            STAMPW(45);
          }
          return;
        }
        ZS(3);
        const bool hi = t & 2;
        float a0 = (hi ? st[2] : st[0]) + __shfl_xor_sync(0xffffffff, hi ? st[0] : st[2], 2);
        float a1 = (hi ? st[3] : st[1]) + __shfl_xor_sync(0xffffffff, hi ? st[1] : st[3], 2);
        a0 = ((t & 1) ? a1 : a0) + __shfl_xor_sync(0xffffffff, (t & 1) ? a0 : a1, 1);
        const uint32_t tag = lds32<0>(sb + OFF_TAG);
        uint2* zs = p.scr->zstat + (rb * 256 + w * 16 + g + (t >> 1) * 8) * 2 + (t & 1);
        st_ll2(zs + cb * 128, __float_as_uint(a0), tag);
        STAMPW(2); ZS(4);
        uint2 u[4];
#pragma unroll
        for (int i = 0; i < 4; i++) u[i] = ld_ll2(zs + i * 128);
        const uint32_t keep = (cb & 2) ? 13 << 5 : 13;
        mbar_arrive_if(sb + BAR_AE + 8 * tid, tid < NA && !((keep >> tid) & 1));
        const uint32_t za = sb + OFF_A + zs0 * A_SLOT + (2 * w + ((lane >> 3) & 1)) * 3072 + (lane >> 4) * 128 + (lane & 7) * 16;
        const float ca = 0.5f * (hi ? s1.y : s0.y), inv = 1.f / 768.f;
        mbar_wait2(sb + BAR_AE + 8 * (zs0 + 2), 0, sb + BAR_XC, 0);
        ZS(6);
        uint32_t t0 = 0;
#pragma unroll 1
        while (!__all_sync(0xffffffff, u[0].y == tag && u[1].y == tag && u[2].y == tag && u[3].y == tag)) {
          spin_guard(t0);
#pragma unroll
          for (int i = 0; i < 4; i++) u[i] = ld_ll2(zs + i * 128);
        }
        STAMPW(3); ZS(7);
        a0 = ((__uint_as_float(u[0].x) + __uint_as_float(u[1].x)) + (__uint_as_float(u[2].x) + __uint_as_float(u[3].x))) * inv;
        a1 = __shfl_xor_sync(0xffffffff, a0, 1);
        const float m = (t & 1) ? a1 : a0, q = (t & 1) ? a0 : a1;
        const float r = bf_lo(pack2(ca * rsqrtf(fmaf(fmaxf(fmaf(-m, m, q), 0.f), ca * ca, 1e-5f)), 0.f));
        const uint32_t rn = pack2(r, -m * r), ro = __shfl_xor_sync(0xffffffff, rn, 2);
        const uint32_t ra2 = prmt(hi ? ro : rn, 0, 0x1010), n2a = prmt(hi ? ro : rn, 0, 0x3232), rb2 = prmt(hi ? rn : ro, 0, 0x1010), n2b = prmt(hi ? rn : ro, 0, 0x3232);
        if (w >= 2) bar_sync(NB_Z, 160);
#pragma unroll
        for (int j = 0; j < 24; j += 2)
          stsm4(za + j * 128, hfma2(z[2 * j], ra2, n2a), hfma2(z[2 * j + 1], rb2, n2b), hfma2(z[2 * j + 2], ra2, n2a), hfma2(z[2 * j + 3], rb2, n2b));
        ZS(8);
        fence_async_smem();
        ZS(9);
        if (w < 2) bar_arrive(NB_Z, 160);
        else bar_arrive(NB_Z2, 96);
        final_load_x(xw, sb + OFF_A, cb, 0, w, lane);
        fence_async_smem();
        bar_sync(NB_WGA, 128);
        mbar_arrive_if(sb + BAR_AE + 8 * tid, tid < NA && ((keep >> tid) & 1));
      }
      {
        const uint32_t zero = lds32<0>(sb + OFF_TAG + 4);
#pragma unroll
        for (int i = 0; i < 20; i++) xw[i / 10][i % 10] |= zero;
      }
      load_taps(k, p, chb + 64, tid_now());
      STAMPW(4);
    }
    const int h = wg >> 1;
    {
    const int tid = tid_now(), lane = tid & 31;
    conv_worker(p, k, sb + OFF_CV + (1 - h) * CV_SZ, sb + OFF_A + 9 * A_SLOT + h * 4096, sb + BAR_XF + 8 * h, NB_WGA + h,
                chb + (h ? 0 : 64), 2 + h, sb + BAR_GO, w, lane, tid, h ? 40 : 5, rb, cb);
    {
      const int t3 = tid_now(), l3 = t3 & 31;
      const uint32_t xs_addr = sb + OFF_XS + (w * 16 + (l3 >> 2)) * 8;
      const float2 s0 = lds64f(xs_addr), s1 = lds64f(xs_addr + 64);
      const uint32_t ya = sb + y_tile(h) + ((l3 >> 4) * 8 + (l3 & 7)) * 128 + (((2 * w + ((l3 >> 3) & 1)) ^ (l3 & 7) ^ (rb & 7)) << 4);
      uint32_t sw[2][10];
      mbar_wait(sb + BAR_XF + 8 * h, h);
      final_s_early(sw, xw, ya, s0, s1);
      uint32_t ph = 1, t0 = 0, y[8];
#pragma unroll 1
      while (true) {
        mbar_wait(sb + BAR_YL + 16 * h, ph);
        if (bar_all(NB_WGA + h, 128, final_late(y, ya))) break;
        spin_guard(t0);
        ph ^= 1;
        if (t3 == 0) load_late_y(p, sb, h, rb, cb, lds32<0>(sb + OFF_TAG) & 1);
      }
#pragma unroll
      for (int e = 0; e < 8; e++) sw[e & 1][4 + (e >> 1)] = hmul2(sw[e & 1][4 + (e >> 1)], ~y[e]);
      __nv_bfloat16* o0 = p.out + (size_t)(w * 512 + rb * 16 + (l3 >> 2)) * kD + seg_col(cb, h);
      STAMPW(h ? 44 : 9);
      bar_sync(h ? NB_Z : NB_WO, 256);
      float d[40];
#pragma unroll
      for (int j = 0; j < 5; j++) {
        const uint4 v = lds128(sb + OFF_A + (h * 5 + j) * 2048 + t3 * 16);
        d[8 * j] = bf_lo(v.x); d[8 * j + 1] = bf_hi(v.x); d[8 * j + 2] = bf_lo(v.y); d[8 * j + 3] = bf_hi(v.y);
        d[8 * j + 4] = bf_lo(v.z); d[8 * j + 5] = bf_hi(v.z); d[8 * j + 6] = bf_lo(v.w); d[8 * j + 7] = bf_hi(v.w);
      }
      final_out(d, xw, sw, s0.y, s1.y, o0, h, l3 & 3);
    }
    }
  }
}

typedef CUresult (*EncodeFn)(CUtensorMap*, CUtensorMapDataType, cuuint32_t, void*, const cuuint64_t*, const cuuint64_t*, const cuuint32_t*,
                             const cuuint32_t*, CUtensorMapInterleave, CUtensorMapSwizzle, CUtensorMapL2promotion, CUtensorMapFloatOOBfill);

void encode(EncodeFn fn, CUtensorMap* m, const void* ptr, int rank, const cuuint64_t* dims, const cuuint64_t* strides, const cuuint32_t* box,
            CUtensorMapSwizzle swz = CU_TENSOR_MAP_SWIZZLE_128B) {
  const cuuint32_t es[3] = {1, 1, 1};
  fn(m, CU_TENSOR_MAP_DATA_TYPE_BFLOAT16, rank, const_cast<void*>(ptr), dims, strides, box, es, CU_TENSOR_MAP_INTERLEAVE_NONE,
     swz, CU_TENSOR_MAP_L2_PROMOTION_L2_128B, CU_TENSOR_MAP_FLOAT_OOB_FILL_NONE);
}

}

extern "C" void kernel_launch(void* const* d_in, const int* in_sizes, int n_in, void* d_out, int out_size) {
  (void)in_sizes; (void)n_in; (void)out_size;
  static EncodeFn enc = nullptr;
  static Scratch* scr = nullptr;
  static int sms = 0;
  if (!enc) {
    void* fn = nullptr;
    cudaDriverEntryPointQueryResult qr;
    cudaGetDriverEntryPoint("cuTensorMapEncodeTiled", &fn, cudaEnableDefault, &qr);
    enc = (EncodeFn)fn;
    cudaFuncSetAttribute(fused_kernel, cudaFuncAttributeMaxDynamicSharedMemorySize, SMEM_BYTES);
    cudaGetSymbolAddress((void**)&scr, g_scr);
    int dev = 0;
    cudaGetDevice(&dev);
    cudaDeviceGetAttribute(&sms, cudaDevAttrMultiProcessorCount, dev);
  }
  Params p;
  p.scr = scr;
  p.by_smid = sms == 132;
  p.k = (const __nv_bfloat16*)d_in[1];
  p.v = (const __nv_bfloat16*)d_in[2];
  p.shift = (const __nv_bfloat16*)d_in[3];
  p.ssmk = (const __nv_bfloat16*)d_in[4];
  p.ssmD = (const __nv_bfloat16*)d_in[5];
  p.wsp = (const __nv_bfloat16*)d_in[8];
  p.bsp = (const __nv_bfloat16*)d_in[9];
  p.wout = (const __nv_bfloat16*)d_in[10];
  p.out = (__nv_bfloat16*)d_out;
  for (int i = 0; i < 2; i++) {
    const cuuint64_t n = i ? kS : kD, dims[3] = {n, 512, 4}, st[2] = {n * 2, n * 1024};
    const cuuint32_t box[3] = {64, 16, 4};
    encode(enc, i ? &p.tmWsp : &p.tmX, d_in[i ? 8 : 0], 3, dims, st, box);
  }
  {
    const cuuint64_t dims[3] = {64, kD, kF / 64}, st[2] = {kF * 2, 128};
    const cuuint32_t box[3] = {64, 64, 3};
    encode(enc, &p.tmW, d_in[7], 3, dims, st, box);
  }
  {
    const cuuint64_t dims[2] = {kS, 896}, st[1] = {kS * 2};
    const cuuint32_t box[2] = {64, 16};
    encode(enc, &p.tmY, scr->y, 2, dims, st, box);
  }
  {
    const cuuint64_t dims[3] = {1024, kD / 2, 4}, st[2] = {8192, 2048};
    const cuuint32_t box[3] = {16, 32, 4};
    encode(enc, &p.tmKV, scr->kvx, 3, dims, st, box, CU_TENSOR_MAP_SWIZZLE_32B);
  }
  fused_kernel<<<132, 512, SMEM_BYTES, cudaStreamPerThread>>>(p);
}
```

```cpp
#include <cuda_runtime.h>
#include <cuda.h>
#include <cuda_bf16.h>
#include <stdint.h>

template <int N> struct WG;
template <> struct WG<16> {
  static __device__ __forceinline__ void rs(float* d, const uint32_t* a, uint64_t db) {
    asm volatile("{\n.reg .pred p;\nsetp.ne.b32 p, 1, 0;\nwgmma.mma_async.sync.aligned.m64n16k16.f32.bf16.bf16 {"
      "%0, %1, %2, %3, %4, %5, %6, %7"
      "}, {%8, %9, %10, %11}, %12, p, 1, 1, 0;\n}\n"
      :
      "+f"(d[0]), "+f"(d[1]), "+f"(d[2]), "+f"(d[3]), "+f"(d[4]), "+f"(d[5]), "+f"(d[6]), "+f"(d[7])
      : "r"(a[0]), "r"(a[1]), "r"(a[2]), "r"(a[3]), "l"(db));
  }
};
template <> struct WG<32> {
  static __device__ __forceinline__ void rs(float* d, const uint32_t* a, uint64_t db) {
    asm volatile("{\n.reg .pred p;\nsetp.ne.b32 p, 1, 0;\nwgmma.mma_async.sync.aligned.m64n32k16.f32.bf16.bf16 {"
      "%0, %1, %2, %3, %4, %5, %6, %7, %8, %9, %10, %11, %12, %13, %14, %15"
      "}, {%16, %17, %18, %19}, %20, p, 1, 1, 0;\n}\n"
      :
      "+f"(d[0]), "+f"(d[1]), "+f"(d[2]), "+f"(d[3]), "+f"(d[4]), "+f"(d[5]), "+f"(d[6]), "+f"(d[7]),
      "+f"(d[8]), "+f"(d[9]), "+f"(d[10]), "+f"(d[11]), "+f"(d[12]), "+f"(d[13]), "+f"(d[14]), "+f"(d[15])
      : "r"(a[0]), "r"(a[1]), "r"(a[2]), "r"(a[3]), "l"(db));
  }
};
template <> struct WG<48> {
  static __device__ __forceinline__ void rs(float* d, const uint32_t* a, uint64_t db) {
    asm volatile("{\n.reg .pred p;\nsetp.ne.b32 p, 1, 0;\nwgmma.mma_async.sync.aligned.m64n48k16.f32.bf16.bf16 {"
      "%0, %1, %2, %3, %4, %5, %6, %7, %8, %9, %10, %11, %12, %13, %14, %15, "
      "%16, %17, %18, %19, %20, %21, %22, %23"
      "}, {%24, %25, %26, %27}, %28, p, 1, 1, 0;\n}\n"
      :
      "+f"(d[0]), "+f"(d[1]), "+f"(d[2]), "+f"(d[3]), "+f"(d[4]), "+f"(d[5]), "+f"(d[6]), "+f"(d[7]),
      "+f"(d[8]), "+f"(d[9]), "+f"(d[10]), "+f"(d[11]), "+f"(d[12]), "+f"(d[13]), "+f"(d[14]), "+f"(d[15]),
      "+f"(d[16]), "+f"(d[17]), "+f"(d[18]), "+f"(d[19]), "+f"(d[20]), "+f"(d[21]), "+f"(d[22]), "+f"(d[23])
      : "r"(a[0]), "r"(a[1]), "r"(a[2]), "r"(a[3]), "l"(db));
  }
};
template <> struct WG<64> {
  static __device__ __forceinline__ void rs(float* d, const uint32_t* a, uint64_t db) {
    asm volatile("{\n.reg .pred p;\nsetp.ne.b32 p, 1, 0;\nwgmma.mma_async.sync.aligned.m64n64k16.f32.bf16.bf16 {"
      "%0, %1, %2, %3, %4, %5, %6, %7, %8, %9, %10, %11, %12, %13, %14, %15, "
      "%16, %17, %18, %19, %20, %21, %22, %23, %24, %25, %26, %27, %28, %29, %30, %31"
      "}, {%32, %33, %34, %35}, %36, p, 1, 1, 0;\n}\n"
      :
      "+f"(d[0]), "+f"(d[1]), "+f"(d[2]), "+f"(d[3]), "+f"(d[4]), "+f"(d[5]), "+f"(d[6]), "+f"(d[7]),
      "+f"(d[8]), "+f"(d[9]), "+f"(d[10]), "+f"(d[11]), "+f"(d[12]), "+f"(d[13]), "+f"(d[14]), "+f"(d[15]),
      "+f"(d[16]), "+f"(d[17]), "+f"(d[18]), "+f"(d[19]), "+f"(d[20]), "+f"(d[21]), "+f"(d[22]), "+f"(d[23]),
      "+f"(d[24]), "+f"(d[25]), "+f"(d[26]), "+f"(d[27]), "+f"(d[28]), "+f"(d[29]), "+f"(d[30]), "+f"(d[31])
      : "r"(a[0]), "r"(a[1]), "r"(a[2]), "r"(a[3]), "l"(db));
  }
};
template <> struct WG<80> {
  static __device__ __forceinline__ void rs(float* d, const uint32_t* a, uint64_t db) {
    asm volatile("{\n.reg .pred p;\nsetp.ne.b32 p, 1, 0;\nwgmma.mma_async.sync.aligned.m64n80k16.f32.bf16.bf16 {"
      "%0, %1, %2, %3, %4, %5, %6, %7, %8, %9, %10, %11, %12, %13, %14, %15, "
      "%16, %17, %18, %19, %20, %21, %22, %23, %24, %25, %26, %27, %28, %29, %30, %31, "
      "%32, %33, %34, %35, %36, %37, %38, %39"
      "}, {%40, %41, %42, %43}, %44, p, 1, 1, 0;\n}\n"
      :
      "+f"(d[0]), "+f"(d[1]), "+f"(d[2]), "+f"(d[3]), "+f"(d[4]), "+f"(d[5]), "+f"(d[6]), "+f"(d[7]),
      "+f"(d[8]), "+f"(d[9]), "+f"(d[10]), "+f"(d[11]), "+f"(d[12]), "+f"(d[13]), "+f"(d[14]), "+f"(d[15]),
      "+f"(d[16]), "+f"(d[17]), "+f"(d[18]), "+f"(d[19]), "+f"(d[20]), "+f"(d[21]), "+f"(d[22]), "+f"(d[23]),
      "+f"(d[24]), "+f"(d[25]), "+f"(d[26]), "+f"(d[27]), "+f"(d[28]), "+f"(d[29]), "+f"(d[30]), "+f"(d[31]),
      "+f"(d[32]), "+f"(d[33]), "+f"(d[34]), "+f"(d[35]), "+f"(d[36]), "+f"(d[37]), "+f"(d[38]), "+f"(d[39])
      : "r"(a[0]), "r"(a[1]), "r"(a[2]), "r"(a[3]), "l"(db));
  }
};
template <> struct WG<96> {
  static __device__ __forceinline__ void rs(float* d, const uint32_t* a, uint64_t db) {
    asm volatile("{\n.reg .pred p;\nsetp.ne.b32 p, 1, 0;\nwgmma.mma_async.sync.aligned.m64n96k16.f32.bf16.bf16 {"
      "%0, %1, %2, %3, %4, %5, %6, %7, %8, %9, %10, %11, %12, %13, %14, %15, "
      "%16, %17, %18, %19, %20, %21, %22, %23, %24, %25, %26, %27, %28, %29, %30, %31, "
      "%32, %33, %34, %35, %36, %37, %38, %39, %40, %41, %42, %43, %44, %45, %46, %47"
      "}, {%48, %49, %50, %51}, %52, p, 1, 1, 0;\n}\n"
      :
      "+f"(d[0]), "+f"(d[1]), "+f"(d[2]), "+f"(d[3]), "+f"(d[4]), "+f"(d[5]), "+f"(d[6]), "+f"(d[7]),
      "+f"(d[8]), "+f"(d[9]), "+f"(d[10]), "+f"(d[11]), "+f"(d[12]), "+f"(d[13]), "+f"(d[14]), "+f"(d[15]),
      "+f"(d[16]), "+f"(d[17]), "+f"(d[18]), "+f"(d[19]), "+f"(d[20]), "+f"(d[21]), "+f"(d[22]), "+f"(d[23]),
      "+f"(d[24]), "+f"(d[25]), "+f"(d[26]), "+f"(d[27]), "+f"(d[28]), "+f"(d[29]), "+f"(d[30]), "+f"(d[31]),
      "+f"(d[32]), "+f"(d[33]), "+f"(d[34]), "+f"(d[35]), "+f"(d[36]), "+f"(d[37]), "+f"(d[38]), "+f"(d[39]),
      "+f"(d[40]), "+f"(d[41]), "+f"(d[42]), "+f"(d[43]), "+f"(d[44]), "+f"(d[45]), "+f"(d[46]), "+f"(d[47])
      : "r"(a[0]), "r"(a[1]), "r"(a[2]), "r"(a[3]), "l"(db));
  }
};
template <> struct WG<112> {
  static __device__ __forceinline__ void rs(float* d, const uint32_t* a, uint64_t db) {
    asm volatile("{\n.reg .pred p;\nsetp.ne.b32 p, 1, 0;\nwgmma.mma_async.sync.aligned.m64n112k16.f32.bf16.bf16 {"
      "%0, %1, %2, %3, %4, %5, %6, %7, %8, %9, %10, %11, %12, %13, %14, %15, "
      "%16, %17, %18, %19, %20, %21, %22, %23, %24, %25, %26, %27, %28, %29, %30, %31, "
      "%32, %33, %34, %35, %36, %37, %38, %39, %40, %41, %42, %43, %44, %45, %46, %47, "
      "%48, %49, %50, %51, %52, %53, %54, %55"
      "}, {%56, %57, %58, %59}, %60, p, 1, 1, 0;\n}\n"
      :
      "+f"(d[0]), "+f"(d[1]), "+f"(d[2]), "+f"(d[3]), "+f"(d[4]), "+f"(d[5]), "+f"(d[6]), "+f"(d[7]),
      "+f"(d[8]), "+f"(d[9]), "+f"(d[10]), "+f"(d[11]), "+f"(d[12]), "+f"(d[13]), "+f"(d[14]), "+f"(d[15]),
      "+f"(d[16]), "+f"(d[17]), "+f"(d[18]), "+f"(d[19]), "+f"(d[20]), "+f"(d[21]), "+f"(d[22]), "+f"(d[23]),
      "+f"(d[24]), "+f"(d[25]), "+f"(d[26]), "+f"(d[27]), "+f"(d[28]), "+f"(d[29]), "+f"(d[30]), "+f"(d[31]),
      "+f"(d[32]), "+f"(d[33]), "+f"(d[34]), "+f"(d[35]), "+f"(d[36]), "+f"(d[37]), "+f"(d[38]), "+f"(d[39]),
      "+f"(d[40]), "+f"(d[41]), "+f"(d[42]), "+f"(d[43]), "+f"(d[44]), "+f"(d[45]), "+f"(d[46]), "+f"(d[47]),
      "+f"(d[48]), "+f"(d[49]), "+f"(d[50]), "+f"(d[51]), "+f"(d[52]), "+f"(d[53]), "+f"(d[54]), "+f"(d[55])
      : "r"(a[0]), "r"(a[1]), "r"(a[2]), "r"(a[3]), "l"(db));
  }
};
template <> struct WG<128> {
  static __device__ __forceinline__ void rs(float* d, const uint32_t* a, uint64_t db) {
    asm volatile("{\n.reg .pred p;\nsetp.ne.b32 p, 1, 0;\nwgmma.mma_async.sync.aligned.m64n128k16.f32.bf16.bf16 {"
      "%0, %1, %2, %3, %4, %5, %6, %7, %8, %9, %10, %11, %12, %13, %14, %15, "
      "%16, %17, %18, %19, %20, %21, %22, %23, %24, %25, %26, %27, %28, %29, %30, %31, "
      "%32, %33, %34, %35, %36, %37, %38, %39, %40, %41, %42, %43, %44, %45, %46, %47, "
      "%48, %49, %50, %51, %52, %53, %54, %55, %56, %57, %58, %59, %60, %61, %62, %63"
      "}, {%64, %65, %66, %67}, %68, p, 1, 1, 0;\n}\n"
      :
      "+f"(d[0]), "+f"(d[1]), "+f"(d[2]), "+f"(d[3]), "+f"(d[4]), "+f"(d[5]), "+f"(d[6]), "+f"(d[7]),
      "+f"(d[8]), "+f"(d[9]), "+f"(d[10]), "+f"(d[11]), "+f"(d[12]), "+f"(d[13]), "+f"(d[14]), "+f"(d[15]),
      "+f"(d[16]), "+f"(d[17]), "+f"(d[18]), "+f"(d[19]), "+f"(d[20]), "+f"(d[21]), "+f"(d[22]), "+f"(d[23]),
      "+f"(d[24]), "+f"(d[25]), "+f"(d[26]), "+f"(d[27]), "+f"(d[28]), "+f"(d[29]), "+f"(d[30]), "+f"(d[31]),
      "+f"(d[32]), "+f"(d[33]), "+f"(d[34]), "+f"(d[35]), "+f"(d[36]), "+f"(d[37]), "+f"(d[38]), "+f"(d[39]),
      "+f"(d[40]), "+f"(d[41]), "+f"(d[42]), "+f"(d[43]), "+f"(d[44]), "+f"(d[45]), "+f"(d[46]), "+f"(d[47]),
      "+f"(d[48]), "+f"(d[49]), "+f"(d[50]), "+f"(d[51]), "+f"(d[52]), "+f"(d[53]), "+f"(d[54]), "+f"(d[55]),
      "+f"(d[56]), "+f"(d[57]), "+f"(d[58]), "+f"(d[59]), "+f"(d[60]), "+f"(d[61]), "+f"(d[62]), "+f"(d[63])
      : "r"(a[0]), "r"(a[1]), "r"(a[2]), "r"(a[3]), "l"(db));
  }
};
template <> struct WG<160> {
  static __device__ __forceinline__ void ss(float* d, uint64_t da, uint64_t db, int sd) {
    asm volatile("{\n.reg .pred p;\nsetp.ne.b32 p, %82, 0;\nwgmma.mma_async.sync.aligned.m64n160k16.f32.bf16.bf16 {"
      "%0, %1, %2, %3, %4, %5, %6, %7, %8, %9, %10, %11, %12, %13, %14, %15, "
      "%16, %17, %18, %19, %20, %21, %22, %23, %24, %25, %26, %27, %28, %29, %30, %31, "
      "%32, %33, %34, %35, %36, %37, %38, %39, %40, %41, %42, %43, %44, %45, %46, %47, "
      "%48, %49, %50, %51, %52, %53, %54, %55, %56, %57, %58, %59, %60, %61, %62, %63, "
      "%64, %65, %66, %67, %68, %69, %70, %71, %72, %73, %74, %75, %76, %77, %78, %79"
      "}, %80, %81, p, 1, 1, 0, 1;\n}\n"
      :
      "+f"(d[0]), "+f"(d[1]), "+f"(d[2]), "+f"(d[3]), "+f"(d[4]), "+f"(d[5]), "+f"(d[6]), "+f"(d[7]),
      "+f"(d[8]), "+f"(d[9]), "+f"(d[10]), "+f"(d[11]), "+f"(d[12]), "+f"(d[13]), "+f"(d[14]), "+f"(d[15]),
      "+f"(d[16]), "+f"(d[17]), "+f"(d[18]), "+f"(d[19]), "+f"(d[20]), "+f"(d[21]), "+f"(d[22]), "+f"(d[23]),
      "+f"(d[24]), "+f"(d[25]), "+f"(d[26]), "+f"(d[27]), "+f"(d[28]), "+f"(d[29]), "+f"(d[30]), "+f"(d[31]),
      "+f"(d[32]), "+f"(d[33]), "+f"(d[34]), "+f"(d[35]), "+f"(d[36]), "+f"(d[37]), "+f"(d[38]), "+f"(d[39]),
      "+f"(d[40]), "+f"(d[41]), "+f"(d[42]), "+f"(d[43]), "+f"(d[44]), "+f"(d[45]), "+f"(d[46]), "+f"(d[47]),
      "+f"(d[48]), "+f"(d[49]), "+f"(d[50]), "+f"(d[51]), "+f"(d[52]), "+f"(d[53]), "+f"(d[54]), "+f"(d[55]),
      "+f"(d[56]), "+f"(d[57]), "+f"(d[58]), "+f"(d[59]), "+f"(d[60]), "+f"(d[61]), "+f"(d[62]), "+f"(d[63]),
      "+f"(d[64]), "+f"(d[65]), "+f"(d[66]), "+f"(d[67]), "+f"(d[68]), "+f"(d[69]), "+f"(d[70]), "+f"(d[71]),
      "+f"(d[72]), "+f"(d[73]), "+f"(d[74]), "+f"(d[75]), "+f"(d[76]), "+f"(d[77]), "+f"(d[78]), "+f"(d[79])
      : "l"(da), "l"(db), "r"(sd));
  }
};
template <> struct WG<192> {
  static __device__ __forceinline__ void ss(float* d, uint64_t da, uint64_t db, int sd) {
    asm volatile("{\n.reg .pred p;\nsetp.ne.b32 p, %98, 0;\nwgmma.mma_async.sync.aligned.m64n192k16.f32.bf16.bf16 {"
      "%0, %1, %2, %3, %4, %5, %6, %7, %8, %9, %10, %11, %12, %13, %14, %15, "
      "%16, %17, %18, %19, %20, %21, %22, %23, %24, %25, %26, %27, %28, %29, %30, %31, "
      "%32, %33, %34, %35, %36, %37, %38, %39, %40, %41, %42, %43, %44, %45, %46, %47, "
      "%48, %49, %50, %51, %52, %53, %54, %55, %56, %57, %58, %59, %60, %61, %62, %63, "
      "%64, %65, %66, %67, %68, %69, %70, %71, %72, %73, %74, %75, %76, %77, %78, %79, "
      "%80, %81, %82, %83, %84, %85, %86, %87, %88, %89, %90, %91, %92, %93, %94, %95"
      "}, %96, %97, p, 1, 1, 0, 1;\n}\n"
      :
      "+f"(d[0]), "+f"(d[1]), "+f"(d[2]), "+f"(d[3]), "+f"(d[4]), "+f"(d[5]), "+f"(d[6]), "+f"(d[7]),
      "+f"(d[8]), "+f"(d[9]), "+f"(d[10]), "+f"(d[11]), "+f"(d[12]), "+f"(d[13]), "+f"(d[14]), "+f"(d[15]),
      "+f"(d[16]), "+f"(d[17]), "+f"(d[18]), "+f"(d[19]), "+f"(d[20]), "+f"(d[21]), "+f"(d[22]), "+f"(d[23]),
      "+f"(d[24]), "+f"(d[25]), "+f"(d[26]), "+f"(d[27]), "+f"(d[28]), "+f"(d[29]), "+f"(d[30]), "+f"(d[31]),
      "+f"(d[32]), "+f"(d[33]), "+f"(d[34]), "+f"(d[35]), "+f"(d[36]), "+f"(d[37]), "+f"(d[38]), "+f"(d[39]),
      "+f"(d[40]), "+f"(d[41]), "+f"(d[42]), "+f"(d[43]), "+f"(d[44]), "+f"(d[45]), "+f"(d[46]), "+f"(d[47]),
      "+f"(d[48]), "+f"(d[49]), "+f"(d[50]), "+f"(d[51]), "+f"(d[52]), "+f"(d[53]), "+f"(d[54]), "+f"(d[55]),
      "+f"(d[56]), "+f"(d[57]), "+f"(d[58]), "+f"(d[59]), "+f"(d[60]), "+f"(d[61]), "+f"(d[62]), "+f"(d[63]),
      "+f"(d[64]), "+f"(d[65]), "+f"(d[66]), "+f"(d[67]), "+f"(d[68]), "+f"(d[69]), "+f"(d[70]), "+f"(d[71]),
      "+f"(d[72]), "+f"(d[73]), "+f"(d[74]), "+f"(d[75]), "+f"(d[76]), "+f"(d[77]), "+f"(d[78]), "+f"(d[79]),
      "+f"(d[80]), "+f"(d[81]), "+f"(d[82]), "+f"(d[83]), "+f"(d[84]), "+f"(d[85]), "+f"(d[86]), "+f"(d[87]),
      "+f"(d[88]), "+f"(d[89]), "+f"(d[90]), "+f"(d[91]), "+f"(d[92]), "+f"(d[93]), "+f"(d[94]), "+f"(d[95])
      : "l"(da), "l"(db), "r"(sd));
  }
  static __device__ __forceinline__ void rst(float* d, const uint32_t* a, uint64_t db) {
    asm volatile("{\n.reg .pred p;\nsetp.ne.b32 p, 1, 0;\nwgmma.mma_async.sync.aligned.m64n192k16.f32.bf16.bf16 {"
      "%0, %1, %2, %3, %4, %5, %6, %7, %8, %9, %10, %11, %12, %13, %14, %15, "
      "%16, %17, %18, %19, %20, %21, %22, %23, %24, %25, %26, %27, %28, %29, %30, %31, "
      "%32, %33, %34, %35, %36, %37, %38, %39, %40, %41, %42, %43, %44, %45, %46, %47, "
      "%48, %49, %50, %51, %52, %53, %54, %55, %56, %57, %58, %59, %60, %61, %62, %63, "
      "%64, %65, %66, %67, %68, %69, %70, %71, %72, %73, %74, %75, %76, %77, %78, %79, "
      "%80, %81, %82, %83, %84, %85, %86, %87, %88, %89, %90, %91, %92, %93, %94, %95"
      "}, {%96, %97, %98, %99}, %100, p, 1, 1, 1;\n}\n"
      :
      "+f"(d[0]), "+f"(d[1]), "+f"(d[2]), "+f"(d[3]), "+f"(d[4]), "+f"(d[5]), "+f"(d[6]), "+f"(d[7]),
      "+f"(d[8]), "+f"(d[9]), "+f"(d[10]), "+f"(d[11]), "+f"(d[12]), "+f"(d[13]), "+f"(d[14]), "+f"(d[15]),
      "+f"(d[16]), "+f"(d[17]), "+f"(d[18]), "+f"(d[19]), "+f"(d[20]), "+f"(d[21]), "+f"(d[22]), "+f"(d[23]),
      "+f"(d[24]), "+f"(d[25]), "+f"(d[26]), "+f"(d[27]), "+f"(d[28]), "+f"(d[29]), "+f"(d[30]), "+f"(d[31]),
      "+f"(d[32]), "+f"(d[33]), "+f"(d[34]), "+f"(d[35]), "+f"(d[36]), "+f"(d[37]), "+f"(d[38]), "+f"(d[39]),
      "+f"(d[40]), "+f"(d[41]), "+f"(d[42]), "+f"(d[43]), "+f"(d[44]), "+f"(d[45]), "+f"(d[46]), "+f"(d[47]),
      "+f"(d[48]), "+f"(d[49]), "+f"(d[50]), "+f"(d[51]), "+f"(d[52]), "+f"(d[53]), "+f"(d[54]), "+f"(d[55]),
      "+f"(d[56]), "+f"(d[57]), "+f"(d[58]), "+f"(d[59]), "+f"(d[60]), "+f"(d[61]), "+f"(d[62]), "+f"(d[63]),
      "+f"(d[64]), "+f"(d[65]), "+f"(d[66]), "+f"(d[67]), "+f"(d[68]), "+f"(d[69]), "+f"(d[70]), "+f"(d[71]),
      "+f"(d[72]), "+f"(d[73]), "+f"(d[74]), "+f"(d[75]), "+f"(d[76]), "+f"(d[77]), "+f"(d[78]), "+f"(d[79]),
      "+f"(d[80]), "+f"(d[81]), "+f"(d[82]), "+f"(d[83]), "+f"(d[84]), "+f"(d[85]), "+f"(d[86]), "+f"(d[87]),
      "+f"(d[88]), "+f"(d[89]), "+f"(d[90]), "+f"(d[91]), "+f"(d[92]), "+f"(d[93]), "+f"(d[94]), "+f"(d[95])
      : "r"(a[0]), "r"(a[1]), "r"(a[2]), "r"(a[3]), "l"(db));
  }
};

#define ZSH 1
#define CS1_T 9500
#define HGRP 3
#define HPACE 150
#define LL_AT 4
#define KV_T0 2300
#define WSP_D 650

namespace {

constexpr int kS = 2048, kD = 640, kF = 1536;
constexpr int NA = 10, NA2 = 9, NB = 5;
constexpr int A_SLOT = 8192, B_SLOT = 24576;
constexpr int LEAD = 2;
constexpr int OFF_A = 0;
constexpr int OFF_B = OFF_A + NA * A_SLOT;
constexpr int XB_PL = 2112;
constexpr int CV_KE = 4224, CV_KO = CV_KE + 4160;
constexpr int CV_SZ = CV_KO + 4160;
constexpr int OFF_CV = OFF_B + NB * B_SLOT;
constexpr int OFF_CS = OFF_CV + 2 * CV_SZ;
constexpr int OFF_BIAS = OFF_CS + 1536;
constexpr int OFF_XS = OFF_BIAS + 128;
constexpr int OFF_BAR = OFF_XS + 512;
constexpr int BAR_AF = OFF_BAR, BAR_ST = BAR_AF + 8 * NA, BAR_XF = BAR_ST + 16, BAR_KV = BAR_XF + 16;
constexpr int BAR_BF = OFF_BAR + 128, BAR_G2 = BAR_BF + 8 * (NB + 1), BAR_XS = BAR_G2 + 8, BAR_KU = BAR_XS + 8, BAR_ZP = BAR_KU + 40, BAR_XC = BAR_ZP + 8, BAR_WO = BAR_XC + 8;
constexpr int BAR_AE = OFF_BAR + 256, BAR_BE = BAR_AE + 8 * NA;
constexpr int BAR_YT = BAR_KU + 24;
constexpr int BAR_Z1 = BAR_ST;
constexpr int BAR_GO1 = BAR_XC;
constexpr int BAR_GO = BAR_XS;
constexpr int BAR_YL = BAR_KU + 16;
constexpr int OFF_TAG = OFF_CS - 32;
constexpr int SMEM_BYTES = OFF_BAR + 384;
static_assert(SMEM_BYTES <= 232448, "smem");
constexpr int NB_WGA = 1, NB_WGC = 2, NB_G1 = 3, NB_WO = 4, NB_CD = 5, NB_Z = 6, NB_WGB = 7, NB_Z2 = 8, NB_H = 11;

constexpr int CSP = 32, EPS = 8;
constexpr int CNT_Y = 0, CNT_Z1 = 2, CNT_KV = 4, CNT_WO = 8;
struct Scratch {
  uint8_t kvx[kD * 4096];
  uint8_t z2[4 * 32 * 24576];
  uint8_t h[32 * 12 * 8192];
  uint8_t wo[4 * 12 * 20480];
  uint8_t y[896 * 4096];
  uint4 xstat[kS];
  uint2 zstat[kS * 8];
  uint2 colsum[kF];
  uint32_t zcnt[4 * 32];
  uint32_t cnt[12 * 32];
  uint32_t hcnt[32 * 32];
  uint32_t epoch[136 * EPS];
};
__device__ __align__(1024) Scratch g_scr;
#define ZS(i)
#define STAMP(i)
#define STAMP2(i)
#define STAMPW(i)

struct Params {
  Scratch* scr;
  int by_smid;
  const __nv_bfloat16 *k, *v, *shift, *ssmk, *ssmD, *wsp, *bsp, *wout;
  __nv_bfloat16* out;
  CUtensorMap tmX, tmW, tmWsp, tmY, tmKV;
};

__device__ __forceinline__ uint64_t mkdesc(uint32_t addr, uint32_t lbo, uint32_t sbo, uint32_t swz) {
  return (uint64_t)((addr & 0x3FFFF) >> 4) | ((uint64_t)(lbo >> 4) << 16) | ((uint64_t)(sbo >> 4) << 32) | ((uint64_t)swz << 62);
}
#define WG_FENCE() asm volatile("wgmma.fence.sync.aligned;" ::: "memory")
#define WG_COMMIT() asm volatile("wgmma.commit_group.sync.aligned;" ::: "memory")
#define WG_WAIT(n) asm volatile("wgmma.wait_group.sync.aligned %0;" ::"n"(n) : "memory")
template <int N> __device__ __forceinline__ void acc_fence(float* d) {
#pragma unroll
  for (int i = 0; i < N; i++) asm volatile("" : "+f"(d[i])::"memory");
}
__device__ __forceinline__ void mbar_init(uint32_t bar, int cnt) { asm volatile("mbarrier.init.shared::cta.b64 [%0], %1;" ::"r"(bar), "r"(cnt) : "memory"); }
__device__ __forceinline__ void mbar_expect(uint32_t bar, uint32_t bytes) { asm volatile("mbarrier.arrive.expect_tx.shared::cta.b64 _, [%0], %1;" ::"r"(bar), "r"(bytes) : "memory"); }
__device__ __forceinline__ void mbar_arrive(uint32_t bar) { asm volatile("mbarrier.arrive.shared::cta.b64 _, [%0];" ::"r"(bar) : "memory"); }
__device__ __forceinline__ void mbar_arrive_if(uint32_t bar, bool c) {
  asm volatile("{\n.reg .pred p;\nsetp.ne.u32 p, %1, 0;\n@p mbarrier.arrive.shared::cta.b64 _, [%0];\n}\n" ::"r"(bar), "r"((uint32_t)c) : "memory");
}
__device__ __forceinline__ void mbar_expect_if(uint32_t bar, uint32_t bytes, bool c) {
  asm volatile("{\n.reg .pred p;\nsetp.ne.u32 p, %2, 0;\n@p mbarrier.arrive.expect_tx.shared::cta.b64 _, [%0], %1;\n}\n" ::"r"(bar), "r"(bytes), "r"((uint32_t)c) : "memory");
}
__device__ __forceinline__ bool mbar_try(uint32_t bar, uint32_t parity) {
  uint32_t ok;
  asm volatile("{\n.reg .pred p;\nmbarrier.try_wait.parity.shared::cta.b64 p, [%1], %2;\nselp.u32 %0, 1, 0, p;\n}\n" : "=r"(ok) : "r"(bar), "r"(parity) : "memory");
  return ok;
}
__device__ __forceinline__ bool mbar_test(uint32_t bar, uint32_t parity) {
  uint32_t ok;
  asm volatile("{\n.reg .pred p;\nmbarrier.test_wait.parity.shared::cta.b64 p, [%1], %2;\nselp.u32 %0, 1, 0, p;\n}\n" : "=r"(ok) : "r"(bar), "r"(parity) : "memory");
  return ok;
}
__device__ __forceinline__ void die() { asm volatile("st.volatile.global.u32 [%0], %1;" ::"l"(0ull), "r"(0) : "memory"); }
__device__ __forceinline__ void spin_guard(uint32_t& n) { if (++n == (1u << 22)) die(); }
__device__ __forceinline__ void mbar_wait(uint32_t bar, uint32_t parity) {
  uint32_t t0 = 0;
#pragma unroll 1
  while (!mbar_try(bar, parity)) spin_guard(t0);
}
__device__ __forceinline__ void mbar_wait2(uint32_t b0, uint32_t p0, uint32_t b1, uint32_t p1) {
  uint32_t t0 = 0;
#pragma unroll 1
  while (true) {
    const bool r0 = mbar_try(b0, p0), r1 = mbar_try(b1, p1);
    if (r0 && r1) break;
    spin_guard(t0);
  }
}
__device__ __forceinline__ int tid_now() { int v; asm volatile("mov.u32 %0, %%tid.x;" : "=r"(v)); return v & 127; }
__device__ __forceinline__ bool elect_one() {
  uint32_t p;
  asm volatile("{\n.reg .pred P;\nelect.sync _|P, 0xffffffff;\nselp.u32 %0, 1, 0, P;\n}\n" : "=r"(p));
  return p;
}
__device__ __forceinline__ void bar_sync(int id, int n) { asm volatile("bar.sync %0, %1;" ::"r"(id), "r"(n) : "memory"); }
__device__ __forceinline__ void bar_arrive(int id, int n) { asm volatile("bar.arrive %0, %1;" ::"r"(id), "r"(n) : "memory"); }
__device__ __forceinline__ void fence_async_smem() { asm volatile("fence.proxy.async.shared::cta;" ::: "memory"); }
__device__ __forceinline__ void bulk_g2s(uint32_t dst, const void* src, uint32_t bytes, uint32_t bar) {
  asm volatile("cp.async.bulk.shared::cluster.global.mbarrier::complete_tx::bytes [%0], [%1], %2, [%3];" ::"r"(dst), "l"(src), "r"(bytes), "r"(bar) : "memory");
}
__device__ __forceinline__ void bulk_s2g(void* dst, uint32_t src, uint32_t bytes) {
  asm volatile("cp.async.bulk.global.shared::cta.bulk_group [%0], [%1], %2;" ::"l"(dst), "r"(src), "r"(bytes) : "memory");
}
__device__ __forceinline__ void tma2d(uint32_t dst, const CUtensorMap* m, int c0, int c1, uint32_t bar) {
  asm volatile("cp.async.bulk.tensor.2d.shared::cluster.global.mbarrier::complete_tx::bytes [%0], [%1, {%3, %4}], [%2];" ::"r"(dst), "l"(m), "r"(bar), "r"(c0), "r"(c1) : "memory");
}
__device__ __forceinline__ void tma3d(uint32_t dst, const CUtensorMap* m, int c0, int c1, int c2, uint32_t bar) {
  asm volatile("cp.async.bulk.tensor.3d.shared::cluster.global.mbarrier::complete_tx::bytes [%0], [%1, {%3, %4, %5}], [%2];" ::"r"(dst), "l"(m), "r"(bar), "r"(c0), "r"(c1), "r"(c2) : "memory");
}
__device__ __forceinline__ void tma_rows(uint32_t dst, const CUtensorMap* m, int c0, int rb, uint32_t bar) { tma3d(dst, m, c0, rb * 16, 0, bar); }
__device__ __forceinline__ uint4 ld_ll4(const void* p) {
  uint64_t a, b;
  asm volatile("ld.relaxed.gpu.global.v2.u64 {%0,%1}, [%2];" : "=l"(a), "=l"(b) : "l"(p) : "memory");
  return make_uint4((uint32_t)a, (uint32_t)(a >> 32), (uint32_t)b, (uint32_t)(b >> 32));
}
__device__ __forceinline__ void st_ll4(void* p, uint32_t a, uint32_t b, uint32_t c, uint32_t d) {
  asm volatile("st.relaxed.gpu.global.v2.u64 [%0], {%1,%2};" ::"l"(p), "l"(a | ((uint64_t)b << 32)), "l"(c | ((uint64_t)d << 32)) : "memory");
}
__device__ __forceinline__ void st_ll2(void* p, uint32_t a, uint32_t b) { asm volatile("st.relaxed.gpu.global.u64 [%0], %1;" ::"l"(p), "l"(a | ((uint64_t)b << 32)) : "memory"); }
__device__ __forceinline__ uint2 ld_ll2(const void* p) {
  uint64_t a;
  asm volatile("ld.relaxed.gpu.global.u64 %0, [%1];" : "=l"(a) : "l"(p) : "memory");
  return make_uint2((uint32_t)a, (uint32_t)(a >> 32));
}
__device__ __forceinline__ void wgmma_colsum(float* d, uint64_t da, uint64_t db) {
  asm volatile("{\n.reg .pred p;\nsetp.ne.b32 p, 1, 0;\nwgmma.mma_async.sync.aligned.m64n8k16.f32.bf16.bf16 {%0, %1, %2, %3}, %4, %5, p, 1, 1, 1, 0;\n}\n"
               : "+f"(d[0]), "+f"(d[1]), "+f"(d[2]), "+f"(d[3]) : "l"(da), "l"(db));
}
__device__ __forceinline__ void prefetch_l2(const void* p) { asm volatile("prefetch.global.L2 [%0];" ::"l"(p)); }
__device__ __forceinline__ void pace(uint32_t& t, uint32_t dt) {
  t += dt;
  while ((int32_t)((uint32_t)clock() - t) < 0) __nanosleep(32);
}
__device__ __forceinline__ void red_relaxed(uint32_t* p) { asm volatile("red.relaxed.gpu.global.add.u32 [%0], 1;" ::"l"(p) : "memory"); }
__device__ __forceinline__ void red_release(uint32_t* p) { asm volatile("red.release.gpu.global.add.u32 [%0], 1;" ::"l"(p) : "memory"); }
__device__ __forceinline__ uint4 ldg4(const void* p) { uint4 v; asm volatile("ld.global.v4.u32 {%0,%1,%2,%3}, [%4];" : "=r"(v.x), "=r"(v.y), "=r"(v.z), "=r"(v.w) : "l"(p) : "memory"); return v; }
__device__ __forceinline__ uint32_t ldg1(const void* p) { uint32_t v; asm volatile("ld.global.u32 %0, [%1];" : "=r"(v) : "l"(p) : "memory"); return v; }
__device__ __forceinline__ void stg4_if(void* p, uint32_t a, uint32_t b, uint32_t c, uint32_t d, bool on) {
  asm volatile("{\n.reg .pred p;\nsetp.ne.u32 p, %5, 0;\n@p st.global.v4.u32 [%0], {%1,%2,%3,%4};\n}\n" ::"l"(p), "r"(a), "r"(b), "r"(c), "r"(d), "r"((uint32_t)on) : "memory");
}
template <int OFF> __device__ __forceinline__ uint32_t lds32(uint32_t a) { uint32_t v; asm volatile("ld.shared.u32 %0, [%1+%2];" : "=r"(v) : "r"(a), "n"(OFF)); return v; }
__device__ __forceinline__ uint4 lds128(uint32_t a) { uint4 v; asm volatile("ld.shared.v4.u32 {%0,%1,%2,%3}, [%4];" : "=r"(v.x), "=r"(v.y), "=r"(v.z), "=r"(v.w) : "r"(a) : "memory"); return v; }
__device__ __forceinline__ float2 lds64f(uint32_t a) { float2 v; asm volatile("ld.shared.v2.f32 {%0,%1}, [%2];" : "=f"(v.x), "=f"(v.y) : "r"(a) : "memory"); return v; }
__device__ __forceinline__ void sts64f(uint32_t a, float x, float y) { asm volatile("st.shared.v2.f32 [%0], {%1,%2};" ::"r"(a), "f"(x), "f"(y) : "memory"); }
__device__ __forceinline__ void sts32(uint32_t a, uint32_t x) { asm volatile("st.shared.u32 [%0], %1;" ::"r"(a), "r"(x) : "memory"); }
__device__ __forceinline__ void sts128(uint32_t a, uint32_t x, uint32_t y, uint32_t z, uint32_t w) { asm volatile("st.shared.v4.u32 [%0], {%1,%2,%3,%4};" ::"r"(a), "r"(x), "r"(y), "r"(z), "r"(w) : "memory"); }
__device__ __forceinline__ void stsm4(uint32_t a, uint32_t r0, uint32_t r1, uint32_t r2, uint32_t r3) {
  asm volatile("stmatrix.sync.aligned.m8n8.x4.shared.b16 [%0], {%1,%2,%3,%4};" ::"r"(a), "r"(r0), "r"(r1), "r"(r2), "r"(r3) : "memory");
}
__device__ __forceinline__ void stsm4t(uint32_t a, uint32_t r0, uint32_t r1, uint32_t r2, uint32_t r3) {
  asm volatile("stmatrix.sync.aligned.m8n8.x4.trans.shared.b16 [%0], {%1,%2,%3,%4};" ::"r"(a), "r"(r0), "r"(r1), "r"(r2), "r"(r3) : "memory");
}
__device__ __forceinline__ void ldsm4t(uint32_t* r, uint32_t a) {
  asm volatile("ldmatrix.sync.aligned.m8n8.x4.trans.shared.b16 {%0,%1,%2,%3}, [%4];" : "=r"(r[0]), "=r"(r[1]), "=r"(r[2]), "=r"(r[3]) : "r"(a) : "memory");
}
__device__ __forceinline__ uint32_t pack2(float lo, float hi) { uint32_t r; asm("cvt.rn.bf16x2.f32 %0, %1, %2;" : "=r"(r) : "f"(hi), "f"(lo)); return r; }
__device__ __forceinline__ float bf_lo(uint32_t u) { return __uint_as_float(u << 16); }
__device__ __forceinline__ float bf_hi(uint32_t u) { return __uint_as_float(u & 0xffff0000u); }
__device__ __forceinline__ float tanh_fast(float x) { float y; asm("tanh.approx.f32 %0, %1;" : "=f"(y) : "f"(x)); return y; }
__device__ __forceinline__ uint32_t hmul2(uint32_t a, uint32_t b) { uint32_t r; asm("mul.rn.bf16x2 %0, %1, %2;" : "=r"(r) : "r"(a), "r"(b)); return r; }
__device__ __forceinline__ uint32_t hfma2(uint32_t a, uint32_t b, uint32_t c) { uint32_t r; asm("fma.rn.bf16x2 %0, %1, %2, %3;" : "=r"(r) : "r"(a), "r"(b), "r"(c)); return r; }
__device__ __forceinline__ uint32_t prmt(uint32_t a, uint32_t b, uint32_t s) { return __byte_perm(a, b, s); }

__device__ __forceinline__ void st_relaxed(uint32_t* p, uint32_t v) { asm volatile("st.relaxed.gpu.global.u32 [%0], %1;" ::"l"(p), "r"(v) : "memory"); }
__device__ __forceinline__ uint32_t ld_relaxed(const uint32_t* p) { uint32_t v; asm volatile("ld.relaxed.gpu.global.u32 %0, [%1];" : "=r"(v) : "l"(p) : "memory"); return v; }
__device__ __forceinline__ void acquire_fence() { asm volatile("fence.acquire.gpu;\nfence.proxy.async.global;" ::: "memory"); }
__device__ __forceinline__ uint32_t load_epoch(const Params& p, int idx, int lane) { return ld_relaxed(&p.scr->epoch[idx * EPS + (((lane * lane) & 3) == 2 ? 1 : 0)]); }
__device__ __forceinline__ void poll_counter(const uint32_t* cnt, uint32_t target) {
  uint32_t t0 = 0;
#pragma unroll 1
  while (!__all_sync(0xffffffff, ld_relaxed(cnt) == target)) spin_guard(t0);
  acquire_fence();
}

__device__ __forceinline__ void poll_one(const uint32_t* cnt, uint32_t target) {
  uint32_t t0 = 0;
#pragma unroll 1
  while (ld_relaxed(cnt) != target) spin_guard(t0);
  acquire_fence();
}
__device__ __forceinline__ uint32_t anchor(uint32_t v) { return __shfl_sync(0xffffffff, v, 0); }
__device__ __forceinline__ int g3_block(int cb, int it) { return it < 3 ? cb * 3 + it : (it - 3 < cb * 3 ? it - 3 : it); }

template <int N, bool A_SWZ, int B_MODE, class Hook>
__device__ __forceinline__ void gemm_loop(float* d, uint32_t sb, int nkb, int sa, int pa, int b0, uint32_t boff, int relA, int relB, int tid, Hook hook) {
  constexpr uint32_t A_STEP = A_SWZ ? 2 : 128;
  constexpr uint32_t B_STEP = B_MODE == 0 ? 128 : (B_MODE == 1 ? 384 : 320);
  const uint64_t da0 = A_SWZ ? mkdesc(sb + OFF_A, 16, 1024, 1) : mkdesc(sb + OFF_A, 1024, 128, 0);
  const uint64_t db0 = B_MODE == 0 ? mkdesc(sb + OFF_B + boff, 8192, 1024, 1) : mkdesc(sb + OFF_B + boff, B_MODE == 1 ? 3072 : 2560, 128, 0);
  constexpr int MODA = B_MODE == 0 ? NA : NA2;
  constexpr int MODB = B_MODE == 2 ? 6 : NB;
  int sbk = b0 % MODB, pb = (b0 / MODB) & 1;
  auto boffs = [](int s_) { return B_MODE == 2 ? (s_ == 5 ? 0 : s_ + 1) * (20480 >> 4) : s_ * (B_SLOT >> 4); };
  uint32_t rel = 0;
  uint64_t da = da0 + sa * (A_SLOT >> 4), db = db0 + boffs(sbk);
  const bool doR = tid < 2 ? tid < relA : tid - 2 < relB;
  mbar_wait2(sb + BAR_AF + 8 * sa, pa, sb + BAR_BF + 8 * sbk, pb);
  if constexpr (B_MODE == 2) {
#pragma unroll
    for (int i = 0; i < N / 2; i++) asm volatile("" : "=f"(d[i]));
#pragma unroll 1
    for (int it = 0; it < nkb; it++) {
      WG_FENCE();
#pragma unroll
      for (int j = 0; j < 4; j++) WG<N>::ss(d, da + j * A_STEP, db + j * B_STEP, j ? 1 : it);
      WG_COMMIT();
      const uint32_t prel = rel;
      rel = sb + BAR_AE + 8 * (tid < 2 ? sa : sbk + NA);
      if (++sa == MODA) { sa = 0; pa ^= 1; }
      if (++sbk == MODB) { sbk = 0; pb ^= 1; }
      da = da0 + sa * (A_SLOT >> 4); db = db0 + boffs(sbk);
      const bool r0 = mbar_test(sb + BAR_AF + 8 * sa, pa), r1 = mbar_test(sb + BAR_BF + 8 * sbk, pb);
      WG_WAIT(1);
      mbar_arrive_if(prel, doR && prel != 0);
      if (it == 2) {
        WG_WAIT(0);
        mbar_expect_if(sb + BAR_AF + 8 * tid, A_SLOT, tid >= 5 && tid < 8);
        mbar_arrive_if(rel, doR);
        rel = 0;
      }
      if (it + 1 < nkb && !(r0 && r1)) {
        mbar_wait2(sb + BAR_AF + 8 * sa, pa, sb + BAR_BF + 8 * sbk, pb);
      }
    }
  } else
#pragma unroll 1
  for (int it = 0; it < nkb; it++) {
    WG_FENCE();
    WG<N>::ss(d, da, db, 1);
    const uint32_t prel = rel;
    rel = sb + BAR_AE + 8 * (tid < 2 ? sa : sbk + NA);
    if (++sa == MODA) { sa = 0; if (B_MODE) pa ^= 1; }
    if (++sbk == MODB) { sbk = 0; pb ^= 1; }
    WG<N>::ss(d, da + A_STEP, db + B_STEP, 1);
    WG_COMMIT();
    WG_WAIT(1);
    WG<N>::ss(d, da + 2 * A_STEP, db + 2 * B_STEP, 1);
    mbar_arrive_if(prel, doR && it != 0);
    const bool r0 = mbar_test(sb + BAR_AF + 8 * sa, pa), r1 = mbar_test(sb + BAR_BF + 8 * sbk, pb);
    const uint64_t da3 = da + 3 * A_STEP, db3 = db + 3 * B_STEP;
    da = da0 + sa * (A_SLOT >> 4); db = db0 + boffs(sbk);
    WG<N>::ss(d, da3, db3, 1);
    WG_COMMIT();
    if (it + 1 < nkb) {
      if (!(r0 && r1)) {
        mbar_wait2(sb + BAR_AF + 8 * sa, pa, sb + BAR_BF + 8 * sbk, pb);
      }
    }
  }
  hook();
  WG_WAIT(0);
  acc_fence<N / 2>(d);
  mbar_arrive_if(rel, doR);
}

__device__ __forceinline__ void fold_mean(float* d, uint32_t cs, float ma, float mb, int t) {
  const uint32_t ha = pack2(-ma, -ma), hb = pack2(-mb, -mb);
  const float la = -ma - bf_lo(ha), lb = -mb - bf_lo(hb);
  const uint32_t a[4] = {t ? 0u : ha, t ? 0u : hb, t ? 0u : pack2(la, la), t ? 0u : pack2(lb, lb)};
  WG_FENCE();
  WG<192>::rst(d, a, mkdesc(cs, 0, 32, 0));
  WG_COMMIT();
}
__device__ __forceinline__ void gelu_tile(const float* d, uint32_t* z, float* st, float ra, float rb) {
  const float kA = 0.7978845608028654f, kB = 0.7978845608028654f * 0.044715f;
  const float c1a = kA * ra, c3a = kB * ra * ra * ra, c1b = kA * rb, c3b = kB * rb * rb * rb;
  float acc[8];
#pragma unroll
  for (int i = 0; i < 8; i++) acc[i] = 0.f;
#pragma unroll
  for (int j = 0; j < 24; j++) {
    float r[4];
#pragma unroll
    for (int e = 0; e < 4; e++) {
      const float v = d[4 * j + e];
      const float a = v * fmaf(v * v, e < 2 ? c3a : c3b, e < 2 ? c1a : c1b);
      r[e] = fmaf(v, tanh_fast(a), v);
      acc[e] += r[e];
      acc[4 + e] = fmaf(r[e], r[e], acc[4 + e]);
    }
    z[2 * j] = pack2(r[0], r[1]);
    z[2 * j + 1] = pack2(r[2], r[3]);
  }
  st[0] = acc[0] + acc[1]; st[1] = acc[4] + acc[5]; st[2] = acc[2] + acc[3]; st[3] = acc[6] + acc[7];
}

template <int Q> __device__ __forceinline__ void conv_load(uint32_t* a, uint32_t ab) {
  a[0] = lds32<512 * Q>(ab);       a[1] = lds32<512 * Q + 256>(ab);  a[2] = lds32<512 * Q + 16>(ab);   a[3] = lds32<512 * Q + 272>(ab);
  a[4] = lds32<512 * Q + 32>(ab);  a[5] = lds32<512 * Q + 288>(ab);  a[6] = lds32<512 * Q + 48>(ab);   a[7] = lds32<512 * Q + 304>(ab);
  a[8] = lds32<512 * Q + 64>(ab);  a[9] = lds32<512 * Q + 320>(ab);  a[10] = lds32<512 * Q + 80>(ab);  a[11] = lds32<512 * Q + 336>(ab);
  a[12] = lds32<512 * Q + 96>(ab); a[13] = lds32<512 * Q + 352>(ab); a[14] = lds32<512 * Q + 112>(ab); a[15] = lds32<512 * Q + 368>(ab);
}
template <int Q, int L> __device__ __forceinline__ void conv_step(float* d, uint32_t (*a)[16], uint32_t ab, uint64_t db) {
  WG_FENCE();
#pragma unroll
  for (int s = 0; s < 4; s++) WG<128 - 16 * Q>::rs(d, a[Q] + 4 * s, db + s + 16 * Q);
  WG_COMMIT();
  WG_WAIT(1);
  if (L >= 0) conv_load<(L >= 0 ? L : 0)>(a[L >= 0 ? L : 0], ab);
  if (Q == 0) WG_WAIT(0);
}

__device__ __forceinline__ int seg_col(int cb, int h) { return (cb >> 1) * 320 + (cb & 1) * 32 + h * 64; }
__device__ __forceinline__ void final_load_x(uint32_t (*xw)[10], uint32_t xt, int cb, int h, int w, int lane) {
  const int g = lane >> 2, t = lane & 3, cc = seg_col(cb, h) >> 3;
  const int c0 = cc + t, c1 = c0 + 24, c2 = cc + 16 - 6 * h + (t >> 1);
  const uint32_t r0 = xt + (w * 16 + g) * 128;
#pragma unroll
  for (int r = 0; r < 2; r++) {
    const uint4 u = lds128(r0 + r * 1024 + (c0 >> 3) * A_SLOT + (((c0 ^ g) & 7) << 4)), v = lds128(r0 + r * 1024 + (c1 >> 3) * A_SLOT + (((c1 ^ g) & 7) << 4));
    const float2 z = lds64f(r0 + r * 1024 + (c2 >> 3) * A_SLOT + (((c2 ^ g) & 7) << 4) + (t & 1) * 8);
    xw[r][0] = u.x; xw[r][1] = u.y; xw[r][2] = u.z; xw[r][3] = u.w;
    xw[r][4] = v.x; xw[r][5] = v.y; xw[r][6] = v.z; xw[r][7] = v.w;
    xw[r][8] = __float_as_uint(z.x); xw[r][9] = __float_as_uint(z.y);
  }
}
__device__ __forceinline__ void final_s_early(uint32_t (*sw)[10], const uint32_t (*xw)[10], uint32_t ya, float2 s0, float2 s1) {
  const uint32_t r2[2] = {pack2(s0.y, s0.y), pack2(s1.y, s1.y)};
  const float na = -s0.x * bf_lo(r2[0]), nb = -s1.x * bf_lo(r2[1]);
  const uint32_t n2[2] = {pack2(na, na), pack2(nb, nb)};
#pragma unroll
  for (int j = 0; j < 10; j += 2) {
    uint32_t y[4];
    if (j < 4 || j == 8) ldsm4t(y, ya + (j < 4 ? j : 4) * 1024);
#pragma unroll
    for (int e = 0; e < 4; e++) {
      const uint32_t xn = hfma2(xw[e & 1][j + (e >> 1)], r2[e & 1], n2[e & 1]);
      sw[e & 1][j + (e >> 1)] = (j < 4 || j == 8) ? hmul2(xn, y[e]) : xn;
    }
  }
}
__device__ __forceinline__ bool final_late(uint32_t* y, uint32_t ya) {
  ldsm4t(y, ya + 6144);
  ldsm4t(y + 4, ya + 8192);
  uint32_t zero = 0;
#pragma unroll
  for (int e = 0; e < 8; e++) zero |= (y[e] - 0x00010001u) & ~y[e];
  return (zero & 0x80008000u) == 0;
}
__device__ __forceinline__ bool bar_all(int id, int n, bool c) {
  uint32_t r;
  asm volatile("{\n.reg .pred p, q;\nsetp.ne.u32 p, %3, 0;\nbar.red.and.pred q, %1, %2, p;\nselp.u32 %0, 1, 0, q;\n}\n" : "=r"(r) : "r"(id), "r"(n), "r"((uint32_t)c) : "memory");
  return r;
}
__device__ __forceinline__ void final_out(const float* d, const uint32_t (*xw)[10], const uint32_t (*sw)[10], float ra, float rb, __nv_bfloat16* o0, int h, int t) {
  const float ca = 0.25f * ra, cb = 0.25f * rb;
  uint32_t o[2][10];
#pragma unroll
  for (int j = 0; j < 10; j++) {
#pragma unroll
    for (int r = 0; r < 2; r++) {
      const float h0 = d[4 * j + 2 * r] * (r ? cb : ca), h1 = d[4 * j + 2 * r + 1] * (r ? cb : ca);
      o[r][j] = hfma2(pack2(fmaf(h0, tanh_fast(h0), h0), fmaf(h1, tanh_fast(h1), h1)), sw[r][j], xw[r][j]);
      __nv_bfloat16* q = o0 + r * 8 * kD;
      if (j == 3) stg4_if(q + t * 8, o[r][0], o[r][1], o[r][2], o[r][3], true);
      if (j == 7) stg4_if(q + 192 + t * 8, o[r][4], o[r][5], o[r][6], o[r][7], true);
      if (j == 9) asm volatile("st.global.v2.u32 [%0], {%1,%2};" ::"l"(q + 128 - 48 * h + t * 4), "r"(o[r][8]), "r"(o[r][9]) : "memory");
    }
  }
}

struct Taps { uint4 r0, r1; uint32_t n0, n1, dd; };
__device__ __forceinline__ void load_taps(Taps& k, const Params& p, int ch, int tid) {
  const uint4* kp = (const uint4*)(p.ssmk + (size_t)ch * kS);
  k.r0 = ldg4(kp + tid); k.r1 = ldg4(kp + 128 + tid);
  k.n0 = ldg1(kp + tid + 1); k.n1 = tid < 127 ? ldg1(kp + 129 + tid) : 0u;
  k.dd = __bfloat16_as_ushort(p.ssmD[ch]);
}
__device__ __forceinline__ void load_convx(const Params& p, uint32_t cv, uint32_t bar, int ch) {
  mbar_expect(bar, 4096);
  bulk_g2s(cv, p.scr->kvx + (size_t)ch * 4096, 2048, bar);
  bulk_g2s(cv + XB_PL, p.scr->kvx + (size_t)ch * 4096 + 2048, 2048, bar);
}
#define CW 3
#define CSTAMP(j)
__device__ __forceinline__ void zero_pads(uint32_t cv, int lane) {
  if (lane < 8) sts128(cv + (lane >> 2) * XB_PL + 2048 + (lane & 3) * 16, 0, 0, 0, 0);
  else if (lane < 12) sts128(cv + ((lane & 2) ? CV_KO : CV_KE) + (lane & 1) * 16, 0, 0, 0, 0);
  fence_async_smem();
  __syncwarp();
}
__device__ __forceinline__ int y_row(int c, uint32_t par) {
  const int hf = c >= 320, cc = c - hf * 320, u = cc >> 6, cb = hf * 2 + ((cc >> 5) & 1);
  if (u == 2) return cb * 96 + ((cc >> 4) & 1) * 48 + 32 + (cc & 1) + ((cc >> 1) & 1) * 8 + ((cc >> 2) & 3) * 2;
  return (u < 2 ? cb * 96 + u * 48 : 384 + par * 256 + cb * 64 + (u - 3) * 32) + (cc & 1) + ((cc >> 1) & 3) * 8 + ((cc >> 3) & 3) * 2;
}
__device__ __forceinline__ void z_store(uint8_t* dst, uint32_t src, int q) {
  dst += q * 16 * B_SLOT;
  bulk_s2g(dst, src + q * 12288, 6144);
  bulk_s2g(dst + 8 * B_SLOT, src + q * 12288 + 6144, 6144);
  asm volatile("cp.async.bulk.commit_group;\ncp.async.bulk.wait_group 0;" ::: "memory");
}
__device__ __forceinline__ void y_store(const Params& p, uint32_t sb, int h, int ch, uint32_t par) {
  uint8_t* dst = p.scr->y + (size_t)y_row(ch, par) * 4096;
  if (elect_one()) {
    bulk_s2g(dst, sb + OFF_A + 9 * A_SLOT + h * 4096, 4096);
    asm volatile("cp.async.bulk.commit_group;\ncp.async.bulk.wait_group 0;" ::: "memory");
  }
  __syncwarp();
}
__device__ __forceinline__ void conv_service(const Params& p, uint32_t sb, int h, int ch, bool first) {
  bar_sync(NB_WGA + 8 + h, 160);
  const bool now = !first || __all_sync(0xffffffff, mbar_test(sb + BAR_KV, 0));
  if (now && elect_one()) load_convx(p, sb + OFF_CV + (1 - h) * CV_SZ, sb + BAR_XF + 8 * h, ch + 128);
  bar_sync(NB_WGA + 8 + h, 160);
  y_store(p, sb, h, ch, 0);
  if (!now) {
    mbar_wait(sb + BAR_KV, 0);
    if (elect_one()) load_convx(p, sb + OFF_CV + (1 - h) * CV_SZ, sb + BAR_XF + 8 * h, ch + 128);
  }
}
__device__ __forceinline__ uint32_t y_tile(int h) { return OFF_CV + (1 - h) * 13312; }
__device__ __forceinline__ void load_late_y(const Params& p, uint32_t sb, int h, int rb, int cb, uint32_t par) {
  mbar_expect(sb + BAR_YL + 16 * h, 4096);
  tma2d(sb + y_tile(h) + 6144, &p.tmY, rb * 64, 384 + par * 256 + cb * 64 + h * 32, sb + BAR_YL + 16 * h);
  tma2d(sb + y_tile(h) + 8192, &p.tmY, rb * 64, 400 + par * 256 + cb * 64 + h * 32, sb + BAR_YL + 16 * h);
}
__device__ __forceinline__ void held_service(const Params& p, uint32_t sb, int h, int ch, int rb, int cb, uint32_t tag, int lane) {
#pragma unroll 1
  for (int i = 0; i < 8; i++) sts128(sb + OFF_A + 9 * A_SLOT + h * 4096 + i * 512 + lane * 16, 0, 0, 0, 0);
  fence_async_smem();
  __syncwarp();
  y_store(p, sb, h, ch, ~tag & 1);
  mbar_wait(sb + BAR_YT, 1);
  uint8_t* dst = p.scr->y + (size_t)y_row(ch, tag & 1) * 4096;
  asm volatile("" : "+l"(dst));
  bar_sync(NB_WGA + 8 + h, 160);
  bar_sync(NB_WGA + 8 + h, 160);
  if (elect_one()) {
    bulk_s2g(dst, sb + OFF_A + 9 * A_SLOT + h * 4096, 4096);
    asm volatile("cp.async.bulk.commit_group;" ::: "memory");
    mbar_expect(sb + BAR_XF + 8 * h, 6144);
#pragma unroll 1
    for (int i = 0; i < 3; i++) tma2d(sb + y_tile(h) + i * 2048, &p.tmY, rb * 64, cb * 96 + h * 48 + i * 16, sb + BAR_XF + 8 * h);
  }
  mbar_wait(sb + BAR_AE + 8 * (LL_AT - 1), 1);
  if (elect_one()) { load_late_y(p, sb, h, rb, cb, tag & 1); asm volatile("cp.async.bulk.wait_group 0;" ::: "memory"); }
}
__device__ __forceinline__ void conv_worker(const Params& p, Taps& k, uint32_t cv, uint32_t yb0,
                                            uint32_t xbar, int nbar, int ch0, int n, uint32_t holdbar, int w, int lane,
                                            int tid, int st0, int rb, int cb) {
  const int g = lane >> 2, t = lane & 3, w0 = w & 1, w1 = w >> 1;
  const uint32_t ab = cv + ((g & 1) ? CV_KE : CV_KO) + 32 + 2 * (64 * w0 + 8 * w1 + ((g - 15) & ~1) + 2 * t);
  const uint32_t scA = cv + (w1 ? CV_KO : CV_KE) + 32, scB = scA + 2048;
  const int dl = (t >> 1) ^ 1;
  if (n == 2) mbar_wait(xbar, 0);
  STAMPW(st0 + 3);
#pragma unroll 1
  for (int i = 0; i < n; i++) {
    if (tid == 0) {
      k.r0.x = (k.r0.x & 0xffff0000u) | (pack2(bf_lo(k.r0.x) + bf_lo(k.dd), 0.f) & 0xffffu);
      sts32(cv + CV_KO + 28, k.r0.x << 16);
    }
    sts128(cv + CV_KE + 32 + tid * 16, k.r0.x, k.r0.y, k.r0.z, k.r0.w);
    sts128(cv + CV_KO + 32 + tid * 16, prmt(k.r0.x, k.r0.y, 0x5432), prmt(k.r0.y, k.r0.z, 0x5432), prmt(k.r0.z, k.r0.w, 0x5432), prmt(k.r0.w, k.n0, 0x5432));
    sts128(cv + CV_KE + 2080 + tid * 16, k.r1.x, k.r1.y, k.r1.z, k.r1.w);
    sts128(cv + CV_KO + 2080 + tid * 16, prmt(k.r1.x, k.r1.y, 0x5432), prmt(k.r1.y, k.r1.z, 0x5432), prmt(k.r1.z, k.r1.w, 0x5432), prmt(k.r1.w, k.n1, 0x5432));
    if (i + 1 < n) load_taps(k, p, ch0 + (i + 1) * 128, tid);
    bar_sync(nbar, 128);
    CSTAMP(0);
    const uint64_t db = mkdesc(cv + (i & 0x1000), XB_PL, 128, 0);
    float d[64];
    uint32_t a[8][16];
    if (i == 0) mbar_wait(xbar, 0);
    conv_load<7>(a[7], ab); conv_load<6>(a[6], ab); conv_load<5>(a[5], ab); conv_load<4>(a[4], ab);
#pragma unroll
    for (int j = 0; j < 64; j++) d[j] = 0.f;
    mbar_wait(xbar, i & 1);
    if (i + 1 == n) mbar_wait(holdbar + (BAR_GO1 - BAR_GO), 1);
    CSTAMP(1);
    conv_step<7, -1>(d, a, ab, db); conv_step<6, -1>(d, a, ab, db); conv_step<5, -1>(d, a, ab, db); conv_step<4, -1>(d, a, ab, db);
    if (i + 1 == n) mbar_wait(holdbar, 1);
    conv_load<3>(a[3], ab);
    conv_step<3, 2>(d, a, ab, db);
    conv_step<2, 1>(d, a, ab, db);
    conv_step<1, 0>(d, a, ab, db);
    conv_step<0, -1>(d, a, ab, db);
    acc_fence<64>(d);
    CSTAMP(2);
    bar_sync(nbar + 8, 160);
    float E[16][2];
#pragma unroll
    for (int j = 0; j < 15; j++) { E[j][0] = d[4 * j] + d[4 * j + 6]; E[j][1] = d[4 * j + 1] + d[4 * j + 7]; }
    E[15][0] = d[60]; E[15][1] = d[61];
    if (w0 == 0) {
#pragma unroll
      for (int j = 8; j < 16; j++) sts64f(scA + (j - 8) * 256 + lane * 8, E[j][0], E[j][1]);
    } else {
      const uint32_t a = scB - dl * 256 + (lane ^ 2) * 8;
#pragma unroll
      for (int j = 1; j < 8; j++) sts64f(a + j * 256, E[j][0], E[j][1]);
      sts64f(scB + (dl ? 7 * 256 : 0) + (lane ^ 2) * 8, dl ? E[8][0] : E[0][0], dl ? E[8][1] : E[0][1]);
    }
    bar_sync(nbar, 128);
    CSTAMP(3);
    uint32_t pk[8];
    if (w0 == 0) {
#pragma unroll
      for (int j = 0; j < 8; j++) { const float2 v = lds64f(scB + j * 256 + lane * 8); pk[j] = pack2(E[j][0] + v.x, E[j][1] + v.y); }
    } else {
      const uint32_t a0 = scA - dl * 256 + (lane ^ 2) * 8;
#pragma unroll
      for (int j = 9; j < 16; j++) { const float2 v = lds64f(a0 + (j - 8) * 256); pk[j - 8] = pack2(E[j][0] + v.x, E[j][1] + v.y); }
      const float2 v = lds64f(scA + (dl ? 7 * 256 : 0) + (lane ^ 2) * 8);
      pk[0] = pack2((dl ? 0.f : E[8][0]) + v.x, (dl ? 0.f : E[8][1]) + v.y);
    }
    CSTAMP(4);
    if (i + 1 == n) {
#pragma unroll
      for (int j = 0; j < 8; j++) pk[j] = ~pk[j];
    }
    const int c1 = (w0 ? 35 : 95) - lane, c0 = (w0 && lane < 4) ? c1 - 32 : c1 + 32;
    stsm4t(yb0 + 128 * (c0 & 31) + (((2 * (c0 >> 5) + w1) ^ (c0 & 7)) << 4), pk[0], pk[1], pk[2], pk[3]);
    stsm4t(yb0 + 128 * (c1 & 31) + (((2 * (c1 >> 5) + w1) ^ (c1 & 7)) << 4), pk[4], pk[5], pk[6], pk[7]);
    fence_async_smem();
    bar_sync(nbar + 8, 160);
    CSTAMP(5);
    STAMPW(st0 + i);
    if (n == 2 && i == 0) {
      const int u = (tid >> 3) % 5, kg = rb * 3 + (tid < 120 ? (tid >> 3) / 5 : 0), c = u < 4 ? (u >> 1) * 10 + (u & 1) * 4 : 8, o2 = u < 4 ? 2 : 10;
      const uint4* wp = (const uint4*)p.wout + (uint32_t)((kg * 8 + (tid & 7)) * (kD / 8) + (seg_col(cb, 0) >> 3) + (u < 4 ? (u >> 1) * 8 + (u & 1) * 24 : 16));
      const uint4 w0 = ldg4(wp), w1 = ldg4(wp + 1), w2 = ldg4(wp + 2), w3 = ldg4(wp + 3);
      uint8_t* dst = p.scr->wo + (uint32_t)(cb * (12 * 20480) + kg * 2560 + c * 128 + (tid & 7) * 16);
      const bool f = u < 4, on = tid < 120;
      stg4_if(dst, w0.x, f ? w1.x : w0.z, f ? w2.x : w1.x, f ? w3.x : w1.z, on);
      stg4_if(dst + 128, w0.y, f ? w1.y : w0.w, f ? w2.y : w1.y, f ? w3.y : w1.w, on);
      stg4_if(dst + o2 * 128, f ? w0.z : w2.x, f ? w1.z : w2.z, f ? w2.z : w3.x, w3.z, on);
      stg4_if(dst + o2 * 128 + 128, f ? w0.w : w2.y, f ? w1.w : w2.w, f ? w2.w : w3.y, w3.w, on);
      bar_arrive(NB_WO, 160);
    }
  }
}

struct KvRegs { uint32_t k[11], v[8]; uint4 sh; };
__device__ __forceinline__ void kv_load(KvRegs& q, const __nv_bfloat16* kp, const __nv_bfloat16* vp, const __nv_bfloat16* sp, bool halo) {
#pragma unroll
  for (int i = 0; i < 11; i++) q.k[i] = (i >= 3 || halo) ? ldg1(kp + i * kD) : 0u;
#pragma unroll
  for (int i = 0; i < 8; i++) q.v[i] = ldg1(vp + i * kD);
  q.sh = ldg4(sp);
}
__device__ __forceinline__ void kv_unit(const KvRegs& q, uint32_t oa) {
  const uint32_t w0 = prmt(q.sh.x, q.sh.z, 0x5410), w1 = prmt(q.sh.x, q.sh.z, 0x7632), w2 = prmt(q.sh.y, q.sh.w, 0x5410), w3 = prmt(q.sh.y, q.sh.w, 0x7632);
  uint32_t r[8];
#pragma unroll
  for (int i = 0; i < 8; i++) r[i] = hmul2(hfma2(q.k[i + 3], w0, hfma2(q.k[i + 2], w1, hfma2(q.k[i + 1], w2, hmul2(q.k[i], w3)))), q.v[i]);
  sts128(oa, prmt(r[7], r[6], 0x5410), prmt(r[5], r[4], 0x5410), prmt(r[3], r[2], 0x5410), prmt(r[1], r[0], 0x5410));
  sts128(oa + 2048, prmt(r[7], r[6], 0x7632), prmt(r[5], r[4], 0x7632), prmt(r[3], r[2], 0x7632), prmt(r[1], r[0], 0x7632));
}

__device__ __forceinline__ void gather_colsum(const Params& p, uint32_t sb, int cb, int part, uint32_t tag, int lane) {
  uint4 v[3];
  uint32_t t0 = 0;
#pragma unroll 1
  while (true) {
    bool ok = true;
#pragma unroll
    for (int i = 0; i < 3; i++) {
      v[i] = ld_ll4(&p.scr->colsum[(part ? 0 : 768) + cb * 192 + i * 64 + lane * 2]);
      ok = ok && v[i].y == tag && v[i].w == tag;
    }
    if (__all_sync(0xffffffff, ok)) break;
    spin_guard(t0);
  }
#pragma unroll
  for (int i = 0; i < 3; i++) {
    const uint32_t hi = pack2(__uint_as_float(v[i].x), __uint_as_float(v[i].z)), ca = sb + OFF_CS + (1 - part) * 768 + i * 256 + (lane >> 2) * 32 + (lane & 3) * 4;
    sts32(ca, hi);
    sts32(ca + 16, pack2(__uint_as_float(v[i].x) - bf_lo(hi), __uint_as_float(v[i].z) - bf_hi(hi)));
  }
  __syncwarp();
  if (lane == 0) mbar_arrive(sb + BAR_ST + 8 * part);
}

__device__ __forceinline__ void helper_cta(const Params& p, uint32_t sb, int cb, int warp, int lane) {
  constexpr int NS = 9, ONES = NS * B_SLOT, BF = ONES + 256, BE = BF + 8 * NS;
  if (warp < NS && elect_one()) {
    mbar_init(sb + BF + 8 * warp, 1); mbar_init(sb + BE + 8 * warp, 1);
    fence_async_smem();
    if (warp == 0) { mbar_expect(sb + BF, B_SLOT); tma3d(sb, &p.tmW, 0, 0, 12 + cb * 3, sb + BF); }
  }
  if (warp == 15) { sts32(sb + ONES + lane * 4, 0x3f803f80u); sts32(sb + ONES + 128 + lane * 4, 0x3f803f80u); fence_async_smem(); }
  __syncthreads();
  if (warp == 4) {
    int s = 1, ph = 1;
#pragma unroll 1
    for (int it = 1; it < 20; it++) {
      mbar_wait(sb + BE + 8 * s, ph);
      if (elect_one()) { mbar_expect(sb + BF + 8 * s, B_SLOT); tma3d(sb + s * B_SLOT, &p.tmW, 0, (it < 10 ? it : it - 10) * 64, (it < 10 ? 12 : 0) + cb * 3, sb + BF + 8 * s); }
      if (++s == NS) { s = 0; ph ^= 1; }
    }
  } else if (warp < 4) {
    const uint32_t tag = load_epoch(p, 128 + cb, lane) + 1;
    const uint64_t db = mkdesc(sb + ONES, 128, 128, 0);
    uint2* dst = p.scr->colsum + cb * 192 + warp * 16 + (lane >> 2);
    if ((lane & 3) == 0) {
#pragma unroll 1
      for (int j = 0; j < 12; j++) st_ll2(dst + (j < 6 ? 768 : 0) + ((j % 6) >> 1) * 64 + (j & 1) * 8, 0, 0);
    }
    int s = 0, ph = 0;
#pragma unroll 1
    for (int part = 0; part < 2; part++) {
      float d[12];
#pragma unroll
      for (int i = 0; i < 12; i++) d[i] = 0.f;
#pragma unroll 1
      for (int it = 0; it < 10; it++) {
        mbar_wait(sb + BF + 8 * s, ph);
        const uint64_t da = mkdesc(sb + s * B_SLOT, 8192, 1024, 1);
        WG_FENCE();
#pragma unroll
        for (int j = 0; j < 12; j++) wgmma_colsum(d + 4 * (j % 3), da + (j % 3) * 512 + (j / 3) * 128, db);
        WG_COMMIT();
        WG_WAIT(1);
        mbar_arrive_if(sb + BE + 8 * (s == 0 ? NS - 1 : s - 1), threadIdx.x == 0 && (it | part) != 0);
        if (++s == NS) { s = 0; ph ^= 1; }
      }
      WG_WAIT(0);
      acc_fence<12>(d);
      if ((lane & 3) == 0) {
#pragma unroll
        for (int j = 0; j < 6; j++) st_ll2(dst + (part ? 0 : 768) + (j >> 1) * 64 + (j & 1) * 8, __float_as_uint(d[2 * j]), tag);
      }
      STAMPW(1 + part);
    }
    if (threadIdx.x == 0) st_relaxed(&p.scr->epoch[(128 + cb) * EPS], tag);
  }
}

__global__ void __launch_bounds__(512, 1) fused_kernel(const __grid_constant__ Params p) {
  extern __shared__ __align__(1024) uint8_t smem[];
  const int warp = __shfl_sync(0xffffffff, (int)(threadIdx.x >> 5), 0);
  const int lane = threadIdx.x & 31, tid = threadIdx.x & 127;
  const uint32_t sb = __shfl_sync(0xffffffff, (uint32_t)__cvta_generic_to_shared(smem), 0);
  const uint32_t tstart = clock();
  if (elect_one()) {
    if (warp < 5) asm volatile("prefetch.tensormap [%0];" ::"l"(&p.tmX + warp) : "memory");
    mbar_init(sb + OFF_BAR + 8 * warp, 1); mbar_init(sb + OFF_BAR + 128 + 8 * warp, 1); mbar_init(sb + OFF_BAR + 256 + 8 * warp, 2);
    asm volatile("fence.mbarrier_init.release.cluster;" ::: "memory");
  }
  int b = blockIdx.x;
  if (p.by_smid) asm volatile("mov.u32 %0, %%smid;" : "=r"(b));
  b = __shfl_sync(0xffffffff, b, 0);
  const int tp = b >> 1, t7 = (tp - 32) / 7;
  const int lin = tp < 32 ? ((tp & 7) ? (tp & 7) * 16 : 8) + (tp >> 3) * 2 + (b & 1)
                          : (tp < 60 ? (tp - 31 - t7 * 7) * 16 + 8 + t7 * 2 + (b & 1) : (tp < 62 ? -1 : b - 124));
  const int hcb = (b & 3) ^ 2;
  if (lin < 0) { helper_cta(p, sb, hcb, warp, lane); return; }
  const int cb = ((lin >> 4) & 1) * 2 + ((lin >> 1) & 1), rb = (lin >> 5) * 8 + ((lin >> 2) & 3) * 2 + (lin & 1);
  const int zs0 = 4 - (cb & 2);
  const int chb = (cb >> 1) * 320 + rb * 2 + (cb & 1);
  if (warp == 0 && elect_one()) {
    mbar_expect(sb + BAR_AF, A_SLOT);
    tma_rows(sb + OFF_A, &p.tmX, 0, rb, sb + BAR_AF);
    mbar_expect(sb + BAR_BF, B_SLOT);
    tma3d(sb + OFF_B, &p.tmW, 0, 0, 12 + cb * 3, sb + BAR_BF);
  }
  if (warp == 1) STAMP(31);
  if (sb & 1023) die();
  __syncthreads();

  if (warp >= 12) {
    asm volatile("setmaxnreg.dec.sync.aligned.u32 32;");
    uint32_t bias2 = 0;
    if (warp == 15) bias2 = ldg1(p.bsp + (lane >> 3) * 512 + rb * 16 + (lane & 7) * 2);
    const uint32_t epoch = load_epoch(p, lin, lane);
    if (warp == 12) {
#pragma unroll 1
      for (int i = 1; i < NA; i++) {
        if (elect_one()) {
          mbar_expect(sb + BAR_AF + 8 * i, A_SLOT);
          tma_rows(sb + OFF_A + i * A_SLOT, &p.tmX, i * 64, rb, sb + BAR_AF + 8 * i);
          if (i < NB) { mbar_expect(sb + BAR_BF + 8 * i, B_SLOT); tma3d(sb + OFF_B + i * B_SLOT, &p.tmW, 0, i * 64, 12 + cb * 3, sb + BAR_BF + 8 * i); }
        }
      }
      STAMP(32);
      uint32_t kvt;
      {
        const int tb = rb * 2 + (cb & 1);
        kvt = __shfl_sync(0xffffffff, (ld_relaxed(p.scr->cnt + (CNT_KV + (cb >> 1)) * CSP) & ~63u) + 64, 0);
        {
          uint32_t tp = tstart;
          pace(tp, KV_T0);
          mbar_arrive_if(sb + BAR_KV + 8, lane == 0);
        }
        mbar_wait2(sb + BAR_XS, 0, sb + BAR_ST, 0);
#pragma unroll 1
        for (int u = 0; u < 5; u++) {
          mbar_wait(sb + BAR_KU + 8 * u, 0);
          fence_async_smem();
          if (elect_one()) {
            asm volatile("cp.async.bulk.tensor.3d.global.shared::cta.bulk_group [%0, {%2, %3, %4}], [%1];\ncp.async.bulk.commit_group;" ::"l"(&p.tmKV),
                         "r"(sb + OFF_CV + CV_SZ + (u < 3 ? u : u - 3) * 4096), "r"((63 - tb) * 16), "r"((cb >> 1) * 160 + u * 32), "r"(0) : "memory");
            if (u == 1 || u == 4) asm volatile("cp.async.bulk.wait_group 0;" ::: "memory");
            if (u == 1) { mbar_arrive(sb + BAR_KU); red_release(p.scr->cnt + (CNT_KV + (cb >> 1)) * CSP); }
          }
          __syncwarp();
          if (u == 1) {
            STAMP(35);
            { const char* q = (const char*)p.ssmk + chb * 4096 + lane * 128; prefetch_l2(q); prefetch_l2(q + 64 * 4096); }
          }
        }
        zero_pads(sb + OFF_CV + CV_SZ, lane);
        if (elect_one()) { mbar_arrive(sb + BAR_KU + 8); red_release(p.scr->cnt + (CNT_KV + 2 + (cb >> 1)) * CSP); }
        STAMP(30);
        if (lane < 24) {
          const char* r = (const char*)p.wout + (rb * 24 + lane) * (kD * 2) + (cb >> 1) * 640 + (cb & 1) * 384;
          prefetch_l2(r); prefetch_l2(r + 128); prefetch_l2(r + 256 - (cb & 1) * 384);
        }
      }
      poll_counter(p.scr->cnt + (CNT_KV + 2 + (cb >> 1)) * CSP, kvt);
      if (elect_one()) mbar_arrive(sb + BAR_KV);
      STAMP(34);
      {
        const char* q = (const char*)p.wsp + (cb * 512 + rb * 16 + (lane >> 1)) * (kS * 2) + (lane & 1) * 128;
        uint32_t tp = clock();
#pragma unroll 1
        for (int i = LEAD / 2; i < 16; i++) {
          prefetch_l2(q + i * 256);
          pace(tp, WSP_D);
        }
      }
      const uint32_t tag = epoch + 1;
      uint8_t* hrow = p.scr->h + anchor(rb * 12 * A_SLOT);
      uint8_t* hown = hrow + anchor(cb * 3 * A_SLOT);
      bar_sync(NB_H, 160);
      if (elect_one()) bulk_s2g(hown, sb + OFF_A + 5 * A_SLOT, A_SLOT);
      mbar_wait(sb + BAR_G2, 0);
      if (elect_one()) {
        bulk_s2g(hown + A_SLOT, sb + OFF_A + 6 * A_SLOT, 2 * A_SLOT);
        asm volatile("cp.async.bulk.commit_group;\ncp.async.bulk.wait_group 0;" ::: "memory");
        red_release(&p.scr->hcnt[(rb >> HGRP) * 32]);
      }
      __syncwarp();
      STAMP(20);
      STAMP(39);
      const uint8_t* hsrc = cb ? hrow : hrow + 3 * A_SLOT;
      if (elect_one()) {
        poll_one(&p.scr->hcnt[(rb >> HGRP) * 32], tag * (4 << HGRP));
        bulk_g2s(sb + OFF_A + 8 * A_SLOT, hsrc, A_SLOT, sb + BAR_AF + 64);
        STAMP(37);
        uint32_t tp = clock();
#pragma unroll 1
        for (int i = 0; i < 8; i++) {
          hsrc += A_SLOT;
          if (hsrc == hown) hsrc += 3 * A_SLOT;
          if (i == 5) mbar_wait(sb + BAR_AE + 56, 0);
          tp += HPACE;
          while ((int32_t)((uint32_t)clock() - tp) < 0) {}
          bulk_g2s(sb + OFF_A + i * A_SLOT, hsrc, A_SLOT, sb + BAR_AF + 8 * i);
        }
      }
      STAMP(21);
    } else if (warp == 13) {
      int s = 0, ph = 0;
#pragma unroll 1
      for (int it = NB; it < 20; it++) {
        mbar_wait(sb + BAR_BE + 8 * s, ph);
        if (elect_one()) { mbar_expect(sb + BAR_BF + 8 * s, B_SLOT); tma3d(sb + OFF_B + s * B_SLOT, &p.tmW, 0, (it < 10 ? it : (it + zs0) % 10) * 64, (it < 10 ? 12 : 0) + cb * 3, sb + BAR_BF + 8 * s); }
        STAMP2(32 + it);
        if (++s == NB) { s = 0; ph ^= 1; }
      }
      mbar_wait(sb + BAR_XC, 0);
#pragma unroll 1
      for (int i = 0; i < LEAD; i++) {
        mbar_wait(sb + BAR_AE + 8 * i, 0);
        if (elect_one()) { mbar_expect(sb + BAR_AF + 8 * i, A_SLOT); tma_rows(sb + OFF_A + i * A_SLOT, &p.tmWsp, i * 64, rb, sb + BAR_AF + 8 * i); }
      }
#pragma unroll 1
      for (int i = 0; i < NB; i++) mbar_wait2(sb + BAR_BE + 8 * i, 1, sb + BAR_AE + 8 * (LEAD + i), 0);
      mbar_expect_if(sb + (lane < NB ? BAR_BF + 8 * lane : BAR_AF + 8 * (LEAD + lane - NB)), lane < NB ? B_SLOT : A_SLOT, lane < 2 * NB);
      const uint8_t* zt = p.scr->z2 + anchor(cb * 32 * B_SLOT);
      if (elect_one()) {
        poll_one(p.scr->zcnt + (cb >> ZSH) * 32, (epoch + 1) * (32 << ZSH));
        bulk_g2s(sb + OFF_B, zt, B_SLOT, sb + BAR_BF);
#pragma unroll 1
        for (int it = 1; it < NB + LEAD; it++) {
          if (it == LEAD) mbar_wait(sb + BAR_ZP, 0);
          if (it >= LEAD) tma_rows(sb + OFF_A + it * A_SLOT, &p.tmWsp, it * 64, rb, sb + BAR_AF + 8 * it);
          if (it < NB) bulk_g2s(sb + OFF_B + it * B_SLOT, zt + it * B_SLOT, B_SLOT, sb + BAR_BF + 8 * it);
        }
      }
      __syncwarp();
      STAMP(22);
      int sa = NB + LEAD, pa = 0;
      ph = 0;
#pragma unroll 1
      for (int it = NB; it < 32; it++) {
        if (it == 16) mbar_wait(sb + BAR_Z1, 1);
        mbar_wait2(sb + BAR_BE + 8 * s, ph, sb + BAR_AE + 8 * sa, pa);
        if (elect_one()) {
          mbar_expect(sb + BAR_BF + 8 * s, B_SLOT);
          bulk_g2s(sb + OFF_B + s * B_SLOT, zt + it * B_SLOT, B_SLOT, sb + BAR_BF + 8 * s);
          if (it + LEAD < 32) { mbar_expect(sb + BAR_AF + 8 * sa, A_SLOT); tma_rows(sb + OFF_A + sa * A_SLOT, &p.tmWsp, (it + LEAD) * 64, rb, sb + BAR_AF + 8 * sa); }
        }
        if (it + LEAD < 31 && ++sa == NA2) { sa = 0; pa ^= 1; }
        STAMP2(52 + it);
        if (++s == NB) { s = 0; ph ^= 1; }
      }
      mbar_wait(sb + BAR_WO, 0);
#pragma unroll 1
      for (int it = 0; it < 12; it++) {
        if (it < 6) mbar_wait(sb + BAR_BE + 8 * ((0x110443 >> (4 * it)) & 7), it < 3 ? 1 : 0);
        else mbar_wait(sb + BAR_BE + 8 * s, ph);
        if (elect_one()) {
          mbar_expect(sb + BAR_BF + 8 * s, 20480);
          bulk_g2s(sb + OFF_B + (s == 5 ? 0 : s + 1) * 20480, p.scr->wo + (size_t)(cb * 12 + g3_block(cb, it)) * 20480, 20480, sb + BAR_BF + 8 * s);
        }
        STAMP2(84 + it);
        if (++s == 6) { s = 0; ph ^= 1; }
      }
    } else if (warp == 14) {
      const uint32_t tag = epoch + 1;
      mbar_wait(sb + BAR_AF + 8 * (NA - 1), 0);
      gather_colsum(p, sb, cb, 0, tag, lane);
      STAMP(27);
      uint8_t* zd = p.scr->z2 + anchor((cb * 32 + (rb >> 2)) * B_SLOT + (rb & 3) * 6144);
      const uint32_t zsrc = anchor(sb + OFF_A + zs0 * A_SLOT);
      bar_sync(NB_Z, 160);
      if (elect_one()) {
        z_store(zd, zsrc, 0);
        STAMP(7);
        red_release(p.scr->zcnt + (cb >> ZSH) * 32);
      }
      STAMP(25);
      bar_sync(NB_Z2, 96);
      if (elect_one()) {
        z_store(zd, zsrc, 1);
        mbar_arrive(sb + BAR_ZP);
        red_release(p.scr->cnt + (CNT_Z1 + (cb >> 1)) * CSP);
      }
      STAMP(28);
      mbar_wait(sb + BAR_AE + 72, 0);
      conv_service(p, sb, 0, chb + 64, true);
      bar_sync(NB_WO, 160);
      bar_sync(NB_CD, 64);
      if (elect_one()) { red_release(p.scr->cnt + (CNT_WO + cb) * CSP); red_relaxed(p.scr->cnt + (CNT_Y + (cb >> 1)) * CSP); }
      STAMP(49);
      poll_counter(p.scr->cnt + (CNT_WO + cb) * CSP, tag * 32);
      if (elect_one()) mbar_arrive(sb + BAR_WO);
      STAMP(46);
      held_service(p, sb, 0, chb + 192, rb, cb, tag, lane);
    } else {
      const uint32_t tag = epoch + 1;
      sts32(sb + OFF_BIAS + lane * 4, bias2);
      if (lane < 2) sts32(sb + OFF_TAG + lane * 4, lane ? 0 : tag);
      fence_async_smem();
      uint32_t t0 = 0;
      mbar_wait(sb + BAR_AF + 8 * (NA - 1), 0);
#pragma unroll 1
      while (true) {
        const uint4 u = ld_ll4(&p.scr->xstat[rb * 64 + lane]), v = ld_ll4(&p.scr->xstat[rb * 64 + 32 + lane]);
        sts64f(sb + OFF_XS + lane * 8, __uint_as_float(u.x), __uint_as_float(u.z));
        sts64f(sb + OFF_XS + 256 + lane * 8, __uint_as_float(v.x), __uint_as_float(v.z));
        if (__all_sync(0xffffffff, u.y == tag && u.w == tag && v.y == tag && v.w == tag)) break;
        spin_guard(t0);
      }
      STAMP(26);
      __syncwarp();
      if (lane == 0) mbar_arrive(sb + BAR_XS);
      { uint32_t tp = tstart; pace(tp, CS1_T); gather_colsum(p, sb, cb, 1, tag, lane); STAMP(38); }
      mbar_wait(sb + BAR_KU, 1);
      poll_counter(p.scr->cnt + (CNT_KV + (cb >> 1)) * CSP, tag * 64);
      if (elect_one()) load_convx(p, sb + OFF_CV, sb + BAR_XF + 8, chb);
      mbar_wait(sb + BAR_KU + 8, 1);
      if (elect_one()) load_convx(p, sb + OFF_CV + CV_SZ, sb + BAR_XF, chb + 64);
      STAMP(48);
      mbar_wait(sb + BAR_AE + 72, 0);
#pragma unroll 1
      for (int i = 0; i < 2; i++) {
        conv_service(p, sb, 1, chb + i * 128, i == 0);
        if (i == 0) {
          poll_counter(p.scr->cnt + (CNT_Z1 + (cb >> 1)) * CSP, tag * 64);
          if (elect_one()) mbar_arrive(sb + BAR_Z1);
          STAMP(24);
        }
      }
      bar_arrive(NB_CD, 64);
      mbar_wait(sb + BAR_WO, 0);
      poll_counter(p.scr->cnt + (CNT_Y + (cb >> 1)) * CSP, tag * 64);
      STAMP(47);
      if (elect_one()) mbar_arrive(sb + BAR_YT);
      held_service(p, sb, 1, chb + 256, rb, cb, tag, lane);
      if (lane == 0) st_relaxed(&p.scr->epoch[lin * EPS], tag);
      STAMP(23);
    }
  } else {
    if (warp == 7) STAMP(36);
    const int wg = warp >> 2, w = warp & 3, g = lane >> 2, t = lane & 3;
    Taps k;
    uint32_t xw[2][10];
    if (wg == 2) {
      asm volatile("setmaxnreg.inc.sync.aligned.u32 160;");
      const int tb = rb * 2 + (cb & 1), c0 = (cb >> 1) * 320;
      const uint32_t cv = sb + OFF_CV + CV_SZ;
      if (w == 0) zero_pads(sb + OFF_CV, lane);
      mbar_wait(sb + BAR_KV + 8, 0);
      const int t0 = tb * 32 + w * 8;
      const __nv_bfloat16* kp = p.k + (size_t)(t0 - 3) * kD + c0 + lane * 2;
      const __nv_bfloat16* vp = p.v + (size_t)t0 * kD + c0 + lane * 2;
      const __nv_bfloat16* sp = p.shift + (c0 + lane * 2) * 4;
      const uint32_t oa = cv + ((3 - w) & 1) * 1024 + lane * 32 + ((((3 - w) >> 1) ^ (lane >> 2)) & 1) * 16;
#pragma unroll 1
      for (int r = 0; r < 2; r++) {
        KvRegs n0, n1, n2;
        STAMPW(r ? 51 : 50);
        kv_load(n0, kp + r * 128, vp + r * 128, sp + r * 512, t0 > 0);
        kv_load(n1, kp + r * 128 + 64, vp + r * 128 + 64, sp + r * 512 + 256, t0 > 0);
        if (r) kv_load(n2, kp + 256, vp + 256, sp + 1024, t0 > 0);
        kv_unit(n0, oa + r * 8192);
        bar_sync(NB_WGC, 128);
        mbar_arrive_if(sb + BAR_KU + 16 * r, tid == 0);
        if (r) mbar_wait(sb + BAR_KU, 1);
        kv_unit(n1, oa + (r ? 0 : 4096));
        bar_sync(NB_WGC, 128);
        mbar_arrive_if(sb + BAR_KU + 16 * r + 8, tid == 0);
        if (r) {
          kv_unit(n2, oa + 4096);
          bar_sync(NB_WGC, 128);
          mbar_arrive_if(sb + BAR_KU + 32, tid == 0);
        } else {
          mbar_wait(sb + BAR_AF + 8 * ((cb >> 1) * 5 + 1), 0);
          mbar_wait2(sb + BAR_AF + 8 * ((cb >> 1) * 5 + 2), 0, sb + BAR_AF + 8 * ((cb >> 1) * 5 + 4), 0);
          final_load_x(xw, sb + OFF_A, cb, 1, w, lane);
          fence_async_smem();
          bar_sync(NB_WGC, 128);
          mbar_arrive_if(sb + BAR_XC, tid == 0);
        }
      }
      STAMPW(13);
      load_taps(k, p, chb, tid);
    } else {
      float d[96];
      if (wg == 0) st_ll2(&p.scr->zstat[(rb * 256 + cb * 64 + w * 16 + g + (t >> 1) * 8) * 2 + (t & 1)], 0, 0);
      else if ((tid & 7) == 0) st_ll4(&p.scr->xstat[rb * 64 + cb * 16 + (tid >> 3)], 0, 0, 0, 0);
      {
        #pragma unroll
        for (int i = 0; i < 96; i++) d[i] = 0.f;
        {
          if (__builtin_expect(wg == 1, 0)) {
            const int tid = tid_now();
            const uint32_t epoch = load_epoch(p, lin, lane);
            float s = 0.f, q = 0.f;
#pragma unroll 1
            for (int i = 0; i < 10; i++) {
              mbar_wait(sb + BAR_AF + 8 * i, 0);
              const uint4 x4 = lds128(sb + OFF_A + i * A_SLOT + cb * 2048 + tid * 16);
              const uint32_t u[4] = {x4.x, x4.y, x4.z, x4.w};
#pragma unroll
              for (int e = 0; e < 4; e++) { const float a = bf_lo(u[e]), c = bf_hi(u[e]); s += a + c; q = fmaf(a, a, q); q = fmaf(c, c, q); }
            }
#pragma unroll
            for (int o = 1; o <= 4; o <<= 1) { s += __shfl_xor_sync(0xffffffff, s, o); q += __shfl_xor_sync(0xffffffff, q, o); }
            const float m = s * (1.f / kD);
            const float r = rsqrtf(fmaxf(fmaf(-m, m, q * (1.f / kD)), 0.f) + 1e-5f);
            if ((tid & 7) == 0) st_ll4(&p.scr->xstat[rb * 64 + cb * 16 + (tid >> 3)], __float_as_uint(m), epoch + 1, __float_as_uint(r), epoch + 1);
            STAMPW(12);
            bar_sync(NB_G1, 256);
          }
          gemm_loop<192, true, 0>(d, sb, 10, wg ? zs0 : 0, 0, 0, 0, wg, 2, tid_now(), [&]() { if (wg == 0) bar_arrive(NB_G1, 256); });
          asm volatile("setmaxnreg.inc.sync.aligned.u32 160;");
          STAMPW(wg ? 14 : 1);
          if (wg == 0) ZS(0);
          mbar_wait2(sb + BAR_XS, 0, sb + BAR_ST + 8 * wg, 0);
          if (wg == 0) ZS(1);
        }
        const int t1 = tid_now();
        const uint32_t xa1 = sb + OFF_XS + (w * 16 + ((t1 & 31) >> 2)) * 8;
        const float2 s0 = lds64f(xa1), s1 = lds64f(xa1 + 64);
        uint32_t z[48];
        float st[4];
        fence_async_smem();
        fold_mean(d, sb + OFF_CS + (1 - wg) * 768, s0.x, s1.x, t1 & 3);
        WG_WAIT(0);
        acc_fence<96>(d);
        if (wg == 0) ZS(2);
        gelu_tile(d, z, st, s0.y, s1.y);
        const int tid = tid_now(), lane = tid & 31, g = lane >> 2, t = lane & 3;
        if (wg == 1) {
          uint32_t bra, brb;
          asm volatile("ld.shared.u16 %0, [%1];" : "=r"(bra) : "r"(sb + OFF_BIAS + (w * 16 + g) * 2));
          asm volatile("ld.shared.u16 %0, [%1+16];" : "=r"(brb) : "r"(sb + OFF_BIAS + (w * 16 + g) * 2));
#pragma unroll
          for (int j = 0; j < 96; j++) d[j] = bf_lo((j & 2) ? brb : bra);
          STAMPW(15);
          gemm_loop<192, true, 1>(d, sb, 32, 0, 1, 20, 0, 2, 2, tid, []() {});
          mbar_arrive_if(sb + BAR_GO1, tid == 0);
          STAMPW(16);
          const int t2 = tid_now(), l2 = t2 & 31;
          const uint32_t ha = sb + OFF_A + 5 * A_SLOT + (l2 >> 4) * 1024 + (2 * w + ((l2 >> 3) & 1)) * 128 + (l2 & 7) * 16;
#pragma unroll
          for (int j = 0; j < 24; j += 2) {
#pragma unroll
            for (int e = 0; e < 4; e++) z[2 * j + e] = hmul2(z[2 * j + e], pack2(d[4 * j + 2 * e], d[4 * j + 2 * e + 1]));
            stsm4(ha + j * 1024, z[2 * j], z[2 * j + 1], z[2 * j + 2], z[2 * j + 3]);
            if (j == 6) {
              fence_async_smem();
              bar_arrive(NB_H, 160);
            }
          }
          fence_async_smem();
          bar_sync(NB_WGB, 128);
          mbar_arrive_if(sb + BAR_AF + 8 * (t2 == 3 ? (BAR_G2 - BAR_AF) / 8 : (t2 == 4 ? (BAR_GO - BAR_AF) / 8 : 5 + t2)), t2 < 5);
          mbar_expect_if(sb + BAR_AF + 8 * (t2 == 5 ? 8 : t2), A_SLOT, t2 < 6);
          STAMPW(17);
          {
            float e[80];
            gemm_loop<160, false, 2>(e, sb, 12, 5, 0, 2, 0, 2, 2, tid_now(), []() {});
            STAMPW(10);
            const int t3 = tid_now();
#pragma unroll
            for (int j = 0; j < 10; j++) {
              sts128(sb + OFF_A + j * 2048 + t3 * 16, pack2(e[8 * j], e[8 * j + 1]), pack2(e[8 * j + 2], e[8 * j + 3]), pack2(e[8 * j + 4], e[8 * j + 5]),
                     pack2(e[8 * j + 6], e[8 * j + 7]));
              if (j == 4) bar_arrive(NB_WO, 256);
            }
            bar_arrive(NB_Z, 256);
            STAMPW(45);
          }
          return;
        }
        ZS(3);
        const bool hi = t & 2;
        float a0 = (hi ? st[2] : st[0]) + __shfl_xor_sync(0xffffffff, hi ? st[0] : st[2], 2);
        float a1 = (hi ? st[3] : st[1]) + __shfl_xor_sync(0xffffffff, hi ? st[1] : st[3], 2);
        a0 = ((t & 1) ? a1 : a0) + __shfl_xor_sync(0xffffffff, (t & 1) ? a0 : a1, 1);
        const uint32_t tag = lds32<0>(sb + OFF_TAG);
        uint2* zs = p.scr->zstat + (rb * 256 + w * 16 + g + (t >> 1) * 8) * 2 + (t & 1);
        st_ll2(zs + cb * 128, __float_as_uint(a0), tag);
        STAMPW(2); ZS(4);
        uint2 u[4];
#pragma unroll
        for (int i = 0; i < 4; i++) u[i] = ld_ll2(zs + i * 128);
        const uint32_t keep = (cb & 2) ? 13 << 5 : 13;
        mbar_arrive_if(sb + BAR_AE + 8 * tid, tid < NA && !((keep >> tid) & 1));
        const uint32_t za = sb + OFF_A + zs0 * A_SLOT + (2 * w + ((lane >> 3) & 1)) * 3072 + (lane >> 4) * 128 + (lane & 7) * 16;
        const float ca = 0.5f * (hi ? s1.y : s0.y), inv = 1.f / 768.f;
        mbar_wait2(sb + BAR_AE + 8 * (zs0 + 2), 0, sb + BAR_XC, 0);
        ZS(6);
        uint32_t t0 = 0;
#pragma unroll 1
        while (!__all_sync(0xffffffff, u[0].y == tag && u[1].y == tag && u[2].y == tag && u[3].y == tag)) {
          spin_guard(t0);
#pragma unroll
          for (int i = 0; i < 4; i++) u[i] = ld_ll2(zs + i * 128);
        }
        STAMPW(3); ZS(7);
        a0 = ((__uint_as_float(u[0].x) + __uint_as_float(u[1].x)) + (__uint_as_float(u[2].x) + __uint_as_float(u[3].x))) * inv;
        a1 = __shfl_xor_sync(0xffffffff, a0, 1);
        const float m = (t & 1) ? a1 : a0, q = (t & 1) ? a0 : a1;
        const float r = bf_lo(pack2(ca * rsqrtf(fmaf(fmaxf(fmaf(-m, m, q), 0.f), ca * ca, 1e-5f)), 0.f));
        const uint32_t rn = pack2(r, -m * r), ro = __shfl_xor_sync(0xffffffff, rn, 2);
        const uint32_t ra2 = prmt(hi ? ro : rn, 0, 0x1010), n2a = prmt(hi ? ro : rn, 0, 0x3232), rb2 = prmt(hi ? rn : ro, 0, 0x1010), n2b = prmt(hi ? rn : ro, 0, 0x3232);
        if (w >= 2) bar_sync(NB_Z, 160);
#pragma unroll
        for (int j = 0; j < 24; j += 2)
          stsm4(za + j * 128, hfma2(z[2 * j], ra2, n2a), hfma2(z[2 * j + 1], rb2, n2b), hfma2(z[2 * j + 2], ra2, n2a), hfma2(z[2 * j + 3], rb2, n2b));
        ZS(8);
        fence_async_smem();
        ZS(9);
        if (w < 2) bar_arrive(NB_Z, 160);
        else bar_arrive(NB_Z2, 96);
        final_load_x(xw, sb + OFF_A, cb, 0, w, lane);
        fence_async_smem();
        bar_sync(NB_WGA, 128);
        mbar_arrive_if(sb + BAR_AE + 8 * tid, tid < NA && ((keep >> tid) & 1));
      }
      {
        const uint32_t zero = lds32<0>(sb + OFF_TAG + 4);
#pragma unroll
        for (int i = 0; i < 20; i++) xw[i / 10][i % 10] |= zero;
      }
      load_taps(k, p, chb + 64, tid_now());
      STAMPW(4);
    }
    const int h = wg >> 1;
    {
    const int tid = tid_now(), lane = tid & 31;
    conv_worker(p, k, sb + OFF_CV + (1 - h) * CV_SZ, sb + OFF_A + 9 * A_SLOT + h * 4096, sb + BAR_XF + 8 * h, NB_WGA + h,
                chb + (h ? 0 : 64), 2 + h, sb + BAR_GO, w, lane, tid, h ? 40 : 5, rb, cb);
    {
      const int t3 = tid_now(), l3 = t3 & 31;
      const uint32_t xs_addr = sb + OFF_XS + (w * 16 + (l3 >> 2)) * 8;
      const float2 s0 = lds64f(xs_addr), s1 = lds64f(xs_addr + 64);
      const uint32_t ya = sb + y_tile(h) + ((l3 >> 4) * 8 + (l3 & 7)) * 128 + (((2 * w + ((l3 >> 3) & 1)) ^ (l3 & 7) ^ (rb & 7)) << 4);
      uint32_t sw[2][10];
      mbar_wait(sb + BAR_XF + 8 * h, h);
      final_s_early(sw, xw, ya, s0, s1);
      uint32_t ph = 1, t0 = 0, y[8];
#pragma unroll 1
      while (true) {
        mbar_wait(sb + BAR_YL + 16 * h, ph);
        if (bar_all(NB_WGA + h, 128, final_late(y, ya))) break;
        spin_guard(t0);
        ph ^= 1;
        if (t3 == 0) load_late_y(p, sb, h, rb, cb, lds32<0>(sb + OFF_TAG) & 1);
      }
#pragma unroll
      for (int e = 0; e < 8; e++) sw[e & 1][4 + (e >> 1)] = hmul2(sw[e & 1][4 + (e >> 1)], ~y[e]);
      __nv_bfloat16* o0 = p.out + (size_t)(w * 512 + rb * 16 + (l3 >> 2)) * kD + seg_col(cb, h);
      STAMPW(h ? 44 : 9);
      bar_sync(h ? NB_Z : NB_WO, 256);
      float d[40];
#pragma unroll
      for (int j = 0; j < 5; j++) {
        const uint4 v = lds128(sb + OFF_A + (h * 5 + j) * 2048 + t3 * 16);
        d[8 * j] = bf_lo(v.x); d[8 * j + 1] = bf_hi(v.x); d[8 * j + 2] = bf_lo(v.y); d[8 * j + 3] = bf_hi(v.y);
        d[8 * j + 4] = bf_lo(v.z); d[8 * j + 5] = bf_hi(v.z); d[8 * j + 6] = bf_lo(v.w); d[8 * j + 7] = bf_hi(v.w);
      }
      final_out(d, xw, sw, s0.y, s1.y, o0, h, l3 & 3);
    }
    }
  }
}

typedef CUresult (*EncodeFn)(CUtensorMap*, CUtensorMapDataType, cuuint32_t, void*, const cuuint64_t*, const cuuint64_t*, const cuuint32_t*,
                             const cuuint32_t*, CUtensorMapInterleave, CUtensorMapSwizzle, CUtensorMapL2promotion, CUtensorMapFloatOOBfill);

void encode(EncodeFn fn, CUtensorMap* m, const void* ptr, int rank, const cuuint64_t* dims, const cuuint64_t* strides, const cuuint32_t* box,
            CUtensorMapSwizzle swz = CU_TENSOR_MAP_SWIZZLE_128B) {
  const cuuint32_t es[3] = {1, 1, 1};
  fn(m, CU_TENSOR_MAP_DATA_TYPE_BFLOAT16, rank, const_cast<void*>(ptr), dims, strides, box, es, CU_TENSOR_MAP_INTERLEAVE_NONE,
     swz, CU_TENSOR_MAP_L2_PROMOTION_L2_128B, CU_TENSOR_MAP_FLOAT_OOB_FILL_NONE);
}

}

extern "C" void kernel_launch(void* const* d_in, const int* in_sizes, int n_in, void* d_out, int out_size) {
  (void)in_sizes; (void)n_in; (void)out_size;
  static EncodeFn enc = nullptr;
  static Scratch* scr = nullptr;
  static int sms = 0;
  if (!enc) {
    void* fn = nullptr;
    cudaDriverEntryPointQueryResult qr;
    cudaGetDriverEntryPoint("cuTensorMapEncodeTiled", &fn, cudaEnableDefault, &qr);
    enc = (EncodeFn)fn;
    cudaFuncSetAttribute(fused_kernel, cudaFuncAttributeMaxDynamicSharedMemorySize, SMEM_BYTES);
    cudaGetSymbolAddress((void**)&scr, g_scr);
    int dev = 0;
    cudaGetDevice(&dev);
    cudaDeviceGetAttribute(&sms, cudaDevAttrMultiProcessorCount, dev);
  }
  Params p;
  p.scr = scr;
  p.by_smid = sms == 132;
  p.k = (const __nv_bfloat16*)d_in[1];
  p.v = (const __nv_bfloat16*)d_in[2];
  p.shift = (const __nv_bfloat16*)d_in[3];
  p.ssmk = (const __nv_bfloat16*)d_in[4];
  p.ssmD = (const __nv_bfloat16*)d_in[5];
  p.wsp = (const __nv_bfloat16*)d_in[8];
  p.bsp = (const __nv_bfloat16*)d_in[9];
  p.wout = (const __nv_bfloat16*)d_in[10];
  p.out = (__nv_bfloat16*)d_out;
  for (int i = 0; i < 2; i++) {
    const cuuint64_t n = i ? kS : kD, dims[3] = {n, 512, 4}, st[2] = {n * 2, n * 1024};
    const cuuint32_t box[3] = {64, 16, 4};
    encode(enc, i ? &p.tmWsp : &p.tmX, d_in[i ? 8 : 0], 3, dims, st, box);
  }
  {
    const cuuint64_t dims[3] = {64, kD, kF / 64}, st[2] = {kF * 2, 128};
    const cuuint32_t box[3] = {64, 64, 3};
    encode(enc, &p.tmW, d_in[7], 3, dims, st, box);
  }
  {
    const cuuint64_t dims[2] = {kS, 896}, st[1] = {kS * 2};
    const cuuint32_t box[2] = {64, 16};
    encode(enc, &p.tmY, scr->y, 2, dims, st, box);
  }
  {
    const cuuint64_t dims[3] = {1024, kD / 2, 4}, st[2] = {8192, 2048};
    const cuuint32_t box[3] = {16, 32, 4};
    encode(enc, &p.tmKV, scr->kvx, 3, dims, st, box, CU_TENSOR_MAP_SWIZZLE_32B);
  }
  fused_kernel<<<132, 512, SMEM_BYTES, cudaStreamPerThread>>>(p);
}
```

```cpp
#include <cuda_runtime.h>
#include <cuda.h>
#include <cuda_bf16.h>
#include <stdint.h>

template <int N> struct WG;
template <> struct WG<16> {
  static __device__ __forceinline__ void rs(float* d, const uint32_t* a, uint64_t db) {
    asm volatile("{\n.reg .pred p;\nsetp.ne.b32 p, 1, 0;\nwgmma.mma_async.sync.aligned.m64n16k16.f32.bf16.bf16 {"
      "%0, %1, %2, %3, %4, %5, %6, %7"
      "}, {%8, %9, %10, %11}, %12, p, 1, 1, 0;\n}\n"
      :
      "+f"(d[0]), "+f"(d[1]), "+f"(d[2]), "+f"(d[3]), "+f"(d[4]), "+f"(d[5]), "+f"(d[6]), "+f"(d[7])
      : "r"(a[0]), "r"(a[1]), "r"(a[2]), "r"(a[3]), "l"(db));
  }
};
template <> struct WG<32> {
  static __device__ __forceinline__ void rs(float* d, const uint32_t* a, uint64_t db) {
    asm volatile("{\n.reg .pred p;\nsetp.ne.b32 p, 1, 0;\nwgmma.mma_async.sync.aligned.m64n32k16.f32.bf16.bf16 {"
      "%0, %1, %2, %3, %4, %5, %6, %7, %8, %9, %10, %11, %12, %13, %14, %15"
      "}, {%16, %17, %18, %19}, %20, p, 1, 1, 0;\n}\n"
      :
      "+f"(d[0]), "+f"(d[1]), "+f"(d[2]), "+f"(d[3]), "+f"(d[4]), "+f"(d[5]), "+f"(d[6]), "+f"(d[7]),
      "+f"(d[8]), "+f"(d[9]), "+f"(d[10]), "+f"(d[11]), "+f"(d[12]), "+f"(d[13]), "+f"(d[14]), "+f"(d[15])
      : "r"(a[0]), "r"(a[1]), "r"(a[2]), "r"(a[3]), "l"(db));
  }
};
template <> struct WG<48> {
  static __device__ __forceinline__ void rs(float* d, const uint32_t* a, uint64_t db) {
    asm volatile("{\n.reg .pred p;\nsetp.ne.b32 p, 1, 0;\nwgmma.mma_async.sync.aligned.m64n48k16.f32.bf16.bf16 {"
      "%0, %1, %2, %3, %4, %5, %6, %7, %8, %9, %10, %11, %12, %13, %14, %15, "
      "%16, %17, %18, %19, %20, %21, %22, %23"
      "}, {%24, %25, %26, %27}, %28, p, 1, 1, 0;\n}\n"
      :
      "+f"(d[0]), "+f"(d[1]), "+f"(d[2]), "+f"(d[3]), "+f"(d[4]), "+f"(d[5]), "+f"(d[6]), "+f"(d[7]),
      "+f"(d[8]), "+f"(d[9]), "+f"(d[10]), "+f"(d[11]), "+f"(d[12]), "+f"(d[13]), "+f"(d[14]), "+f"(d[15]),
      "+f"(d[16]), "+f"(d[17]), "+f"(d[18]), "+f"(d[19]), "+f"(d[20]), "+f"(d[21]), "+f"(d[22]), "+f"(d[23])
      : "r"(a[0]), "r"(a[1]), "r"(a[2]), "r"(a[3]), "l"(db));
  }
};
template <> struct WG<64> {
  static __device__ __forceinline__ void rs(float* d, const uint32_t* a, uint64_t db) {
    asm volatile("{\n.reg .pred p;\nsetp.ne.b32 p, 1, 0;\nwgmma.mma_async.sync.aligned.m64n64k16.f32.bf16.bf16 {"
      "%0, %1, %2, %3, %4, %5, %6, %7, %8, %9, %10, %11, %12, %13, %14, %15, "
      "%16, %17, %18, %19, %20, %21, %22, %23, %24, %25, %26, %27, %28, %29, %30, %31"
      "}, {%32, %33, %34, %35}, %36, p, 1, 1, 0;\n}\n"
      :
      "+f"(d[0]), "+f"(d[1]), "+f"(d[2]), "+f"(d[3]), "+f"(d[4]), "+f"(d[5]), "+f"(d[6]), "+f"(d[7]),
      "+f"(d[8]), "+f"(d[9]), "+f"(d[10]), "+f"(d[11]), "+f"(d[12]), "+f"(d[13]), "+f"(d[14]), "+f"(d[15]),
      "+f"(d[16]), "+f"(d[17]), "+f"(d[18]), "+f"(d[19]), "+f"(d[20]), "+f"(d[21]), "+f"(d[22]), "+f"(d[23]),
      "+f"(d[24]), "+f"(d[25]), "+f"(d[26]), "+f"(d[27]), "+f"(d[28]), "+f"(d[29]), "+f"(d[30]), "+f"(d[31])
      : "r"(a[0]), "r"(a[1]), "r"(a[2]), "r"(a[3]), "l"(db));
  }
};
template <> struct WG<80> {
  static __device__ __forceinline__ void rs(float* d, const uint32_t* a, uint64_t db) {
    asm volatile("{\n.reg .pred p;\nsetp.ne.b32 p, 1, 0;\nwgmma.mma_async.sync.aligned.m64n80k16.f32.bf16.bf16 {"
      "%0, %1, %2, %3, %4, %5, %6, %7, %8, %9, %10, %11, %12, %13, %14, %15, "
      "%16, %17, %18, %19, %20, %21, %22, %23, %24, %25, %26, %27, %28, %29, %30, %31, "
      "%32, %33, %34, %35, %36, %37, %38, %39"
      "}, {%40, %41, %42, %43}, %44, p, 1, 1, 0;\n}\n"
      :
      "+f"(d[0]), "+f"(d[1]), "+f"(d[2]), "+f"(d[3]), "+f"(d[4]), "+f"(d[5]), "+f"(d[6]), "+f"(d[7]),
      "+f"(d[8]), "+f"(d[9]), "+f"(d[10]), "+f"(d[11]), "+f"(d[12]), "+f"(d[13]), "+f"(d[14]), "+f"(d[15]),
      "+f"(d[16]), "+f"(d[17]), "+f"(d[18]), "+f"(d[19]), "+f"(d[20]), "+f"(d[21]), "+f"(d[22]), "+f"(d[23]),
      "+f"(d[24]), "+f"(d[25]), "+f"(d[26]), "+f"(d[27]), "+f"(d[28]), "+f"(d[29]), "+f"(d[30]), "+f"(d[31]),
      "+f"(d[32]), "+f"(d[33]), "+f"(d[34]), "+f"(d[35]), "+f"(d[36]), "+f"(d[37]), "+f"(d[38]), "+f"(d[39])
      : "r"(a[0]), "r"(a[1]), "r"(a[2]), "r"(a[3]), "l"(db));
  }
};
template <> struct WG<96> {
  static __device__ __forceinline__ void rs(float* d, const uint32_t* a, uint64_t db) {
    asm volatile("{\n.reg .pred p;\nsetp.ne.b32 p, 1, 0;\nwgmma.mma_async.sync.aligned.m64n96k16.f32.bf16.bf16 {"
      "%0, %1, %2, %3, %4, %5, %6, %7, %8, %9, %10, %11, %12, %13, %14, %15, "
      "%16, %17, %18, %19, %20, %21, %22, %23, %24, %25, %26, %27, %28, %29, %30, %31, "
      "%32, %33, %34, %35, %36, %37, %38, %39, %40, %41, %42, %43, %44, %45, %46, %47"
      "}, {%48, %49, %50, %51}, %52, p, 1, 1, 0;\n}\n"
      :
      "+f"(d[0]), "+f"(d[1]), "+f"(d[2]), "+f"(d[3]), "+f"(d[4]), "+f"(d[5]), "+f"(d[6]), "+f"(d[7]),
      "+f"(d[8]), "+f"(d[9]), "+f"(d[10]), "+f"(d[11]), "+f"(d[12]), "+f"(d[13]), "+f"(d[14]), "+f"(d[15]),
      "+f"(d[16]), "+f"(d[17]), "+f"(d[18]), "+f"(d[19]), "+f"(d[20]), "+f"(d[21]), "+f"(d[22]), "+f"(d[23]),
      "+f"(d[24]), "+f"(d[25]), "+f"(d[26]), "+f"(d[27]), "+f"(d[28]), "+f"(d[29]), "+f"(d[30]), "+f"(d[31]),
      "+f"(d[32]), "+f"(d[33]), "+f"(d[34]), "+f"(d[35]), "+f"(d[36]), "+f"(d[37]), "+f"(d[38]), "+f"(d[39]),
      "+f"(d[40]), "+f"(d[41]), "+f"(d[42]), "+f"(d[43]), "+f"(d[44]), "+f"(d[45]), "+f"(d[46]), "+f"(d[47])
      : "r"(a[0]), "r"(a[1]), "r"(a[2]), "r"(a[3]), "l"(db));
  }
};
template <> struct WG<112> {
  static __device__ __forceinline__ void rs(float* d, const uint32_t* a, uint64_t db) {
    asm volatile("{\n.reg .pred p;\nsetp.ne.b32 p, 1, 0;\nwgmma.mma_async.sync.aligned.m64n112k16.f32.bf16.bf16 {"
      "%0, %1, %2, %3, %4, %5, %6, %7, %8, %9, %10, %11, %12, %13, %14, %15, "
      "%16, %17, %18, %19, %20, %21, %22, %23, %24, %25, %26, %27, %28, %29, %30, %31, "
      "%32, %33, %34, %35, %36, %37, %38, %39, %40, %41, %42, %43, %44, %45, %46, %47, "
      "%48, %49, %50, %51, %52, %53, %54, %55"
      "}, {%56, %57, %58, %59}, %60, p, 1, 1, 0;\n}\n"
      :
      "+f"(d[0]), "+f"(d[1]), "+f"(d[2]), "+f"(d[3]), "+f"(d[4]), "+f"(d[5]), "+f"(d[6]), "+f"(d[7]),
      "+f"(d[8]), "+f"(d[9]), "+f"(d[10]), "+f"(d[11]), "+f"(d[12]), "+f"(d[13]), "+f"(d[14]), "+f"(d[15]),
      "+f"(d[16]), "+f"(d[17]), "+f"(d[18]), "+f"(d[19]), "+f"(d[20]), "+f"(d[21]), "+f"(d[22]), "+f"(d[23]),
      "+f"(d[24]), "+f"(d[25]), "+f"(d[26]), "+f"(d[27]), "+f"(d[28]), "+f"(d[29]), "+f"(d[30]), "+f"(d[31]),
      "+f"(d[32]), "+f"(d[33]), "+f"(d[34]), "+f"(d[35]), "+f"(d[36]), "+f"(d[37]), "+f"(d[38]), "+f"(d[39]),
      "+f"(d[40]), "+f"(d[41]), "+f"(d[42]), "+f"(d[43]), "+f"(d[44]), "+f"(d[45]), "+f"(d[46]), "+f"(d[47]),
      "+f"(d[48]), "+f"(d[49]), "+f"(d[50]), "+f"(d[51]), "+f"(d[52]), "+f"(d[53]), "+f"(d[54]), "+f"(d[55])
      : "r"(a[0]), "r"(a[1]), "r"(a[2]), "r"(a[3]), "l"(db));
  }
};
template <> struct WG<128> {
  static __device__ __forceinline__ void rs(float* d, const uint32_t* a, uint64_t db) {
    asm volatile("{\n.reg .pred p;\nsetp.ne.b32 p, 1, 0;\nwgmma.mma_async.sync.aligned.m64n128k16.f32.bf16.bf16 {"
      "%0, %1, %2, %3, %4, %5, %6, %7, %8, %9, %10, %11, %12, %13, %14, %15, "
      "%16, %17, %18, %19, %20, %21, %22, %23, %24, %25, %26, %27, %28, %29, %30, %31, "
      "%32, %33, %34, %35, %36, %37, %38, %39, %40, %41, %42, %43, %44, %45, %46, %47, "
      "%48, %49, %50, %51, %52, %53, %54, %55, %56, %57, %58, %59, %60, %61, %62, %63"
      "}, {%64, %65, %66, %67}, %68, p, 1, 1, 0;\n}\n"
      :
      "+f"(d[0]), "+f"(d[1]), "+f"(d[2]), "+f"(d[3]), "+f"(d[4]), "+f"(d[5]), "+f"(d[6]), "+f"(d[7]),
      "+f"(d[8]), "+f"(d[9]), "+f"(d[10]), "+f"(d[11]), "+f"(d[12]), "+f"(d[13]), "+f"(d[14]), "+f"(d[15]),
      "+f"(d[16]), "+f"(d[17]), "+f"(d[18]), "+f"(d[19]), "+f"(d[20]), "+f"(d[21]), "+f"(d[22]), "+f"(d[23]),
      "+f"(d[24]), "+f"(d[25]), "+f"(d[26]), "+f"(d[27]), "+f"(d[28]), "+f"(d[29]), "+f"(d[30]), "+f"(d[31]),
      "+f"(d[32]), "+f"(d[33]), "+f"(d[34]), "+f"(d[35]), "+f"(d[36]), "+f"(d[37]), "+f"(d[38]), "+f"(d[39]),
      "+f"(d[40]), "+f"(d[41]), "+f"(d[42]), "+f"(d[43]), "+f"(d[44]), "+f"(d[45]), "+f"(d[46]), "+f"(d[47]),
      "+f"(d[48]), "+f"(d[49]), "+f"(d[50]), "+f"(d[51]), "+f"(d[52]), "+f"(d[53]), "+f"(d[54]), "+f"(d[55]),
      "+f"(d[56]), "+f"(d[57]), "+f"(d[58]), "+f"(d[59]), "+f"(d[60]), "+f"(d[61]), "+f"(d[62]), "+f"(d[63])
      : "r"(a[0]), "r"(a[1]), "r"(a[2]), "r"(a[3]), "l"(db));
  }
};
template <> struct WG<160> {
  static __device__ __forceinline__ void ss(float* d, uint64_t da, uint64_t db, int sd) {
    asm volatile("{\n.reg .pred p;\nsetp.ne.b32 p, %82, 0;\nwgmma.mma_async.sync.aligned.m64n160k16.f32.bf16.bf16 {"
      "%0, %1, %2, %3, %4, %5, %6, %7, %8, %9, %10, %11, %12, %13, %14, %15, "
      "%16, %17, %18, %19, %20, %21, %22, %23, %24, %25, %26, %27, %28, %29, %30, %31, "
      "%32, %33, %34, %35, %36, %37, %38, %39, %40, %41, %42, %43, %44, %45, %46, %47, "
      "%48, %49, %50, %51, %52, %53, %54, %55, %56, %57, %58, %59, %60, %61, %62, %63, "
      "%64, %65, %66, %67, %68, %69, %70, %71, %72, %73, %74, %75, %76, %77, %78, %79"
      "}, %80, %81, p, 1, 1, 0, 1;\n}\n"
      :
      "+f"(d[0]), "+f"(d[1]), "+f"(d[2]), "+f"(d[3]), "+f"(d[4]), "+f"(d[5]), "+f"(d[6]), "+f"(d[7]),
      "+f"(d[8]), "+f"(d[9]), "+f"(d[10]), "+f"(d[11]), "+f"(d[12]), "+f"(d[13]), "+f"(d[14]), "+f"(d[15]),
      "+f"(d[16]), "+f"(d[17]), "+f"(d[18]), "+f"(d[19]), "+f"(d[20]), "+f"(d[21]), "+f"(d[22]), "+f"(d[23]),
      "+f"(d[24]), "+f"(d[25]), "+f"(d[26]), "+f"(d[27]), "+f"(d[28]), "+f"(d[29]), "+f"(d[30]), "+f"(d[31]),
      "+f"(d[32]), "+f"(d[33]), "+f"(d[34]), "+f"(d[35]), "+f"(d[36]), "+f"(d[37]), "+f"(d[38]), "+f"(d[39]),
      "+f"(d[40]), "+f"(d[41]), "+f"(d[42]), "+f"(d[43]), "+f"(d[44]), "+f"(d[45]), "+f"(d[46]), "+f"(d[47]),
      "+f"(d[48]), "+f"(d[49]), "+f"(d[50]), "+f"(d[51]), "+f"(d[52]), "+f"(d[53]), "+f"(d[54]), "+f"(d[55]),
      "+f"(d[56]), "+f"(d[57]), "+f"(d[58]), "+f"(d[59]), "+f"(d[60]), "+f"(d[61]), "+f"(d[62]), "+f"(d[63]),
      "+f"(d[64]), "+f"(d[65]), "+f"(d[66]), "+f"(d[67]), "+f"(d[68]), "+f"(d[69]), "+f"(d[70]), "+f"(d[71]),
      "+f"(d[72]), "+f"(d[73]), "+f"(d[74]), "+f"(d[75]), "+f"(d[76]), "+f"(d[77]), "+f"(d[78]), "+f"(d[79])
      : "l"(da), "l"(db), "r"(sd));
  }
};
template <> struct WG<192> {
  static __device__ __forceinline__ void ss(float* d, uint64_t da, uint64_t db, int sd) {
    asm volatile("{\n.reg .pred p;\nsetp.ne.b32 p, %98, 0;\nwgmma.mma_async.sync.aligned.m64n192k16.f32.bf16.bf16 {"
      "%0, %1, %2, %3, %4, %5, %6, %7, %8, %9, %10, %11, %12, %13, %14, %15, "
      "%16, %17, %18, %19, %20, %21, %22, %23, %24, %25, %26, %27, %28, %29, %30, %31, "
      "%32, %33, %34, %35, %36, %37, %38, %39, %40, %41, %42, %43, %44, %45, %46, %47, "
      "%48, %49, %50, %51, %52, %53, %54, %55, %56, %57, %58, %59, %60, %61, %62, %63, "
      "%64, %65, %66, %67, %68, %69, %70, %71, %72, %73, %74, %75, %76, %77, %78, %79, "
      "%80, %81, %82, %83, %84, %85, %86, %87, %88, %89, %90, %91, %92, %93, %94, %95"
      "}, %96, %97, p, 1, 1, 0, 1;\n}\n"
      :
      "+f"(d[0]), "+f"(d[1]), "+f"(d[2]), "+f"(d[3]), "+f"(d[4]), "+f"(d[5]), "+f"(d[6]), "+f"(d[7]),
      "+f"(d[8]), "+f"(d[9]), "+f"(d[10]), "+f"(d[11]), "+f"(d[12]), "+f"(d[13]), "+f"(d[14]), "+f"(d[15]),
      "+f"(d[16]), "+f"(d[17]), "+f"(d[18]), "+f"(d[19]), "+f"(d[20]), "+f"(d[21]), "+f"(d[22]), "+f"(d[23]),
      "+f"(d[24]), "+f"(d[25]), "+f"(d[26]), "+f"(d[27]), "+f"(d[28]), "+f"(d[29]), "+f"(d[30]), "+f"(d[31]),
      "+f"(d[32]), "+f"(d[33]), "+f"(d[34]), "+f"(d[35]), "+f"(d[36]), "+f"(d[37]), "+f"(d[38]), "+f"(d[39]),
      "+f"(d[40]), "+f"(d[41]), "+f"(d[42]), "+f"(d[43]), "+f"(d[44]), "+f"(d[45]), "+f"(d[46]), "+f"(d[47]),
      "+f"(d[48]), "+f"(d[49]), "+f"(d[50]), "+f"(d[51]), "+f"(d[52]), "+f"(d[53]), "+f"(d[54]), "+f"(d[55]),
      "+f"(d[56]), "+f"(d[57]), "+f"(d[58]), "+f"(d[59]), "+f"(d[60]), "+f"(d[61]), "+f"(d[62]), "+f"(d[63]),
      "+f"(d[64]), "+f"(d[65]), "+f"(d[66]), "+f"(d[67]), "+f"(d[68]), "+f"(d[69]), "+f"(d[70]), "+f"(d[71]),
      "+f"(d[72]), "+f"(d[73]), "+f"(d[74]), "+f"(d[75]), "+f"(d[76]), "+f"(d[77]), "+f"(d[78]), "+f"(d[79]),
      "+f"(d[80]), "+f"(d[81]), "+f"(d[82]), "+f"(d[83]), "+f"(d[84]), "+f"(d[85]), "+f"(d[86]), "+f"(d[87]),
      "+f"(d[88]), "+f"(d[89]), "+f"(d[90]), "+f"(d[91]), "+f"(d[92]), "+f"(d[93]), "+f"(d[94]), "+f"(d[95])
      : "l"(da), "l"(db), "r"(sd));
  }
  static __device__ __forceinline__ void rst(float* d, const uint32_t* a, uint64_t db) {
    asm volatile("{\n.reg .pred p;\nsetp.ne.b32 p, 1, 0;\nwgmma.mma_async.sync.aligned.m64n192k16.f32.bf16.bf16 {"
      "%0, %1, %2, %3, %4, %5, %6, %7, %8, %9, %10, %11, %12, %13, %14, %15, "
      "%16, %17, %18, %19, %20, %21, %22, %23, %24, %25, %26, %27, %28, %29, %30, %31, "
      "%32, %33, %34, %35, %36, %37, %38, %39, %40, %41, %42, %43, %44, %45, %46, %47, "
      "%48, %49, %50, %51, %52, %53, %54, %55, %56, %57, %58, %59, %60, %61, %62, %63, "
      "%64, %65, %66, %67, %68, %69, %70, %71, %72, %73, %74, %75, %76, %77, %78, %79, "
      "%80, %81, %82, %83, %84, %85, %86, %87, %88, %89, %90, %91, %92, %93, %94, %95"
      "}, {%96, %97, %98, %99}, %100, p, 1, 1, 1;\n}\n"
      :
      "+f"(d[0]), "+f"(d[1]), "+f"(d[2]), "+f"(d[3]), "+f"(d[4]), "+f"(d[5]), "+f"(d[6]), "+f"(d[7]),
      "+f"(d[8]), "+f"(d[9]), "+f"(d[10]), "+f"(d[11]), "+f"(d[12]), "+f"(d[13]), "+f"(d[14]), "+f"(d[15]),
      "+f"(d[16]), "+f"(d[17]), "+f"(d[18]), "+f"(d[19]), "+f"(d[20]), "+f"(d[21]), "+f"(d[22]), "+f"(d[23]),
      "+f"(d[24]), "+f"(d[25]), "+f"(d[26]), "+f"(d[27]), "+f"(d[28]), "+f"(d[29]), "+f"(d[30]), "+f"(d[31]),
      "+f"(d[32]), "+f"(d[33]), "+f"(d[34]), "+f"(d[35]), "+f"(d[36]), "+f"(d[37]), "+f"(d[38]), "+f"(d[39]),
      "+f"(d[40]), "+f"(d[41]), "+f"(d[42]), "+f"(d[43]), "+f"(d[44]), "+f"(d[45]), "+f"(d[46]), "+f"(d[47]),
      "+f"(d[48]), "+f"(d[49]), "+f"(d[50]), "+f"(d[51]), "+f"(d[52]), "+f"(d[53]), "+f"(d[54]), "+f"(d[55]),
      "+f"(d[56]), "+f"(d[57]), "+f"(d[58]), "+f"(d[59]), "+f"(d[60]), "+f"(d[61]), "+f"(d[62]), "+f"(d[63]),
      "+f"(d[64]), "+f"(d[65]), "+f"(d[66]), "+f"(d[67]), "+f"(d[68]), "+f"(d[69]), "+f"(d[70]), "+f"(d[71]),
      "+f"(d[72]), "+f"(d[73]), "+f"(d[74]), "+f"(d[75]), "+f"(d[76]), "+f"(d[77]), "+f"(d[78]), "+f"(d[79]),
      "+f"(d[80]), "+f"(d[81]), "+f"(d[82]), "+f"(d[83]), "+f"(d[84]), "+f"(d[85]), "+f"(d[86]), "+f"(d[87]),
      "+f"(d[88]), "+f"(d[89]), "+f"(d[90]), "+f"(d[91]), "+f"(d[92]), "+f"(d[93]), "+f"(d[94]), "+f"(d[95])
      : "r"(a[0]), "r"(a[1]), "r"(a[2]), "r"(a[3]), "l"(db));
  }
};

#define WARM 0
#define ZSH 1
#define CS1_T 9500
#define HGRP 3
#define HPACE 150
#define LL_AT 4
#define KV_T0 2300
#define WSP_D 650

namespace {

constexpr int kS = 2048, kD = 640, kF = 1536;
constexpr int NA = 10, NA2 = 9, NB = 5;
constexpr int A_SLOT = 8192, B_SLOT = 24576;
constexpr int LEAD = 2;
constexpr int OFF_A = 0;
constexpr int OFF_B = OFF_A + NA * A_SLOT;
constexpr int XB_PL = 2112;
constexpr int CV_KE = 4224, CV_KO = CV_KE + 4160;
constexpr int CV_SZ = CV_KO + 4160;
constexpr int OFF_CV = OFF_B + NB * B_SLOT;
constexpr int OFF_CS = OFF_CV + 2 * CV_SZ;
constexpr int OFF_BIAS = OFF_CS + 1536;
constexpr int OFF_XS = OFF_BIAS + 128;
constexpr int OFF_BAR = OFF_XS + 512;
constexpr int BAR_AF = OFF_BAR, BAR_ST = BAR_AF + 8 * NA, BAR_XF = BAR_ST + 16, BAR_KV = BAR_XF + 16;
constexpr int BAR_BF = OFF_BAR + 128, BAR_G2 = BAR_BF + 8 * (NB + 1), BAR_XS = BAR_G2 + 8, BAR_KU = BAR_XS + 8, BAR_ZP = BAR_KU + 40, BAR_XC = BAR_ZP + 8, BAR_WO = BAR_XC + 8;
constexpr int BAR_AE = OFF_BAR + 256, BAR_BE = BAR_AE + 8 * NA;
constexpr int BAR_YT = BAR_KU + 24;
constexpr int BAR_Z1 = BAR_ST;
constexpr int BAR_GO1 = BAR_XC;
constexpr int BAR_GO = BAR_XS;
constexpr int BAR_YL = BAR_KU + 16;
constexpr int OFF_TAG = OFF_CS - 32;
constexpr int SMEM_BYTES = OFF_BAR + 384;
static_assert(SMEM_BYTES <= 232448, "smem");
constexpr int NB_WGA = 1, NB_WGC = 2, NB_G1 = 3, NB_WO = 4, NB_CD = 5, NB_Z = 6, NB_WGB = 7, NB_Z2 = 8, NB_H = 11;

constexpr int CSP = 32, EPS = 8;
constexpr int CNT_Y = 0, CNT_Z1 = 2, CNT_KV = 4, CNT_WO = 8;
struct Scratch {
  uint8_t kvx[kD * 4096];
  uint8_t z2[4 * 32 * 24576];
  uint8_t h[32 * 12 * 8192];
  uint8_t wo[4 * 12 * 20480];
  uint8_t y[896 * 4096];
  uint4 xstat[kS];
  uint2 zstat[kS * 8];
  uint2 colsum[kF];
  uint32_t zcnt[4 * 32];
  uint32_t cnt[12 * 32];
  uint32_t hcnt[32 * 32];
  uint32_t epoch[136 * EPS];
};
__device__ __align__(1024) Scratch g_scr;
#define ZS(i)
#define STAMP(i)
#define STAMP2(i)
#define STAMPW(i)

struct Params {
  Scratch* scr;
  int by_smid;
  const __nv_bfloat16 *k, *v, *shift, *ssmk, *ssmD, *wsp, *bsp, *wout;
  __nv_bfloat16* out;
  CUtensorMap tmX, tmW, tmWsp, tmY, tmKV;
};

__device__ __forceinline__ uint64_t mkdesc(uint32_t addr, uint32_t lbo, uint32_t sbo, uint32_t swz) {
  return (uint64_t)((addr & 0x3FFFF) >> 4) | ((uint64_t)(lbo >> 4) << 16) | ((uint64_t)(sbo >> 4) << 32) | ((uint64_t)swz << 62);
}
#define WG_FENCE() asm volatile("wgmma.fence.sync.aligned;" ::: "memory")
#define WG_COMMIT() asm volatile("wgmma.commit_group.sync.aligned;" ::: "memory")
#define WG_WAIT(n) asm volatile("wgmma.wait_group.sync.aligned %0;" ::"n"(n) : "memory")
template <int N> __device__ __forceinline__ void acc_fence(float* d) {
#pragma unroll
  for (int i = 0; i < N; i++) asm volatile("" : "+f"(d[i])::"memory");
}
__device__ __forceinline__ void mbar_init(uint32_t bar, int cnt) { asm volatile("mbarrier.init.shared::cta.b64 [%0], %1;" ::"r"(bar), "r"(cnt) : "memory"); }
__device__ __forceinline__ void mbar_expect(uint32_t bar, uint32_t bytes) { asm volatile("mbarrier.arrive.expect_tx.shared::cta.b64 _, [%0], %1;" ::"r"(bar), "r"(bytes) : "memory"); }
__device__ __forceinline__ void mbar_arrive(uint32_t bar) { asm volatile("mbarrier.arrive.shared::cta.b64 _, [%0];" ::"r"(bar) : "memory"); }
__device__ __forceinline__ void mbar_arrive_if(uint32_t bar, bool c) {
  asm volatile("{\n.reg .pred p;\nsetp.ne.u32 p, %1, 0;\n@p mbarrier.arrive.shared::cta.b64 _, [%0];\n}\n" ::"r"(bar), "r"((uint32_t)c) : "memory");
}
__device__ __forceinline__ void mbar_expect_if(uint32_t bar, uint32_t bytes, bool c) {
  asm volatile("{\n.reg .pred p;\nsetp.ne.u32 p, %2, 0;\n@p mbarrier.arrive.expect_tx.shared::cta.b64 _, [%0], %1;\n}\n" ::"r"(bar), "r"(bytes), "r"((uint32_t)c) : "memory");
}
__device__ __forceinline__ bool mbar_try(uint32_t bar, uint32_t parity) {
  uint32_t ok;
  asm volatile("{\n.reg .pred p;\nmbarrier.try_wait.parity.shared::cta.b64 p, [%1], %2;\nselp.u32 %0, 1, 0, p;\n}\n" : "=r"(ok) : "r"(bar), "r"(parity) : "memory");
  return ok;
}
__device__ __forceinline__ bool mbar_test(uint32_t bar, uint32_t parity) {
  uint32_t ok;
  asm volatile("{\n.reg .pred p;\nmbarrier.test_wait.parity.shared::cta.b64 p, [%1], %2;\nselp.u32 %0, 1, 0, p;\n}\n" : "=r"(ok) : "r"(bar), "r"(parity) : "memory");
  return ok;
}
__device__ __forceinline__ void die() { asm volatile("st.volatile.global.u32 [%0], %1;" ::"l"(0ull), "r"(0) : "memory"); }
__device__ __forceinline__ void spin_guard(uint32_t& n) { if (++n == (1u << 22)) die(); }
__device__ __forceinline__ void mbar_wait(uint32_t bar, uint32_t parity) {
  uint32_t t0 = 0;
#pragma unroll 1
  while (!mbar_try(bar, parity)) spin_guard(t0);
}
__device__ __forceinline__ void mbar_wait2(uint32_t b0, uint32_t p0, uint32_t b1, uint32_t p1) {
  uint32_t t0 = 0;
#pragma unroll 1
  while (true) {
    const bool r0 = mbar_try(b0, p0), r1 = mbar_try(b1, p1);
    if (r0 && r1) break;
    spin_guard(t0);
  }
}
__device__ __forceinline__ int tid_now() { int v; asm volatile("mov.u32 %0, %%tid.x;" : "=r"(v)); return v & 127; }
__device__ __forceinline__ bool elect_one() {
  uint32_t p;
  asm volatile("{\n.reg .pred P;\nelect.sync _|P, 0xffffffff;\nselp.u32 %0, 1, 0, P;\n}\n" : "=r"(p));
  return p;
}
__device__ __forceinline__ void bar_sync(int id, int n) { asm volatile("bar.sync %0, %1;" ::"r"(id), "r"(n) : "memory"); }
__device__ __forceinline__ void bar_arrive(int id, int n) { asm volatile("bar.arrive %0, %1;" ::"r"(id), "r"(n) : "memory"); }
__device__ __forceinline__ void fence_async_smem() { asm volatile("fence.proxy.async.shared::cta;" ::: "memory"); }
__device__ __forceinline__ void bulk_g2s(uint32_t dst, const void* src, uint32_t bytes, uint32_t bar) {
  asm volatile("cp.async.bulk.shared::cluster.global.mbarrier::complete_tx::bytes [%0], [%1], %2, [%3];" ::"r"(dst), "l"(src), "r"(bytes), "r"(bar) : "memory");
}
__device__ __forceinline__ void bulk_s2g(void* dst, uint32_t src, uint32_t bytes) {
  asm volatile("cp.async.bulk.global.shared::cta.bulk_group [%0], [%1], %2;" ::"l"(dst), "r"(src), "r"(bytes) : "memory");
}
__device__ __forceinline__ void tma2d(uint32_t dst, const CUtensorMap* m, int c0, int c1, uint32_t bar) {
  asm volatile("cp.async.bulk.tensor.2d.shared::cluster.global.mbarrier::complete_tx::bytes [%0], [%1, {%3, %4}], [%2];" ::"r"(dst), "l"(m), "r"(bar), "r"(c0), "r"(c1) : "memory");
}
__device__ __forceinline__ void tma3d(uint32_t dst, const CUtensorMap* m, int c0, int c1, int c2, uint32_t bar) {
  asm volatile("cp.async.bulk.tensor.3d.shared::cluster.global.mbarrier::complete_tx::bytes [%0], [%1, {%3, %4, %5}], [%2];" ::"r"(dst), "l"(m), "r"(bar), "r"(c0), "r"(c1), "r"(c2) : "memory");
}
__device__ __forceinline__ void tma_rows(uint32_t dst, const CUtensorMap* m, int c0, int rb, uint32_t bar) { tma3d(dst, m, c0, rb * 16, 0, bar); }
__device__ __forceinline__ uint4 ld_ll4(const void* p) {
  uint64_t a, b;
  asm volatile("ld.relaxed.gpu.global.v2.u64 {%0,%1}, [%2];" : "=l"(a), "=l"(b) : "l"(p) : "memory");
  return make_uint4((uint32_t)a, (uint32_t)(a >> 32), (uint32_t)b, (uint32_t)(b >> 32));
}
__device__ __forceinline__ void st_ll4(void* p, uint32_t a, uint32_t b, uint32_t c, uint32_t d) {
  asm volatile("st.relaxed.gpu.global.v2.u64 [%0], {%1,%2};" ::"l"(p), "l"(a | ((uint64_t)b << 32)), "l"(c | ((uint64_t)d << 32)) : "memory");
}
__device__ __forceinline__ void st_ll2(void* p, uint32_t a, uint32_t b) { asm volatile("st.relaxed.gpu.global.u64 [%0], %1;" ::"l"(p), "l"(a | ((uint64_t)b << 32)) : "memory"); }
__device__ __forceinline__ uint2 ld_ll2(const void* p) {
  uint64_t a;
  asm volatile("ld.relaxed.gpu.global.u64 %0, [%1];" : "=l"(a) : "l"(p) : "memory");
  return make_uint2((uint32_t)a, (uint32_t)(a >> 32));
}
__device__ __forceinline__ void wgmma_colsum(float* d, uint64_t da, uint64_t db) {
  asm volatile("{\n.reg .pred p;\nsetp.ne.b32 p, 1, 0;\nwgmma.mma_async.sync.aligned.m64n8k16.f32.bf16.bf16 {%0, %1, %2, %3}, %4, %5, p, 1, 1, 1, 0;\n}\n"
               : "+f"(d[0]), "+f"(d[1]), "+f"(d[2]), "+f"(d[3]) : "l"(da), "l"(db));
}
__device__ __forceinline__ void prefetch_l2(const void* p) { asm volatile("prefetch.global.L2 [%0];" ::"l"(p)); }
__device__ __forceinline__ void pace(uint32_t& t, uint32_t dt) {
  t += dt;
  while ((int32_t)((uint32_t)clock() - t) < 0) __nanosleep(32);
}
__device__ __forceinline__ void red_relaxed(uint32_t* p) { asm volatile("red.relaxed.gpu.global.add.u32 [%0], 1;" ::"l"(p) : "memory"); }
__device__ __forceinline__ void red_release(uint32_t* p) { asm volatile("red.release.gpu.global.add.u32 [%0], 1;" ::"l"(p) : "memory"); }
__device__ __forceinline__ uint4 ldg4(const void* p) { uint4 v; asm volatile("ld.global.v4.u32 {%0,%1,%2,%3}, [%4];" : "=r"(v.x), "=r"(v.y), "=r"(v.z), "=r"(v.w) : "l"(p) : "memory"); return v; }
__device__ __forceinline__ uint32_t ldg1(const void* p) { uint32_t v; asm volatile("ld.global.u32 %0, [%1];" : "=r"(v) : "l"(p) : "memory"); return v; }
__device__ __forceinline__ void stg4_if(void* p, uint32_t a, uint32_t b, uint32_t c, uint32_t d, bool on) {
  asm volatile("{\n.reg .pred p;\nsetp.ne.u32 p, %5, 0;\n@p st.global.v4.u32 [%0], {%1,%2,%3,%4};\n}\n" ::"l"(p), "r"(a), "r"(b), "r"(c), "r"(d), "r"((uint32_t)on) : "memory");
}
template <int OFF> __device__ __forceinline__ uint32_t lds32(uint32_t a) { uint32_t v; asm volatile("ld.shared.u32 %0, [%1+%2];" : "=r"(v) : "r"(a), "n"(OFF)); return v; }
__device__ __forceinline__ uint4 lds128(uint32_t a) { uint4 v; asm volatile("ld.shared.v4.u32 {%0,%1,%2,%3}, [%4];" : "=r"(v.x), "=r"(v.y), "=r"(v.z), "=r"(v.w) : "r"(a) : "memory"); return v; }
__device__ __forceinline__ float2 lds64f(uint32_t a) { float2 v; asm volatile("ld.shared.v2.f32 {%0,%1}, [%2];" : "=f"(v.x), "=f"(v.y) : "r"(a) : "memory"); return v; }
__device__ __forceinline__ void sts64f(uint32_t a, float x, float y) { asm volatile("st.shared.v2.f32 [%0], {%1,%2};" ::"r"(a), "f"(x), "f"(y) : "memory"); }
__device__ __forceinline__ void sts32(uint32_t a, uint32_t x) { asm volatile("st.shared.u32 [%0], %1;" ::"r"(a), "r"(x) : "memory"); }
__device__ __forceinline__ void sts128(uint32_t a, uint32_t x, uint32_t y, uint32_t z, uint32_t w) { asm volatile("st.shared.v4.u32 [%0], {%1,%2,%3,%4};" ::"r"(a), "r"(x), "r"(y), "r"(z), "r"(w) : "memory"); }
__device__ __forceinline__ void stsm4(uint32_t a, uint32_t r0, uint32_t r1, uint32_t r2, uint32_t r3) {
  asm volatile("stmatrix.sync.aligned.m8n8.x4.shared.b16 [%0], {%1,%2,%3,%4};" ::"r"(a), "r"(r0), "r"(r1), "r"(r2), "r"(r3) : "memory");
}
__device__ __forceinline__ void stsm4t(uint32_t a, uint32_t r0, uint32_t r1, uint32_t r2, uint32_t r3) {
  asm volatile("stmatrix.sync.aligned.m8n8.x4.trans.shared.b16 [%0], {%1,%2,%3,%4};" ::"r"(a), "r"(r0), "r"(r1), "r"(r2), "r"(r3) : "memory");
}
__device__ __forceinline__ void ldsm4t(uint32_t* r, uint32_t a) {
  asm volatile("ldmatrix.sync.aligned.m8n8.x4.trans.shared.b16 {%0,%1,%2,%3}, [%4];" : "=r"(r[0]), "=r"(r[1]), "=r"(r[2]), "=r"(r[3]) : "r"(a) : "memory");
}
__device__ __forceinline__ uint32_t pack2(float lo, float hi) { uint32_t r; asm("cvt.rn.bf16x2.f32 %0, %1, %2;" : "=r"(r) : "f"(hi), "f"(lo)); return r; }
__device__ __forceinline__ float bf_lo(uint32_t u) { return __uint_as_float(u << 16); }
__device__ __forceinline__ float bf_hi(uint32_t u) { return __uint_as_float(u & 0xffff0000u); }
__device__ __forceinline__ float tanh_fast(float x) { float y; asm("tanh.approx.f32 %0, %1;" : "=f"(y) : "f"(x)); return y; }
__device__ __forceinline__ uint32_t hmul2(uint32_t a, uint32_t b) { uint32_t r; asm("mul.rn.bf16x2 %0, %1, %2;" : "=r"(r) : "r"(a), "r"(b)); return r; }
__device__ __forceinline__ uint32_t hfma2(uint32_t a, uint32_t b, uint32_t c) { uint32_t r; asm("fma.rn.bf16x2 %0, %1, %2, %3;" : "=r"(r) : "r"(a), "r"(b), "r"(c)); return r; }
__device__ __forceinline__ uint32_t prmt(uint32_t a, uint32_t b, uint32_t s) { return __byte_perm(a, b, s); }

__device__ __forceinline__ void st_relaxed(uint32_t* p, uint32_t v) { asm volatile("st.relaxed.gpu.global.u32 [%0], %1;" ::"l"(p), "r"(v) : "memory"); }
__device__ __forceinline__ uint32_t ld_relaxed(const uint32_t* p) { uint32_t v; asm volatile("ld.relaxed.gpu.global.u32 %0, [%1];" : "=r"(v) : "l"(p) : "memory"); return v; }
__device__ __forceinline__ void acquire_fence() { asm volatile("fence.acquire.gpu;\nfence.proxy.async.global;" ::: "memory"); }
__device__ __forceinline__ uint32_t load_epoch(const Params& p, int idx, int lane) { return ld_relaxed(&p.scr->epoch[idx * EPS + (((lane * lane) & 3) == 2 ? 1 : 0)]); }
__device__ __forceinline__ void poll_counter(const uint32_t* cnt, uint32_t target) {
  uint32_t t0 = 0;
#pragma unroll 1
  while (!__all_sync(0xffffffff, ld_relaxed(cnt) == target)) spin_guard(t0);
  acquire_fence();
}

__device__ __forceinline__ void poll_one(const uint32_t* cnt, uint32_t target) {
  uint32_t t0 = 0;
#pragma unroll 1
  while (ld_relaxed(cnt) != target) spin_guard(t0);
  acquire_fence();
}
__device__ __forceinline__ uint32_t anchor(uint32_t v) { return __shfl_sync(0xffffffff, v, 0); }
__device__ __forceinline__ int g3_block(int cb, int it) { return it < 3 ? cb * 3 + it : (it - 3 < cb * 3 ? it - 3 : it); }

template <int N, bool A_SWZ, int B_MODE, class Hook>
__device__ __forceinline__ void gemm_loop(float* d, uint32_t sb, int nkb, int sa, int pa, int b0, uint32_t boff, int relA, int relB, int tid, Hook hook) {
  constexpr uint32_t A_STEP = A_SWZ ? 2 : 128;
  constexpr uint32_t B_STEP = B_MODE == 0 ? 128 : (B_MODE == 1 ? 384 : 320);
  const uint64_t da0 = A_SWZ ? mkdesc(sb + OFF_A, 16, 1024, 1) : mkdesc(sb + OFF_A, 1024, 128, 0);
  const uint64_t db0 = B_MODE == 0 ? mkdesc(sb + OFF_B + boff, 8192, 1024, 1) : mkdesc(sb + OFF_B + boff, B_MODE == 1 ? 3072 : 2560, 128, 0);
  constexpr int MODA = B_MODE == 0 ? NA : NA2;
  constexpr int MODB = B_MODE == 2 ? 6 : NB;
  int sbk = b0 % MODB, pb = (b0 / MODB) & 1;
  auto boffs = [](int s_) { return B_MODE == 2 ? (s_ == 5 ? 0 : s_ + 1) * (20480 >> 4) : s_ * (B_SLOT >> 4); };
  uint32_t rel = 0;
  uint64_t da = da0 + sa * (A_SLOT >> 4), db = db0 + boffs(sbk);
  const bool doR = tid < 2 ? tid < relA : tid - 2 < relB;
  mbar_wait2(sb + BAR_AF + 8 * sa, pa, sb + BAR_BF + 8 * sbk, pb);
  if constexpr (B_MODE == 2) {
#pragma unroll
    for (int i = 0; i < N / 2; i++) asm volatile("" : "=f"(d[i]));
#pragma unroll 1
    for (int it = 0; it < nkb; it++) {
      WG_FENCE();
#pragma unroll
      for (int j = 0; j < 4; j++) WG<N>::ss(d, da + j * A_STEP, db + j * B_STEP, j ? 1 : it);
      WG_COMMIT();
      const uint32_t prel = rel;
      rel = sb + BAR_AE + 8 * (tid < 2 ? sa : sbk + NA);
      if (++sa == MODA) { sa = 0; pa ^= 1; }
      if (++sbk == MODB) { sbk = 0; pb ^= 1; }
      da = da0 + sa * (A_SLOT >> 4); db = db0 + boffs(sbk);
      const bool r0 = mbar_test(sb + BAR_AF + 8 * sa, pa), r1 = mbar_test(sb + BAR_BF + 8 * sbk, pb);
      WG_WAIT(1);
      mbar_arrive_if(prel, doR && prel != 0);
      if (it == 2) {
        WG_WAIT(0);
        mbar_expect_if(sb + BAR_AF + 8 * tid, A_SLOT, tid >= 5 && tid < 8);
        mbar_arrive_if(rel, doR);
        rel = 0;
      }
      if (it + 1 < nkb && !(r0 && r1)) {
        mbar_wait2(sb + BAR_AF + 8 * sa, pa, sb + BAR_BF + 8 * sbk, pb);
      }
    }
  } else
#pragma unroll 1
  for (int it = 0; it < nkb; it++) {
    WG_FENCE();
    WG<N>::ss(d, da, db, 1);
    const uint32_t prel = rel;
    rel = sb + BAR_AE + 8 * (tid < 2 ? sa : sbk + NA);
    if (++sa == MODA) { sa = 0; if (B_MODE) pa ^= 1; }
    if (++sbk == MODB) { sbk = 0; pb ^= 1; }
    WG<N>::ss(d, da + A_STEP, db + B_STEP, 1);
    WG_COMMIT();
    WG_WAIT(1);
    WG<N>::ss(d, da + 2 * A_STEP, db + 2 * B_STEP, 1);
    mbar_arrive_if(prel, doR && it != 0);
    const bool r0 = mbar_test(sb + BAR_AF + 8 * sa, pa), r1 = mbar_test(sb + BAR_BF + 8 * sbk, pb);
    const uint64_t da3 = da + 3 * A_STEP, db3 = db + 3 * B_STEP;
    da = da0 + sa * (A_SLOT >> 4); db = db0 + boffs(sbk);
    WG<N>::ss(d, da3, db3, 1);
    WG_COMMIT();
    if (it + 1 < nkb) {
      if (!(r0 && r1)) {
        mbar_wait2(sb + BAR_AF + 8 * sa, pa, sb + BAR_BF + 8 * sbk, pb);
      }
    }
  }
  hook();
  WG_WAIT(0);
  acc_fence<N / 2>(d);
  mbar_arrive_if(rel, doR);
}

__device__ __forceinline__ void fold_mean(float* d, uint32_t cs, float ma, float mb, int t) {
  const uint32_t ha = pack2(-ma, -ma), hb = pack2(-mb, -mb);
  const float la = -ma - bf_lo(ha), lb = -mb - bf_lo(hb);
  const uint32_t a[4] = {t ? 0u : ha, t ? 0u : hb, t ? 0u : pack2(la, la), t ? 0u : pack2(lb, lb)};
  WG_FENCE();
  WG<192>::rst(d, a, mkdesc(cs, 0, 32, 0));
  WG_COMMIT();
}
__device__ __forceinline__ void gelu_tile(const float* d, uint32_t* z, float* st, float ra, float rb) {
  const float kA = 0.7978845608028654f, kB = 0.7978845608028654f * 0.044715f;
  const float c1a = kA * ra, c3a = kB * ra * ra * ra, c1b = kA * rb, c3b = kB * rb * rb * rb;
  float acc[8];
#pragma unroll
  for (int i = 0; i < 8; i++) acc[i] = 0.f;
#pragma unroll
  for (int j = 0; j < 24; j++) {
    float r[4];
#pragma unroll
    for (int e = 0; e < 4; e++) {
      const float v = d[4 * j + e];
      const float a = v * fmaf(v * v, e < 2 ? c3a : c3b, e < 2 ? c1a : c1b);
      r[e] = fmaf(v, tanh_fast(a), v);
      acc[e] += r[e];
      acc[4 + e] = fmaf(r[e], r[e], acc[4 + e]);
    }
    z[2 * j] = pack2(r[0], r[1]);
    z[2 * j + 1] = pack2(r[2], r[3]);
  }
  st[0] = acc[0] + acc[1]; st[1] = acc[4] + acc[5]; st[2] = acc[2] + acc[3]; st[3] = acc[6] + acc[7];
}

template <int Q> __device__ __forceinline__ void conv_load(uint32_t* a, uint32_t ab) {
  a[0] = lds32<512 * Q>(ab);       a[1] = lds32<512 * Q + 256>(ab);  a[2] = lds32<512 * Q + 16>(ab);   a[3] = lds32<512 * Q + 272>(ab);
  a[4] = lds32<512 * Q + 32>(ab);  a[5] = lds32<512 * Q + 288>(ab);  a[6] = lds32<512 * Q + 48>(ab);   a[7] = lds32<512 * Q + 304>(ab);
  a[8] = lds32<512 * Q + 64>(ab);  a[9] = lds32<512 * Q + 320>(ab);  a[10] = lds32<512 * Q + 80>(ab);  a[11] = lds32<512 * Q + 336>(ab);
  a[12] = lds32<512 * Q + 96>(ab); a[13] = lds32<512 * Q + 352>(ab); a[14] = lds32<512 * Q + 112>(ab); a[15] = lds32<512 * Q + 368>(ab);
}
template <int Q, int L> __device__ __forceinline__ void conv_step(float* d, uint32_t (*a)[16], uint32_t ab, uint64_t db) {
  WG_FENCE();
#pragma unroll
  for (int s = 0; s < 4; s++) WG<128 - 16 * Q>::rs(d, a[Q] + 4 * s, db + s + 16 * Q);
  WG_COMMIT();
  WG_WAIT(1);
  if (L >= 0) conv_load<(L >= 0 ? L : 0)>(a[L >= 0 ? L : 0], ab);
  if (Q == 0) WG_WAIT(0);
}

__device__ __forceinline__ int seg_col(int cb, int h) { return (cb >> 1) * 320 + (cb & 1) * 32 + h * 64; }
__device__ __forceinline__ void final_load_x(uint32_t (*xw)[10], uint32_t xt, int cb, int h, int w, int lane) {
  const int g = lane >> 2, t = lane & 3, cc = seg_col(cb, h) >> 3;
  const int c0 = cc + t, c1 = c0 + 24, c2 = cc + 16 - 6 * h + (t >> 1);
  const uint32_t r0 = xt + (w * 16 + g) * 128;
#pragma unroll
  for (int r = 0; r < 2; r++) {
    const uint4 u = lds128(r0 + r * 1024 + (c0 >> 3) * A_SLOT + (((c0 ^ g) & 7) << 4)), v = lds128(r0 + r * 1024 + (c1 >> 3) * A_SLOT + (((c1 ^ g) & 7) << 4));
    const float2 z = lds64f(r0 + r * 1024 + (c2 >> 3) * A_SLOT + (((c2 ^ g) & 7) << 4) + (t & 1) * 8);
    xw[r][0] = u.x; xw[r][1] = u.y; xw[r][2] = u.z; xw[r][3] = u.w;
    xw[r][4] = v.x; xw[r][5] = v.y; xw[r][6] = v.z; xw[r][7] = v.w;
    xw[r][8] = __float_as_uint(z.x); xw[r][9] = __float_as_uint(z.y);
  }
}
__device__ __forceinline__ void final_s_early(uint32_t (*sw)[10], const uint32_t (*xw)[10], uint32_t ya, float2 s0, float2 s1) {
  const uint32_t r2[2] = {pack2(s0.y, s0.y), pack2(s1.y, s1.y)};
  const float na = -s0.x * bf_lo(r2[0]), nb = -s1.x * bf_lo(r2[1]);
  const uint32_t n2[2] = {pack2(na, na), pack2(nb, nb)};
#pragma unroll
  for (int j = 0; j < 10; j += 2) {
    uint32_t y[4];
    if (j < 4 || j == 8) ldsm4t(y, ya + (j < 4 ? j : 4) * 1024);
#pragma unroll
    for (int e = 0; e < 4; e++) {
      const uint32_t xn = hfma2(xw[e & 1][j + (e >> 1)], r2[e & 1], n2[e & 1]);
      sw[e & 1][j + (e >> 1)] = (j < 4 || j == 8) ? hmul2(xn, y[e]) : xn;
    }
  }
}
__device__ __forceinline__ bool final_late(uint32_t* y, uint32_t ya) {
  ldsm4t(y, ya + 6144);
  ldsm4t(y + 4, ya + 8192);
  uint32_t zero = 0;
#pragma unroll
  for (int e = 0; e < 8; e++) zero |= (y[e] - 0x00010001u) & ~y[e];
  return (zero & 0x80008000u) == 0;
}
__device__ __forceinline__ bool bar_all(int id, int n, bool c) {
  uint32_t r;
  asm volatile("{\n.reg .pred p, q;\nsetp.ne.u32 p, %3, 0;\nbar.red.and.pred q, %1, %2, p;\nselp.u32 %0, 1, 0, q;\n}\n" : "=r"(r) : "r"(id), "r"(n), "r"((uint32_t)c) : "memory");
  return r;
}
__device__ __forceinline__ void final_out(const float* d, const uint32_t (*xw)[10], const uint32_t (*sw)[10], float ra, float rb, __nv_bfloat16* o0, int h, int t) {
  const float ca = 0.25f * ra, cb = 0.25f * rb;
  uint32_t o[2][10];
#pragma unroll
  for (int j = 0; j < 10; j++) {
#pragma unroll
    for (int r = 0; r < 2; r++) {
      const float h0 = d[4 * j + 2 * r] * (r ? cb : ca), h1 = d[4 * j + 2 * r + 1] * (r ? cb : ca);
      o[r][j] = hfma2(pack2(fmaf(h0, tanh_fast(h0), h0), fmaf(h1, tanh_fast(h1), h1)), sw[r][j], xw[r][j]);
      __nv_bfloat16* q = o0 + r * 8 * kD;
      if (j == 3) stg4_if(q + t * 8, o[r][0], o[r][1], o[r][2], o[r][3], true);
      if (j == 7) stg4_if(q + 192 + t * 8, o[r][4], o[r][5], o[r][6], o[r][7], true);
      if (j == 9) asm volatile("st.global.v2.u32 [%0], {%1,%2};" ::"l"(q + 128 - 48 * h + t * 4), "r"(o[r][8]), "r"(o[r][9]) : "memory");
    }
  }
}

struct Taps { uint4 r0, r1; uint32_t n0, n1, dd; };
__device__ __forceinline__ void load_taps(Taps& k, const Params& p, int ch, int tid) {
  const uint4* kp = (const uint4*)(p.ssmk + (size_t)ch * kS);
  k.r0 = ldg4(kp + tid); k.r1 = ldg4(kp + 128 + tid);
  k.n0 = ldg1(kp + tid + 1); k.n1 = tid < 127 ? ldg1(kp + 129 + tid) : 0u;
  k.dd = __bfloat16_as_ushort(p.ssmD[ch]);
}
__device__ __forceinline__ void load_convx(const Params& p, uint32_t cv, uint32_t bar, int ch) {
  mbar_expect(bar, 4096);
  bulk_g2s(cv, p.scr->kvx + (size_t)ch * 4096, 2048, bar);
  bulk_g2s(cv + XB_PL, p.scr->kvx + (size_t)ch * 4096 + 2048, 2048, bar);
}
#define CW 3
#define CSTAMP(j)
__device__ __forceinline__ void zero_pads(uint32_t cv, int lane) {
  if (lane < 8) sts128(cv + (lane >> 2) * XB_PL + 2048 + (lane & 3) * 16, 0, 0, 0, 0);
  else if (lane < 12) sts128(cv + ((lane & 2) ? CV_KO : CV_KE) + (lane & 1) * 16, 0, 0, 0, 0);
  fence_async_smem();
  __syncwarp();
}
__device__ __forceinline__ int y_row(int c, uint32_t par) {
  const int hf = c >= 320, cc = c - hf * 320, u = cc >> 6, cb = hf * 2 + ((cc >> 5) & 1);
  if (u == 2) return cb * 96 + ((cc >> 4) & 1) * 48 + 32 + (cc & 1) + ((cc >> 1) & 1) * 8 + ((cc >> 2) & 3) * 2;
  return (u < 2 ? cb * 96 + u * 48 : 384 + par * 256 + cb * 64 + (u - 3) * 32) + (cc & 1) + ((cc >> 1) & 3) * 8 + ((cc >> 3) & 3) * 2;
}
__device__ __forceinline__ void z_store(uint8_t* dst, uint32_t src, int q) {
  dst += q * 16 * B_SLOT;
  bulk_s2g(dst, src + q * 12288, 6144);
  bulk_s2g(dst + 8 * B_SLOT, src + q * 12288 + 6144, 6144);
  asm volatile("cp.async.bulk.commit_group;\ncp.async.bulk.wait_group 0;" ::: "memory");
}
__device__ __forceinline__ void y_store(const Params& p, uint32_t sb, int h, int ch, uint32_t par) {
  uint8_t* dst = p.scr->y + (size_t)y_row(ch, par) * 4096;
  if (elect_one()) {
    bulk_s2g(dst, sb + OFF_A + 9 * A_SLOT + h * 4096, 4096);
    asm volatile("cp.async.bulk.commit_group;\ncp.async.bulk.wait_group 0;" ::: "memory");
  }
  __syncwarp();
}
__device__ __forceinline__ void conv_service(const Params& p, uint32_t sb, int h, int ch, bool first) {
  bar_sync(NB_WGA + 8 + h, 160);
  const bool now = !first || __all_sync(0xffffffff, mbar_test(sb + BAR_KV, 0));
  if (now && elect_one()) load_convx(p, sb + OFF_CV + (1 - h) * CV_SZ, sb + BAR_XF + 8 * h, ch + 128);
  bar_sync(NB_WGA + 8 + h, 160);
  y_store(p, sb, h, ch, 0);
  if (!now) {
    mbar_wait(sb + BAR_KV, 0);
    if (elect_one()) load_convx(p, sb + OFF_CV + (1 - h) * CV_SZ, sb + BAR_XF + 8 * h, ch + 128);
  }
}
__device__ __forceinline__ uint32_t y_tile(int h) { return OFF_CV + (1 - h) * 13312; }
__device__ __forceinline__ void load_late_y(const Params& p, uint32_t sb, int h, int rb, int cb, uint32_t par) {
  mbar_expect(sb + BAR_YL + 16 * h, 4096);
  tma2d(sb + y_tile(h) + 6144, &p.tmY, rb * 64, 384 + par * 256 + cb * 64 + h * 32, sb + BAR_YL + 16 * h);
  tma2d(sb + y_tile(h) + 8192, &p.tmY, rb * 64, 400 + par * 256 + cb * 64 + h * 32, sb + BAR_YL + 16 * h);
}
__device__ __forceinline__ void held_service(const Params& p, uint32_t sb, int h, int ch, int rb, int cb, uint32_t tag, int lane) {
#pragma unroll 1
  for (int i = 0; i < 8; i++) sts128(sb + OFF_A + 9 * A_SLOT + h * 4096 + i * 512 + lane * 16, 0, 0, 0, 0);
  fence_async_smem();
  __syncwarp();
  y_store(p, sb, h, ch, ~tag & 1);
  mbar_wait(sb + BAR_YT, 1);
  uint8_t* dst = p.scr->y + (size_t)y_row(ch, tag & 1) * 4096;
  asm volatile("" : "+l"(dst));
  bar_sync(NB_WGA + 8 + h, 160);
  bar_sync(NB_WGA + 8 + h, 160);
  if (elect_one()) {
    bulk_s2g(dst, sb + OFF_A + 9 * A_SLOT + h * 4096, 4096);
    asm volatile("cp.async.bulk.commit_group;" ::: "memory");
    mbar_expect(sb + BAR_XF + 8 * h, 6144);
#pragma unroll 1
    for (int i = 0; i < 3; i++) tma2d(sb + y_tile(h) + i * 2048, &p.tmY, rb * 64, cb * 96 + h * 48 + i * 16, sb + BAR_XF + 8 * h);
  }
  mbar_wait(sb + BAR_AE + 8 * (LL_AT - 1), 1);
  if (elect_one()) { load_late_y(p, sb, h, rb, cb, tag & 1); asm volatile("cp.async.bulk.wait_group 0;" ::: "memory"); }
}
__device__ __forceinline__ void conv_worker(const Params& p, Taps& k, uint32_t cv, uint32_t yb0,
                                            uint32_t xbar, int nbar, int ch0, int n, uint32_t holdbar, int w, int lane,
                                            int tid, int st0, int rb, int cb) {
  const int g = lane >> 2, t = lane & 3, w0 = w & 1, w1 = w >> 1;
  const uint32_t ab = cv + ((g & 1) ? CV_KE : CV_KO) + 32 + 2 * (64 * w0 + 8 * w1 + ((g - 15) & ~1) + 2 * t);
  const uint32_t scA = cv + (w1 ? CV_KO : CV_KE) + 32, scB = scA + 2048;
  const int dl = (t >> 1) ^ 1;
  if (n == 2) mbar_wait(xbar, 0);
  STAMPW(st0 + 3);
#pragma unroll 1
  for (int i = 0; i < n; i++) {
    if (tid == 0) {
      k.r0.x = (k.r0.x & 0xffff0000u) | (pack2(bf_lo(k.r0.x) + bf_lo(k.dd), 0.f) & 0xffffu);
      sts32(cv + CV_KO + 28, k.r0.x << 16);
    }
    sts128(cv + CV_KE + 32 + tid * 16, k.r0.x, k.r0.y, k.r0.z, k.r0.w);
    sts128(cv + CV_KO + 32 + tid * 16, prmt(k.r0.x, k.r0.y, 0x5432), prmt(k.r0.y, k.r0.z, 0x5432), prmt(k.r0.z, k.r0.w, 0x5432), prmt(k.r0.w, k.n0, 0x5432));
    sts128(cv + CV_KE + 2080 + tid * 16, k.r1.x, k.r1.y, k.r1.z, k.r1.w);
    sts128(cv + CV_KO + 2080 + tid * 16, prmt(k.r1.x, k.r1.y, 0x5432), prmt(k.r1.y, k.r1.z, 0x5432), prmt(k.r1.z, k.r1.w, 0x5432), prmt(k.r1.w, k.n1, 0x5432));
    if (i + 1 < n) load_taps(k, p, ch0 + (i + 1) * 128, tid);
    bar_sync(nbar, 128);
    CSTAMP(0);
    const uint64_t db = mkdesc(cv + (i & 0x1000), XB_PL, 128, 0);
    float d[64];
    uint32_t a[8][16];
    if (i == 0) mbar_wait(xbar, 0);
    conv_load<7>(a[7], ab); conv_load<6>(a[6], ab); conv_load<5>(a[5], ab); conv_load<4>(a[4], ab);
#pragma unroll
    for (int j = 0; j < 64; j++) d[j] = 0.f;
    mbar_wait(xbar, i & 1);
    if (i + 1 == n) mbar_wait(holdbar + (BAR_GO1 - BAR_GO), 1);
    CSTAMP(1);
    conv_step<7, -1>(d, a, ab, db); conv_step<6, -1>(d, a, ab, db); conv_step<5, -1>(d, a, ab, db); conv_step<4, -1>(d, a, ab, db);
    if (i + 1 == n) mbar_wait(holdbar, 1);
    conv_load<3>(a[3], ab);
    conv_step<3, 2>(d, a, ab, db);
    conv_step<2, 1>(d, a, ab, db);
    conv_step<1, 0>(d, a, ab, db);
    conv_step<0, -1>(d, a, ab, db);
    acc_fence<64>(d);
    CSTAMP(2);
    bar_sync(nbar + 8, 160);
    float E[16][2];
#pragma unroll
    for (int j = 0; j < 15; j++) { E[j][0] = d[4 * j] + d[4 * j + 6]; E[j][1] = d[4 * j + 1] + d[4 * j + 7]; }
    E[15][0] = d[60]; E[15][1] = d[61];
    if (w0 == 0) {
#pragma unroll
      for (int j = 8; j < 16; j++) sts64f(scA + (j - 8) * 256 + lane * 8, E[j][0], E[j][1]);
    } else {
      const uint32_t a = scB - dl * 256 + (lane ^ 2) * 8;
#pragma unroll
      for (int j = 1; j < 8; j++) sts64f(a + j * 256, E[j][0], E[j][1]);
      sts64f(scB + (dl ? 7 * 256 : 0) + (lane ^ 2) * 8, dl ? E[8][0] : E[0][0], dl ? E[8][1] : E[0][1]);
    }
    bar_sync(nbar, 128);
    CSTAMP(3);
    uint32_t pk[8];
    if (w0 == 0) {
#pragma unroll
      for (int j = 0; j < 8; j++) { const float2 v = lds64f(scB + j * 256 + lane * 8); pk[j] = pack2(E[j][0] + v.x, E[j][1] + v.y); }
    } else {
      const uint32_t a0 = scA - dl * 256 + (lane ^ 2) * 8;
#pragma unroll
      for (int j = 9; j < 16; j++) { const float2 v = lds64f(a0 + (j - 8) * 256); pk[j - 8] = pack2(E[j][0] + v.x, E[j][1] + v.y); }
      const float2 v = lds64f(scA + (dl ? 7 * 256 : 0) + (lane ^ 2) * 8);
      pk[0] = pack2((dl ? 0.f : E[8][0]) + v.x, (dl ? 0.f : E[8][1]) + v.y);
    }
    CSTAMP(4);
    if (i + 1 == n) {
#pragma unroll
      for (int j = 0; j < 8; j++) pk[j] = ~pk[j];
    }
    const int c1 = (w0 ? 35 : 95) - lane, c0 = (w0 && lane < 4) ? c1 - 32 : c1 + 32;
    stsm4t(yb0 + 128 * (c0 & 31) + (((2 * (c0 >> 5) + w1) ^ (c0 & 7)) << 4), pk[0], pk[1], pk[2], pk[3]);
    stsm4t(yb0 + 128 * (c1 & 31) + (((2 * (c1 >> 5) + w1) ^ (c1 & 7)) << 4), pk[4], pk[5], pk[6], pk[7]);
    fence_async_smem();
    bar_sync(nbar + 8, 160);
    CSTAMP(5);
    STAMPW(st0 + i);
    if (n == 2 && i == 0) {
      const int u = (tid >> 3) % 5, kg = rb * 3 + (tid < 120 ? (tid >> 3) / 5 : 0), c = u < 4 ? (u >> 1) * 10 + (u & 1) * 4 : 8, o2 = u < 4 ? 2 : 10;
      const uint4* wp = (const uint4*)p.wout + (uint32_t)((kg * 8 + (tid & 7)) * (kD / 8) + (seg_col(cb, 0) >> 3) + (u < 4 ? (u >> 1) * 8 + (u & 1) * 24 : 16));
      const uint4 w0 = ldg4(wp), w1 = ldg4(wp + 1), w2 = ldg4(wp + 2), w3 = ldg4(wp + 3);
      uint8_t* dst = p.scr->wo + (uint32_t)(cb * (12 * 20480) + kg * 2560 + c * 128 + (tid & 7) * 16);
      const bool f = u < 4, on = tid < 120;
      stg4_if(dst, w0.x, f ? w1.x : w0.z, f ? w2.x : w1.x, f ? w3.x : w1.z, on);
      stg4_if(dst + 128, w0.y, f ? w1.y : w0.w, f ? w2.y : w1.y, f ? w3.y : w1.w, on);
      stg4_if(dst + o2 * 128, f ? w0.z : w2.x, f ? w1.z : w2.z, f ? w2.z : w3.x, w3.z, on);
      stg4_if(dst + o2 * 128 + 128, f ? w0.w : w2.y, f ? w1.w : w2.w, f ? w2.w : w3.y, w3.w, on);
      bar_arrive(NB_WO, 160);
    }
  }
}

struct KvRegs { uint32_t k[11], v[8]; uint4 sh; };
__device__ __forceinline__ void kv_load(KvRegs& q, const __nv_bfloat16* kp, const __nv_bfloat16* vp, const __nv_bfloat16* sp, bool halo) {
#pragma unroll
  for (int i = 0; i < 11; i++) q.k[i] = (i >= 3 || halo) ? ldg1(kp + i * kD) : 0u;
#pragma unroll
  for (int i = 0; i < 8; i++) q.v[i] = ldg1(vp + i * kD);
  q.sh = ldg4(sp);
}
__device__ __forceinline__ void kv_unit(const KvRegs& q, uint32_t oa) {
  const uint32_t w0 = prmt(q.sh.x, q.sh.z, 0x5410), w1 = prmt(q.sh.x, q.sh.z, 0x7632), w2 = prmt(q.sh.y, q.sh.w, 0x5410), w3 = prmt(q.sh.y, q.sh.w, 0x7632);
  uint32_t r[8];
#pragma unroll
  for (int i = 0; i < 8; i++) r[i] = hmul2(hfma2(q.k[i + 3], w0, hfma2(q.k[i + 2], w1, hfma2(q.k[i + 1], w2, hmul2(q.k[i], w3)))), q.v[i]);
  sts128(oa, prmt(r[7], r[6], 0x5410), prmt(r[5], r[4], 0x5410), prmt(r[3], r[2], 0x5410), prmt(r[1], r[0], 0x5410));
  sts128(oa + 2048, prmt(r[7], r[6], 0x7632), prmt(r[5], r[4], 0x7632), prmt(r[3], r[2], 0x7632), prmt(r[1], r[0], 0x7632));
}

__device__ __forceinline__ void gather_colsum(const Params& p, uint32_t sb, int cb, int part, uint32_t tag, int lane) {
  uint4 v[3];
  uint32_t t0 = 0;
#pragma unroll 1
  while (true) {
    bool ok = true;
#pragma unroll
    for (int i = 0; i < 3; i++) {
      v[i] = ld_ll4(&p.scr->colsum[(part ? 0 : 768) + cb * 192 + i * 64 + lane * 2]);
      ok = ok && v[i].y == tag && v[i].w == tag;
    }
    if (__all_sync(0xffffffff, ok)) break;
    spin_guard(t0);
  }
#pragma unroll
  for (int i = 0; i < 3; i++) {
    const uint32_t hi = pack2(__uint_as_float(v[i].x), __uint_as_float(v[i].z)), ca = sb + OFF_CS + (1 - part) * 768 + i * 256 + (lane >> 2) * 32 + (lane & 3) * 4;
    sts32(ca, hi);
    sts32(ca + 16, pack2(__uint_as_float(v[i].x) - bf_lo(hi), __uint_as_float(v[i].z) - bf_hi(hi)));
  }
  __syncwarp();
  if (lane == 0) mbar_arrive(sb + BAR_ST + 8 * part);
}

__device__ __forceinline__ void helper_cta(const Params& p, uint32_t sb, int cb, int warp, int lane) {
  constexpr int NS = 9, ONES = NS * B_SLOT, BF = ONES + 256, BE = BF + 8 * NS;
  if (warp < NS && elect_one()) {
    mbar_init(sb + BF + 8 * warp, 1); mbar_init(sb + BE + 8 * warp, 1);
    fence_async_smem();
    if (warp == 0) { mbar_expect(sb + BF, B_SLOT); tma3d(sb, &p.tmW, 0, 0, 12 + cb * 3, sb + BF); }
  }
  if (warp == 15) { sts32(sb + ONES + lane * 4, 0x3f803f80u); sts32(sb + ONES + 128 + lane * 4, 0x3f803f80u); fence_async_smem(); }
  __syncthreads();
  if (warp == 4) {
    int s = 1, ph = 1;
#pragma unroll 1
    for (int it = 1; it < 20; it++) {
      mbar_wait(sb + BE + 8 * s, ph);
      if (elect_one()) { mbar_expect(sb + BF + 8 * s, B_SLOT); tma3d(sb + s * B_SLOT, &p.tmW, 0, (it < 10 ? it : it - 10) * 64, (it < 10 ? 12 : 0) + cb * 3, sb + BF + 8 * s); }
      if (++s == NS) { s = 0; ph ^= 1; }
    }
  } else if (warp < 4) {
    const uint32_t tag = load_epoch(p, 128 + cb, lane) + 1;
    const uint64_t db = mkdesc(sb + ONES, 128, 128, 0);
    uint2* dst = p.scr->colsum + cb * 192 + warp * 16 + (lane >> 2);
    if ((lane & 3) == 0) {
#pragma unroll 1
      for (int j = 0; j < 12; j++) st_ll2(dst + (j < 6 ? 768 : 0) + ((j % 6) >> 1) * 64 + (j & 1) * 8, 0, 0);
    }
    int s = 0, ph = 0;
#pragma unroll 1
    for (int part = 0; part < 2; part++) {
      float d[12];
#pragma unroll
      for (int i = 0; i < 12; i++) d[i] = 0.f;
#pragma unroll 1
      for (int it = 0; it < 10; it++) {
        mbar_wait(sb + BF + 8 * s, ph);
        const uint64_t da = mkdesc(sb + s * B_SLOT, 8192, 1024, 1);
        WG_FENCE();
#pragma unroll
        for (int j = 0; j < 12; j++) wgmma_colsum(d + 4 * (j % 3), da + (j % 3) * 512 + (j / 3) * 128, db);
        WG_COMMIT();
        WG_WAIT(1);
        mbar_arrive_if(sb + BE + 8 * (s == 0 ? NS - 1 : s - 1), threadIdx.x == 0 && (it | part) != 0);
        if (++s == NS) { s = 0; ph ^= 1; }
      }
      WG_WAIT(0);
      acc_fence<12>(d);
      if ((lane & 3) == 0) {
#pragma unroll
        for (int j = 0; j < 6; j++) st_ll2(dst + (part ? 0 : 768) + (j >> 1) * 64 + (j & 1) * 8, __float_as_uint(d[2 * j]), tag);
      }
      STAMPW(1 + part);
    }
    if (threadIdx.x == 0) st_relaxed(&p.scr->epoch[(128 + cb) * EPS], tag);
  }
}

__global__ void __launch_bounds__(512, 1) fused_kernel(const __grid_constant__ Params p) {
  extern __shared__ __align__(1024) uint8_t smem[];
  const int warp = __shfl_sync(0xffffffff, (int)(threadIdx.x >> 5), 0);
  const int lane = threadIdx.x & 31, tid = threadIdx.x & 127;
  const uint32_t sb = __shfl_sync(0xffffffff, (uint32_t)__cvta_generic_to_shared(smem), 0);
  const uint32_t tstart = clock();
  if (elect_one()) {
    if (warp < 5) asm volatile("prefetch.tensormap [%0];" ::"l"(&p.tmX + warp) : "memory");
    mbar_init(sb + OFF_BAR + 8 * warp, 1); mbar_init(sb + OFF_BAR + 128 + 8 * warp, 1); mbar_init(sb + OFF_BAR + 256 + 8 * warp, 2);
    asm volatile("fence.mbarrier_init.release.cluster;" ::: "memory");
  }
  int b = blockIdx.x;
  if (p.by_smid) asm volatile("mov.u32 %0, %%smid;" : "=r"(b));
  b = __shfl_sync(0xffffffff, b, 0);
  const int tp = b >> 1, t7 = (tp - 32) / 7;
  const int lin = tp < 32 ? ((tp & 7) ? (tp & 7) * 16 : 8) + (tp >> 3) * 2 + (b & 1)
                          : (tp < 60 ? (tp - 31 - t7 * 7) * 16 + 8 + t7 * 2 + (b & 1) : (tp < 62 ? -1 : b - 124));
  const int hcb = (b & 3) ^ 2;
  if (lin < 0) { helper_cta(p, sb, hcb, warp, lane); return; }
  const int cb = ((lin >> 4) & 1) * 2 + ((lin >> 1) & 1), rb = (lin >> 5) * 8 + ((lin >> 2) & 3) * 2 + (lin & 1);
  const int zs0 = 4 - (cb & 2);
  const int chb = (cb >> 1) * 320 + rb * 2 + (cb & 1);
  if (warp == 0 && elect_one()) {
    mbar_expect(sb + BAR_AF, A_SLOT);
    tma_rows(sb + OFF_A, &p.tmX, 0, rb, sb + BAR_AF);
    mbar_expect(sb + BAR_BF, B_SLOT);
    tma3d(sb + OFF_B, &p.tmW, 0, 0, 12 + cb * 3, sb + BAR_BF);
  }
  if (warp == 1) STAMP(31);
  if (sb & 1023) die();
  __syncthreads();

  if (warp >= 12) {
    asm volatile("setmaxnreg.dec.sync.aligned.u32 32;");
    uint32_t bias2 = 0;
    if (warp == 15) bias2 = ldg1(p.bsp + (lane >> 3) * 512 + rb * 16 + (lane & 7) * 2);
    uint32_t epoch = 0;
    if (!WARM || warp != 12) epoch = load_epoch(p, lin, lane);
    if (warp == 12) {
#pragma unroll 1
      for (int i = 1; i < NA; i++) {
        if (elect_one()) {
          mbar_expect(sb + BAR_AF + 8 * i, A_SLOT);
          tma_rows(sb + OFF_A + i * A_SLOT, &p.tmX, i * 64, rb, sb + BAR_AF + 8 * i);
          if (i < NB) { mbar_expect(sb + BAR_BF + 8 * i, B_SLOT); tma3d(sb + OFF_B + i * B_SLOT, &p.tmW, 0, i * 64, 12 + cb * 3, sb + BAR_BF + 8 * i); }
        }
      }
      STAMP(32);
      uint32_t kvt;
      {
        const int tb = rb * 2 + (cb & 1);
        kvt = __shfl_sync(0xffffffff, (ld_relaxed(p.scr->cnt + (CNT_KV + (cb >> 1)) * CSP) & ~63u) + 64, 0);
        {
          uint32_t tp = tstart;
          pace(tp, KV_T0);
          mbar_arrive_if(sb + BAR_KV + 8, lane == 0);
        }
        mbar_wait2(sb + BAR_XS, 0, sb + BAR_ST, 0);
#pragma unroll 1
        for (int u = 0; u < 5; u++) {
          mbar_wait(sb + BAR_KU + 8 * u, 0);
          fence_async_smem();
          if (elect_one()) {
            asm volatile("cp.async.bulk.tensor.3d.global.shared::cta.bulk_group [%0, {%2, %3, %4}], [%1];\ncp.async.bulk.commit_group;" ::"l"(&p.tmKV),
                         "r"(sb + OFF_CV + CV_SZ + (u < 3 ? u : u - 3) * 4096), "r"((63 - tb) * 16), "r"((cb >> 1) * 160 + u * 32), "r"(0) : "memory");
            if (u == 1 || u == 4) asm volatile("cp.async.bulk.wait_group 0;" ::: "memory");
            if (u == 1) { mbar_arrive(sb + BAR_KU); red_release(p.scr->cnt + (CNT_KV + (cb >> 1)) * CSP); }
          }
          __syncwarp();
          if (u == 1) {
            STAMP(35);
            { const char* q = (const char*)p.ssmk + chb * 4096 + lane * 128; prefetch_l2(q); prefetch_l2(q + 64 * 4096); }
          }
        }
        zero_pads(sb + OFF_CV + CV_SZ, lane);
        if (elect_one()) { mbar_arrive(sb + BAR_KU + 8); red_release(p.scr->cnt + (CNT_KV + 2 + (cb >> 1)) * CSP); }
        STAMP(30);
        if (lane < 24) {
          const char* r = (const char*)p.wout + (rb * 24 + lane) * (kD * 2) + (cb >> 1) * 640 + (cb & 1) * 384;
          prefetch_l2(r); prefetch_l2(r + 128); prefetch_l2(r + 256 - (cb & 1) * 384);
        }
      }
      poll_counter(p.scr->cnt + (CNT_KV + 2 + (cb >> 1)) * CSP, kvt);
      if (elect_one()) mbar_arrive(sb + BAR_KV);
      STAMP(34);
      {
        const char* q = (const char*)p.wsp + (cb * 512 + rb * 16 + (lane >> 1)) * (kS * 2) + (lane & 1) * 128;
        uint32_t tp = clock();
#pragma unroll 1
        for (int i = LEAD / 2; i < 16; i++) {
          prefetch_l2(q + i * 256);
          pace(tp, WSP_D);
        }
      }
      const uint32_t ht = (WARM & 1) ? (ld_relaxed(&p.scr->hcnt[(rb >> HGRP) * 32]) & ~((4u << HGRP) - 1)) + (4 << HGRP) : (epoch + 1) * (4 << HGRP);
      uint8_t* hrow = p.scr->h + anchor(rb * 12 * A_SLOT);
      uint8_t* hown = hrow + anchor(cb * 3 * A_SLOT);
      bar_sync(NB_H, 160);
      if (elect_one()) bulk_s2g(hown, sb + OFF_A + 5 * A_SLOT, A_SLOT);
      mbar_wait(sb + BAR_G2, 0);
      if (elect_one()) {
        bulk_s2g(hown + A_SLOT, sb + OFF_A + 6 * A_SLOT, 2 * A_SLOT);
        asm volatile("cp.async.bulk.commit_group;\ncp.async.bulk.wait_group 0;" ::: "memory");
        red_release(&p.scr->hcnt[(rb >> HGRP) * 32]);
      }
      __syncwarp();
      STAMP(20);
      STAMP(39);
      const uint8_t* hsrc = cb ? hrow : hrow + 3 * A_SLOT;
      if (elect_one()) {
        poll_one(&p.scr->hcnt[(rb >> HGRP) * 32], ht);
        bulk_g2s(sb + OFF_A + 8 * A_SLOT, hsrc, A_SLOT, sb + BAR_AF + 64);
        STAMP(37);
        uint32_t tp = clock();
#pragma unroll 1
        for (int i = 0; i < 8; i++) {
          hsrc += A_SLOT;
          if (hsrc == hown) hsrc += 3 * A_SLOT;
          if (i == 5) mbar_wait(sb + BAR_AE + 56, 0);
          tp += HPACE;
          while ((int32_t)((uint32_t)clock() - tp) < 0) {}
          bulk_g2s(sb + OFF_A + i * A_SLOT, hsrc, A_SLOT, sb + BAR_AF + 8 * i);
        }
      }
      STAMP(21);
    } else if (warp == 13) {
      int s = 0, ph = 0;
#pragma unroll 1
      for (int it = NB; it < 20; it++) {
        mbar_wait(sb + BAR_BE + 8 * s, ph);
        if (elect_one()) { mbar_expect(sb + BAR_BF + 8 * s, B_SLOT); tma3d(sb + OFF_B + s * B_SLOT, &p.tmW, 0, (it < 10 ? it : (it + zs0) % 10) * 64, (it < 10 ? 12 : 0) + cb * 3, sb + BAR_BF + 8 * s); }
        STAMP2(32 + it);
        if (++s == NB) { s = 0; ph ^= 1; }
      }
      mbar_wait(sb + BAR_XC, 0);
#pragma unroll 1
      for (int i = 0; i < LEAD; i++) {
        mbar_wait(sb + BAR_AE + 8 * i, 0);
        if (elect_one()) { mbar_expect(sb + BAR_AF + 8 * i, A_SLOT); tma_rows(sb + OFF_A + i * A_SLOT, &p.tmWsp, i * 64, rb, sb + BAR_AF + 8 * i); }
      }
#pragma unroll 1
      for (int i = 0; i < NB; i++) mbar_wait2(sb + BAR_BE + 8 * i, 1, sb + BAR_AE + 8 * (LEAD + i), 0);
      mbar_expect_if(sb + (lane < NB ? BAR_BF + 8 * lane : BAR_AF + 8 * (LEAD + lane - NB)), lane < NB ? B_SLOT : A_SLOT, lane < 2 * NB);
      const uint8_t* zt = p.scr->z2 + anchor(cb * 32 * B_SLOT);
      if (elect_one()) {
        poll_one(p.scr->zcnt + (cb >> ZSH) * 32, (epoch + 1) * (32 << ZSH));
        bulk_g2s(sb + OFF_B, zt, B_SLOT, sb + BAR_BF);
#pragma unroll 1
        for (int it = 1; it < NB + LEAD; it++) {
          if (it == LEAD) mbar_wait(sb + BAR_ZP, 0);
          if (it >= LEAD) tma_rows(sb + OFF_A + it * A_SLOT, &p.tmWsp, it * 64, rb, sb + BAR_AF + 8 * it);
          if (it < NB) bulk_g2s(sb + OFF_B + it * B_SLOT, zt + it * B_SLOT, B_SLOT, sb + BAR_BF + 8 * it);
        }
      }
      __syncwarp();
      STAMP(22);
      int sa = NB + LEAD, pa = 0;
      ph = 0;
#pragma unroll 1
      for (int it = NB; it < 32; it++) {
        if (it == 16) mbar_wait(sb + BAR_Z1, 1);
        mbar_wait2(sb + BAR_BE + 8 * s, ph, sb + BAR_AE + 8 * sa, pa);
        if (elect_one()) {
          mbar_expect(sb + BAR_BF + 8 * s, B_SLOT);
          bulk_g2s(sb + OFF_B + s * B_SLOT, zt + it * B_SLOT, B_SLOT, sb + BAR_BF + 8 * s);
          if (it + LEAD < 32) { mbar_expect(sb + BAR_AF + 8 * sa, A_SLOT); tma_rows(sb + OFF_A + sa * A_SLOT, &p.tmWsp, (it + LEAD) * 64, rb, sb + BAR_AF + 8 * sa); }
        }
        if (it + LEAD < 31 && ++sa == NA2) { sa = 0; pa ^= 1; }
        STAMP2(52 + it);
        if (++s == NB) { s = 0; ph ^= 1; }
      }
      mbar_wait(sb + BAR_WO, 0);
#pragma unroll 1
      for (int it = 0; it < 12; it++) {
        if (it < 6) mbar_wait(sb + BAR_BE + 8 * ((0x110443 >> (4 * it)) & 7), it < 3 ? 1 : 0);
        else mbar_wait(sb + BAR_BE + 8 * s, ph);
        if (elect_one()) {
          mbar_expect(sb + BAR_BF + 8 * s, 20480);
          bulk_g2s(sb + OFF_B + (s == 5 ? 0 : s + 1) * 20480, p.scr->wo + (size_t)(cb * 12 + g3_block(cb, it)) * 20480, 20480, sb + BAR_BF + 8 * s);
        }
        STAMP2(84 + it);
        if (++s == 6) { s = 0; ph ^= 1; }
      }
    } else if (warp == 14) {
      const uint32_t tag = epoch + 1;
      mbar_wait(sb + BAR_AF + 8 * (NA - 1), 0);
      gather_colsum(p, sb, cb, 0, tag, lane);
      STAMP(27);
      uint8_t* zd = p.scr->z2 + anchor((cb * 32 + (rb >> 2)) * B_SLOT + (rb & 3) * 6144);
      const uint32_t zsrc = anchor(sb + OFF_A + zs0 * A_SLOT);
      bar_sync(NB_Z, 160);
      if (elect_one()) {
        z_store(zd, zsrc, 0);
        STAMP(7);
        red_release(p.scr->zcnt + (cb >> ZSH) * 32);
      }
      STAMP(25);
      bar_sync(NB_Z2, 96);
      if (elect_one()) {
        z_store(zd, zsrc, 1);
        mbar_arrive(sb + BAR_ZP);
        red_release(p.scr->cnt + (CNT_Z1 + (cb >> 1)) * CSP);
      }
      STAMP(28);
      mbar_wait(sb + BAR_AE + 72, 0);
      conv_service(p, sb, 0, chb + 64, true);
      bar_sync(NB_WO, 160);
      bar_sync(NB_CD, 64);
      if (elect_one()) { red_release(p.scr->cnt + (CNT_WO + cb) * CSP); red_relaxed(p.scr->cnt + (CNT_Y + (cb >> 1)) * CSP); }
      STAMP(49);
      poll_counter(p.scr->cnt + (CNT_WO + cb) * CSP, tag * 32);
      if (elect_one()) mbar_arrive(sb + BAR_WO);
      STAMP(46);
      held_service(p, sb, 0, chb + 192, rb, cb, tag, lane);
    } else {
      const uint32_t tag = epoch + 1;
      sts32(sb + OFF_BIAS + lane * 4, bias2);
      if (lane < 2) sts32(sb + OFF_TAG + lane * 4, lane ? 0 : tag);
      fence_async_smem();
      uint32_t t0 = 0;
      mbar_wait(sb + BAR_AF + 8 * (NA - 1), 0);
#pragma unroll 1
      while (true) {
        const uint4 u = ld_ll4(&p.scr->xstat[rb * 64 + lane]), v = ld_ll4(&p.scr->xstat[rb * 64 + 32 + lane]);
        sts64f(sb + OFF_XS + lane * 8, __uint_as_float(u.x), __uint_as_float(u.z));
        sts64f(sb + OFF_XS + 256 + lane * 8, __uint_as_float(v.x), __uint_as_float(v.z));
        if (__all_sync(0xffffffff, u.y == tag && u.w == tag && v.y == tag && v.w == tag)) break;
        spin_guard(t0);
      }
      STAMP(26);
      __syncwarp();
      if (lane == 0) mbar_arrive(sb + BAR_XS);
      { uint32_t tp = tstart; pace(tp, CS1_T); gather_colsum(p, sb, cb, 1, tag, lane); STAMP(38); }
      mbar_wait(sb + BAR_KU, 1);
      poll_counter(p.scr->cnt + (CNT_KV + (cb >> 1)) * CSP, tag * 64);
      if (elect_one()) load_convx(p, sb + OFF_CV, sb + BAR_XF + 8, chb);
      mbar_wait(sb + BAR_KU + 8, 1);
      if (elect_one()) load_convx(p, sb + OFF_CV + CV_SZ, sb + BAR_XF, chb + 64);
      STAMP(48);
      mbar_wait(sb + BAR_AE + 72, 0);
#pragma unroll 1
      for (int i = 0; i < 2; i++) {
        conv_service(p, sb, 1, chb + i * 128, i == 0);
        if (i == 0) {
          poll_counter(p.scr->cnt + (CNT_Z1 + (cb >> 1)) * CSP, tag * 64);
          if (elect_one()) mbar_arrive(sb + BAR_Z1);
          STAMP(24);
        }
      }
      bar_arrive(NB_CD, 64);
      mbar_wait(sb + BAR_WO, 0);
      poll_counter(p.scr->cnt + (CNT_Y + (cb >> 1)) * CSP, tag * 64);
      STAMP(47);
      if (elect_one()) mbar_arrive(sb + BAR_YT);
      held_service(p, sb, 1, chb + 256, rb, cb, tag, lane);
      if (lane == 0) st_relaxed(&p.scr->epoch[lin * EPS], tag);
      STAMP(23);
    }
  } else {
    if (warp == 7) STAMP(36);
    const int wg = warp >> 2, w = warp & 3, g = lane >> 2, t = lane & 3;
    Taps k;
    uint32_t xw[2][10];
    if (wg == 2) {
      asm volatile("setmaxnreg.inc.sync.aligned.u32 160;");
      const int tb = rb * 2 + (cb & 1), c0 = (cb >> 1) * 320;
      const uint32_t cv = sb + OFF_CV + CV_SZ;
      if (w == 0) zero_pads(sb + OFF_CV, lane);
      mbar_wait(sb + BAR_KV + 8, 0);
      const int t0 = tb * 32 + w * 8;
      const __nv_bfloat16* kp = p.k + (size_t)(t0 - 3) * kD + c0 + lane * 2;
      const __nv_bfloat16* vp = p.v + (size_t)t0 * kD + c0 + lane * 2;
      const __nv_bfloat16* sp = p.shift + (c0 + lane * 2) * 4;
      const uint32_t oa = cv + ((3 - w) & 1) * 1024 + lane * 32 + ((((3 - w) >> 1) ^ (lane >> 2)) & 1) * 16;
#pragma unroll 1
      for (int r = 0; r < 2; r++) {
        KvRegs n0, n1, n2;
        STAMPW(r ? 51 : 50);
        kv_load(n0, kp + r * 128, vp + r * 128, sp + r * 512, t0 > 0);
        kv_load(n1, kp + r * 128 + 64, vp + r * 128 + 64, sp + r * 512 + 256, t0 > 0);
        if (r) kv_load(n2, kp + 256, vp + 256, sp + 1024, t0 > 0);
        kv_unit(n0, oa + r * 8192);
        bar_sync(NB_WGC, 128);
        mbar_arrive_if(sb + BAR_KU + 16 * r, tid == 0);
        if (r) mbar_wait(sb + BAR_KU, 1);
        kv_unit(n1, oa + (r ? 0 : 4096));
        bar_sync(NB_WGC, 128);
        mbar_arrive_if(sb + BAR_KU + 16 * r + 8, tid == 0);
        if (r) {
          kv_unit(n2, oa + 4096);
          bar_sync(NB_WGC, 128);
          mbar_arrive_if(sb + BAR_KU + 32, tid == 0);
        } else {
          mbar_wait(sb + BAR_AF + 8 * ((cb >> 1) * 5 + 1), 0);
          mbar_wait2(sb + BAR_AF + 8 * ((cb >> 1) * 5 + 2), 0, sb + BAR_AF + 8 * ((cb >> 1) * 5 + 4), 0);
          final_load_x(xw, sb + OFF_A, cb, 1, w, lane);
          fence_async_smem();
          bar_sync(NB_WGC, 128);
          mbar_arrive_if(sb + BAR_XC, tid == 0);
        }
      }
      STAMPW(13);
      load_taps(k, p, chb, tid);
    } else {
      float d[96];
      if (wg == 0) st_ll2(&p.scr->zstat[(rb * 256 + cb * 64 + w * 16 + g + (t >> 1) * 8) * 2 + (t & 1)], 0, 0);
      else if ((tid & 7) == 0) st_ll4(&p.scr->xstat[rb * 64 + cb * 16 + (tid >> 3)], 0, 0, 0, 0);
      {
        #pragma unroll
        for (int i = 0; i < 96; i++) d[i] = 0.f;
        {
          if (__builtin_expect(wg == 1, 0)) {
            const int tid = tid_now();
            const uint32_t epoch = load_epoch(p, lin, lane);
            float s = 0.f, q = 0.f;
#pragma unroll 1
            for (int i = 0; i < 10; i++) {
              mbar_wait(sb + BAR_AF + 8 * i, 0);
              const uint4 x4 = lds128(sb + OFF_A + i * A_SLOT + cb * 2048 + tid * 16);
              const uint32_t u[4] = {x4.x, x4.y, x4.z, x4.w};
#pragma unroll
              for (int e = 0; e < 4; e++) { const float a = bf_lo(u[e]), c = bf_hi(u[e]); s += a + c; q = fmaf(a, a, q); q = fmaf(c, c, q); }
            }
#pragma unroll
            for (int o = 1; o <= 4; o <<= 1) { s += __shfl_xor_sync(0xffffffff, s, o); q += __shfl_xor_sync(0xffffffff, q, o); }
            const float m = s * (1.f / kD);
            const float r = rsqrtf(fmaxf(fmaf(-m, m, q * (1.f / kD)), 0.f) + 1e-5f);
            if ((tid & 7) == 0) st_ll4(&p.scr->xstat[rb * 64 + cb * 16 + (tid >> 3)], __float_as_uint(m), epoch + 1, __float_as_uint(r), epoch + 1);
            STAMPW(12);
            bar_sync(NB_G1, 256);
          }
          gemm_loop<192, true, 0>(d, sb, 10, wg ? zs0 : 0, 0, 0, 0, wg, 2, tid_now(), [&]() { if (wg == 0) bar_arrive(NB_G1, 256); });
          asm volatile("setmaxnreg.inc.sync.aligned.u32 160;");
          STAMPW(wg ? 14 : 1);
          if (wg == 0) ZS(0);
          mbar_wait2(sb + BAR_XS, 0, sb + BAR_ST + 8 * wg, 0);
          if (wg == 0) ZS(1);
        }
        const int t1 = tid_now();
        const uint32_t xa1 = sb + OFF_XS + (w * 16 + ((t1 & 31) >> 2)) * 8;
        const float2 s0 = lds64f(xa1), s1 = lds64f(xa1 + 64);
        uint32_t z[48];
        float st[4];
        fence_async_smem();
        fold_mean(d, sb + OFF_CS + (1 - wg) * 768, s0.x, s1.x, t1 & 3);
        WG_WAIT(0);
        acc_fence<96>(d);
        if (wg == 0) ZS(2);
        gelu_tile(d, z, st, s0.y, s1.y);
        const int tid = tid_now(), lane = tid & 31, g = lane >> 2, t = lane & 3;
        if (wg == 1) {
          uint32_t bra, brb;
          asm volatile("ld.shared.u16 %0, [%1];" : "=r"(bra) : "r"(sb + OFF_BIAS + (w * 16 + g) * 2));
          asm volatile("ld.shared.u16 %0, [%1+16];" : "=r"(brb) : "r"(sb + OFF_BIAS + (w * 16 + g) * 2));
#pragma unroll
          for (int j = 0; j < 96; j++) d[j] = bf_lo((j & 2) ? brb : bra);
          STAMPW(15);
          gemm_loop<192, true, 1>(d, sb, 32, 0, 1, 20, 0, 2, 2, tid, []() {});
          mbar_arrive_if(sb + BAR_GO1, tid == 0);
          STAMPW(16);
          const int t2 = tid_now(), l2 = t2 & 31;
          const uint32_t ha = sb + OFF_A + 5 * A_SLOT + (l2 >> 4) * 1024 + (2 * w + ((l2 >> 3) & 1)) * 128 + (l2 & 7) * 16;
#pragma unroll
          for (int j = 0; j < 24; j += 2) {
#pragma unroll
            for (int e = 0; e < 4; e++) z[2 * j + e] = hmul2(z[2 * j + e], pack2(d[4 * j + 2 * e], d[4 * j + 2 * e + 1]));
            stsm4(ha + j * 1024, z[2 * j], z[2 * j + 1], z[2 * j + 2], z[2 * j + 3]);
            if (j == 6) {
              fence_async_smem();
              bar_arrive(NB_H, 160);
            }
          }
          fence_async_smem();
          bar_sync(NB_WGB, 128);
          mbar_arrive_if(sb + BAR_AF + 8 * (t2 == 3 ? (BAR_G2 - BAR_AF) / 8 : (t2 == 4 ? (BAR_GO - BAR_AF) / 8 : 5 + t2)), t2 < 5);
          mbar_expect_if(sb + BAR_AF + 8 * (t2 == 5 ? 8 : t2), A_SLOT, t2 < 6);
          STAMPW(17);
          {
            float e[80];
            gemm_loop<160, false, 2>(e, sb, 12, 5, 0, 2, 0, 2, 2, tid_now(), []() {});
            STAMPW(10);
            const int t3 = tid_now();
#pragma unroll
            for (int j = 0; j < 10; j++) {
              sts128(sb + OFF_A + j * 2048 + t3 * 16, pack2(e[8 * j], e[8 * j + 1]), pack2(e[8 * j + 2], e[8 * j + 3]), pack2(e[8 * j + 4], e[8 * j + 5]),
                     pack2(e[8 * j + 6], e[8 * j + 7]));
              if (j == 4) bar_arrive(NB_WO, 256);
            }
            bar_arrive(NB_Z, 256);
            STAMPW(45);
          }
          return;
        }
        ZS(3);
        const bool hi = t & 2;
        float a0 = (hi ? st[2] : st[0]) + __shfl_xor_sync(0xffffffff, hi ? st[0] : st[2], 2);
        float a1 = (hi ? st[3] : st[1]) + __shfl_xor_sync(0xffffffff, hi ? st[1] : st[3], 2);
        a0 = ((t & 1) ? a1 : a0) + __shfl_xor_sync(0xffffffff, (t & 1) ? a0 : a1, 1);
        const uint32_t tag = lds32<0>(sb + OFF_TAG);
        uint2* zs = p.scr->zstat + (rb * 256 + w * 16 + g + (t >> 1) * 8) * 2 + (t & 1);
        st_ll2(zs + cb * 128, __float_as_uint(a0), tag);
        STAMPW(2); ZS(4);
        uint2 u[4];
#pragma unroll
        for (int i = 0; i < 4; i++) u[i] = ld_ll2(zs + i * 128);
        const uint32_t keep = (cb & 2) ? 13 << 5 : 13;
        mbar_arrive_if(sb + BAR_AE + 8 * tid, tid < NA && !((keep >> tid) & 1));
        const uint32_t za = sb + OFF_A + zs0 * A_SLOT + (2 * w + ((lane >> 3) & 1)) * 3072 + (lane >> 4) * 128 + (lane & 7) * 16;
        const float ca = 0.5f * (hi ? s1.y : s0.y), inv = 1.f / 768.f;
        mbar_wait2(sb + BAR_AE + 8 * (zs0 + 2), 0, sb + BAR_XC, 0);
        ZS(6);
        uint32_t t0 = 0;
#pragma unroll 1
        while (!__all_sync(0xffffffff, u[0].y == tag && u[1].y == tag && u[2].y == tag && u[3].y == tag)) {
          spin_guard(t0);
#pragma unroll
          for (int i = 0; i < 4; i++) u[i] = ld_ll2(zs + i * 128);
        }
        STAMPW(3); ZS(7);
        a0 = ((__uint_as_float(u[0].x) + __uint_as_float(u[1].x)) + (__uint_as_float(u[2].x) + __uint_as_float(u[3].x))) * inv;
        a1 = __shfl_xor_sync(0xffffffff, a0, 1);
        const float m = (t & 1) ? a1 : a0, q = (t & 1) ? a0 : a1;
        const float r = bf_lo(pack2(ca * rsqrtf(fmaf(fmaxf(fmaf(-m, m, q), 0.f), ca * ca, 1e-5f)), 0.f));
        const uint32_t rn = pack2(r, -m * r), ro = __shfl_xor_sync(0xffffffff, rn, 2);
        const uint32_t ra2 = prmt(hi ? ro : rn, 0, 0x1010), n2a = prmt(hi ? ro : rn, 0, 0x3232), rb2 = prmt(hi ? rn : ro, 0, 0x1010), n2b = prmt(hi ? rn : ro, 0, 0x3232);
        if (w >= 2) bar_sync(NB_Z, 160);
#pragma unroll
        for (int j = 0; j < 24; j += 2)
          stsm4(za + j * 128, hfma2(z[2 * j], ra2, n2a), hfma2(z[2 * j + 1], rb2, n2b), hfma2(z[2 * j + 2], ra2, n2a), hfma2(z[2 * j + 3], rb2, n2b));
        ZS(8);
        fence_async_smem();
        ZS(9);
        if (w < 2) bar_arrive(NB_Z, 160);
        else bar_arrive(NB_Z2, 96);
        final_load_x(xw, sb + OFF_A, cb, 0, w, lane);
        fence_async_smem();
        bar_sync(NB_WGA, 128);
        mbar_arrive_if(sb + BAR_AE + 8 * tid, tid < NA && ((keep >> tid) & 1));
      }
      {
        const uint32_t zero = lds32<0>(sb + OFF_TAG + 4);
#pragma unroll
        for (int i = 0; i < 20; i++) xw[i / 10][i % 10] |= zero;
      }
      load_taps(k, p, chb + 64, tid_now());
      STAMPW(4);
    }
    const int h = wg >> 1;
    {
    const int tid = tid_now(), lane = tid & 31;
    conv_worker(p, k, sb + OFF_CV + (1 - h) * CV_SZ, sb + OFF_A + 9 * A_SLOT + h * 4096, sb + BAR_XF + 8 * h, NB_WGA + h,
                chb + (h ? 0 : 64), 2 + h, sb + BAR_GO, w, lane, tid, h ? 40 : 5, rb, cb);
    {
      const int t3 = tid_now(), l3 = t3 & 31;
      const uint32_t xs_addr = sb + OFF_XS + (w * 16 + (l3 >> 2)) * 8;
      const float2 s0 = lds64f(xs_addr), s1 = lds64f(xs_addr + 64);
      const uint32_t ya = sb + y_tile(h) + ((l3 >> 4) * 8 + (l3 & 7)) * 128 + (((2 * w + ((l3 >> 3) & 1)) ^ (l3 & 7) ^ (rb & 7)) << 4);
      uint32_t sw[2][10];
      mbar_wait(sb + BAR_XF + 8 * h, h);
      final_s_early(sw, xw, ya, s0, s1);
      uint32_t ph = 1, t0 = 0, y[8];
#pragma unroll 1
      while (true) {
        mbar_wait(sb + BAR_YL + 16 * h, ph);
        if (bar_all(NB_WGA + h, 128, final_late(y, ya))) break;
        spin_guard(t0);
        ph ^= 1;
        if (t3 == 0) load_late_y(p, sb, h, rb, cb, lds32<0>(sb + OFF_TAG) & 1);
      }
#pragma unroll
      for (int e = 0; e < 8; e++) sw[e & 1][4 + (e >> 1)] = hmul2(sw[e & 1][4 + (e >> 1)], ~y[e]);
      __nv_bfloat16* o0 = p.out + (size_t)(w * 512 + rb * 16 + (l3 >> 2)) * kD + seg_col(cb, h);
      STAMPW(h ? 44 : 9);
      bar_sync(h ? NB_Z : NB_WO, 256);
      float d[40];
#pragma unroll
      for (int j = 0; j < 5; j++) {
        const uint4 v = lds128(sb + OFF_A + (h * 5 + j) * 2048 + t3 * 16);
        d[8 * j] = bf_lo(v.x); d[8 * j + 1] = bf_hi(v.x); d[8 * j + 2] = bf_lo(v.y); d[8 * j + 3] = bf_hi(v.y);
        d[8 * j + 4] = bf_lo(v.z); d[8 * j + 5] = bf_hi(v.z); d[8 * j + 6] = bf_lo(v.w); d[8 * j + 7] = bf_hi(v.w);
      }
      final_out(d, xw, sw, s0.y, s1.y, o0, h, l3 & 3);
    }
    }
  }
}

typedef CUresult (*EncodeFn)(CUtensorMap*, CUtensorMapDataType, cuuint32_t, void*, const cuuint64_t*, const cuuint64_t*, const cuuint32_t*,
                             const cuuint32_t*, CUtensorMapInterleave, CUtensorMapSwizzle, CUtensorMapL2promotion, CUtensorMapFloatOOBfill);

void encode(EncodeFn fn, CUtensorMap* m, const void* ptr, int rank, const cuuint64_t* dims, const cuuint64_t* strides, const cuuint32_t* box,
            CUtensorMapSwizzle swz = CU_TENSOR_MAP_SWIZZLE_128B) {
  const cuuint32_t es[3] = {1, 1, 1};
  fn(m, CU_TENSOR_MAP_DATA_TYPE_BFLOAT16, rank, const_cast<void*>(ptr), dims, strides, box, es, CU_TENSOR_MAP_INTERLEAVE_NONE,
     swz, CU_TENSOR_MAP_L2_PROMOTION_L2_128B, CU_TENSOR_MAP_FLOAT_OOB_FILL_NONE);
}

}

extern "C" void kernel_launch(void* const* d_in, const int* in_sizes, int n_in, void* d_out, int out_size) {
  (void)in_sizes; (void)n_in; (void)out_size;
  static EncodeFn enc = nullptr;
  static Scratch* scr = nullptr;
  static int sms = 0;
  if (!enc) {
    void* fn = nullptr;
    cudaDriverEntryPointQueryResult qr;
    cudaGetDriverEntryPoint("cuTensorMapEncodeTiled", &fn, cudaEnableDefault, &qr);
    enc = (EncodeFn)fn;
    cudaFuncSetAttribute(fused_kernel, cudaFuncAttributeMaxDynamicSharedMemorySize, SMEM_BYTES);
    cudaGetSymbolAddress((void**)&scr, g_scr);
    int dev = 0;
    cudaGetDevice(&dev);
    cudaDeviceGetAttribute(&sms, cudaDevAttrMultiProcessorCount, dev);
  }
  Params p;
  p.scr = scr;
  p.by_smid = sms == 132;
  p.k = (const __nv_bfloat16*)d_in[1];
  p.v = (const __nv_bfloat16*)d_in[2];
  p.shift = (const __nv_bfloat16*)d_in[3];
  p.ssmk = (const __nv_bfloat16*)d_in[4];
  p.ssmD = (const __nv_bfloat16*)d_in[5];
  p.wsp = (const __nv_bfloat16*)d_in[8];
  p.bsp = (const __nv_bfloat16*)d_in[9];
  p.wout = (const __nv_bfloat16*)d_in[10];
  p.out = (__nv_bfloat16*)d_out;
  for (int i = 0; i < 2; i++) {
    const cuuint64_t n = i ? kS : kD, dims[3] = {n, 512, 4}, st[2] = {n * 2, n * 1024};
    const cuuint32_t box[3] = {64, 16, 4};
    encode(enc, i ? &p.tmWsp : &p.tmX, d_in[i ? 8 : 0], 3, dims, st, box);
  }
  {
    const cuuint64_t dims[3] = {64, kD, kF / 64}, st[2] = {kF * 2, 128};
    const cuuint32_t box[3] = {64, 64, 3};
    encode(enc, &p.tmW, d_in[7], 3, dims, st, box);
  }
  {
    const cuuint64_t dims[2] = {kS, 896}, st[1] = {kS * 2};
    const cuuint32_t box[2] = {64, 16};
    encode(enc, &p.tmY, scr->y, 2, dims, st, box);
  }
  {
    const cuuint64_t dims[3] = {1024, kD / 2, 4}, st[2] = {8192, 2048};
    const cuuint32_t box[3] = {16, 32, 4};
    encode(enc, &p.tmKV, scr->kvx, 3, dims, st, box, CU_TENSOR_MAP_SWIZZLE_32B);
  }
  fused_kernel<<<132, 512, SMEM_BYTES, cudaStreamPerThread>>>(p);
}
```
